```python
import torch

def _softmax(x, axis=-1):
    return torch.softmax(x, dim=axis)
def _gelu(x):
    return torch.nn.functional.gelu(x, approximate="tanh")
def _silu(x):
    return torch.nn.functional.silu(x)
def _sigmoid(x):
    return torch.sigmoid(x)
def _layernorm(x, axis=-1, eps=1e-5):
    m = x.mean(dim=axis, keepdim=True)
    v = x.var(dim=axis, keepdim=True, unbiased=False)
    return (x - m) / torch.sqrt(v + eps)
def _scatter_add(tgt, idx, src, axis=0):
    return tgt.clone().index_add_(axis, idx, src)
def _segment_sum(src, seg, n):
    out = torch.zeros((n,) + src.shape[1:], dtype=src.dtype)
    return out.index_add_(0, seg, src)
def _pad(x, pw):
    flat = tuple(v for pair in reversed(pw) for v in pair)
    return torch.nn.functional.pad(x, flat)

kernel_name = 'concat_heads__sliding_local_dilated__spectral_fnet__prompt'

def setup_inputs():

    _w = (lambda a: (lambda t: t.to(torch.bfloat16) if t.is_floating_point() else t)(torch.as_tensor(a)))
    def _A_setup():
        B, S, D = 1, 2048, 448
        return {
            "x": _w((lambda *s: torch.randn(*s, dtype=torch.bfloat16) * 0.2)(B, S, D)),
            "wqkv": _w((lambda *s: torch.randn(*s, dtype=torch.bfloat16) * 0.8)(D, 3 * D)),
            "wo": _w((lambda *s: torch.randn(*s, dtype=torch.bfloat16) * 0.2)(D, D)),
        }
    _A_in = _A_setup()

    def _B_setup():
        B, S, D = 1, 2048, 448
        ns = torch.arange(S)[:, None] * torch.arange(S)[None, :]
        nd = torch.arange(D)[:, None] * torch.arange(D)[None, :]
        Ws_re = torch.cos(-2.0 * torch.pi * ns / S).to(float)
        Ws_im = torch.sin(-2.0 * torch.pi * ns / S).to(float)
        Wd_re = torch.cos(-2.0 * torch.pi * nd / D).to(float)
        Wd_im = torch.sin(-2.0 * torch.pi * nd / D).to(float)
        return {
            "x": _w((lambda *s: torch.randn(*s, dtype=torch.bfloat16) * 0.05)(B, S, D)),
            "dft_seq_re": _w(Ws_re),
            "dft_seq_im": _w(Ws_im),
            "dft_hid_re": _w(Wd_re),
            "dft_hid_im": _w(Wd_im),
        }
    _B_in = _B_setup()

    return {
        "A_x": _A_in["x"],
        "A_wqkv": _A_in["wqkv"],
        "A_wo": _A_in["wo"],
        "B_x": _B_in["x"],
        "B_dft_seq_re": _B_in["dft_seq_re"],
        "B_dft_seq_im": _B_in["dft_seq_im"],
        "B_dft_hid_re": _B_in["dft_hid_re"],
        "B_dft_hid_im": _B_in["dft_hid_im"],
    }

def reference(A_x, A_wqkv, A_wo, B_x, B_dft_seq_re, B_dft_seq_im, B_dft_hid_re, B_dft_hid_im):
    def _A_ref(x, wqkv, wo):
        B, S, D = x.shape
        H = 16; Dh = D // H
        W, dil = 8, 2
        qkv = (lambda x, *d: x.permute(*d))((x @ wqkv).reshape(B, S, 3, H, Dh), 2, 0, 3, 1, 4)
        q, k, v = qkv[0], qkv[1], qkv[2]
        scale = Dh ** -0.5
        pos = torch.arange(S)
        off = torch.arange(W) * dil
        idx = pos[:, None] - off[None, :]
        mask = idx >= 0
        idx_c = torch.where(mask, idx, 0).reshape(-1)
        kg = k[:, :, idx_c, :].reshape(B, H, S, W, Dh)
        vg = v[:, :, idx_c, :].reshape(B, H, S, W, Dh)
        logits = torch.einsum("bhsd,bhswd->bhsw", q, kg) * scale
        logits = torch.where(mask[None, None, :, :], logits, -1e9)
        attn = _softmax(logits, axis=-1)
        o = torch.einsum("bhsw,bhswd->bhsd", attn, vg)
        return (lambda x, *d: x.permute(*d))(o, 0, 2, 1, 3).reshape(B, S, D) @ wo

    def _B_ref(x, dft_seq_re, dft_seq_im, dft_hid_re, dft_hid_im):
        a = torch.einsum("bsd,ed->bse", x, dft_hid_re)
        b = torch.einsum("bsd,ed->bse", x, dft_hid_im)
        y = torch.einsum("ts,bse->bte", dft_seq_re, a) - torch.einsum("ts,bse->bte", dft_seq_im, b)
        return y

    a = _A_ref(A_x, A_wqkv, A_wo)
    b = _B_ref(B_x, B_dft_seq_re, B_dft_seq_im, B_dft_hid_re, B_dft_hid_im)
    return torch.concatenate([a, b], axis=-1)
```

```cpp
#include <cuda.h>
#include <cuda_bf16.h>
#include <cuda_runtime.h>
#include <stdint.h>

namespace {

constexpr int NSLOT = 6;
constexpr uint32_t SLOT = 32768;
constexpr uint32_t BOFF = 16384;
constexpr uint32_t STG = NSLOT * SLOT;
constexpr uint32_t WSLOT = 3584;
constexpr uint32_t BLOB = 14336;
constexpr uint32_t BARS = STG + 9 * WSLOT;
constexpr uint32_t BAR_FULL = BARS;
constexpr uint32_t BAR_EMPTY = BARS + 64;
constexpr uint32_t BAR_HALO = BARS + 128;
constexpr uint32_t SMEM_BYTES = BARS + 256 + 1024;
constexpr int NSTAGE = 53;
constexpr int SPIN_LIMIT = 1 << 16;

enum { M_XA32, M_XA64, M_WKV, M_WQ, M_WO, M_XB, M_WR, M_WI, M_CR, M_CI, M_OST, M_OLD, M_OUTA, M_OUTB, M_COUNT };
struct __align__(64) Maps { CUtensorMap m[M_COUNT]; };

enum { NB_READY = 1, NB_FREE = 3, NB_HALO = 5, NB_SKEW = 6 };

constexpr int CNT_A = 0;
constexpr int CNT_B = 8;
constexpr int CNT_O = 16;
constexpr int CNT_H = 32;
constexpr int CNT_COUNT = 96;

__device__ __align__(1024) uint8_t g_ab[2 * 32 * 4 * BLOB];
__device__ __align__(1024) __nv_bfloat16 g_o[2048 * 448];
__device__ __align__(1024) uint8_t g_halo[64 * WSLOT];
__device__ __align__(128) unsigned g_cnt[CNT_COUNT * 32];
__device__ __align__(128) unsigned g_epoch[128 * 4 * 8];

#define PROF(idx)

__device__ __forceinline__ void mbar_init(uint32_t bar, uint32_t cnt) {
    asm volatile("mbarrier.init.shared::cta.b64 [%0], %1;" ::"r"(bar), "r"(cnt) : "memory");
}
__device__ __forceinline__ void mbar_expect(uint32_t bar, uint32_t bytes) {
    asm volatile("mbarrier.arrive.expect_tx.shared::cta.b64 _, [%0], %1;" ::"r"(bar), "r"(bytes) : "memory");
}
__device__ __forceinline__ void mbar_arrive(uint32_t bar) {
    asm volatile("mbarrier.arrive.shared::cta.b64 _, [%0];" ::"r"(bar) : "memory");
}
__device__ __forceinline__ bool mbar_try(uint32_t bar, uint32_t parity) {
    uint32_t ok;
    asm volatile("{\n.reg .pred p;\nmbarrier.try_wait.parity.shared::cta.b64 p, [%1], %2;\nselp.u32 %0, 1, 0, p;\n}\n"
                 : "=r"(ok) : "r"(bar), "r"(parity) : "memory");
    return ok;
}
__device__ __forceinline__ void mbar_wait(uint32_t bar, uint32_t parity) {
    if (mbar_try(bar, parity)) return;
    int n = 0;
    while (!mbar_try(bar, parity))
        if (++n > SPIN_LIMIT) break;
}
__device__ __forceinline__ void nb_sync(int id, int n) { asm volatile("bar.sync %0, %1;" ::"r"(id), "r"(n) : "memory"); }
__device__ __forceinline__ void nb_arrive(int id, int n) { asm volatile("bar.arrive %0, %1;" ::"r"(id), "r"(n) : "memory"); }

__device__ __forceinline__ void tma_ld2(uint32_t dst, const CUtensorMap* m, int c0, int c1, uint32_t bar) {
    asm volatile("cp.async.bulk.tensor.2d.shared::cluster.global.mbarrier::complete_tx::bytes [%0], [%1, {%3, %4}], [%2];"
                 ::"r"(dst), "l"(m), "r"(bar), "r"(c0), "r"(c1) : "memory");
}
__device__ __forceinline__ void tma_ld3(uint32_t dst, const CUtensorMap* m, int c0, int c1, int c2, uint32_t bar) {
    asm volatile("cp.async.bulk.tensor.3d.shared::cluster.global.mbarrier::complete_tx::bytes [%0], [%1, {%3, %4, %5}], [%2];"
                 ::"r"(dst), "l"(m), "r"(bar), "r"(c0), "r"(c1), "r"(c2) : "memory");
}
__device__ __forceinline__ void bulk_ld(uint32_t dst, const void* src, uint32_t bytes, uint32_t bar) {
    asm volatile("cp.async.bulk.shared::cluster.global.mbarrier::complete_tx::bytes [%0], [%1], %2, [%3];"
                 ::"r"(dst), "l"(src), "r"(bytes), "r"(bar) : "memory");
}
__device__ __forceinline__ void bulk_st(void* dst, uint32_t src, uint32_t bytes) {
    asm volatile("cp.async.bulk.global.shared::cta.bulk_group [%0], [%1], %2;" ::"l"(dst), "r"(src), "r"(bytes) : "memory");
}
__device__ __forceinline__ void tma_st2(const CUtensorMap* m, int c0, int c1, uint32_t src) {
    asm volatile("cp.async.bulk.tensor.2d.global.shared::cta.bulk_group [%0, {%1, %2}], [%3];"
                 ::"l"(m), "r"(c0), "r"(c1), "r"(src) : "memory");
}
__device__ __forceinline__ void tma_red2(const CUtensorMap* m, int c0, int c1, uint32_t src) {
    asm volatile("cp.reduce.async.bulk.tensor.2d.global.shared::cta.add.bulk_group [%0, {%1, %2}], [%3];"
                 ::"l"(m), "r"(c0), "r"(c1), "r"(src) : "memory");
}
__device__ __forceinline__ void bulk_commit() { asm volatile("cp.async.bulk.commit_group;" ::: "memory"); }
__device__ __forceinline__ void bulk_wait_all() { asm volatile("cp.async.bulk.wait_group 0;" ::: "memory"); }
__device__ __forceinline__ void bulk_wait_read() { asm volatile("cp.async.bulk.wait_group.read 0;" ::: "memory"); }
__device__ __forceinline__ void fence_async_smem() { asm volatile("fence.proxy.async.shared::cta;" ::: "memory"); }
__device__ __forceinline__ void fence_async_global() { asm volatile("fence.proxy.async.global;" ::: "memory"); }

__device__ __forceinline__ void signal(int idx) {
    fence_async_global();
    asm volatile("red.release.gpu.global.add.u32 [%0], 1;" ::"l"(&g_cnt[idx * 32]) : "memory");
}
__device__ __forceinline__ void await(int idx, unsigned target) {
    unsigned v;
    int n = 0;
    do {
        asm volatile("ld.acquire.gpu.global.u32 %0, [%1];" : "=r"(v) : "l"(&g_cnt[idx * 32]) : "memory");
        if (++n > SPIN_LIMIT) break;
    } while ((int)(v - target) < 0);
    fence_async_global();
}

#define WG_REGS                                                                                                     \
    "{%0,%1,%2,%3,%4,%5,%6,%7,%8,%9,%10,%11,%12,%13,%14,%15,%16,%17,%18,%19,%20,%21,%22,%23,%24,%25,%26,%27,"       \
    "%28,%29,%30,%31,%32,%33,%34,%35,%36,%37,%38,%39,%40,%41,%42,%43,%44,%45,%46,%47,%48,%49,%50,%51,%52,%53,%54,%55}"
#define WG_OPS(C)                                                                                                   \
    C(d[0]), C(d[1]), C(d[2]), C(d[3]), C(d[4]), C(d[5]), C(d[6]), C(d[7]), C(d[8]), C(d[9]), C(d[10]), C(d[11]),   \
    C(d[12]), C(d[13]), C(d[14]), C(d[15]), C(d[16]), C(d[17]), C(d[18]), C(d[19]), C(d[20]), C(d[21]), C(d[22]),   \
    C(d[23]), C(d[24]), C(d[25]), C(d[26]), C(d[27]), C(d[28]), C(d[29]), C(d[30]), C(d[31]), C(d[32]), C(d[33]),   \
    C(d[34]), C(d[35]), C(d[36]), C(d[37]), C(d[38]), C(d[39]), C(d[40]), C(d[41]), C(d[42]), C(d[43]), C(d[44]),   \
    C(d[45]), C(d[46]), C(d[47]), C(d[48]), C(d[49]), C(d[50]), C(d[51]), C(d[52]), C(d[53]), C(d[54]), C(d[55])

template <int TB, int SB, bool INIT>
__device__ __forceinline__ void wgmma112(float (&d)[56], uint64_t da, uint64_t db) {
    if (INIT) {
        asm volatile("{\n.reg .pred p;\nsetp.ne.b32 p, 0, 0;\n"
                     "wgmma.mma_async.sync.aligned.m64n112k16.f32.bf16.bf16 " WG_REGS ", %56, %57, p, 1, %59, 0, %58;\n}\n"
                     : WG_OPS("=f") : "l"(da), "l"(db), "n"(TB), "n"(SB));
    } else {
        asm volatile("{\n.reg .pred p;\nsetp.ne.b32 p, 1, 0;\n"
                     "wgmma.mma_async.sync.aligned.m64n112k16.f32.bf16.bf16 " WG_REGS ", %56, %57, p, 1, %59, 0, %58;\n}\n"
                     : WG_OPS("+f") : "l"(da), "l"(db), "n"(TB), "n"(SB));
    }
}
__device__ __forceinline__ void acc_fence(float (&d)[56]) {
#pragma unroll
    for (int i = 0; i < 56; i++) asm volatile("" : "+f"(d[i])::"memory");
}
__device__ __forceinline__ uint64_t mkdesc(uint32_t addr, uint32_t lbo16, uint32_t sbo16, uint32_t mode) {
    return (uint64_t)(((addr & 0x3FFFF) >> 4) | (lbo16 << 16)) | ((uint64_t)(sbo16 | (mode << 30)) << 32);
}

__device__ __forceinline__ uint32_t pack2(float lo, float hi) {
    uint32_t r;
    asm("cvt.rn.bf16x2.f32 %0, %1, %2;" : "=r"(r) : "f"(hi), "f"(lo));
    return r;
}
__device__ __forceinline__ uint32_t movm(uint32_t a) {
    uint32_t r;
    asm volatile("movmatrix.sync.aligned.m8n8.trans.b16 %0, %1;" : "=r"(r) : "r"(a));
    return r;
}
template <bool TRANS>
__device__ __forceinline__ void stsm4(uint32_t addr, uint32_t a, uint32_t b, uint32_t c, uint32_t d) {
    if (TRANS) asm volatile("stmatrix.sync.aligned.m8n8.x4.trans.shared.b16 [%0], {%1,%2,%3,%4};" ::"r"(addr), "r"(a), "r"(b), "r"(c), "r"(d) : "memory");
    else asm volatile("stmatrix.sync.aligned.m8n8.x4.shared.b16 [%0], {%1,%2,%3,%4};" ::"r"(addr), "r"(a), "r"(b), "r"(c), "r"(d) : "memory");
}
__device__ __forceinline__ void stsm2t(uint32_t addr, uint32_t a, uint32_t b) {
    asm volatile("stmatrix.sync.aligned.m8n8.x2.trans.shared.b16 [%0], {%1,%2};" ::"r"(addr), "r"(a), "r"(b) : "memory");
}
__device__ __forceinline__ void sts4(uint32_t addr, uint32_t a, uint32_t b, uint32_t c, uint32_t d) {
    asm volatile("st.shared.v4.b32 [%0], {%1,%2,%3,%4};" ::"r"(addr), "r"(a), "r"(b), "r"(c), "r"(d) : "memory");
}
__device__ __forceinline__ void lds4(uint32_t addr, uint32_t& a, uint32_t& b, uint32_t& c, uint32_t& d) {
    asm volatile("ld.shared.v4.b32 {%0,%1,%2,%3}, [%4];" : "=r"(a), "=r"(b), "=r"(c), "=r"(d) : "r"(addr) : "memory");
}
__device__ __forceinline__ void mma16816(float (&d)[4], uint32_t a0, uint32_t a1, uint32_t a2, uint32_t a3, uint32_t b0, uint32_t b1) {
    asm volatile("mma.sync.aligned.m16n8k16.row.col.f32.bf16.bf16.f32 {%0,%1,%2,%3}, {%4,%5,%6,%7}, {%8,%9}, {%0,%1,%2,%3};"
                 : "+f"(d[0]), "+f"(d[1]), "+f"(d[2]), "+f"(d[3]) : "r"(a0), "r"(a1), "r"(a2), "r"(a3), "r"(b0), "r"(b1));
}
__device__ __forceinline__ float bf_lo(uint32_t v) { return __uint_as_float(v << 16); }
__device__ __forceinline__ float bf_hi(uint32_t v) { return __uint_as_float(v & 0xFFFF0000u); }
__device__ __forceinline__ float ex2(float x) { float r; asm("ex2.approx.ftz.f32 %0, %1;" : "=f"(r) : "f"(x)); return r; }

__host__ __device__ constexpr int hw_tile(int c) { return (c + 8) % 14; }

struct Ring {
    uint32_t base;
    uint32_t wg;
    uint32_t slot;
    uint32_t phase;
    uint32_t prev;
    bool leader;
    __device__ __forceinline__ uint32_t begin() {
        mbar_wait(base + BAR_FULL + slot * 8, phase);
        asm volatile("wgmma.fence.sync.aligned;" ::: "memory");
        return base + slot * SLOT;
    }
    template <bool RELEASE>
    __device__ __forceinline__ void end() {
        asm volatile("wgmma.commit_group.sync.aligned;" ::: "memory");
        asm volatile("wgmma.wait_group.sync.aligned 1;" ::: "memory");
        if (RELEASE && leader) mbar_arrive(base + BAR_EMPTY + prev * 8);
        prev = slot;
        if (++slot == NSLOT) { slot = 0; phase ^= 1; }
    }
    template <int SB, bool INIT, bool RELEASE = true>
    __device__ __forceinline__ void stage_kk(float (&d)[56]) {
        const uint32_t s = begin();
        const uint64_t da = mkdesc(s + wg * 8192, 1, 64, 1), db = mkdesc(s + BOFF, 1, 64, 1);
        wgmma112<0, SB, INIT>(d, da, db);
        wgmma112<0, SB, false>(d, da + 2, db + 2);
        wgmma112<0, SB, false>(d, da + 4, db + 4);
        wgmma112<0, SB, false>(d, da + 6, db + 6);
        end<RELEASE>();
    }
    template <bool INIT>
    __device__ __forceinline__ void stage_kn(float (&d)[56]) {
        const uint32_t s = begin();
        const uint64_t da = mkdesc(s + wg * 8192, 1, 64, 1), db = mkdesc(s + BOFF, 512, 64, 1);
        wgmma112<1, 1, INIT>(d, da, db);
        wgmma112<1, 1, false>(d, da + 2, db + 128);
        wgmma112<1, 1, false>(d, da + 4, db + 256);
        wgmma112<1, 1, false>(d, da + 6, db + 384);
        end<true>();
    }
    template <bool INIT>
    __device__ __forceinline__ void stage_kv(float (&dk)[56], float (&dv)[56]) {
        const uint32_t s = begin();
        const uint64_t da = mkdesc(s + wg * 4096, 1, 32, 2), db = mkdesc(s + BOFF, 512, 64, 1);
        wgmma112<1, 1, INIT>(dk, da, db);
        wgmma112<1, 1, INIT>(dv, da, db + 256);
        wgmma112<1, 1, false>(dk, da + 2, db + 128);
        wgmma112<1, 1, false>(dv, da + 2, db + 384);
        end<!INIT>();
    }
};

template <bool PERM>
__device__ __forceinline__ void store_rows(const float (&d)[56], uint32_t lane_addr) {
#pragma unroll
    for (int c = 0; c < 14; c += 2) {
        const int j = PERM ? hw_tile(c) : c;
        stsm4<false>(lane_addr + c * 16, pack2(d[4 * j], d[4 * j + 1]), pack2(d[4 * j + 2], d[4 * j + 3]),
                     pack2(d[4 * j + 4], d[4 * j + 5]), pack2(d[4 * j + 6], d[4 * j + 7]));
    }
}
__device__ __forceinline__ void store_blob(const float (&d)[56], uint32_t lane_addr) {
#pragma unroll
    for (int j = 0; j < 14; j += 2)
        stsm4<true>(lane_addr + j * 1024, pack2(d[4 * j], d[4 * j + 1]), pack2(d[4 * j + 2], d[4 * j + 3]),
                    pack2(d[4 * j + 4], d[4 * j + 5]), pack2(d[4 * j + 6], d[4 * j + 7]));
}

__global__ void __launch_bounds__(384, 1) fused_kernel(const __grid_constant__ Maps maps) {
    extern __shared__ uint8_t smem_raw[];
    const uint32_t base = ((uint32_t)__cvta_generic_to_shared(smem_raw) + 1023u) & ~1023u;
    const int warp = __shfl_sync(0xffffffffu, threadIdx.x >> 5, 0);
    const int lane = threadIdx.x & 31;
    const int bid = blockIdx.x;
    const int roleL = (bid >> 3) & 1;
    const int mt = ((bid >> 4) << 1) | ((bid >> 2) & 1);
    const int ns = bid & 3;
    const int par = mt >> 3, blk = mt & 7;

    if (warp == 8) {
        if (lane < NSLOT) mbar_init(base + BAR_FULL + lane * 8, 2);
        else if (lane < 2 * NSLOT) mbar_init(base + BAR_EMPTY + (lane - NSLOT) * 8, 8);
        else if (lane == 2 * NSLOT) mbar_init(base + BAR_HALO, 9);
        asm volatile("fence.mbarrier_init.release.cluster;" ::: "memory");
    }
    __syncthreads();

    if (warp >= 8) {
        asm volatile("setmaxnreg.dec.sync.aligned.u32 72;");
        unsigned* epoch_ptr = &g_epoch[(bid * 4 + (warp - 8)) * 8];
        if (warp == 8) {
            if (lane == 0) {
                const unsigned ep = *epoch_ptr + 1;
                uint32_t slot = 0, phase = 1;
                for (int i = 0; i < NSTAGE; i++) {
                    if (i >= NSLOT) mbar_wait(base + BAR_EMPTY + slot * 8, phase);
                    const uint32_t dst = base + slot * SLOT, bar = base + BAR_FULL + slot * 8;
                    if (!roleL) {
                        if (i == 46) await(CNT_O + mt, ep * 8);
                        mbar_expect(bar, 16384);
                        if (i < 14) tma_ld3(dst, &maps.m[M_XB], (i < 7 ? i : i - 7) * 64, mt * 64, 0, bar);
                        else if (i < 46) tma_ld2(dst, &maps.m[M_CR], (i - 14) * 64, mt * 128, bar);
                        else tma_ld2(dst, &maps.m[M_OLD], (i - 46) * 64, mt * 128, bar);
                    } else {
                        mbar_expect(bar, i < 14 ? 8192 : 16384);
                        if (i < 14) tma_ld2(dst, &maps.m[M_XA32], par * 448 + i * 32, blk * 128, bar);
                        else if (i < 21) tma_ld2(dst, &maps.m[M_XA64], par * 448 + (i - 14) * 64, blk * 128, bar);
                        else tma_ld2(dst, &maps.m[M_CI], (i - 21) * 64, mt * 128, bar);
                    }
                    if (++slot == NSLOT) { slot = 0; phase ^= 1; }
                }
                *epoch_ptr = ep;
            }
        } else if (warp == 11) {
            if (lane == 0) {
                const unsigned ep = *epoch_ptr + 1;
                uint32_t slot = 0, phase = 1;
                const int big0 = roleL ? 21 : 14;
                const int cnt = (roleL ? CNT_B : CNT_A) + ns * 2;
                const uint8_t* blobs = g_ab + (size_t)(roleL * 128 + ns) * BLOB;
                for (int i = 0; i < NSTAGE; i++) {
                    if (i >= NSLOT) mbar_wait(base + BAR_EMPTY + slot * 8, phase);
                    const uint32_t dst = base + slot * SLOT + BOFF, bar = base + BAR_FULL + slot * 8;
                    const int kb = i - big0;
                    if (kb >= 0 && kb < 32) {
                        if ((kb & 15) == 0) {
                            await(cnt + (kb >> 4), ep * 16);
                        }
                        mbar_expect(bar, BLOB);
                        bulk_ld(dst, blobs + (size_t)kb * 4 * BLOB, BLOB, bar);
                    } else if (!roleL) {
                        if (i < 14) {
                            mbar_expect(bar, BLOB);
                            tma_ld2(dst, &maps.m[i < 7 ? M_WR : M_WI], (i < 7 ? i : i - 7) * 64, ns * 112, bar);
                        } else {
                            mbar_expect(bar, 16384);
                            tma_ld2(dst, &maps.m[M_WO], ns * 112 + 48, (i - 46) * 64, bar);
                            tma_ld2(dst + 8192, &maps.m[M_WO], ns * 112, (i - 46) * 64, bar);
                        }
                    } else {
                        mbar_expect(bar, 16384);
                        if (i < 14) {
                            tma_ld3(dst, &maps.m[M_WKV], ns * 112 + 48, i * 32, 1, bar);
                            tma_ld3(dst + 8192, &maps.m[M_WKV], ns * 112, i * 32, 1, bar);
                        } else {
                            tma_ld2(dst, &maps.m[M_WQ], ns * 112 + 48, (i - 14) * 64, bar);
                            tma_ld2(dst + 8192, &maps.m[M_WQ], ns * 112, (i - 14) * 64, bar);
                        }
                    }
                    if (++slot == NSLOT) { slot = 0; phase ^= 1; }
                }
                *epoch_ptr = ep;
            }
        } else {
            const int h = warp - 9;
            const uint32_t stg = base + STG + h * BLOB;
            if (!roleL) {
#pragma unroll 1
                for (int m = 0; m < 2; m++) {
                    nb_sync(NB_READY + h, 160);
                    if (lane == 0) {
                        bulk_st(g_ab + (size_t)((m * 32 + h * 16 + mt) * 4 + ns) * BLOB, stg, BLOB);
                        bulk_commit();
                        bulk_wait_all();
                    }
                    __syncwarp();
                    nb_arrive(NB_FREE + h, 160);
                    if (lane == 0) {
                        signal((m ? CNT_B : CNT_A) + ns * 2 + h);
                    }
                    __syncwarp();
                }
            } else {
                if (h == 0) {
                    unsigned ep = 0;
                    if (lane == 0) ep = *epoch_ptr + 1;
#pragma unroll
                    for (int i = 0; i < 7; i++) sts4(stg + i * 512 + lane * 16, 0, 0, 0, 0);
                    fence_async_smem();
                    __syncwarp();
                    if (lane == 0) {
                        mbar_wait(base + BAR_FULL + 8, 0);
#pragma unroll 1
                        for (int i = 0; i < 8; i++) tma_st2(&maps.m[M_OUTB], 448 + ns * 112, mt * 128 + i * 16, stg);
                        bulk_commit();
                        bulk_wait_all();
                        fence_async_global();
                        asm volatile("fence.acq_rel.gpu;" ::: "memory");
                        if (blk > 0) {
                            await(CNT_H + (mt - 1) * 4 + ns, ep);
                            mbar_expect(base + BAR_HALO, WSLOT);
                            bulk_ld(stg, g_halo + (size_t)((mt - 1) * 4 + ns) * WSLOT, WSLOT, base + BAR_HALO);
                        } else {
                            mbar_arrive(base + BAR_HALO);
                        }
                        *epoch_ptr = ep;
                    }
                    __syncwarp();
                } else {
                    nb_sync(NB_HALO, 64);
                    if (lane == 0 && blk < 7) {
                        bulk_st(g_halo + (size_t)(mt * 4 + ns) * WSLOT, base + STG + 8 * WSLOT, WSLOT);
                        bulk_commit();
                        bulk_wait_all();
                        signal(CNT_H + mt * 4 + ns);
                    }
                    __syncwarp();
                }
                nb_sync(NB_READY + h, 160);
                if (lane == 0) {
                    tma_st2(&maps.m[M_OST], ns * 112, mt * 128 + h * 64, stg);
                    bulk_commit();
                    bulk_wait_all();
                }
                __syncwarp();
                nb_arrive(NB_FREE + h, 160);
                if (lane == 0) {
                    signal(CNT_O + mt);
                }
            }
        }
    } else {
        asm volatile("setmaxnreg.inc.sync.aligned.u32 216;");
        Ring r;
        r.base = base;
        r.wg = warp >> 2;
        r.slot = 0;
        r.phase = 0;
        r.prev = 0;
        r.leader = lane == 0;
        const int wg = warp >> 2;
        const uint32_t wslot = base + STG + warp * WSLOT;
        const uint32_t row_addr = wslot + (lane & 15) * 224 + (lane >> 4) * 16;

        if (!roleL) {
            const uint32_t blob_addr = base + STG + wg * BLOB + ((lane >> 4) * 8 + (lane & 7)) * 128 +
                                       (((2 * (warp & 3) + ((lane >> 3) & 1)) ^ (lane & 7)) << 4);
            float x0[56], x1[56];
            r.stage_kk<1, true, false>(x0);
#pragma unroll 1
            for (int i = 1; i < 7; i++) r.stage_kk<1, false>(x0);

            r.stage_kk<1, true>(x1);
            acc_fence(x0);
            store_blob(x0, blob_addr);
            fence_async_smem();
            nb_arrive(NB_READY + wg, 160);
#pragma unroll 1
            for (int i = 1; i < 7; i++) r.stage_kk<1, false>(x1);

            r.stage_kk<1, true>(x0);
            acc_fence(x1);
            nb_sync(NB_FREE + wg, 160);
            store_blob(x1, blob_addr);
            fence_async_smem();
            nb_arrive(NB_READY + wg, 160);
#pragma unroll 1
            for (int i = 1; i < 32; i++) r.stage_kk<1, false>(x0);

            r.stage_kn<true>(x1);
            acc_fence(x0);
            nb_sync(NB_FREE + wg, 160);
            store_rows<false>(x0, row_addr);
            fence_async_smem();
            __syncwarp();
            if (lane == 0) {
                tma_red2(&maps.m[M_OUTB], 448 + ns * 112, mt * 128 + warp * 16, wslot);
                bulk_commit();
            }
#pragma unroll 1
            for (int i = 1; i < 7; i++) r.stage_kn<false>(x1);

            if (lane == 0) bulk_wait_read();
            __syncwarp();
            asm volatile("wgmma.wait_group.sync.aligned 0;" ::: "memory");
            acc_fence(x1);
            store_rows<true>(x1, row_addr);
            fence_async_smem();
            __syncwarp();
            if (lane == 0) {
                tma_st2(&maps.m[M_OUTA], par * 896 + ns * 112, blk * 128 + warp * 16, wslot);
                bulk_commit();
                bulk_wait_read();
            }
        } else {
            const int g = lane >> 2, tig = lane & 3;
            float y0[56], y1[56], y2[56];
            r.stage_kv<true>(y0, y1);
#pragma unroll 1
            for (int i = 1; i < 14; i++) r.stage_kv<false>(y0, y1);

            uint32_t kl[14], kh[14], vl[14], vh[14];
            r.stage_kn<true>(y2);
            acc_fence(y0);
            acc_fence(y1);
#pragma unroll
            for (int c = 0; c < 14; c++) {
                const int j = hw_tile(c);
                kl[c] = pack2(y0[4 * j], y0[4 * j + 1]);
                kh[c] = pack2(y0[4 * j + 2], y0[4 * j + 3]);
                vh[c] = movm(pack2(y1[4 * j + 2], y1[4 * j + 3]));
            }
            {
                const uint32_t pub = wslot + WSLOT + lane * 16;
                sts4(pub, kh[0], kh[1], kh[2], kh[3]);
                sts4(pub + 512, kh[4], kh[5], kh[6], kh[7]);
                sts4(pub + 1024, kh[8], kh[9], kh[10], kh[11]);
                sts4(pub + 1536, kh[12], kh[13], vh[0], vh[1]);
                sts4(pub + 2048, vh[2], vh[3], vh[4], vh[5]);
                sts4(pub + 2560, vh[6], vh[7], vh[8], vh[9]);
                sts4(pub + 3072, vh[10], vh[11], vh[12], vh[13]);
                if (warp == 7) {
                    fence_async_smem();
                    nb_arrive(NB_HALO, 64);
                }
                __syncwarp();
                if (lane == 0) mbar_arrive(base + BAR_HALO);
            }
            r.stage_kn<false>(y2);
#pragma unroll
            for (int c = 0; c < 14; c++) {
                const int j = hw_tile(c);
                vl[c] = movm(pack2(y1[4 * j], y1[4 * j + 1]));
            }
#pragma unroll 1
            for (int i = 2; i < 7; i++) r.stage_kn<false>(y2);

            r.stage_kk<-1, true>(y0);
            acc_fence(y2);
            uint32_t ql[14], qh[14], kp[14], vp[14];
#pragma unroll
            for (int c = 0; c < 14; c++) {
                const int j = hw_tile(c);
                ql[c] = pack2(y2[4 * j], y2[4 * j + 1]);
                qh[c] = pack2(y2[4 * j + 2], y2[4 * j + 3]);
            }
            mbar_wait(base + BAR_HALO, 0);
            const uint32_t sub = wslot + lane * 16;
            lds4(sub, kp[0], kp[1], kp[2], kp[3]);
            lds4(sub + 512, kp[4], kp[5], kp[6], kp[7]);
            lds4(sub + 1024, kp[8], kp[9], kp[10], kp[11]);
            lds4(sub + 1536, kp[12], kp[13], vp[0], vp[1]);

            r.stage_kk<-1, false>(y0);
            uint32_t st[8];
            {
                const bool cur0 = g <= 2 * tig, cur1 = g <= 2 * tig + 1;
#pragma unroll
                for (int h = 0; h < 4; h++) {
                    const int c0 = 7 * (h >> 1) + 3 * (h & 1);
                    const bool keep = (h & 1) ? (tig >= 2) : (tig < 2);
#pragma unroll
                    for (int b = 0; b < 2; b++) {
                        const uint32_t* q = b ? qh : ql;
                        const uint32_t* kprev = b ? kl : kp;
                        const uint32_t* kcur = b ? kh : kl;
                        uint32_t q0 = q[c0], q3 = q[c0 + 3];
                        if (h & 1) q0 = keep ? q0 : 0u;
                        else q3 = keep ? q3 : 0u;
                        float s[4] = {0.f, 0.f, 0.f, 0.f};
                        mma16816(s, kprev[c0], kcur[c0], kprev[c0 + 1], kcur[c0 + 1], q0, q[c0 + 1]);
                        mma16816(s, kprev[c0 + 2], kcur[c0 + 2], kprev[c0 + 3], kcur[c0 + 3], q[c0 + 2], q3);
                        st[2 * h + b] = pack2(cur0 ? s[2] : s[0], cur1 ? s[3] : s[1]);
                    }
                }
#pragma unroll
                for (int i = 0; i < 8; i++) st[i] = movm(st[i]);
            }

            r.stage_kk<-1, false>(y0);
            const bool c0ok = 2 * tig <= g, c1ok = 2 * tig + 1 <= g;
            float e0[8], e1[8];
            {
                const bool seq_start = blk == 0 && warp == 0;
                float mx[8];
#pragma unroll
                for (int i = 0; i < 8; i++) {
                    const uint32_t l = pack2(bf_lo(st[i]) * 0.18898223650461362f, bf_hi(st[i]) * 0.18898223650461362f);
                    e0[i] = bf_lo(l);
                    e1[i] = bf_hi(l);
                    if ((i & 1) == 0) {
                        if (seq_start && !c0ok) e0[i] = -1e9f;
                        if (seq_start && !c1ok) e1[i] = -1e9f;
                    }
                    mx[i] = fmaxf(e0[i], e1[i]);
                }
#pragma unroll
                for (int i = 0; i < 8; i++) mx[i] = fmaxf(mx[i], __shfl_xor_sync(0xffffffffu, mx[i], 1));
#pragma unroll
                for (int i = 0; i < 8; i++) mx[i] = fmaxf(mx[i], __shfl_xor_sync(0xffffffffu, mx[i], 2));
#pragma unroll
                for (int i = 0; i < 8; i++) {
                    e0[i] = ex2((e0[i] - mx[i]) * 1.4426950408889634f);
                    e1[i] = ex2((e1[i] - mx[i]) * 1.4426950408889634f);
                }
            }

            r.stage_kk<-1, false>(y0);
            uint32_t pr[8];
            {
                float sm[8];
#pragma unroll
                for (int i = 0; i < 8; i++) sm[i] = e0[i] + e1[i];
#pragma unroll
                for (int i = 0; i < 8; i++) sm[i] += __shfl_xor_sync(0xffffffffu, sm[i], 1);
#pragma unroll
                for (int i = 0; i < 8; i++) sm[i] += __shfl_xor_sync(0xffffffffu, sm[i], 2);
#pragma unroll
                for (int i = 0; i < 8; i++) {
                    const float inv = __frcp_rn(sm[i]);
                    pr[i] = pack2(e0[i] * inv, e1[i] * inv);
                }
            }
            lds4(sub + 2048, vp[2], vp[3], vp[4], vp[5]);
            lds4(sub + 2560, vp[6], vp[7], vp[8], vp[9]);
            lds4(sub + 3072, vp[10], vp[11], vp[12], vp[13]);
            __syncwarp();

            const uint32_t curmask = (c0ok ? 0x0000FFFFu : 0u) | (c1ok ? 0xFFFF0000u : 0u);
#pragma unroll
            for (int hp = 0; hp < 2; hp++) {
                r.stage_kk<-1, false>(y0);
                const int cb = 7 * hp;
                uint32_t ot[2][7];
#pragma unroll
                for (int b = 0; b < 2; b++) {
                    const uint32_t* vprev = b ? vl : vp;
                    const uint32_t* vcur = b ? vh : vl;
                    const uint32_t pe = pr[4 * hp + b], po = pr[4 * hp + 2 + b];
                    float o0[4] = {0.f, 0.f, 0.f, 0.f}, o1[4] = {0.f, 0.f, 0.f, 0.f};
                    float o2[4] = {0.f, 0.f, 0.f, 0.f}, o3[4] = {0.f, 0.f, 0.f, 0.f};
                    mma16816(o0, vprev[cb], vprev[cb + 1], vcur[cb], vcur[cb + 1], pe & ~curmask, pe & curmask);
                    mma16816(o1, vprev[cb + 2], vprev[cb + 3], vcur[cb + 2], vcur[cb + 3], pe & ~curmask, pe & curmask);
                    mma16816(o2, vprev[cb + 3], vprev[cb + 4], vcur[cb + 3], vcur[cb + 4], po & ~curmask, po & curmask);
                    mma16816(o3, vprev[cb + 5], vprev[cb + 6], vcur[cb + 5], vcur[cb + 6], po & ~curmask, po & curmask);
                    ot[b][0] = pack2(o0[0], o0[1]);
                    ot[b][1] = pack2(o0[2], o0[3]);
                    ot[b][2] = pack2(o1[0], o1[1]);
                    ot[b][3] = g < 4 ? pack2(o1[2], o1[3]) : pack2(o2[0], o2[1]);
                    ot[b][4] = pack2(o2[2], o2[3]);
                    ot[b][5] = pack2(o3[0], o3[1]);
                    ot[b][6] = pack2(o3[2], o3[3]);
                }
#pragma unroll
                for (int c = 0; c < 6; c += 2)
                    stsm4<true>(row_addr + (cb + c) * 16, ot[0][c], ot[1][c], ot[0][c + 1], ot[1][c + 1]);
                stsm2t(row_addr + (cb + 6) * 16, ot[0][6], ot[1][6]);
            }
            fence_async_smem();
            nb_arrive(NB_READY + wg, 160);

#pragma unroll 1
            for (int i = 6; i < 32; i++) r.stage_kk<-1, false>(y0);

            nb_sync(NB_FREE + wg, 160);
            asm volatile("wgmma.wait_group.sync.aligned 0;" ::: "memory");
            acc_fence(y0);
            store_rows<false>(y0, row_addr);
            fence_async_smem();
            __syncwarp();
            if (lane == 0) {
                tma_red2(&maps.m[M_OUTB], 448 + ns * 112, mt * 128 + warp * 16, wslot);
                bulk_commit();
                bulk_wait_read();
            }
        }
    }
}

typedef CUresult (*EncodeFn)(CUtensorMap*, CUtensorMapDataType, cuuint32_t, void*, const cuuint64_t*, const cuuint64_t*,
                             const cuuint32_t*, const cuuint32_t*, CUtensorMapInterleave, CUtensorMapSwizzle,
                             CUtensorMapL2promotion, CUtensorMapFloatOOBfill);

void encode(EncodeFn fn, CUtensorMap* m, const void* ptr, int rank, uint64_t d0, uint64_t d1, uint64_t d2, uint64_t s1,
            uint64_t s2, uint32_t b0, uint32_t b1, uint32_t b2, CUtensorMapSwizzle sw) {
    const cuuint64_t dims[3] = {d0, d1, d2};
    const cuuint64_t strides[2] = {s1, s2};
    const cuuint32_t box[3] = {b0, b1, b2};
    const cuuint32_t es[3] = {1, 1, 1};
    fn(m, CU_TENSOR_MAP_DATA_TYPE_BFLOAT16, rank, const_cast<void*>(ptr), dims, strides, box, es,
       CU_TENSOR_MAP_INTERLEAVE_NONE, sw, CU_TENSOR_MAP_L2_PROMOTION_L2_128B, CU_TENSOR_MAP_FLOAT_OOB_FILL_NONE);
}

}

extern "C" void kernel_launch(void* const* d_in, const int* in_sizes, int n_in, void* d_out, int out_size) {
    (void)in_sizes; (void)n_in; (void)out_size;
    void* fnp = nullptr;
    cudaDriverEntryPointQueryResult st;
    cudaGetDriverEntryPoint("cuTensorMapEncodeTiled", &fnp, cudaEnableDefault, &st);
    EncodeFn fn = (EncodeFn)fnp;
    void* o_ptr = nullptr;
    cudaGetSymbolAddress(&o_ptr, g_o);
    cudaFuncSetAttribute(fused_kernel, cudaFuncAttributeMaxDynamicSharedMemorySize, SMEM_BYTES);

    const CUtensorMapSwizzle S128 = CU_TENSOR_MAP_SWIZZLE_128B, S64 = CU_TENSOR_MAP_SWIZZLE_64B, S0 = CU_TENSOR_MAP_SWIZZLE_NONE;
    Maps maps;
    encode(fn, &maps.m[M_XA32], d_in[0], 2, 896, 1024, 1, 1792, 0, 32, 128, 1, S64);
    encode(fn, &maps.m[M_XA64], d_in[0], 2, 896, 1024, 1, 1792, 0, 64, 128, 1, S128);
    encode(fn, &maps.m[M_WKV], d_in[1], 3, 448, 448, 3, 2688, 896, 64, 32, 2, S128);
    encode(fn, &maps.m[M_WQ], d_in[1], 2, 448, 448, 1, 2688, 0, 64, 64, 1, S128);
    encode(fn, &maps.m[M_WO], d_in[2], 2, 448, 448, 1, 896, 0, 64, 64, 1, S128);
    encode(fn, &maps.m[M_XB], d_in[3], 3, 448, 1024, 2, 896, 896 * 1024, 64, 64, 2, S128);
    encode(fn, &maps.m[M_CR], d_in[4], 2, 2048, 2048, 1, 4096, 0, 64, 128, 1, S128);
    encode(fn, &maps.m[M_CI], d_in[5], 2, 2048, 2048, 1, 4096, 0, 64, 128, 1, S128);
    encode(fn, &maps.m[M_WR], d_in[6], 2, 448, 448, 1, 896, 0, 64, 112, 1, S128);
    encode(fn, &maps.m[M_WI], d_in[7], 2, 448, 448, 1, 896, 0, 64, 112, 1, S128);
    encode(fn, &maps.m[M_OST], o_ptr, 2, 448, 2048, 1, 896, 0, 112, 64, 1, S0);
    encode(fn, &maps.m[M_OLD], o_ptr, 2, 448, 2048, 1, 896, 0, 64, 128, 1, S128);
    encode(fn, &maps.m[M_OUTA], d_out, 2, 1792, 1024, 1, 3584, 0, 112, 16, 1, S0);
    encode(fn, &maps.m[M_OUTB], d_out, 2, 896, 2048, 1, 1792, 0, 112, 16, 1, S0);

    fused_kernel<<<128, 384, SMEM_BYTES>>>(maps);
}
```

```cpp
#include <cuda.h>
#include <cuda_bf16.h>
#include <cuda_runtime.h>
#include <stdint.h>

namespace {

constexpr int NSLOT = 6;
constexpr uint32_t SLOT = 32768;
constexpr uint32_t BOFF = 16384;
constexpr uint32_t STG = NSLOT * SLOT;
constexpr uint32_t WSLOT = 3584;
constexpr uint32_t BLOB = 14336;
constexpr uint32_t BARS = STG + 9 * WSLOT;
constexpr uint32_t BAR_FULL = BARS;
constexpr uint32_t BAR_EMPTY = BARS + 64;
constexpr uint32_t BAR_HALO = BARS + 128;
constexpr uint32_t BAR_BST = BARS + 136;
constexpr uint32_t SMEM_BYTES = BARS + 256 + 1024;
constexpr int NSTAGE = 53;
constexpr int SPIN_LIMIT = 1 << 16;

#define PF_DIST 8
#define AHI_DELAY 300
#define PACE_B 300
#define PACE_Z 200
#define PACE_O 300
#define ATT_DELAY 1

enum { M_XA32, M_XA64, M_WKV, M_WQ, M_WO, M_XB, M_WR, M_WI, M_CR, M_CI, M_OST, M_OLD, M_OUTA, M_OUTB, M_COUNT };
struct __align__(64) Maps {
    CUtensorMap m[M_COUNT];
    const uint8_t *xa, *wqkv, *wo, *wi;
};

enum { NB_READY = 1, NB_FREE = 3, NB_HALO = 5, NB_SKEW = 6 };

constexpr int CNT_A = 0;
constexpr int CNT_B = 8;
constexpr int CNT_O = 16;
constexpr int CNT_H = 32;
constexpr int CNT_COUNT = 96;

__device__ __align__(1024) uint8_t g_ab[2 * 32 * 4 * BLOB];
__device__ __align__(1024) __nv_bfloat16 g_o[2048 * 448];
__device__ __align__(1024) uint8_t g_halo[64 * WSLOT];
__device__ __align__(128) unsigned g_cnt[CNT_COUNT * 32];
__device__ __align__(128) unsigned g_epoch[128 * 4 * 8];

#define PROF(idx)

__device__ __forceinline__ void mbar_init(uint32_t bar, uint32_t cnt) {
    asm volatile("mbarrier.init.shared::cta.b64 [%0], %1;" ::"r"(bar), "r"(cnt) : "memory");
}
__device__ __forceinline__ void mbar_expect(uint32_t bar, uint32_t bytes) {
    asm volatile("mbarrier.arrive.expect_tx.shared::cta.b64 _, [%0], %1;" ::"r"(bar), "r"(bytes) : "memory");
}
__device__ __forceinline__ void mbar_arrive(uint32_t bar) {
    asm volatile("mbarrier.arrive.shared::cta.b64 _, [%0];" ::"r"(bar) : "memory");
}
__device__ __forceinline__ bool mbar_try(uint32_t bar, uint32_t parity) {
    uint32_t ok;
    asm volatile("{\n.reg .pred p;\nmbarrier.try_wait.parity.shared::cta.b64 p, [%1], %2;\nselp.u32 %0, 1, 0, p;\n}\n"
                 : "=r"(ok) : "r"(bar), "r"(parity) : "memory");
    return ok;
}
__device__ __forceinline__ void mbar_wait(uint32_t bar, uint32_t parity) {
#pragma unroll 1
    for (int n = 0; n < SPIN_LIMIT; n++)
        if (mbar_try(bar, parity)) break;
}
__device__ __forceinline__ void nb_sync(int id, int n) { asm volatile("bar.sync %0, %1;" ::"r"(id), "r"(n) : "memory"); }
__device__ __forceinline__ void nb_arrive(int id, int n) { asm volatile("bar.arrive %0, %1;" ::"r"(id), "r"(n) : "memory"); }

__device__ __forceinline__ void tma_ld2(uint32_t dst, const CUtensorMap* m, int c0, int c1, uint32_t bar) {
    asm volatile("cp.async.bulk.tensor.2d.shared::cluster.global.mbarrier::complete_tx::bytes [%0], [%1, {%3, %4}], [%2];"
                 ::"r"(dst), "l"(m), "r"(bar), "r"(c0), "r"(c1) : "memory");
}
__device__ __forceinline__ void tma_ld3(uint32_t dst, const CUtensorMap* m, int c0, int c1, int c2, uint32_t bar) {
    asm volatile("cp.async.bulk.tensor.3d.shared::cluster.global.mbarrier::complete_tx::bytes [%0], [%1, {%3, %4, %5}], [%2];"
                 ::"r"(dst), "l"(m), "r"(bar), "r"(c0), "r"(c1), "r"(c2) : "memory");
}
__device__ __forceinline__ void bulk_ld(uint32_t dst, const void* src, uint32_t bytes, uint32_t bar) {
    asm volatile("cp.async.bulk.shared::cluster.global.mbarrier::complete_tx::bytes [%0], [%1], %2, [%3];"
                 ::"r"(dst), "l"(src), "r"(bytes), "r"(bar) : "memory");
}
__device__ __forceinline__ void bulk_st(void* dst, uint32_t src, uint32_t bytes) {
    asm volatile("cp.async.bulk.global.shared::cta.bulk_group [%0], [%1], %2;" ::"l"(dst), "r"(src), "r"(bytes) : "memory");
}
__device__ __forceinline__ void tma_st2(const CUtensorMap* m, int c0, int c1, uint32_t src) {
    asm volatile("cp.async.bulk.tensor.2d.global.shared::cta.bulk_group [%0, {%1, %2}], [%3];"
                 ::"l"(m), "r"(c0), "r"(c1), "r"(src) : "memory");
}
__device__ __forceinline__ void tma_red2(const CUtensorMap* m, int c0, int c1, uint32_t src) {
    asm volatile("cp.reduce.async.bulk.tensor.2d.global.shared::cta.add.bulk_group [%0, {%1, %2}], [%3];"
                 ::"l"(m), "r"(c0), "r"(c1), "r"(src) : "memory");
}
__device__ __forceinline__ void bulk_commit() { asm volatile("cp.async.bulk.commit_group;" ::: "memory"); }
__device__ __forceinline__ void bulk_wait_all() { asm volatile("cp.async.bulk.wait_group 0;" ::: "memory"); }
__device__ __forceinline__ void bulk_wait_read() { asm volatile("cp.async.bulk.wait_group.read 0;" ::: "memory"); }
__device__ __forceinline__ void fence_async_smem() { asm volatile("fence.proxy.async.shared::cta;" ::: "memory"); }
__device__ __forceinline__ void fence_async_global() { asm volatile("fence.proxy.async.global;" ::: "memory"); }

__device__ __forceinline__ void tma_pf2(const CUtensorMap* m, int c0, int c1) {
    asm volatile("cp.async.bulk.prefetch.tensor.2d.L2.global [%0, {%1, %2}];" ::"l"(m), "r"(c0), "r"(c1) : "memory");
}
__device__ __forceinline__ void bulk_pf(const void* src, uint32_t bytes) {
    asm volatile("cp.async.bulk.prefetch.L2.global [%0], %1;" ::"l"(src), "r"(bytes) : "memory");
}

__device__ __forceinline__ void signal(int idx) {
    fence_async_global();
    asm volatile("red.release.gpu.global.add.u32 [%0], 1;" ::"l"(&g_cnt[idx * 32]) : "memory");
}
__device__ __forceinline__ unsigned peek(int idx) {
    unsigned v;
    asm volatile("ld.relaxed.gpu.global.u32 %0, [%1];" : "=r"(v) : "l"(&g_cnt[idx * 32]) : "memory");
    return v;
}
__device__ __forceinline__ void await(int idx, unsigned target, unsigned v) {
#pragma unroll 1
    for (int n = 0; n < SPIN_LIMIT && (int)(v - target) < 0; n++) v = peek(idx);
    asm volatile("fence.acquire.gpu;" ::: "memory");
    fence_async_global();
}

#define WG_REGS                                                                                                     \
    "{%0,%1,%2,%3,%4,%5,%6,%7,%8,%9,%10,%11,%12,%13,%14,%15,%16,%17,%18,%19,%20,%21,%22,%23,%24,%25,%26,%27,"       \
    "%28,%29,%30,%31,%32,%33,%34,%35,%36,%37,%38,%39,%40,%41,%42,%43,%44,%45,%46,%47,%48,%49,%50,%51,%52,%53,%54,%55}"
#define WG_OPS(C)                                                                                                   \
    C(d[0]), C(d[1]), C(d[2]), C(d[3]), C(d[4]), C(d[5]), C(d[6]), C(d[7]), C(d[8]), C(d[9]), C(d[10]), C(d[11]),   \
    C(d[12]), C(d[13]), C(d[14]), C(d[15]), C(d[16]), C(d[17]), C(d[18]), C(d[19]), C(d[20]), C(d[21]), C(d[22]),   \
    C(d[23]), C(d[24]), C(d[25]), C(d[26]), C(d[27]), C(d[28]), C(d[29]), C(d[30]), C(d[31]), C(d[32]), C(d[33]),   \
    C(d[34]), C(d[35]), C(d[36]), C(d[37]), C(d[38]), C(d[39]), C(d[40]), C(d[41]), C(d[42]), C(d[43]), C(d[44]),   \
    C(d[45]), C(d[46]), C(d[47]), C(d[48]), C(d[49]), C(d[50]), C(d[51]), C(d[52]), C(d[53]), C(d[54]), C(d[55])

template <int TB, int SB, bool INIT>
__device__ __forceinline__ void wgmma112(float (&d)[56], uint64_t da, uint64_t db) {
    if (INIT) {
        asm volatile("{\n.reg .pred p;\nsetp.ne.b32 p, 0, 0;\n"
                     "wgmma.mma_async.sync.aligned.m64n112k16.f32.bf16.bf16 " WG_REGS ", %56, %57, p, 1, %59, 0, %58;\n}\n"
                     : WG_OPS("=f") : "l"(da), "l"(db), "n"(TB), "n"(SB));
    } else {
        asm volatile("{\n.reg .pred p;\nsetp.ne.b32 p, 1, 0;\n"
                     "wgmma.mma_async.sync.aligned.m64n112k16.f32.bf16.bf16 " WG_REGS ", %56, %57, p, 1, %59, 0, %58;\n}\n"
                     : WG_OPS("+f") : "l"(da), "l"(db), "n"(TB), "n"(SB));
    }
}
__device__ __forceinline__ void acc_fence(float (&d)[56]) {
#pragma unroll
    for (int i = 0; i < 56; i++) asm volatile("" : "+f"(d[i])::"memory");
}
__device__ __forceinline__ uint64_t mkdesc(uint32_t addr, uint32_t lbo16, uint32_t sbo16, uint32_t mode) {
    return (uint64_t)(((addr & 0x3FFFF) >> 4) | (lbo16 << 16)) | ((uint64_t)(sbo16 | (mode << 30)) << 32);
}

__device__ __forceinline__ uint32_t pack2(float lo, float hi) {
    uint32_t r;
    asm("cvt.rn.bf16x2.f32 %0, %1, %2;" : "=r"(r) : "f"(hi), "f"(lo));
    return r;
}
__device__ __forceinline__ uint32_t movm(uint32_t a) {
    uint32_t r;
    asm volatile("movmatrix.sync.aligned.m8n8.trans.b16 %0, %1;" : "=r"(r) : "r"(a));
    return r;
}
template <bool TRANS>
__device__ __forceinline__ void stsm4(uint32_t addr, uint32_t a, uint32_t b, uint32_t c, uint32_t d) {
    if (TRANS) asm volatile("stmatrix.sync.aligned.m8n8.x4.trans.shared.b16 [%0], {%1,%2,%3,%4};" ::"r"(addr), "r"(a), "r"(b), "r"(c), "r"(d) : "memory");
    else asm volatile("stmatrix.sync.aligned.m8n8.x4.shared.b16 [%0], {%1,%2,%3,%4};" ::"r"(addr), "r"(a), "r"(b), "r"(c), "r"(d) : "memory");
}
__device__ __forceinline__ void sts4(uint32_t addr, uint32_t a, uint32_t b, uint32_t c, uint32_t d) {
    asm volatile("st.shared.v4.b32 [%0], {%1,%2,%3,%4};" ::"r"(addr), "r"(a), "r"(b), "r"(c), "r"(d) : "memory");
}
__device__ __forceinline__ void lds4(uint32_t addr, uint32_t& a, uint32_t& b, uint32_t& c, uint32_t& d) {
    asm volatile("ld.shared.v4.b32 {%0,%1,%2,%3}, [%4];" : "=r"(a), "=r"(b), "=r"(c), "=r"(d) : "r"(addr) : "memory");
}
__device__ __forceinline__ void mma16816(float (&d)[4], uint32_t a0, uint32_t a1, uint32_t a2, uint32_t a3, uint32_t b0, uint32_t b1) {
    asm volatile("mma.sync.aligned.m16n8k16.row.col.f32.bf16.bf16.f32 {%0,%1,%2,%3}, {%4,%5,%6,%7}, {%8,%9}, {%0,%1,%2,%3};"
                 : "+f"(d[0]), "+f"(d[1]), "+f"(d[2]), "+f"(d[3]) : "r"(a0), "r"(a1), "r"(a2), "r"(a3), "r"(b0), "r"(b1));
}
__device__ __forceinline__ float bf_lo(uint32_t v) { return __uint_as_float(v << 16); }
__device__ __forceinline__ float bf_hi(uint32_t v) { return __uint_as_float(v & 0xFFFF0000u); }
__device__ __forceinline__ float rcp(float x) { float r; asm("rcp.approx.ftz.f32 %0, %1;" : "=f"(r) : "f"(x)); return r; }
__device__ __forceinline__ float ex2(float x) { float r; asm("ex2.approx.ftz.f32 %0, %1;" : "=f"(r) : "f"(x)); return r; }

__host__ __device__ constexpr int hw_tile(int c) { return (c + 8) % 14; }

__device__ __forceinline__ int big_block(int roleL, int i, int mt) {
    int n, off;
    if (!roleL) {
        if (i < 14 || i >= 46) return -1;
        if (i < 18) return (i - 14) * 16 + mt;
        if (i < 33) { n = i - 18; off = 0; } else { n = i - 33; off = 32; }
    } else {
        if (i < 21 || i >= 53) return -1;
        if (i < 36) { n = i - 21; off = 16; } else if (i < 51) { n = i - 36; off = 48; } else { n = i - 38; off = 32; }
    }
    return off + (n == mt ? 15 : n);
}

struct Ring {
    uint32_t base;
    uint32_t wg;
    uint32_t slot;
    uint32_t phase;
    uint32_t prev;
    uint32_t pphase;
    bool leader;
    __device__ __forceinline__ uint32_t begin() {
        mbar_wait(base + BAR_FULL + slot * 8, phase);
        asm volatile("wgmma.fence.sync.aligned;" ::: "memory");
        return base + slot * SLOT;
    }
    template <bool RELEASE>
    __device__ __forceinline__ void end() {
        asm volatile("wgmma.commit_group.sync.aligned;" ::: "memory");
        asm volatile("wgmma.wait_group.sync.aligned 1;" ::: "memory");
        if (RELEASE && leader) mbar_arrive(base + BAR_EMPTY + prev * 8);
        prev = slot;
        pphase = phase;
        if (++slot == NSLOT) { slot = 0; phase ^= 1; }
    }
    __device__ __forceinline__ void pin() { mbar_wait(base + BAR_FULL + prev * 8, pphase); }
    template <int SB, bool INIT, bool RELEASE = true>
    __device__ __forceinline__ void stage_kk(float (&d)[56], int stg = -1) {
        const uint32_t s = begin();
        const uint32_t sb = stg >= 0 ? base + STG + stg * BLOB : s + BOFF;
        const uint64_t da = mkdesc(s + wg * 8192, 1, 64, 1), db = mkdesc(sb, 1, 64, 1);
        wgmma112<0, SB, INIT>(d, da, db);
        wgmma112<0, SB, false>(d, da + 2, db + 2);
        wgmma112<0, SB, false>(d, da + 4, db + 4);
        wgmma112<0, SB, false>(d, da + 6, db + 6);
        end<RELEASE>();
    }
    template <bool INIT>
    __device__ __forceinline__ void stage_kn(float (&d)[56]) {
        const uint32_t s = begin();
        const uint64_t da = mkdesc(s + wg * 8192, 1, 64, 1), db = mkdesc(s + BOFF, 512, 64, 1);
        wgmma112<1, 1, INIT>(d, da, db);
        wgmma112<1, 1, false>(d, da + 2, db + 128);
        wgmma112<1, 1, false>(d, da + 4, db + 256);
        wgmma112<1, 1, false>(d, da + 6, db + 384);
        end<true>();
    }
    template <bool INIT>
    __device__ __forceinline__ void stage_kv(float (&dk)[56], float (&dv)[56]) {
        const uint32_t s = begin();
        const uint64_t da = mkdesc(s + wg * 4096, 1, 32, 2), db = mkdesc(s + BOFF, 512, 64, 1);
        wgmma112<1, 1, INIT>(dk, da, db);
        wgmma112<1, 1, INIT>(dv, da, db + 256);
        wgmma112<1, 1, false>(dk, da + 2, db + 128);
        wgmma112<1, 1, false>(dv, da + 2, db + 384);
        end<!INIT>();
    }
};

template <bool PERM>
__device__ __forceinline__ void store_rows(const float (&d)[56], uint32_t lane_addr) {
#pragma unroll
    for (int c = 0; c < 14; c += 2) {
        const int j = PERM ? hw_tile(c) : c;
        stsm4<false>(lane_addr + c * 16, pack2(d[4 * j], d[4 * j + 1]), pack2(d[4 * j + 2], d[4 * j + 3]),
                     pack2(d[4 * j + 4], d[4 * j + 5]), pack2(d[4 * j + 6], d[4 * j + 7]));
    }
}
__device__ __forceinline__ void store_blob(const float (&d)[56], uint32_t lane_addr) {
#pragma unroll
    for (int j = 0; j < 14; j += 2)
        stsm4<true>(lane_addr + j * 1024, pack2(d[4 * j], d[4 * j + 1]), pack2(d[4 * j + 2], d[4 * j + 3]),
                    pack2(d[4 * j + 4], d[4 * j + 5]), pack2(d[4 * j + 6], d[4 * j + 7]));
}

__global__ void __launch_bounds__(384, 1) fused_kernel(const __grid_constant__ Maps maps) {
    extern __shared__ uint8_t smem_raw[];
    const uint32_t base = ((uint32_t)__cvta_generic_to_shared(smem_raw) + 1023u) & ~1023u;
    const int warp = __shfl_sync(0xffffffffu, threadIdx.x >> 5, 0);
    const int lane = threadIdx.x & 31;
    const int bid = blockIdx.x;
    const int roleL = (bid >> 3) & 1;
    const int mt = ((bid >> 4) << 1) | ((bid >> 2) & 1);
    const int ns = bid & 3;
    const int par = mt >> 3, blk = mt & 7;

    if (threadIdx.x == 256) {
        PROF(128);
#pragma unroll
        for (int i = 0; i < NSLOT; i++) {
            mbar_init(base + BAR_FULL + i * 8, 2);
            mbar_init(base + BAR_EMPTY + i * 8, 8);
        }
        mbar_init(base + BAR_HALO, 9);
        mbar_init(base + BAR_BST, 2);
        asm volatile("fence.mbarrier_init.release.cluster;" ::: "memory");
    }
    __syncthreads();

    if (warp >= 8) {
        asm volatile("setmaxnreg.dec.sync.aligned.u32 72;");
        unsigned* epoch_ptr = &g_epoch[(bid * 4 + (warp - 8)) * 8];
        if (warp == 8) {
            if (lane == 0) {
                PROF(129);
                unsigned ep = 0, seen = 0;
                uint32_t slot = 0, phase = 1;
#pragma unroll 1
                for (int i = 0; i < NSTAGE; i++) {
                    if (i == 45 && !roleL) ep = *epoch_ptr;
                    if (i == 46 && !roleL) seen = peek(CNT_O + mt);
                    if (i >= NSLOT) mbar_wait(base + BAR_EMPTY + slot * 8, phase);
                    const uint32_t dst = base + slot * SLOT, bar = base + BAR_FULL + slot * 8;
                    const int kb = big_block(roleL, i, mt);
                    if (kb >= 0) {
                        mbar_expect(bar, 16384);
                        tma_ld2(dst, &maps.m[M_CR + (kb >> 5)], (kb & 31) * 64, mt * 128, bar);
                    } else if (!roleL) {
                        if (i == 46) {
                            await(CNT_O + mt, (ep + 1) * 8, seen);
                            *epoch_ptr = ep + 1;
                            PROF(146);
                        }
                        mbar_expect(bar, 16384);
                        if (i < 14) tma_ld3(dst, &maps.m[M_XB], (i < 7 ? i : i - 7) * 64, mt * 64, 0, bar);
                        else tma_ld2(dst, &maps.m[M_OLD], (i - 46) * 64, mt * 128, bar);
                    } else {
                        mbar_expect(bar, i < 14 ? 8192 : 16384);
                        if (i < 14) tma_ld2(dst, &maps.m[M_XA32], par * 448 + i * 32, blk * 128, bar);
                        else tma_ld2(dst, &maps.m[M_XA64], par * 448 + (i - 14) * 64, blk * 128, bar);
                    }
                    if (i >= NSLOT) {
                        const int pi = i + PF_DIST;
                        const int pk = big_block(roleL, pi, mt);
                        if (pk >= 0 && (pi & 3) == ns) tma_pf2(&maps.m[M_CR + (pk >> 5)], (pk & 31) * 64, mt * 128);
                    }
                    if (++slot == NSLOT) { slot = 0; phase ^= 1; }
                }
            }
        } else if (warp == 11) {
            if (lane == 0) {
                unsigned ep = 0;
                uint32_t slot = 0, phase = 1;
#pragma unroll 1
                for (int i = 0; i < NSTAGE; i++) {
                    if (i == NSLOT) {
                        ep = *epoch_ptr;
                        bulk_pf(maps.xa + bid * 14336, 14336);
                        bulk_pf(maps.wqkv + bid * 9408, 9408);
                        bulk_pf(maps.wi + bid * 3136, 3136);
                        bulk_pf(maps.wo + bid * 3136, 3136);
                    }
                    const int kb = big_block(roleL, i, mt);
                    if (roleL || i < 14 || i >= 18) {
                        const bool dep = roleL ? (i == 21 || i == 36 || i == 51) : (i == 18 || i == 33);
                        const int cnt = CNT_A + (kb >> 5) * 8 + ns * 2 + ((kb >> 4) & 1);
                        unsigned seen = 0;
                        if (dep) seen = peek(cnt);
                        if (i >= NSLOT) mbar_wait(base + BAR_EMPTY + slot * 8, phase);
                        uint32_t dst = base + slot * SLOT + BOFF;
                        const uint32_t bar = base + BAR_FULL + slot * 8;
                        if (kb >= 0) {
                            if (dep) {
                                await(cnt, (ep + 1) * 16, seen);
                                PROF(i + 140);
                            }
                            if (!roleL) {
                                if ((i >> 1) == 11) dst = base + STG + (i & 1) * BLOB;
                                if (i == 28) mbar_wait(base + BAR_BST, 0);
                            }
                            mbar_expect(bar, BLOB);
                            bulk_ld(dst, g_ab + (size_t)(kb * 4 + ns) * BLOB, BLOB, bar);
                        } else if (!roleL) {
                            if (i < 14) {
                                mbar_expect(bar, BLOB);
                                tma_ld2(dst, &maps.m[i < 7 ? M_WR : M_WI], (i < 7 ? i : i - 7) * 64, ns * 112, bar);
                            } else {
                                mbar_expect(bar, 16384);
                                tma_ld2(dst, &maps.m[M_WO], ns * 112 + 48, (i - 46) * 64, bar);
                                tma_ld2(dst + 8192, &maps.m[M_WO], ns * 112, (i - 46) * 64, bar);
                            }
                        } else {
                            mbar_expect(bar, 16384);
                            if (i < 14) {
                                tma_ld3(dst, &maps.m[M_WKV], ns * 112 + 48, i * 32, 1, bar);
                                tma_ld3(dst + 8192, &maps.m[M_WKV], ns * 112, i * 32, 1, bar);
                            } else {
                                tma_ld2(dst, &maps.m[M_WQ], ns * 112 + 48, (i - 14) * 64, bar);
                                tma_ld2(dst + 8192, &maps.m[M_WQ], ns * 112, (i - 14) * 64, bar);
                            }
                        }
                    }
                    if (++slot == NSLOT) { slot = 0; phase ^= 1; }
                }
                *epoch_ptr = ep + 1;
            }
        } else {
            const int h = warp - 9;
            const uint32_t stg = base + STG + h * BLOB;
            if (!roleL) {
                nb_sync(NB_READY + h, 160);
                if (lane == 0) {
                    PROF(130 + h);
                    fence_async_smem();
                    if (h) __nanosleep(AHI_DELAY);
                    bulk_st(g_ab + (size_t)((h * 16 + mt) * 4 + ns) * BLOB, stg, BLOB);
                    bulk_commit();
                    bulk_wait_all();
                    PROF(132 + h);
                    mbar_wait(base + BAR_FULL + (2 + h) * 8, 1);
                    mbar_arrive(base + BAR_FULL + (2 + h) * 8);
                    signal(CNT_A + ns * 2 + h);
                    PROF(134 + h);
                }
                __syncwarp();
                nb_sync(NB_READY + h, 160);
                if (lane == 0) {
                    fence_async_smem();
                    mbar_arrive(base + BAR_FULL + (4 + h) * 8);
                    PROF(136 + h);
#pragma unroll 1
                    for (int p = 0; p < 4; p++) {
                        __nanosleep(PACE_B);
                        bulk_st(g_ab + (size_t)((32 + h * 16 + mt) * 4 + ns) * BLOB + p * WSLOT,
                                base + (4 + h) * SLOT + BOFF + p * WSLOT, WSLOT);
                    }
                    bulk_commit();
                    bulk_wait_all();
                    mbar_arrive(base + BAR_BST);
                    signal(CNT_B + ns * 2 + h);
                    PROF(138 + h);
                }
                __syncwarp();
                nb_sync(NB_READY + h, 160);
                if (lane == 0) {
                    fence_async_smem();
                    mbar_wait(base + BAR_EMPTY + 4 * 8, 1);
                    PROF(140 + h);
#pragma unroll 1
                    for (int p = 0; p < 4; p++)
                        tma_red2(&maps.m[M_OUTB], 448 + ns * 112, mt * 128 + h * 64 + p * 16, stg + p * WSLOT);
                    bulk_commit();
                    bulk_wait_read();
                    PROF(142 + h);
                }
                __syncwarp();
                nb_arrive(NB_FREE + h, 160);
            } else {
                if (h == 0) {
#pragma unroll
                    for (int i = 0; i < 7; i++) sts4(stg + i * 512 + lane * 16, 0, 0, 0, 0);
                    fence_async_smem();
                    __syncwarp();
                    if (lane == 0) {
                        const unsigned ep = *epoch_ptr + 1;
                        mbar_wait(base + BAR_FULL + 5 * 8, 0);
#pragma unroll 1
                        for (int i = 0; i < 8; i++) {
                            tma_st2(&maps.m[M_OUTB], 448 + ns * 112, mt * 128 + i * 16, stg);
                            __nanosleep(PACE_Z);
                        }
                        bulk_commit();
                        bulk_wait_all();
                        fence_async_global();
                        asm volatile("fence.release.gpu;" ::: "memory");
                        PROF(130);
                        if (blk > 0) {
                            const int cnt = CNT_H + (mt - 1) * 4 + ns;
                            await(cnt, ep, peek(cnt));
                            mbar_expect(base + BAR_HALO, WSLOT);
                            bulk_ld(stg, g_halo + (size_t)((mt - 1) * 4 + ns) * WSLOT, WSLOT, base + BAR_HALO);
                        } else {
                            mbar_arrive(base + BAR_HALO);
                        }
                        *epoch_ptr = ep;
                        PROF(131);
                    }
                    __syncwarp();
                } else {
                    nb_sync(NB_HALO, 64);
                    if (lane == 0 && blk < 7) {
                        fence_async_smem();
                        bulk_st(g_halo + (size_t)(mt * 4 + ns) * WSLOT, base + STG + 8 * WSLOT, WSLOT);
                        bulk_commit();
                        bulk_wait_all();
                        signal(CNT_H + mt * 4 + ns);
                    }
                    __syncwarp();
                }
                nb_sync(NB_READY + h, 160);
                if (lane == 0) {
                    PROF(132 + h);
                    fence_async_smem();
#pragma unroll 1
                    for (int p = 0; p < 4; p++) {
                        if (p) __nanosleep(PACE_O);
                        tma_st2(&maps.m[M_OST], ns * 112, mt * 128 + h * 64 + p * 16, stg + p * WSLOT);
                    }
                    bulk_commit();
                    bulk_wait_all();
                    PROF(134 + h);
                }
                __syncwarp();
                nb_arrive(NB_FREE + h, 160);
                if (lane == 0) {
                    signal(CNT_O + mt);
                    PROF(136 + h);
                }
            }
        }
    } else {
        asm volatile("setmaxnreg.inc.sync.aligned.u32 216;");
        Ring r;
        r.base = base;
        r.wg = warp >> 2;
        r.slot = 0;
        r.phase = 0;
        r.prev = 0;
        r.pphase = 0;
        r.leader = lane == 0;
        const int wg = warp >> 2;
        const uint32_t wslot = base + STG + warp * WSLOT;
        const uint32_t row_addr = wslot + (lane & 15) * 224 + (lane >> 4) * 16;

        if (!roleL) {
            const uint32_t blob_off = ((lane >> 4) * 8 + (lane & 7)) * 128 +
                                      (((2 * (warp & 3) + ((lane >> 3) & 1)) ^ (lane & 7)) << 4);
            float x0[56], x1[56];
            r.stage_kk<1, true, false>(x0);
#pragma unroll 1
            for (int i = 1; i < 7; i++) r.stage_kk<1, false>(x0);

            r.stage_kk<-1, true>(x1);
            acc_fence(x0);
            store_blob(x0, base + STG + wg * BLOB + blob_off);
            nb_arrive(NB_READY + wg, 160);
#pragma unroll 1
            for (int i = 1; i < 7; i++) r.stage_kk<-1, false>(x1);

            r.stage_kk<1, true>(x0, 0);
            acc_fence(x1);
            mbar_wait(base + BAR_EMPTY + (4 + wg) * 8, 1);
            store_blob(x1, base + (4 + wg) * SLOT + BOFF + blob_off);
            nb_arrive(NB_READY + wg, 160);
#pragma unroll 1
            for (int i = 15; i < 46; i++) r.stage_kk<1, false>(x0, (i == 15 || (i >> 1) == 11) ? (i & 1) : -1);

            r.stage_kn<true>(x1);
            acc_fence(x0);
            store_rows<false>(x0, row_addr);
            nb_arrive(NB_READY + wg, 160);
#pragma unroll 1
            for (int i = 1; i < 7; i++) r.stage_kn<false>(x1);

            nb_sync(NB_FREE + wg, 160);
            asm volatile("wgmma.wait_group.sync.aligned 0;" ::: "memory");
            acc_fence(x1);
            store_rows<true>(x1, row_addr);
            fence_async_smem();
            __syncwarp();
            if (lane == 0) {
                tma_st2(&maps.m[M_OUTA], par * 896 + ns * 112, blk * 128 + warp * 16, wslot);
                bulk_commit();
                bulk_wait_read();
            }
        } else {
            const int g = lane >> 2, tig = lane & 3;
            float y0[56], y1[56], y2[56];
            r.stage_kv<true>(y0, y1);
#pragma unroll 1
            for (int i = 1; i < 14; i++) r.stage_kv<false>(y0, y1);

            uint32_t kl[14], kh[14], vl[14], vh[14];
            r.stage_kn<true>(y2);
            acc_fence(y0);
            acc_fence(y1);
#pragma unroll
            for (int c = 0; c < 14; c++) {
                const int j = hw_tile(c);
                kh[c] = pack2(y0[4 * j + 2], y0[4 * j + 3]);
                vh[c] = movm(pack2(y1[4 * j + 2], y1[4 * j + 3]));
            }
            {
                const uint32_t pub = wslot + WSLOT + lane * 16;
                sts4(pub, kh[0], kh[1], kh[2], kh[3]);
                sts4(pub + 512, kh[4], kh[5], kh[6], kh[7]);
                sts4(pub + 1024, kh[8], kh[9], kh[10], kh[11]);
                sts4(pub + 1536, kh[12], kh[13], vh[0], vh[1]);
                sts4(pub + 2048, vh[2], vh[3], vh[4], vh[5]);
                sts4(pub + 2560, vh[6], vh[7], vh[8], vh[9]);
                sts4(pub + 3072, vh[10], vh[11], vh[12], vh[13]);
                if (warp == 7) nb_arrive(NB_HALO, 64);
                __syncwarp();
                if (lane == 0) mbar_arrive(base + BAR_HALO);
            }
            r.stage_kn<false>(y2);
            r.pin();
#pragma unroll
            for (int c = 0; c < 14; c++) {
                const int j = hw_tile(c);
                kl[c] = pack2(y0[4 * j], y0[4 * j + 1]);
                vl[c] = movm(pack2(y1[4 * j], y1[4 * j + 1]));
            }
#pragma unroll 1
            for (int i = 2; i < 7; i++) r.stage_kn<false>(y2);

            r.stage_kk<1, true>(y0);
            acc_fence(y2);
            uint32_t ql[14], qh[14], kp[14], vp[14];
#pragma unroll
            for (int c = 0; c < 14; c++) {
                const int j = hw_tile(c);
                ql[c] = pack2(y2[4 * j], y2[4 * j + 1]);
                qh[c] = pack2(y2[4 * j + 2], y2[4 * j + 3]);
            }
#pragma unroll 1
            for (int i = 0; i < ATT_DELAY + wg; i++) r.stage_kk<1, false>(y0);

            mbar_wait(base + BAR_HALO, 0);
            const uint32_t sub = wslot + lane * 16;
            lds4(sub, kp[0], kp[1], kp[2], kp[3]);
            lds4(sub + 512, kp[4], kp[5], kp[6], kp[7]);
            lds4(sub + 1024, kp[8], kp[9], kp[10], kp[11]);
            lds4(sub + 1536, kp[12], kp[13], vp[0], vp[1]);
            float s[8][4];
#pragma unroll
            for (int step = 0; step < 2; step++) {
#pragma unroll
                for (int i = 0; i < 8; i++) {
                    const int b = 1 - (i >> 2), h = i & 3;
                    const int c0 = 7 * (h >> 1) + 3 * (h & 1) + 2 * step;
                    const uint32_t* q = b ? qh : ql;
                    const uint32_t* kprev = b ? kl : kp;
                    const uint32_t* kcur = b ? kh : kl;
                    uint32_t q0 = q[c0], q1 = q[c0 + 1];
                    if ((h & 1) && step == 0) q0 = tig >= 2 ? q0 : 0u;
                    if (!(h & 1) && step == 1) q1 = tig < 2 ? q1 : 0u;
                    float (&d)[4] = s[2 * h + b];
                    if (step == 0) d[0] = d[1] = d[2] = d[3] = 0.f;
                    mma16816(d, kprev[c0], kcur[c0], kprev[c0 + 1], kcur[c0 + 1], q0, q1);
                }
            }
            r.stage_kk<1, false>(y0);
            r.stage_kk<1, false>(y0);
            r.pin();

            const bool c0ok = 2 * tig <= g, c1ok = 2 * tig + 1 <= g;
            uint32_t pr[8];
            {
                const bool cur0 = g <= 2 * tig, cur1 = g <= 2 * tig + 1;
                const bool seq_start = blk == 0 && warp == 0;
                float e0[8], e1[8], mx[8];
#pragma unroll
                for (int i = 0; i < 8; i++) pr[i] = movm(pack2(cur0 ? s[i][2] : s[i][0], cur1 ? s[i][3] : s[i][1]));
                lds4(sub + 2048, vp[2], vp[3], vp[4], vp[5]);
                lds4(sub + 2560, vp[6], vp[7], vp[8], vp[9]);
                lds4(sub + 3072, vp[10], vp[11], vp[12], vp[13]);
#pragma unroll
                for (int i = 0; i < 8; i++) {
                    const uint32_t l = pack2(bf_lo(pr[i]) * 0.18898223650461362f, bf_hi(pr[i]) * 0.18898223650461362f);
                    e0[i] = bf_lo(l);
                    e1[i] = bf_hi(l);
                    if ((i & 1) == 0) {
                        if (seq_start && !c0ok) e0[i] = -1e9f;
                        if (seq_start && !c1ok) e1[i] = -1e9f;
                    }
                    mx[i] = fmaxf(e0[i], e1[i]);
                }
#pragma unroll
                for (int i = 0; i < 8; i++) mx[i] = fmaxf(mx[i], __shfl_xor_sync(0xffffffffu, mx[i], 1));
#pragma unroll
                for (int i = 0; i < 8; i++) mx[i] = fmaxf(mx[i], __shfl_xor_sync(0xffffffffu, mx[i], 2));
#pragma unroll
                for (int i = 0; i < 8; i++) {
                    e0[i] = ex2((e0[i] - mx[i]) * 1.4426950408889634f);
                    e1[i] = ex2((e1[i] - mx[i]) * 1.4426950408889634f);
                }
                r.stage_kk<1, false>(y0);
                r.stage_kk<1, false>(y0);
                r.pin();
#pragma unroll
                for (int i = 0; i < 8; i++) mx[i] = e0[i] + e1[i];
#pragma unroll
                for (int i = 0; i < 8; i++) mx[i] += __shfl_xor_sync(0xffffffffu, mx[i], 1);
#pragma unroll
                for (int i = 0; i < 8; i++) mx[i] += __shfl_xor_sync(0xffffffffu, mx[i], 2);
#pragma unroll
                for (int i = 0; i < 8; i++) {
                    const float inv = rcp(mx[i]);
                    pr[i] = pack2(e0[i] * inv, e1[i] * inv);
                }
            }

            const uint32_t curmask = (c0ok ? 0x0000FFFFu : 0u) | (c1ok ? 0xFFFF0000u : 0u);
            float o[16][4];
#pragma unroll
            for (int i = 0; i < 16; i++) {
                const int h = i >> 2, b = (i >> 1) & 1;
                const int c0 = 7 * (h >> 1) + 3 * (h & 1) + 2 * (i & 1);
                const uint32_t* vprev = b ? vl : vp;
                const uint32_t* vcur = b ? vh : vl;
                const uint32_t p = pr[2 * h + b];
                o[i][0] = o[i][1] = o[i][2] = o[i][3] = 0.f;
                mma16816(o[i], vprev[c0], vprev[c0 + 1], vcur[c0], vcur[c0 + 1], p & ~curmask, p & curmask);
            }
            r.stage_kk<1, false>(y0);
            r.stage_kk<1, false>(y0);
            r.pin();
            {
                uint32_t ot[2][14];
#pragma unroll
                for (int hp = 0; hp < 2; hp++) {
#pragma unroll
                    for (int b = 0; b < 2; b++) {
                        const int e = 8 * hp + 2 * b, d = e + 4, cb = 7 * hp;
                        ot[b][cb] = pack2(o[e][0], o[e][1]);
                        ot[b][cb + 1] = pack2(o[e][2], o[e][3]);
                        ot[b][cb + 2] = pack2(o[e + 1][0], o[e + 1][1]);
                        ot[b][cb + 3] = pack2(g < 4 ? o[e + 1][2] : o[d][0], g < 4 ? o[e + 1][3] : o[d][1]);
                        ot[b][cb + 4] = pack2(o[d][2], o[d][3]);
                        ot[b][cb + 5] = pack2(o[d + 1][0], o[d + 1][1]);
                        ot[b][cb + 6] = pack2(o[d + 1][2], o[d + 1][3]);
                    }
                }
#pragma unroll
                for (int c = 0; c < 14; c += 2) stsm4<true>(row_addr + c * 16, ot[0][c], ot[1][c], ot[0][c + 1], ot[1][c + 1]);
            }
            nb_arrive(NB_READY + wg, 160);

#pragma unroll 1
            for (int i = 7 + ATT_DELAY + wg; i < 32; i++) r.stage_kk<1, false>(y0);

            nb_sync(NB_FREE + wg, 160);
            asm volatile("wgmma.wait_group.sync.aligned 0;" ::: "memory");
            acc_fence(y0);
            store_rows<false>(y0, row_addr);
            fence_async_smem();
            __syncwarp();
            if (lane == 0) {
                tma_red2(&maps.m[M_OUTB], 448 + ns * 112, mt * 128 + warp * 16, wslot);
                bulk_commit();
                bulk_wait_read();
            }
        }
    }
}

typedef CUresult (*EncodeFn)(CUtensorMap*, CUtensorMapDataType, cuuint32_t, void*, const cuuint64_t*, const cuuint64_t*,
                             const cuuint32_t*, const cuuint32_t*, CUtensorMapInterleave, CUtensorMapSwizzle,
                             CUtensorMapL2promotion, CUtensorMapFloatOOBfill);

void encode(EncodeFn fn, CUtensorMap* m, const void* ptr, int rank, uint64_t d0, uint64_t d1, uint64_t d2, uint64_t s1,
            uint64_t s2, uint32_t b0, uint32_t b1, uint32_t b2, CUtensorMapSwizzle sw) {
    const cuuint64_t dims[3] = {d0, d1, d2};
    const cuuint64_t strides[2] = {s1, s2};
    const cuuint32_t box[3] = {b0, b1, b2};
    const cuuint32_t es[3] = {1, 1, 1};
    fn(m, CU_TENSOR_MAP_DATA_TYPE_BFLOAT16, rank, const_cast<void*>(ptr), dims, strides, box, es,
       CU_TENSOR_MAP_INTERLEAVE_NONE, sw, CU_TENSOR_MAP_L2_PROMOTION_L2_128B, CU_TENSOR_MAP_FLOAT_OOB_FILL_NONE);
}

}

extern "C" void kernel_launch(void* const* d_in, const int* in_sizes, int n_in, void* d_out, int out_size) {
    (void)in_sizes; (void)n_in; (void)out_size;
    void* fnp = nullptr;
    cudaDriverEntryPointQueryResult st;
    cudaGetDriverEntryPoint("cuTensorMapEncodeTiled", &fnp, cudaEnableDefault, &st);
    EncodeFn fn = (EncodeFn)fnp;
    void* o_ptr = nullptr;
    cudaGetSymbolAddress(&o_ptr, g_o);
    cudaFuncSetAttribute(fused_kernel, cudaFuncAttributeMaxDynamicSharedMemorySize, SMEM_BYTES);

    const CUtensorMapSwizzle S128 = CU_TENSOR_MAP_SWIZZLE_128B, S64 = CU_TENSOR_MAP_SWIZZLE_64B, S0 = CU_TENSOR_MAP_SWIZZLE_NONE;
    Maps maps;
    encode(fn, &maps.m[M_XA32], d_in[0], 2, 896, 1024, 1, 1792, 0, 32, 128, 1, S64);
    encode(fn, &maps.m[M_XA64], d_in[0], 2, 896, 1024, 1, 1792, 0, 64, 128, 1, S128);
    encode(fn, &maps.m[M_WKV], d_in[1], 3, 448, 448, 3, 2688, 896, 64, 32, 2, S128);
    encode(fn, &maps.m[M_WQ], d_in[1], 2, 448, 448, 1, 2688, 0, 64, 64, 1, S128);
    encode(fn, &maps.m[M_WO], d_in[2], 2, 448, 448, 1, 896, 0, 64, 64, 1, S128);
    encode(fn, &maps.m[M_XB], d_in[3], 3, 448, 1024, 2, 896, 896 * 1024, 64, 64, 2, S128);
    encode(fn, &maps.m[M_CR], d_in[4], 2, 2048, 2048, 1, 4096, 0, 64, 128, 1, S128);
    encode(fn, &maps.m[M_CI], d_in[5], 2, 2048, 2048, 1, 4096, 0, 64, 128, 1, S128);
    encode(fn, &maps.m[M_WR], d_in[6], 2, 448, 448, 1, 896, 0, 64, 112, 1, S128);
    encode(fn, &maps.m[M_WI], d_in[7], 2, 448, 448, 1, 896, 0, 64, 112, 1, S128);
    encode(fn, &maps.m[M_OST], o_ptr, 2, 448, 2048, 1, 896, 0, 112, 16, 1, S0);
    encode(fn, &maps.m[M_OLD], o_ptr, 2, 448, 2048, 1, 896, 0, 64, 128, 1, S128);
    encode(fn, &maps.m[M_OUTA], d_out, 2, 1792, 1024, 1, 3584, 0, 112, 16, 1, S0);
    encode(fn, &maps.m[M_OUTB], d_out, 2, 896, 2048, 1, 1792, 0, 112, 16, 1, S0);

    maps.xa = (const uint8_t*)d_in[0];
    maps.wqkv = (const uint8_t*)d_in[1];
    maps.wo = (const uint8_t*)d_in[2];
    maps.wi = (const uint8_t*)d_in[7];

    fused_kernel<<<128, 384, SMEM_BYTES>>>(maps);
}
```

```cpp
#include <cuda.h>
#include <cuda_bf16.h>
#include <cuda_runtime.h>
#include <stdint.h>

namespace {

constexpr int NSLOT = 6;
constexpr uint32_t SLOT = 32768;
constexpr uint32_t BOFF = 16384;
constexpr uint32_t STG = NSLOT * SLOT;
constexpr uint32_t WSLOT = 3584;
constexpr uint32_t BLOB = 14336;
constexpr uint32_t BARS = STG + 9 * WSLOT;
constexpr uint32_t BAR_FULL = BARS;
constexpr uint32_t BAR_EMPTY = BARS + 64;
constexpr uint32_t BAR_HALO = BARS + 128;
constexpr uint32_t BAR_BST = BARS + 136;
constexpr uint32_t BAR_RDY = BARS + 144;
constexpr uint32_t BAR_FREE = BARS + 160;
constexpr uint32_t BAR_PUB = BARS + 176;
constexpr uint32_t SMEM_BYTES = BARS + 256 + 1024;
constexpr uint32_t base = 1024;
constexpr int SPIN_LIMIT = 1 << 16;

#define E_EXTRA 0
#define PF_ON 1
#define AHI_DELAY 400
#define PACE_B 400
#define PACE_Z 100
#define PACE_O 300
#define PACE_0 0
constexpr int NBE = 13 + E_EXTRA;
constexpr int POUT = 33 + NBE;

enum { M_XA32, M_XA64, M_WKV, M_WQ, M_WO, M_XB, M_WR, M_WI, M_CR, M_CI, M_OST, M_OLD, M_OUTA, M_OUTB, M_COUNT };
struct __align__(64) Maps {
    CUtensorMap m[M_COUNT];
    const uint8_t *xa, *wqkv, *wo, *wi;
    uint8_t* out;
};

constexpr int CNT_A = 0;
constexpr int CNT_B = 8;
constexpr int CNT_O = 16;
constexpr int CNT_COUNT = 32;

__device__ __align__(1024) uint8_t g_ab[2 * 32 * 4 * BLOB];
__device__ __align__(1024) __nv_bfloat16 g_o[2048 * 448];
__device__ __align__(1024) uint8_t g_halo[64 * 2 * WSLOT];
__device__ __align__(128) unsigned g_cnt[CNT_COUNT * 32];
__device__ __align__(128) unsigned g_epoch[128 * 4 * 8];

__device__ __forceinline__ unsigned clk32() { unsigned c; asm volatile("mov.u32 %0, %%clock;" : "=r"(c)); return c; }
__device__ __forceinline__ void pause(unsigned cycles) {
    const unsigned t0 = clk32();
    while (clk32() - t0 < cycles) {}
}

#define PROF(idx)

__device__ __forceinline__ void mbar_init(uint32_t bar, uint32_t cnt) {
    asm volatile("mbarrier.init.shared::cta.b64 [%0], %1;" ::"r"(bar), "r"(cnt) : "memory");
}
__device__ __forceinline__ void mbar_expect(uint32_t bar, uint32_t bytes) {
    asm volatile("mbarrier.arrive.expect_tx.shared::cta.b64 _, [%0], %1;" ::"r"(bar), "r"(bytes) : "memory");
}
__device__ __forceinline__ void mbar_arrive(uint32_t bar) {
    asm volatile("mbarrier.arrive.shared::cta.b64 _, [%0];" ::"r"(bar) : "memory");
}
__device__ __forceinline__ bool mbar_try(uint32_t bar, uint32_t parity) {
    uint32_t ok;
    asm volatile("{\n.reg .pred p;\nmbarrier.try_wait.parity.shared::cta.b64 p, [%1], %2;\nselp.u32 %0, 1, 0, p;\n}\n"
                 : "=r"(ok) : "r"(bar), "r"(parity) : "memory");
    return ok;
}
__device__ __forceinline__ void mbar_wait(uint32_t bar, uint32_t parity) {
#pragma unroll 1
    for (int n = 0; n < SPIN_LIMIT; n++)
        if (mbar_try(bar, parity)) break;
}
__device__ __forceinline__ bool elect() {
    uint32_t p;
    asm volatile("{\n.reg .pred p;\nelect.sync _|p, 0xffffffff;\nselp.u32 %0, 1, 0, p;\n}\n" : "=r"(p));
    return p;
}
__device__ __forceinline__ void nb_sync(int id, int n) { asm volatile("bar.sync %0, %1;" ::"r"(id), "r"(n) : "memory"); }
__device__ __forceinline__ void warp_arrive(uint32_t bar) {
    __syncwarp();
    if ((threadIdx.x & 31) == 0) mbar_arrive(bar);
}

__device__ __forceinline__ void tma_ld2(uint32_t dst, const CUtensorMap* m, int c0, int c1, uint32_t bar) {
    asm volatile("cp.async.bulk.tensor.2d.shared::cluster.global.mbarrier::complete_tx::bytes [%0], [%1, {%3, %4}], [%2];"
                 ::"r"(dst), "l"(m), "r"(bar), "r"(c0), "r"(c1) : "memory");
}
__device__ __forceinline__ void tma_ld3(uint32_t dst, const CUtensorMap* m, int c0, int c1, int c2, uint32_t bar) {
    asm volatile("cp.async.bulk.tensor.3d.shared::cluster.global.mbarrier::complete_tx::bytes [%0], [%1, {%3, %4, %5}], [%2];"
                 ::"r"(dst), "l"(m), "r"(bar), "r"(c0), "r"(c1), "r"(c2) : "memory");
}
__device__ __forceinline__ void bulk_ld(uint32_t dst, const void* src, uint32_t bytes, uint32_t bar) {
    asm volatile("cp.async.bulk.shared::cluster.global.mbarrier::complete_tx::bytes [%0], [%1], %2, [%3];"
                 ::"r"(dst), "l"(src), "r"(bytes), "r"(bar) : "memory");
}
__device__ __forceinline__ void bulk_st(void* dst, uint32_t src, uint32_t bytes) {
    asm volatile("cp.async.bulk.global.shared::cta.bulk_group [%0], [%1], %2;" ::"l"(dst), "r"(src), "r"(bytes) : "memory");
}
__device__ __forceinline__ void tma_st2(const CUtensorMap* m, int c0, int c1, uint32_t src) {
    asm volatile("cp.async.bulk.tensor.2d.global.shared::cta.bulk_group [%0, {%1, %2}], [%3];"
                 ::"l"(m), "r"(c0), "r"(c1), "r"(src) : "memory");
}
__device__ __forceinline__ void tma_red2(const CUtensorMap* m, int c0, int c1, uint32_t src) {
    asm volatile("cp.reduce.async.bulk.tensor.2d.global.shared::cta.add.bulk_group [%0, {%1, %2}], [%3];"
                 ::"l"(m), "r"(c0), "r"(c1), "r"(src) : "memory");
}
__device__ __forceinline__ void bulk_commit() { asm volatile("cp.async.bulk.commit_group;" ::: "memory"); }
__device__ __forceinline__ void bulk_wait_all() { asm volatile("cp.async.bulk.wait_group 0;" ::: "memory"); }
__device__ __forceinline__ void bulk_wait_read() { asm volatile("cp.async.bulk.wait_group.read 0;" ::: "memory"); }
__device__ __forceinline__ void fence_async_smem() { asm volatile("fence.proxy.async.shared::cta;" ::: "memory"); }
__device__ __forceinline__ void fence_async_global() { asm volatile("fence.proxy.async.global;" ::: "memory"); }

__device__ __forceinline__ void tma_pf2(const CUtensorMap* m, int c0, int c1) {
    asm volatile("cp.async.bulk.prefetch.tensor.2d.L2.global [%0, {%1, %2}];" ::"l"(m), "r"(c0), "r"(c1) : "memory");
}
__device__ __forceinline__ void bulk_pf(const void* src, uint32_t bytes) {
    asm volatile("cp.async.bulk.prefetch.L2.global [%0], %1;" ::"l"(src), "r"(bytes) : "memory");
}

__device__ __forceinline__ void signal(int idx) {
    fence_async_global();
    asm volatile("red.release.gpu.global.add.u32 [%0], 1;" ::"l"(&g_cnt[idx * 32]) : "memory");
}
__device__ __forceinline__ unsigned peek(int idx) {
    unsigned v;
    asm volatile("ld.relaxed.gpu.global.u32 %0, [%1];" : "=r"(v) : "l"(&g_cnt[idx * 32]) : "memory");
    return v;
}
__device__ __forceinline__ void await(int idx, unsigned target, unsigned v) {
#pragma unroll 1
    for (int n = 0; n < SPIN_LIMIT && (int)(v - target) < 0; n++) v = peek(idx);
    asm volatile("fence.acquire.gpu;" ::: "memory");
    fence_async_global();
}

#define WG_REGS                                                                                                     \
    "{%0,%1,%2,%3,%4,%5,%6,%7,%8,%9,%10,%11,%12,%13,%14,%15,%16,%17,%18,%19,%20,%21,%22,%23,%24,%25,%26,%27,"       \
    "%28,%29,%30,%31,%32,%33,%34,%35,%36,%37,%38,%39,%40,%41,%42,%43,%44,%45,%46,%47,%48,%49,%50,%51,%52,%53,%54,%55}"
#define WG_OPS(C)                                                                                                   \
    C(d[0]), C(d[1]), C(d[2]), C(d[3]), C(d[4]), C(d[5]), C(d[6]), C(d[7]), C(d[8]), C(d[9]), C(d[10]), C(d[11]),   \
    C(d[12]), C(d[13]), C(d[14]), C(d[15]), C(d[16]), C(d[17]), C(d[18]), C(d[19]), C(d[20]), C(d[21]), C(d[22]),   \
    C(d[23]), C(d[24]), C(d[25]), C(d[26]), C(d[27]), C(d[28]), C(d[29]), C(d[30]), C(d[31]), C(d[32]), C(d[33]),   \
    C(d[34]), C(d[35]), C(d[36]), C(d[37]), C(d[38]), C(d[39]), C(d[40]), C(d[41]), C(d[42]), C(d[43]), C(d[44]),   \
    C(d[45]), C(d[46]), C(d[47]), C(d[48]), C(d[49]), C(d[50]), C(d[51]), C(d[52]), C(d[53]), C(d[54]), C(d[55])

template <int TB, int SB, bool INIT>
__device__ __forceinline__ void wgmma112(float (&d)[56], uint64_t da, uint64_t db) {
    if (INIT) {
        asm volatile("{\n.reg .pred p;\nsetp.ne.b32 p, 0, 0;\n"
                     "wgmma.mma_async.sync.aligned.m64n112k16.f32.bf16.bf16 " WG_REGS ", %56, %57, p, 1, %59, 0, %58;\n}\n"
                     : WG_OPS("=f") : "l"(da), "l"(db), "n"(TB), "n"(SB));
    } else {
        asm volatile("{\n.reg .pred p;\nsetp.ne.b32 p, 1, 0;\n"
                     "wgmma.mma_async.sync.aligned.m64n112k16.f32.bf16.bf16 " WG_REGS ", %56, %57, p, 1, %59, 0, %58;\n}\n"
                     : WG_OPS("+f") : "l"(da), "l"(db), "n"(TB), "n"(SB));
    }
}
__device__ __forceinline__ void acc_fence(float (&d)[56]) {
#pragma unroll
    for (int i = 0; i < 56; i++) asm volatile("" : "+f"(d[i])::"memory");
}
__device__ __forceinline__ uint64_t mkdesc(uint32_t addr, uint32_t lbo16, uint32_t sbo16, uint32_t mode) {
    return (uint64_t)(((addr & 0x3FFFF) >> 4) | (lbo16 << 16)) | ((uint64_t)(sbo16 | (mode << 30)) << 32);
}

__device__ __forceinline__ uint32_t pack2(float lo, float hi) {
    uint32_t r;
    asm("cvt.rn.bf16x2.f32 %0, %1, %2;" : "=r"(r) : "f"(hi), "f"(lo));
    return r;
}
__device__ __forceinline__ uint32_t movm(uint32_t a) {
    uint32_t r;
    asm volatile("movmatrix.sync.aligned.m8n8.trans.b16 %0, %1;" : "=r"(r) : "r"(a));
    return r;
}
template <bool TRANS>
__device__ __forceinline__ void stsm4(uint32_t addr, uint32_t a, uint32_t b, uint32_t c, uint32_t d) {
    if (TRANS) asm volatile("stmatrix.sync.aligned.m8n8.x4.trans.shared.b16 [%0], {%1,%2,%3,%4};" ::"r"(addr), "r"(a), "r"(b), "r"(c), "r"(d) : "memory");
    else asm volatile("stmatrix.sync.aligned.m8n8.x4.shared.b16 [%0], {%1,%2,%3,%4};" ::"r"(addr), "r"(a), "r"(b), "r"(c), "r"(d) : "memory");
}
__device__ __forceinline__ void sts4(uint32_t addr, uint32_t a, uint32_t b, uint32_t c, uint32_t d) {
    asm volatile("st.shared.v4.b32 [%0], {%1,%2,%3,%4};" ::"r"(addr), "r"(a), "r"(b), "r"(c), "r"(d) : "memory");
}
__device__ __forceinline__ void lds4(uint32_t addr, uint32_t& a, uint32_t& b, uint32_t& c, uint32_t& d) {
    asm volatile("ld.shared.v4.b32 {%0,%1,%2,%3}, [%4];" : "=r"(a), "=r"(b), "=r"(c), "=r"(d) : "r"(addr) : "memory");
}
__device__ __forceinline__ void mma16816(float (&d)[4], uint32_t a0, uint32_t a1, uint32_t a2, uint32_t a3, uint32_t b0, uint32_t b1) {
    asm volatile("mma.sync.aligned.m16n8k16.row.col.f32.bf16.bf16.f32 {%0,%1,%2,%3}, {%4,%5,%6,%7}, {%8,%9}, {%0,%1,%2,%3};"
                 : "+f"(d[0]), "+f"(d[1]), "+f"(d[2]), "+f"(d[3]) : "r"(a0), "r"(a1), "r"(a2), "r"(a3), "r"(b0), "r"(b1));
}
__device__ __forceinline__ uint32_t max2(uint32_t a, uint32_t b) {
    uint32_t r;
    asm("max.bf16x2 %0, %1, %2;" : "=r"(r) : "r"(a), "r"(b));
    return r;
}
__device__ __forceinline__ void st_tagged(uint8_t* p, uint32_t a, uint32_t b, uint32_t tag) {
    asm volatile("{\n.reg .b64 x, y;\nmov.b64 x, {%1, %3};\nmov.b64 y, {%2, %3};\nst.relaxed.gpu.global.v2.b64 [%0], {x, y};\n}\n"
                 ::"l"(p), "r"(a), "r"(b), "r"(tag) : "memory");
}
__device__ __forceinline__ void ld_tagged(const uint8_t* p, uint32_t& a, uint32_t& ta, uint32_t& b, uint32_t& tb) {
    asm volatile("{\n.reg .b64 x, y;\nld.relaxed.gpu.global.v2.b64 {x, y}, [%4];\nmov.b64 {%0, %1}, x;\nmov.b64 {%2, %3}, y;\n}\n"
                 : "=r"(a), "=r"(ta), "=r"(b), "=r"(tb) : "l"(p) : "memory");
}
__device__ __forceinline__ float bf_lo(uint32_t v) { return __uint_as_float(v << 16); }
__device__ __forceinline__ float bf_hi(uint32_t v) { return __uint_as_float(v & 0xFFFF0000u); }
__device__ __forceinline__ float rcp(float x) { float r; asm("rcp.approx.ftz.f32 %0, %1;" : "=f"(r) : "f"(x)); return r; }
__device__ __forceinline__ float ex2(float x) { float r; asm("ex2.approx.ftz.f32 %0, %1;" : "=f"(r) : "f"(x)); return r; }

__host__ __device__ constexpr int hw_tile(int c) { return (c + 8) % 14; }

struct Feed {
    uint32_t dst, bar, phase;
    __device__ __forceinline__ void init(uint32_t off) { dst = base + off; bar = base + BAR_FULL; phase = 0; }
    __device__ __forceinline__ void acquire() { mbar_wait(bar + (BAR_EMPTY - BAR_FULL), phase); }
    __device__ __forceinline__ void next() {
        dst += SLOT;
        bar += 8;
        if (bar == base + BAR_FULL + NSLOT * 8) { dst -= NSLOT * SLOT; bar -= NSLOT * 8; phase ^= 1; }
    }
};
__device__ __forceinline__ int skip_own(int n, int mt) { return n == mt ? 15 : n; }

struct Ring {
    uint32_t wg;
    uint32_t slot;
    uint32_t phase;
    uint32_t prev;
    uint32_t pphase;
    bool leader;
    __device__ __forceinline__ uint32_t begin() {
        mbar_wait(base + BAR_FULL + slot * 8, phase);
        asm volatile("wgmma.fence.sync.aligned;" ::: "memory");
        return base + slot * SLOT;
    }
    template <bool RELEASE>
    __device__ __forceinline__ void end() {
        asm volatile("wgmma.commit_group.sync.aligned;" ::: "memory");
        asm volatile("wgmma.wait_group.sync.aligned 1;" ::: "memory");
        if (RELEASE && leader) mbar_arrive(base + BAR_EMPTY + prev * 8);
        prev = slot;
        pphase = phase;
        if (++slot == NSLOT) { slot = 0; phase ^= 1; }
    }
    __device__ __forceinline__ void pin() { mbar_wait(base + BAR_FULL + prev * 8, pphase); }
    template <int SB, bool INIT, bool RELEASE = true>
    __device__ __forceinline__ void stage_kk(float (&d)[56], int stg = -1) {
        const uint32_t s = begin();
        const uint32_t sb = stg >= 0 ? base + STG + stg * BLOB : s + BOFF;
        const uint64_t da = mkdesc(s + wg * 8192, 1, 64, 1), db = mkdesc(sb, 1, 64, 1);
        wgmma112<0, SB, INIT>(d, da, db);
        wgmma112<0, SB, false>(d, da + 2, db + 2);
        wgmma112<0, SB, false>(d, da + 4, db + 4);
        wgmma112<0, SB, false>(d, da + 6, db + 6);
        end<RELEASE>();
    }
    template <bool INIT>
    __device__ __forceinline__ void stage_kn(float (&d)[56]) {
        const uint32_t s = begin();
        const uint64_t da = mkdesc(s + wg * 8192, 1, 64, 1), db = mkdesc(s + BOFF, 512, 64, 1);
        wgmma112<1, 1, INIT>(d, da, db);
        wgmma112<1, 1, false>(d, da + 2, db + 128);
        wgmma112<1, 1, false>(d, da + 4, db + 256);
        wgmma112<1, 1, false>(d, da + 6, db + 384);
        end<true>();
    }
    template <bool INIT>
    __device__ __forceinline__ void stage_kv(float (&dk)[56], float (&dv)[56]) {
        const uint32_t s = begin();
        const uint64_t da = mkdesc(s + wg * 4096, 1, 32, 2), db = mkdesc(s + BOFF, 512, 64, 1);
        wgmma112<1, 1, INIT>(dk, da, db);
        wgmma112<1, 1, INIT>(dv, da, db + 256);
        wgmma112<1, 1, false>(dk, da + 2, db + 128);
        wgmma112<1, 1, false>(dv, da + 2, db + 384);
        end<!INIT>();
    }
};

template <bool TRANS>
__device__ __forceinline__ void store_pair(uint32_t addr, bool swap, uint32_t lo0, uint32_t hi0, uint32_t lo1, uint32_t hi1) {
    stsm4<TRANS>(addr, swap ? lo1 : lo0, swap ? hi1 : hi0, swap ? lo0 : lo1, swap ? hi0 : hi1);
}
template <bool PERM>
__device__ __forceinline__ void store_rows(const float (&d)[56], uint32_t lane_addr) {
    const bool swap = threadIdx.x & 16;
#pragma unroll
    for (int c = 0; c < 14; c += 2) {
        const int j = PERM ? hw_tile(c) : c;
        store_pair<false>(lane_addr + c * 16, swap, pack2(d[4 * j], d[4 * j + 1]), pack2(d[4 * j + 2], d[4 * j + 3]),
                          pack2(d[4 * j + 4], d[4 * j + 5]), pack2(d[4 * j + 6], d[4 * j + 7]));
    }
}
__device__ __forceinline__ void store_blob(const float (&d)[56], uint32_t lane_addr) {
#pragma unroll
    for (int j = 0; j < 14; j += 2)
        stsm4<true>(lane_addr + j * 1024, pack2(d[4 * j], d[4 * j + 1]), pack2(d[4 * j + 2], d[4 * j + 3]),
                    pack2(d[4 * j + 4], d[4 * j + 5]), pack2(d[4 * j + 6], d[4 * j + 7]));
}

__global__ void __launch_bounds__(384, 1) fused_kernel(const __grid_constant__ Maps maps) {
    extern __shared__ uint8_t smem_raw[];
    if ((uint32_t)__cvta_generic_to_shared(smem_raw) != base) return;
    const int warp = __shfl_sync(0xffffffffu, threadIdx.x >> 5, 0);
    const int lane = threadIdx.x & 31;
    const int bid = blockIdx.x;
    const int roleL = (bid >> 3) & 1;
    const int mt = ((bid >> 4) << 1) | ((bid >> 2) & 1);
    const int ns = bid & 3;
    const int par = mt >> 3, blk = mt & 7;

    if (warp == 8) {
        if (elect()) {
#pragma unroll
            for (int i = 0; i < NSLOT; i++) mbar_init(base + BAR_FULL + i * 8, 2);
            asm volatile("fence.mbarrier_init.release.cluster;" ::: "memory");
        }
    } else if (warp == 9) {
        if (elect()) {
#pragma unroll
            for (int i = 0; i < NSLOT; i++) mbar_init(base + BAR_EMPTY + i * 8, 8);
            mbar_init(base + BAR_HALO, 9);
            mbar_init(base + BAR_BST, 2);
            mbar_init(base + BAR_RDY, 4);
            mbar_init(base + BAR_RDY + 8, 4);
            mbar_init(base + BAR_FREE, 1);
            mbar_init(base + BAR_FREE + 8, 1);
            mbar_init(base + BAR_PUB, 1);
            asm volatile("fence.mbarrier_init.release.cluster;" ::: "memory");
        }
    }
    __syncthreads();

    const int col = ns * 112;
    if (warp == 8) {
        if (elect()) {
#pragma unroll 1
            for (int i = 0; i < NSLOT; i++) {
                const uint32_t dst = base + i * SLOT, bar = base + BAR_FULL + i * 8;
                mbar_expect(bar, roleL ? 8192 : 16384);
                if (roleL) tma_ld2(dst, &maps.m[M_XA32], par * 448 + i * 32, blk * 128, bar);
                else tma_ld3(dst, &maps.m[M_XB], i * 64, mt * 64, 0, bar);
                if (PACE_0) pause(PACE_0);
            }
        }
    } else if (warp == 11) {
        if (elect()) {
#pragma unroll 1
            for (int i = 0; i < NSLOT; i++) {
                const uint32_t dst = base + i * SLOT + BOFF, bar = base + BAR_FULL + i * 8;
                mbar_expect(bar, roleL ? 16384 : BLOB);
                if (roleL) {
                    tma_ld3(dst, &maps.m[M_WKV], col + 48, i * 32, 1, bar);
                    tma_ld3(dst + 8192, &maps.m[M_WKV], col, i * 32, 1, bar);
                } else {
                    tma_ld2(dst, &maps.m[M_WR], i * 64, col, bar);
                }
                if (PACE_0) pause(PACE_0);
            }
        }
    }

    if (warp >= 8) {
        asm volatile("setmaxnreg.dec.sync.aligned.u32 72;");
        unsigned* epoch_ptr = &g_epoch[(bid * 4 + (warp - 8)) * 8];
#define PROF_FEED_A
#define PROF_FEED_B
        if (warp == 8) {
            if (elect()) {
                Feed f;
                f.init(0);
                const int row = mt * 128;
                auto c_run = [&](const CUtensorMap* m, int off, int n0, int n1, const CUtensorMap* pm) {
#pragma unroll 1
                    for (int n = n0; n < n1; n++) {
                        f.acquire();
                        mbar_expect(f.bar, 16384);
                        tma_ld2(f.dst, m, (off + skip_own(n, mt)) * 64, row, f.bar);
                        PROF_FEED_A;
                        if (PF_ON && (n & 3) == ns) {
                            if (n < 8) tma_pf2(m, (off + n + 8) * 64, row);
                            else if (pm) tma_pf2(pm, (off + n - 8) * 64, row);
                        }
                        f.next();
                    }
                };
                if (!roleL) {
#pragma unroll 1
                    for (int i = NSLOT; i < 14; i++) {
                        f.acquire();
                        mbar_expect(f.bar, 16384);
                        tma_ld3(f.dst, &maps.m[M_XB], (i < 7 ? i : i - 7) * 64, mt * 64, 0, f.bar);
                        PROF_FEED_A;
                        if (PF_ON) {
                            if (i == 7) tma_pf2(&maps.m[M_CR + (ns >> 1)], ((ns & 1) * 16 + mt) * 64, row);
                            if (i == 8) tma_pf2(&maps.m[M_CR], ns * 64, row);
                            if (i == 9) tma_pf2(&maps.m[M_CR], (4 + ns) * 64, row);
                        }
                        f.next();
                    }
#pragma unroll 1
                    for (int i = 0; i < 4; i++) {
                        f.acquire();
                        mbar_expect(f.bar, 16384);
                        tma_ld2(f.dst, &maps.m[M_CR + (i >> 1)], ((i & 1) * 16 + mt) * 64, row, f.bar);
                        PROF_FEED_A;
                        f.next();
                    }
                    const unsigned ep = *epoch_ptr;
                    c_run(&maps.m[M_CR], 0, 0, 15, &maps.m[M_CI]);
                    if (PF_ON && ns == 3) tma_pf2(&maps.m[M_CI], 7 * 64, row);
                    c_run(&maps.m[M_CI], 0, 0, NBE, nullptr);
                    await(CNT_O + mt, (ep + 1) * 8, peek(CNT_O + mt));
                    PROF(146);
#pragma unroll 1
                    for (int i = 0; i < 7; i++) {
                        f.acquire();
                        mbar_expect(f.bar, 16384);
                        tma_ld2(f.dst, &maps.m[M_OLD], i * 64, row, f.bar);
                        PROF_FEED_A;
                        f.next();
                    }
                    *epoch_ptr = ep + 1;
                } else {
#pragma unroll 1
                    for (int i = NSLOT; i < 14; i++) {
                        f.acquire();
                        mbar_expect(f.bar, 8192);
                        tma_ld2(f.dst, &maps.m[M_XA32], par * 448 + i * 32, blk * 128, f.bar);
                        PROF_FEED_A;
                        f.next();
                    }
#pragma unroll 1
                    for (int i = 0; i < 7; i++) {
                        f.acquire();
                        mbar_expect(f.bar, 16384);
                        tma_ld2(f.dst, &maps.m[M_XA64], par * 448 + i * 64, blk * 128, f.bar);
                        PROF_FEED_A;
                        if (PF_ON) {
                            if (i == 0) tma_pf2(&maps.m[M_CR], (16 + ns) * 64, row);
                            if (i == 3) tma_pf2(&maps.m[M_CR], (20 + ns) * 64, row);
                        }
                        f.next();
                    }
                    c_run(&maps.m[M_CR], 16, 0, 15, &maps.m[M_CI]);
                    if (PF_ON && ns == 3) tma_pf2(&maps.m[M_CI], 23 * 64, row);
                    c_run(&maps.m[M_CI], 16, 0, 15, nullptr);
                    c_run(&maps.m[M_CI], 0, NBE, 15, nullptr);
                }
            }
        } else if (warp == 11) {
            if (elect()) {
                Feed f;
                f.init(BOFF);
                const unsigned target = (*epoch_ptr + 1) * 16;
                auto blob_run = [&](int quarter, int n0, int n1) {
                    const int cnt = CNT_A + (quarter >> 1) * 8 + ns * 2 + (quarter & 1);
                    const uint8_t* src = g_ab + (size_t)(quarter * 64 + ns) * BLOB;
                    await(cnt, target, peek(cnt));
                    PROF(150 + quarter);
#pragma unroll 1
                    for (int n = n0; n < n1; n++) {
                        f.acquire();
                        uint32_t dst = f.dst;
                        if (quarter == 0) {
                            if ((n >> 1) == 2) dst = base + STG + (n & 1) * BLOB;
                            if (n == 10) mbar_wait(base + BAR_BST, 0);
                        }
                        mbar_expect(f.bar, BLOB);
                        bulk_ld(dst, src + skip_own(n, mt) * (4 * BLOB), BLOB, f.bar);
                        PROF_FEED_B;
                        f.next();
                    }
                };
                auto warm = [&]() {
                    bulk_pf(maps.wi + bid * 3136, 3136);
                    bulk_pf(maps.xa + bid * 14336, 14336);
                    bulk_pf(maps.wqkv + bid * 9408, 9408);
                    bulk_pf(maps.wo + bid * 3136, 3136);
                };
                if (!roleL) {
#pragma unroll 1
                    for (int i = NSLOT; i < 14; i++) {
                        f.acquire();
                        mbar_expect(f.bar, BLOB);
                        tma_ld2(f.dst, &maps.m[i < 7 ? M_WR : M_WI], (i < 7 ? i : i - 7) * 64, col, f.bar);
                        if (i == NSLOT) warm();
                        PROF_FEED_B;
                        f.next();
                    }
#pragma unroll 1
                    for (int i = 0; i < 4; i++) {
                        f.acquire();
                        mbar_wait(base + BAR_RDY + (i & 1) * 8, i >> 1);
                        fence_async_smem();
                        mbar_arrive(f.bar);
                        PROF_FEED_B;
                        f.next();
                    }
                    blob_run(0, 0, 15);
                    blob_run(2, 0, NBE);
#pragma unroll 1
                    for (int i = 0; i < 7; i++) {
                        f.acquire();
                        mbar_expect(f.bar, 16384);
                        tma_ld2(f.dst, &maps.m[M_WO], col + 48, i * 64, f.bar);
                        tma_ld2(f.dst + 8192, &maps.m[M_WO], col, i * 64, f.bar);
                        PROF_FEED_B;
                        f.next();
                    }
                } else {
#pragma unroll 1
                    for (int i = NSLOT; i < 14; i++) {
                        f.acquire();
                        mbar_expect(f.bar, 16384);
                        tma_ld3(f.dst, &maps.m[M_WKV], col + 48, i * 32, 1, f.bar);
                        tma_ld3(f.dst + 8192, &maps.m[M_WKV], col, i * 32, 1, f.bar);
                        if (i == NSLOT) warm();
                        PROF_FEED_B;
                        f.next();
                    }
#pragma unroll 1
                    for (int i = 0; i < 7; i++) {
                        f.acquire();
                        mbar_expect(f.bar, 16384);
                        tma_ld2(f.dst, &maps.m[M_WQ], col + 48, i * 64, f.bar);
                        tma_ld2(f.dst + 8192, &maps.m[M_WQ], col, i * 64, f.bar);
                        PROF_FEED_B;
                        f.next();
                    }
                    blob_run(1, 0, 15);
                    blob_run(3, 0, 15);
                    if (NBE < 15) blob_run(2, NBE, 15);
                }
                *epoch_ptr = target >> 4;
            }
        } else {
            const int h = warp - 9;
            const uint32_t stg = base + STG + h * BLOB;
            if (!roleL) {
                if (elect()) {
                    mbar_wait(base + BAR_RDY + h * 8, 0);
                    PROF(130 + h);
                    fence_async_smem();
                    if (h) pause(AHI_DELAY);
                    bulk_st(g_ab + (size_t)((h * 16 + mt) * 4 + ns) * BLOB, stg, BLOB);
                    bulk_commit();
                    bulk_wait_all();
                    PROF(132 + h);
                    signal(CNT_A + ns * 2 + h);
                    PROF(134 + h);

                    mbar_wait(base + BAR_RDY + h * 8, 1);
                    fence_async_smem();
                    PROF(136 + h);
#pragma unroll 1
                    for (int p = 0; p < 4; p++) {
                        if (p) pause(PACE_B);
                        bulk_st(g_ab + (size_t)((32 + h * 16 + mt) * 4 + ns) * BLOB + p * WSLOT,
                                base + (4 + h) * SLOT + BOFF + p * WSLOT, WSLOT);
                    }
                    bulk_commit();
                    bulk_wait_all();
                    mbar_arrive(base + BAR_BST);
                    signal(CNT_B + ns * 2 + h);
                    PROF(138 + h);

                    mbar_wait(base + BAR_RDY + h * 8, 0);
                    fence_async_smem();
                    mbar_wait(base + BAR_EMPTY + (POUT % NSLOT) * 8, (POUT / NSLOT) & 1);
                    PROF(140 + h);
#pragma unroll 1
                    for (int p = 0; p < 4; p++)
                        tma_red2(&maps.m[M_OUTB], 448 + col, mt * 128 + h * 64 + p * 16, stg + p * WSLOT);
                    bulk_commit();
                    bulk_wait_read();
                    mbar_arrive(base + BAR_FREE + h * 8);
                    PROF(142 + h);
                }
            } else {
                const unsigned tag = *epoch_ptr + 1;
                mbar_wait(base + BAR_FULL + 5 * 8, 0);
                {
                    uint8_t* dst = maps.out + (size_t)(mt * 128 + h * 64 + (lane >> 4)) * 1792 + 896 + ns * 224 + (lane & 15) * 16;
#pragma unroll 1
                    for (int i = 0; i < 32; i++) {
                        if ((lane & 15) < 14) *reinterpret_cast<uint4*>(dst + i * 3584) = make_uint4(0, 0, 0, 0);
                        pause(PACE_Z);
                    }
                }
                if (lane == 0) PROF(130 + h);
                mbar_wait(base + BAR_PUB, 0);
                if (h == 0) {
                    const uint8_t* src = g_halo + (size_t)((mt - 1) * 4 + ns) * (2 * WSLOT) + lane * 16;
#pragma unroll
                    for (int part = 0; part < 2; part++) {
                        constexpr int NV = 8;
                        uint32_t v[2 * NV], t[2 * NV];
#pragma unroll
                        for (int i = 0; i < 2 * NV; i++) v[i] = 0;
                        const int nv = part ? 6 : 8;
                        if (blk > 0) {
#pragma unroll 1
                            for (int n = 0; n < SPIN_LIMIT; n++) {
                                bool ok = true;
#pragma unroll
                                for (int i = 0; i < nv; i++) ld_tagged(src + (part * NV + i) * 512, v[2 * i], t[2 * i], v[2 * i + 1], t[2 * i + 1]);
#pragma unroll
                                for (int i = 0; i < 2 * nv; i++) ok = ok && t[i] == tag;
                                if (__all_sync(0xffffffffu, ok)) break;
                            }
                        }
#pragma unroll
                        for (int i = 0; i < nv / 2; i++)
                            sts4(base + STG + (part * 4 + i) * 512 + lane * 16, v[4 * i], v[4 * i + 1], v[4 * i + 2], v[4 * i + 3]);
                    }
                    warp_arrive(base + BAR_HALO);
                    if (lane == 0) PROF(138);
                } else if (blk < 7) {
                    uint8_t* dst = g_halo + (size_t)(mt * 4 + ns) * (2 * WSLOT) + lane * 16;
                    uint32_t v[28];
#pragma unroll
                    for (int i = 0; i < 7; i++) lds4(base + STG + 8 * WSLOT + i * 512 + lane * 16, v[4 * i], v[4 * i + 1], v[4 * i + 2], v[4 * i + 3]);
#pragma unroll
                    for (int i = 0; i < 14; i++) st_tagged(dst + i * 512, v[2 * i], v[2 * i + 1], tag);
                }
                __syncwarp();
                if (elect()) {
                    *epoch_ptr = tag;
                    mbar_wait(base + BAR_RDY + h * 8, 0);
                    PROF(132 + h);
                    fence_async_smem();
#pragma unroll 1
                    for (int p = 0; p < 4; p++) {
                        if (p) pause(PACE_O);
                        tma_st2(&maps.m[M_OST], col, mt * 128 + h * 64 + p * 16, stg + p * WSLOT);
                    }
                    bulk_commit();
                    bulk_wait_all();
                    PROF(134 + h);
                    signal(CNT_O + mt);
                    mbar_arrive(base + BAR_FREE + h * 8);
                    PROF(136 + h);
                }
            }
        }
    } else {
        asm volatile("setmaxnreg.inc.sync.aligned.u32 216;");
        Ring r;
        r.wg = warp >> 2;
        r.slot = 0;
        r.phase = 0;
        r.prev = 0;
        r.pphase = 0;
        r.leader = lane == 0;
        const int wg = warp >> 2;
        const uint32_t wslot = base + STG + warp * WSLOT;
        const uint32_t row_addr = wslot + (lane & 15) * 224 + (((lane >> 4) ^ (lane >> 2)) & 1) * 16;

        if (!roleL) {
            const uint32_t blob_off = ((lane >> 4) * 8 + (lane & 7)) * 128 +
                                      (((2 * (warp & 3) + ((lane >> 3) & 1)) ^ (lane & 7)) << 4);
            float x0[56], x1[56];
            r.stage_kk<1, true, false>(x0);
#pragma unroll 1
            for (int i = 1; i < 7; i++) r.stage_kk<1, false>(x0);

            r.stage_kk<-1, true>(x1);
            acc_fence(x0);
            store_blob(x0, base + STG + wg * BLOB + blob_off);
            warp_arrive(base + BAR_RDY + wg * 8);
#pragma unroll 1
            for (int i = 1; i < 7; i++) r.stage_kk<-1, false>(x1);

            r.stage_kk<1, true>(x0, 0);
            acc_fence(x1);
            mbar_wait(base + BAR_EMPTY + (4 + wg) * 8, 1);
            store_blob(x1, base + (4 + wg) * SLOT + BOFF + blob_off);
            warp_arrive(base + BAR_RDY + wg * 8);
#pragma unroll 1
            for (int i = 15; i < POUT; i++) r.stage_kk<1, false>(x0, (i == 15 || (i >> 1) == 11) ? (i & 1) : -1);

            r.stage_kn<true>(x1);
            acc_fence(x0);
            store_rows<false>(x0, row_addr);
            warp_arrive(base + BAR_RDY + wg * 8);
#pragma unroll 1
            for (int i = 1; i < 7; i++) r.stage_kn<false>(x1);

            mbar_wait(base + BAR_FREE + wg * 8, 0);
            asm volatile("wgmma.wait_group.sync.aligned 0;" ::: "memory");
            acc_fence(x1);
            store_rows<true>(x1, row_addr);
            fence_async_smem();
            __syncwarp();
            if (elect()) {
                tma_st2(&maps.m[M_OUTA], par * 896 + col, blk * 128 + warp * 16, wslot);
                bulk_commit();
                bulk_wait_read();
            }
        } else {
            const int g = lane >> 2, tig = lane & 3;
            float y0[56], y1[56], y2[56];
            r.stage_kv<true>(y0, y1);
#pragma unroll 1
            for (int i = 1; i < 14; i++) r.stage_kv<false>(y0, y1);

            uint32_t kl[14], kh[14], vl[14], vh[14];
            r.stage_kn<true>(y2);
            acc_fence(y0);
            acc_fence(y1);
#pragma unroll
            for (int c = 0; c < 14; c++) {
                const int j = hw_tile(c);
                kh[c] = pack2(y0[4 * j + 2], y0[4 * j + 3]);
                vh[c] = movm(pack2(y1[4 * j + 2], y1[4 * j + 3]));
            }
            r.stage_kn<false>(y2);
            r.pin();
            {
                const uint32_t pub = wslot + WSLOT + lane * 16;
                sts4(pub, kh[0], kh[1], kh[2], kh[3]);
                sts4(pub + 512, kh[4], kh[5], kh[6], kh[7]);
                sts4(pub + 1024, kh[8], kh[9], kh[10], kh[11]);
                sts4(pub + 1536, kh[12], kh[13], vh[0], vh[1]);
                sts4(pub + 2048, vh[2], vh[3], vh[4], vh[5]);
                sts4(pub + 2560, vh[6], vh[7], vh[8], vh[9]);
                sts4(pub + 3072, vh[10], vh[11], vh[12], vh[13]);
                warp_arrive(base + BAR_HALO);
                if (threadIdx.x == 224) mbar_arrive(base + BAR_PUB);
            }
            r.stage_kn<false>(y2);
            r.stage_kn<false>(y2);
            r.pin();
#pragma unroll
            for (int c = 0; c < 14; c++) {
                const int j = hw_tile(c);
                kl[c] = pack2(y0[4 * j], y0[4 * j + 1]);
                vl[c] = movm(pack2(y1[4 * j], y1[4 * j + 1]));
            }
#pragma unroll 1
            for (int i = 4; i < 7; i++) r.stage_kn<false>(y2);

            r.stage_kk<1, true>(y0);
            acc_fence(y2);
            uint32_t ql[14], qh[14], kp[14], vp[14];
            mbar_wait(base + BAR_HALO, 0);
            const uint32_t sub = wslot + lane * 16;
            lds4(sub, kp[0], kp[1], kp[2], kp[3]);
            lds4(sub + 512, kp[4], kp[5], kp[6], kp[7]);
            lds4(sub + 1024, kp[8], kp[9], kp[10], kp[11]);
            lds4(sub + 1536, kp[12], kp[13], vp[0], vp[1]);
#pragma unroll
            for (int c = 0; c < 14; c++) {
                const int j = hw_tile(c);
                ql[c] = pack2(y2[4 * j], y2[4 * j + 1]);
                qh[c] = pack2(y2[4 * j + 2], y2[4 * j + 3]);
            }
            float s[8][4];
#pragma unroll
            for (int step = 0; step < 2; step++) {
#pragma unroll
                for (int i = 0; i < 8; i++) {
                    const int b = 1 - (i >> 2), h = i & 3;
                    const int c0 = 7 * (h >> 1) + 3 * (h & 1) + 2 * step;
                    const uint32_t* q = b ? qh : ql;
                    const uint32_t* kprev = b ? kl : kp;
                    const uint32_t* kcur = b ? kh : kl;
                    uint32_t q0 = q[c0], q1 = q[c0 + 1];
                    if ((h & 1) && step == 0) q0 = tig >= 2 ? q0 : 0u;
                    if (!(h & 1) && step == 1) q1 = tig < 2 ? q1 : 0u;
                    float (&d)[4] = s[2 * h + b];
                    if (step == 0) d[0] = d[1] = d[2] = d[3] = 0.f;
                    mma16816(d, kprev[c0], kcur[c0], kprev[c0 + 1], kcur[c0 + 1], q0, q1);
                }
            }
            r.stage_kk<1, false>(y0);
            r.pin();

            const uint32_t curmask = (2 * tig <= g ? 0x0000FFFFu : 0u) | (2 * tig + 1 <= g ? 0xFFFF0000u : 0u);
            uint32_t pr[8], mx[4];
            {
                const bool cur0 = g <= 2 * tig, cur1 = g <= 2 * tig + 1;
                const uint32_t keep = (blk == 0 && warp == 0) ? curmask : 0xFFFFFFFFu;
#pragma unroll
                for (int i = 0; i < 8; i++) pr[i] = movm(pack2(cur0 ? s[i][2] : s[i][0], cur1 ? s[i][3] : s[i][1]));
#pragma unroll
                for (int i = 0; i < 8; i++) {
                    pr[i] = pack2(bf_lo(pr[i]) * 0.18898223650461362f, bf_hi(pr[i]) * 0.18898223650461362f);
                    if ((i & 1) == 0) pr[i] = (pr[i] & keep) | (0xCE6ECE6Eu & ~keep);
                }
            }
            r.stage_kk<1, false>(y0);
            r.pin();
            float e0[8], e1[8];
#pragma unroll
            for (int i = 0; i < 4; i++) mx[i] = max2(__byte_perm(pr[2 * i], pr[2 * i + 1], 0x5410), __byte_perm(pr[2 * i], pr[2 * i + 1], 0x7632));
#pragma unroll
            for (int i = 0; i < 4; i++) mx[i] = max2(mx[i], __shfl_xor_sync(0xffffffffu, mx[i], 1));
#pragma unroll
            for (int i = 0; i < 4; i++) mx[i] = max2(mx[i], __shfl_xor_sync(0xffffffffu, mx[i], 2));
#pragma unroll
            for (int i = 0; i < 8; i++) {
                const float m = (i & 1) ? bf_hi(mx[i >> 1]) : bf_lo(mx[i >> 1]);
                e0[i] = bf_lo(pr[i]) - m;
                e1[i] = bf_hi(pr[i]) - m;
            }
            r.stage_kk<1, false>(y0);
            r.pin();
            float sm[8];
#pragma unroll
            for (int i = 0; i < 8; i++) {
                e0[i] = ex2(e0[i] * 1.4426950408889634f);
                e1[i] = ex2(e1[i] * 1.4426950408889634f);
                sm[i] = e0[i] + e1[i];
            }
#pragma unroll
            for (int i = 0; i < 8; i++) sm[i] += __shfl_xor_sync(0xffffffffu, sm[i], 1);
            r.stage_kk<1, false>(y0);
            r.pin();
#pragma unroll
            for (int i = 0; i < 8; i++) sm[i] += __shfl_xor_sync(0xffffffffu, sm[i], 2);
#pragma unroll
            for (int i = 0; i < 8; i++) {
                const float inv = rcp(sm[i]);
                pr[i] = pack2(e0[i] * inv, e1[i] * inv);
            }
            r.stage_kk<1, false>(y0);
            r.pin();
            lds4(sub + 2048, vp[2], vp[3], vp[4], vp[5]);
            lds4(sub + 2560, vp[6], vp[7], vp[8], vp[9]);
            lds4(sub + 3072, vp[10], vp[11], vp[12], vp[13]);
            float o[16][4];
#pragma unroll
            for (int ii = 0; ii < 16; ii++) {
                const int b = 1 - (ii >> 3), h = (ii >> 1) & 3, i = 4 * h + 2 * b + (ii & 1);
                const int c0 = 7 * (h >> 1) + 3 * (h & 1) + 2 * (i & 1);
                const uint32_t* vprev = b ? vl : vp;
                const uint32_t* vcur = b ? vh : vl;
                const uint32_t p = pr[2 * h + b];
                o[i][0] = o[i][1] = o[i][2] = o[i][3] = 0.f;
                mma16816(o[i], vprev[c0], vprev[c0 + 1], vcur[c0], vcur[c0 + 1], p & ~curmask, p & curmask);
            }
            r.stage_kk<1, false>(y0);
            r.pin();
            {
                uint32_t ot[2][14];
#pragma unroll
                for (int hp = 0; hp < 2; hp++) {
#pragma unroll
                    for (int b = 0; b < 2; b++) {
                        const int e = 8 * hp + 2 * b, d = e + 4, cb = 7 * hp;
                        ot[b][cb] = pack2(o[e][0], o[e][1]);
                        ot[b][cb + 1] = pack2(o[e][2], o[e][3]);
                        ot[b][cb + 2] = pack2(o[e + 1][0], o[e + 1][1]);
                        ot[b][cb + 3] = pack2(g < 4 ? o[e + 1][2] : o[d][0], g < 4 ? o[e + 1][3] : o[d][1]);
                        ot[b][cb + 4] = pack2(o[d][2], o[d][3]);
                        ot[b][cb + 5] = pack2(o[d + 1][0], o[d + 1][1]);
                        ot[b][cb + 6] = pack2(o[d + 1][2], o[d + 1][3]);
                    }
                }
#pragma unroll
                for (int c = 0; c < 14; c += 2)
                    store_pair<true>(row_addr + c * 16, tig >= 2, ot[0][c], ot[1][c], ot[0][c + 1], ot[1][c + 1]);
            }
            warp_arrive(base + BAR_RDY + wg * 8);

#pragma unroll 1
            for (int i = 7; i < 32 - E_EXTRA; i++) r.stage_kk<1, false>(y0);

            mbar_wait(base + BAR_FREE + wg * 8, 0);
            asm volatile("wgmma.wait_group.sync.aligned 0;" ::: "memory");
            acc_fence(y0);
            store_rows<false>(y0, row_addr);
            fence_async_smem();
            __syncwarp();
            if (elect()) {
                tma_red2(&maps.m[M_OUTB], 448 + col, mt * 128 + warp * 16, wslot);
                bulk_commit();
                bulk_wait_read();
            }
        }
    }
}

typedef CUresult (*EncodeFn)(CUtensorMap*, CUtensorMapDataType, cuuint32_t, void*, const cuuint64_t*, const cuuint64_t*,
                             const cuuint32_t*, const cuuint32_t*, CUtensorMapInterleave, CUtensorMapSwizzle,
                             CUtensorMapL2promotion, CUtensorMapFloatOOBfill);

void encode(EncodeFn fn, CUtensorMap* m, const void* ptr, int rank, uint64_t d0, uint64_t d1, uint64_t d2, uint64_t s1,
            uint64_t s2, uint32_t b0, uint32_t b1, uint32_t b2, CUtensorMapSwizzle sw) {
    const cuuint64_t dims[3] = {d0, d1, d2};
    const cuuint64_t strides[2] = {s1, s2};
    const cuuint32_t box[3] = {b0, b1, b2};
    const cuuint32_t es[3] = {1, 1, 1};
    fn(m, CU_TENSOR_MAP_DATA_TYPE_BFLOAT16, rank, const_cast<void*>(ptr), dims, strides, box, es,
       CU_TENSOR_MAP_INTERLEAVE_NONE, sw, CU_TENSOR_MAP_L2_PROMOTION_L2_128B, CU_TENSOR_MAP_FLOAT_OOB_FILL_NONE);
}

}

extern "C" void kernel_launch(void* const* d_in, const int* in_sizes, int n_in, void* d_out, int out_size) {
    (void)in_sizes; (void)n_in; (void)out_size;
    void* fnp = nullptr;
    cudaDriverEntryPointQueryResult st;
    cudaGetDriverEntryPoint("cuTensorMapEncodeTiled", &fnp, cudaEnableDefault, &st);
    EncodeFn fn = (EncodeFn)fnp;
    void* o_ptr = nullptr;
    cudaGetSymbolAddress(&o_ptr, g_o);
    cudaFuncSetAttribute(fused_kernel, cudaFuncAttributeMaxDynamicSharedMemorySize, SMEM_BYTES);

    const CUtensorMapSwizzle S128 = CU_TENSOR_MAP_SWIZZLE_128B, S64 = CU_TENSOR_MAP_SWIZZLE_64B, S0 = CU_TENSOR_MAP_SWIZZLE_NONE;
    Maps maps;
    encode(fn, &maps.m[M_XA32], d_in[0], 2, 896, 1024, 1, 1792, 0, 32, 128, 1, S64);
    encode(fn, &maps.m[M_XA64], d_in[0], 2, 896, 1024, 1, 1792, 0, 64, 128, 1, S128);
    encode(fn, &maps.m[M_WKV], d_in[1], 3, 448, 448, 3, 2688, 896, 64, 32, 2, S128);
    encode(fn, &maps.m[M_WQ], d_in[1], 2, 448, 448, 1, 2688, 0, 64, 64, 1, S128);
    encode(fn, &maps.m[M_WO], d_in[2], 2, 448, 448, 1, 896, 0, 64, 64, 1, S128);
    encode(fn, &maps.m[M_XB], d_in[3], 3, 448, 1024, 2, 896, 896 * 1024, 64, 64, 2, S128);
    encode(fn, &maps.m[M_CR], d_in[4], 2, 2048, 2048, 1, 4096, 0, 64, 128, 1, S128);
    encode(fn, &maps.m[M_CI], d_in[5], 2, 2048, 2048, 1, 4096, 0, 64, 128, 1, S128);
    encode(fn, &maps.m[M_WR], d_in[6], 2, 448, 448, 1, 896, 0, 64, 112, 1, S128);
    encode(fn, &maps.m[M_WI], d_in[7], 2, 448, 448, 1, 896, 0, 64, 112, 1, S128);
    encode(fn, &maps.m[M_OST], o_ptr, 2, 448, 2048, 1, 896, 0, 112, 16, 1, S0);
    encode(fn, &maps.m[M_OLD], o_ptr, 2, 448, 2048, 1, 896, 0, 64, 128, 1, S128);
    encode(fn, &maps.m[M_OUTA], d_out, 2, 1792, 1024, 1, 3584, 0, 112, 16, 1, S0);
    encode(fn, &maps.m[M_OUTB], d_out, 2, 896, 2048, 1, 1792, 0, 112, 16, 1, S0);

    maps.xa = (const uint8_t*)d_in[0];
    maps.wqkv = (const uint8_t*)d_in[1];
    maps.wo = (const uint8_t*)d_in[2];
    maps.wi = (const uint8_t*)d_in[7];
    maps.out = (uint8_t*)d_out;

    fused_kernel<<<128, 384, SMEM_BYTES>>>(maps);
}
```

```cpp
#include <cuda.h>
#include <cuda_bf16.h>
#include <cuda_runtime.h>
#include <stdint.h>

namespace {

constexpr int NSLOT = 6;
constexpr uint32_t SLOT = 32768;
constexpr uint32_t BOFF = 16384;
constexpr uint32_t STG = NSLOT * SLOT;
constexpr uint32_t WSLOT = 3584;
constexpr uint32_t BLOB = 14336;
constexpr uint32_t BARS = STG + 9 * WSLOT;
constexpr uint32_t BAR_FULL = BARS;
constexpr uint32_t BAR_EMPTY = BARS + 64;
constexpr uint32_t BAR_HALO = BARS + 128;
constexpr uint32_t BAR_PUB = BARS + 136;
constexpr uint32_t BAR_OUT = BARS + 144;
constexpr uint32_t BAR_FREE = BARS + 160;
constexpr uint32_t BAR_RDY = BARS + 176;
constexpr uint32_t SMEM_BYTES = BARS + 256 + 1024;
constexpr uint32_t base = 1024;
constexpr int SPIN_LIMIT = 1 << 16;

#define E_EXTRA 0
#define PF_ON 1
#define AHI_DELAY 400
#define PACE_B 400
#define PACE_Z 200
#define PACE_O 300
#define HALO_DELAY 600
#define MAPPING 0
#define PACE_0 0
constexpr int NBE = 13 + E_EXTRA;
constexpr int POUT = 33 + NBE;

enum { M_XA32, M_XA64, M_WKV, M_WQ, M_WO, M_XB, M_WR, M_WI, M_CR, M_CI, M_OST, M_OLD, M_OUTA, M_OUTB, M_COUNT };
struct __align__(64) Maps {
    CUtensorMap m[M_COUNT];
    const uint8_t *xa, *wqkv, *wo, *wi;
    uint8_t* out;
};

constexpr int CNT_A = 0;
constexpr int CNT_B = 8;
constexpr int CNT_O = 16;
constexpr int CNT_COUNT = 32;

__device__ __align__(1024) uint8_t g_ab[2 * 32 * 4 * BLOB];
__device__ __align__(1024) __nv_bfloat16 g_o[2048 * 448];
__device__ __align__(1024) uint8_t g_halo[64 * 2 * WSLOT];
__device__ __align__(128) unsigned g_cnt[CNT_COUNT * 32];
__device__ __align__(128) unsigned g_epoch[128 * 4 * 8];

__device__ __forceinline__ unsigned clk32() { unsigned c; asm volatile("mov.u32 %0, %%clock;" : "=r"(c)); return c; }
__device__ __forceinline__ void pause(unsigned cycles) {
    const unsigned t0 = clk32();
    while (clk32() - t0 < cycles) {}
}

#define PROF(idx)

__device__ __forceinline__ void mbar_init(uint32_t bar, uint32_t cnt) {
    asm volatile("mbarrier.init.shared::cta.b64 [%0], %1;" ::"r"(bar), "r"(cnt) : "memory");
}
__device__ __forceinline__ void mbar_expect(uint32_t bar, uint32_t bytes) {
    asm volatile("mbarrier.arrive.expect_tx.shared::cta.b64 _, [%0], %1;" ::"r"(bar), "r"(bytes) : "memory");
}
__device__ __forceinline__ void mbar_arrive(uint32_t bar) {
    asm volatile("mbarrier.arrive.shared::cta.b64 _, [%0];" ::"r"(bar) : "memory");
}
__device__ __forceinline__ bool mbar_try(uint32_t bar, uint32_t parity) {
    uint32_t ok;
    asm volatile("{\n.reg .pred p;\nmbarrier.try_wait.parity.shared::cta.b64 p, [%1], %2;\nselp.u32 %0, 1, 0, p;\n}\n"
                 : "=r"(ok) : "r"(bar), "r"(parity) : "memory");
    return ok;
}
__device__ __forceinline__ void mbar_wait(uint32_t bar, uint32_t parity) {
#pragma unroll 1
    for (int n = 0; n < SPIN_LIMIT; n++)
        if (mbar_try(bar, parity)) break;
}
__device__ __forceinline__ bool elect() {
    uint32_t p;
    asm volatile("{\n.reg .pred p;\nelect.sync _|p, 0xffffffff;\nselp.u32 %0, 1, 0, p;\n}\n" : "=r"(p));
    return p;
}
__device__ __forceinline__ void nb_sync(int id, int n) { asm volatile("bar.sync %0, %1;" ::"r"(id), "r"(n) : "memory"); }
__device__ __forceinline__ void warp_arrive(uint32_t bar) {
    __syncwarp();
    if ((threadIdx.x & 31) == 0) mbar_arrive(bar);
}

__device__ __forceinline__ void tma_ld2(uint32_t dst, const CUtensorMap* m, int c0, int c1, uint32_t bar) {
    asm volatile("cp.async.bulk.tensor.2d.shared::cluster.global.mbarrier::complete_tx::bytes [%0], [%1, {%3, %4}], [%2];"
                 ::"r"(dst), "l"(m), "r"(bar), "r"(c0), "r"(c1) : "memory");
}
__device__ __forceinline__ void tma_ld3(uint32_t dst, const CUtensorMap* m, int c0, int c1, int c2, uint32_t bar) {
    asm volatile("cp.async.bulk.tensor.3d.shared::cluster.global.mbarrier::complete_tx::bytes [%0], [%1, {%3, %4, %5}], [%2];"
                 ::"r"(dst), "l"(m), "r"(bar), "r"(c0), "r"(c1), "r"(c2) : "memory");
}
__device__ __forceinline__ void bulk_ld(uint32_t dst, const void* src, uint32_t bytes, uint32_t bar) {
    asm volatile("cp.async.bulk.shared::cluster.global.mbarrier::complete_tx::bytes [%0], [%1], %2, [%3];"
                 ::"r"(dst), "l"(src), "r"(bytes), "r"(bar) : "memory");
}
__device__ __forceinline__ void bulk_st(void* dst, uint32_t src, uint32_t bytes) {
    asm volatile("cp.async.bulk.global.shared::cta.bulk_group [%0], [%1], %2;" ::"l"(dst), "r"(src), "r"(bytes) : "memory");
}
__device__ __forceinline__ void tma_st2(const CUtensorMap* m, int c0, int c1, uint32_t src) {
    asm volatile("cp.async.bulk.tensor.2d.global.shared::cta.bulk_group [%0, {%1, %2}], [%3];"
                 ::"l"(m), "r"(c0), "r"(c1), "r"(src) : "memory");
}
__device__ __forceinline__ void tma_red2(const CUtensorMap* m, int c0, int c1, uint32_t src) {
    asm volatile("cp.reduce.async.bulk.tensor.2d.global.shared::cta.add.bulk_group [%0, {%1, %2}], [%3];"
                 ::"l"(m), "r"(c0), "r"(c1), "r"(src) : "memory");
}
__device__ __forceinline__ void bulk_commit() { asm volatile("cp.async.bulk.commit_group;" ::: "memory"); }
__device__ __forceinline__ void bulk_wait_all() { asm volatile("cp.async.bulk.wait_group 0;" ::: "memory"); }
__device__ __forceinline__ void bulk_wait_read() { asm volatile("cp.async.bulk.wait_group.read 0;" ::: "memory"); }
__device__ __forceinline__ void fence_async_smem() { asm volatile("fence.proxy.async.shared::cta;" ::: "memory"); }
__device__ __forceinline__ void fence_async_global() { asm volatile("fence.proxy.async.global;" ::: "memory"); }

__device__ __forceinline__ void tma_pf2(const CUtensorMap* m, int c0, int c1) {
    asm volatile("cp.async.bulk.prefetch.tensor.2d.L2.global [%0, {%1, %2}];" ::"l"(m), "r"(c0), "r"(c1) : "memory");
}
__device__ __forceinline__ void bulk_pf(const void* src, uint32_t bytes) {
    asm volatile("cp.async.bulk.prefetch.L2.global [%0], %1;" ::"l"(src), "r"(bytes) : "memory");
}

__device__ __forceinline__ void signal(int idx) {
    fence_async_global();
    asm volatile("red.release.gpu.global.add.u32 [%0], 1;" ::"l"(&g_cnt[idx * 32]) : "memory");
}
__device__ __forceinline__ unsigned peek(int idx) {
    unsigned v;
    asm volatile("ld.relaxed.gpu.global.u32 %0, [%1];" : "=r"(v) : "l"(&g_cnt[idx * 32]) : "memory");
    return v;
}
__device__ __forceinline__ void await(int idx, unsigned target, unsigned v) {
#pragma unroll 1
    for (int n = 0; n < SPIN_LIMIT && (int)(v - target) < 0; n++) v = peek(idx);
    asm volatile("fence.acquire.gpu;" ::: "memory");
    fence_async_global();
}

#define WG_REGS                                                                                                     \
    "{%0,%1,%2,%3,%4,%5,%6,%7,%8,%9,%10,%11,%12,%13,%14,%15,%16,%17,%18,%19,%20,%21,%22,%23,%24,%25,%26,%27,"       \
    "%28,%29,%30,%31,%32,%33,%34,%35,%36,%37,%38,%39,%40,%41,%42,%43,%44,%45,%46,%47,%48,%49,%50,%51,%52,%53,%54,%55}"
#define WG_OPS(C)                                                                                                   \
    C(d[0]), C(d[1]), C(d[2]), C(d[3]), C(d[4]), C(d[5]), C(d[6]), C(d[7]), C(d[8]), C(d[9]), C(d[10]), C(d[11]),   \
    C(d[12]), C(d[13]), C(d[14]), C(d[15]), C(d[16]), C(d[17]), C(d[18]), C(d[19]), C(d[20]), C(d[21]), C(d[22]),   \
    C(d[23]), C(d[24]), C(d[25]), C(d[26]), C(d[27]), C(d[28]), C(d[29]), C(d[30]), C(d[31]), C(d[32]), C(d[33]),   \
    C(d[34]), C(d[35]), C(d[36]), C(d[37]), C(d[38]), C(d[39]), C(d[40]), C(d[41]), C(d[42]), C(d[43]), C(d[44]),   \
    C(d[45]), C(d[46]), C(d[47]), C(d[48]), C(d[49]), C(d[50]), C(d[51]), C(d[52]), C(d[53]), C(d[54]), C(d[55])

template <int TB, int SB, bool INIT>
__device__ __forceinline__ void wgmma112(float (&d)[56], uint64_t da, uint64_t db) {
    if (INIT) {
        asm volatile("{\n.reg .pred p;\nsetp.ne.b32 p, 0, 0;\n"
                     "wgmma.mma_async.sync.aligned.m64n112k16.f32.bf16.bf16 " WG_REGS ", %56, %57, p, 1, %59, 0, %58;\n}\n"
                     : WG_OPS("=f") : "l"(da), "l"(db), "n"(TB), "n"(SB));
    } else {
        asm volatile("{\n.reg .pred p;\nsetp.ne.b32 p, 1, 0;\n"
                     "wgmma.mma_async.sync.aligned.m64n112k16.f32.bf16.bf16 " WG_REGS ", %56, %57, p, 1, %59, 0, %58;\n}\n"
                     : WG_OPS("+f") : "l"(da), "l"(db), "n"(TB), "n"(SB));
    }
}
__device__ __forceinline__ void acc_fence(float (&d)[56]) {
#pragma unroll
    for (int i = 0; i < 56; i++) asm volatile("" : "+f"(d[i])::"memory");
}
__device__ __forceinline__ uint64_t mkdesc(uint32_t addr, uint32_t lbo16, uint32_t sbo16, uint32_t mode) {
    return (uint64_t)(((addr & 0x3FFFF) >> 4) | (lbo16 << 16)) | ((uint64_t)(sbo16 | (mode << 30)) << 32);
}

__device__ __forceinline__ uint32_t pack2(float lo, float hi) {
    uint32_t r;
    asm volatile("cvt.rn.bf16x2.f32 %0, %1, %2;" : "=r"(r) : "f"(hi), "f"(lo));
    return r;
}
__device__ __forceinline__ uint32_t movm(uint32_t a) {
    uint32_t r;
    asm volatile("movmatrix.sync.aligned.m8n8.trans.b16 %0, %1;" : "=r"(r) : "r"(a));
    return r;
}
template <bool TRANS>
__device__ __forceinline__ void stsm4(uint32_t addr, uint32_t a, uint32_t b, uint32_t c, uint32_t d) {
    if (TRANS) asm volatile("stmatrix.sync.aligned.m8n8.x4.trans.shared.b16 [%0], {%1,%2,%3,%4};" ::"r"(addr), "r"(a), "r"(b), "r"(c), "r"(d) : "memory");
    else asm volatile("stmatrix.sync.aligned.m8n8.x4.shared.b16 [%0], {%1,%2,%3,%4};" ::"r"(addr), "r"(a), "r"(b), "r"(c), "r"(d) : "memory");
}
__device__ __forceinline__ void sts4(uint32_t addr, uint32_t a, uint32_t b, uint32_t c, uint32_t d) {
    asm volatile("st.shared.v4.b32 [%0], {%1,%2,%3,%4};" ::"r"(addr), "r"(a), "r"(b), "r"(c), "r"(d) : "memory");
}
__device__ __forceinline__ void lds4(uint32_t addr, uint32_t& a, uint32_t& b, uint32_t& c, uint32_t& d) {
    asm volatile("ld.shared.v4.b32 {%0,%1,%2,%3}, [%4];" : "=r"(a), "=r"(b), "=r"(c), "=r"(d) : "r"(addr) : "memory");
}
__device__ __forceinline__ void mma16816(float (&d)[4], uint32_t a0, uint32_t a1, uint32_t a2, uint32_t a3, uint32_t b0, uint32_t b1) {
    asm volatile("mma.sync.aligned.m16n8k16.row.col.f32.bf16.bf16.f32 {%0,%1,%2,%3}, {%4,%5,%6,%7}, {%8,%9}, {%0,%1,%2,%3};"
                 : "+f"(d[0]), "+f"(d[1]), "+f"(d[2]), "+f"(d[3]) : "r"(a0), "r"(a1), "r"(a2), "r"(a3), "r"(b0), "r"(b1));
}
__device__ __forceinline__ uint32_t max2(uint32_t a, uint32_t b) {
    uint32_t r;
    asm("max.bf16x2 %0, %1, %2;" : "=r"(r) : "r"(a), "r"(b));
    return r;
}
__device__ __forceinline__ void st_tagged(uint8_t* p, uint32_t a, uint32_t b, uint32_t tag) {
    asm volatile("{\n.reg .b64 x, y;\nmov.b64 x, {%1, %3};\nmov.b64 y, {%2, %3};\nst.relaxed.gpu.global.v2.b64 [%0], {x, y};\n}\n"
                 ::"l"(p), "r"(a), "r"(b), "r"(tag) : "memory");
}
__device__ __forceinline__ void ld_tagged(const uint8_t* p, uint32_t& a, uint32_t& ta, uint32_t& b, uint32_t& tb) {
    asm volatile("{\n.reg .b64 x, y;\nld.relaxed.gpu.global.v2.b64 {x, y}, [%4];\nmov.b64 {%0, %1}, x;\nmov.b64 {%2, %3}, y;\n}\n"
                 : "=r"(a), "=r"(ta), "=r"(b), "=r"(tb) : "l"(p) : "memory");
}
__device__ __forceinline__ float bf_lo(uint32_t v) { return __uint_as_float(v << 16); }
__device__ __forceinline__ float bf_hi(uint32_t v) { return __uint_as_float(v & 0xFFFF0000u); }
__device__ __forceinline__ float rcp(float x) { float r; asm("rcp.approx.ftz.f32 %0, %1;" : "=f"(r) : "f"(x)); return r; }
__device__ __forceinline__ float ex2(float x) { float r; asm volatile("ex2.approx.ftz.f32 %0, %1;" : "=f"(r) : "f"(x)); return r; }

__host__ __device__ constexpr int hw_tile(int c) { return (c + 8) % 14; }

struct Feed {
    uint32_t dst, bar, phase;
    __device__ __forceinline__ void init(uint32_t off) { dst = base + off; bar = base + BAR_FULL; phase = 0; }
    __device__ __forceinline__ void acquire() { mbar_wait(bar + (BAR_EMPTY - BAR_FULL), phase); }
    __device__ __forceinline__ void next() {
        dst += SLOT;
        bar += 8;
        if (bar == base + BAR_FULL + NSLOT * 8) { dst -= NSLOT * SLOT; bar -= NSLOT * 8; phase ^= 1; }
    }
};
__device__ __forceinline__ int skip_own(int n, int mt) { return n == mt ? 15 : n; }

struct Ring {
    uint32_t wg;
    uint32_t slot;
    uint32_t phase;
    uint32_t prev;
    uint32_t zero;
    bool leader;
    __device__ __forceinline__ uint32_t begin() {
        mbar_wait(base + BAR_FULL + slot * 8, phase);
        asm volatile("wgmma.fence.sync.aligned;" ::: "memory");
        return base + slot * SLOT;
    }
    template <bool RELEASE>
    __device__ __forceinline__ void end() {
        asm volatile("wgmma.commit_group.sync.aligned;" ::: "memory");
        asm volatile("wgmma.wait_group.sync.aligned 1;" ::: "memory");
        if (RELEASE && leader) mbar_arrive(base + BAR_EMPTY + prev * 8);
        prev = slot;
        if (++slot == NSLOT) { slot = 0; phase ^= 1; }
    }
    __device__ __forceinline__ void pin() {
#pragma unroll 1
        for (uint32_t n = 0; n < zero; n++) asm volatile("nanosleep.u32 0;" ::: "memory");
    }
    template <int SB, bool INIT, bool RELEASE = true>
    __device__ __forceinline__ void stage_kk(float (&d)[56], int stg = -1) {
        const uint32_t s = begin();
        const uint32_t sb = stg >= 0 ? base + STG + stg * BLOB : s + BOFF;
        const uint64_t da = mkdesc(s + wg * 8192, 1, 64, 1), db = mkdesc(sb, 1, 64, 1);
        wgmma112<0, SB, INIT>(d, da, db);
        wgmma112<0, SB, false>(d, da + 2, db + 2);
        wgmma112<0, SB, false>(d, da + 4, db + 4);
        wgmma112<0, SB, false>(d, da + 6, db + 6);
        end<RELEASE>();
    }
    template <bool INIT>
    __device__ __forceinline__ void stage_kn(float (&d)[56]) {
        const uint32_t s = begin();
        const uint64_t da = mkdesc(s + wg * 8192, 1, 64, 1), db = mkdesc(s + BOFF, 512, 64, 1);
        wgmma112<1, 1, INIT>(d, da, db);
        wgmma112<1, 1, false>(d, da + 2, db + 128);
        wgmma112<1, 1, false>(d, da + 4, db + 256);
        wgmma112<1, 1, false>(d, da + 6, db + 384);
        end<true>();
    }
    template <bool INIT>
    __device__ __forceinline__ void stage_kv(float (&dk)[56], float (&dv)[56]) {
        const uint32_t s = begin();
        const uint64_t da = mkdesc(s + wg * 4096, 1, 32, 2), db = mkdesc(s + BOFF, 512, 64, 1);
        wgmma112<1, 1, INIT>(dk, da, db);
        wgmma112<1, 1, INIT>(dv, da, db + 256);
        wgmma112<1, 1, false>(dk, da + 2, db + 128);
        wgmma112<1, 1, false>(dv, da + 2, db + 384);
        end<!INIT>();
    }
};

template <bool TRANS>
__device__ __forceinline__ void store_pair(uint32_t addr, bool swap, uint32_t lo0, uint32_t hi0, uint32_t lo1, uint32_t hi1) {
    stsm4<TRANS>(addr, swap ? lo1 : lo0, swap ? hi1 : hi0, swap ? lo0 : lo1, swap ? hi0 : hi1);
}
template <bool PERM>
__device__ __forceinline__ void store_rows(const float (&d)[56], uint32_t lane_addr) {
    const bool swap = threadIdx.x & 16;
#pragma unroll
    for (int c = 0; c < 14; c += 2) {
        const int j = PERM ? hw_tile(c) : c;
        store_pair<false>(lane_addr + c * 16, swap, pack2(d[4 * j], d[4 * j + 1]), pack2(d[4 * j + 2], d[4 * j + 3]),
                          pack2(d[4 * j + 4], d[4 * j + 5]), pack2(d[4 * j + 6], d[4 * j + 7]));
    }
}
__device__ __forceinline__ void store_blob(const float (&d)[56], uint32_t lane_addr) {
#pragma unroll
    for (int j = 0; j < 14; j += 2)
        stsm4<true>(lane_addr + j * 1024, pack2(d[4 * j], d[4 * j + 1]), pack2(d[4 * j + 2], d[4 * j + 3]),
                    pack2(d[4 * j + 4], d[4 * j + 5]), pack2(d[4 * j + 6], d[4 * j + 7]));
}

__global__ void __launch_bounds__(384, 1) fused_kernel(const __grid_constant__ Maps maps) {
    extern __shared__ uint8_t smem_raw[];
    if ((uint32_t)__cvta_generic_to_shared(smem_raw) != base) return;
    const int warp = __shfl_sync(0xffffffffu, threadIdx.x >> 5, 0);
    const int lane = threadIdx.x & 31;
    const int bid = blockIdx.x;
    const int roleL = (bid >> 3) & 1;
    const int mt = ((bid >> 4) << 1) | ((bid >> 2) & 1);
    const int ns = bid & 3;
    const int par = mt >> 3, blk = mt & 7;

    if (warp == 8) {
        if (elect()) {
#pragma unroll
            for (int i = 0; i < NSLOT; i++) mbar_init(base + BAR_FULL + i * 8, 2);
            asm volatile("fence.mbarrier_init.release.cluster;" ::: "memory");
        }
    } else if (warp == 9) {
        if (elect()) {
#pragma unroll
            for (int i = 0; i < NSLOT; i++) mbar_init(base + BAR_EMPTY + i * 8, 8);
            mbar_init(base + BAR_HALO, 10);
            mbar_init(base + BAR_PUB, 1);
            asm volatile("fence.mbarrier_init.release.cluster;" ::: "memory");
        }
    } else if (warp == 10) {
        if (elect()) {
#pragma unroll
            for (int i = 0; i < 2; i++) {
                mbar_init(base + BAR_OUT + i * 8, 2);
                mbar_init(base + BAR_FREE + i * 8, 1);
            }
#pragma unroll
            for (int i = 0; i < 6; i++) mbar_init(base + BAR_RDY + i * 8, 4);
            asm volatile("fence.mbarrier_init.release.cluster;" ::: "memory");
        }
    }
    __syncthreads();

    const int col = ns * 112;
    if (warp == 8) {
        if (elect()) {
#pragma unroll 1
            for (int i = 0; i < NSLOT; i++) {
                const uint32_t dst = base + i * SLOT, bar = base + BAR_FULL + i * 8;
                mbar_expect(bar, roleL ? 8192 : 16384);
                if (roleL) tma_ld2(dst, &maps.m[M_XA32], par * 448 + i * 32, blk * 128, bar);
                else tma_ld3(dst, &maps.m[M_XB], i * 64, mt * 64, 0, bar);
                if (PACE_0) pause(PACE_0);
            }
        }
    } else if (warp == 11) {
        if (elect()) {
#pragma unroll 1
            for (int i = 0; i < NSLOT; i++) {
                const uint32_t dst = base + i * SLOT + BOFF, bar = base + BAR_FULL + i * 8;
                mbar_expect(bar, roleL ? 16384 : BLOB);
                if (roleL) {
                    tma_ld3(dst, &maps.m[M_WKV], col + 48, i * 32, 1, bar);
                    tma_ld3(dst + 8192, &maps.m[M_WKV], col, i * 32, 1, bar);
                } else {
                    tma_ld2(dst, &maps.m[M_WR], i * 64, col, bar);
                }
                if (PACE_0) pause(PACE_0);
            }
        }
    }

    if (warp >= 8) {
        asm volatile("setmaxnreg.dec.sync.aligned.u32 56;");
        unsigned* epoch_ptr = &g_epoch[(bid * 4 + (warp - 8)) * 8];
#define PROF_FEED_A
#define PROF_FEED_B
        if (warp == 8) {
            if (elect()) {
                Feed f;
                f.init(0);
                const int row = mt * 128;
                auto c_run = [&](const CUtensorMap* m, int off, int n0, int n1, const CUtensorMap* pm) {
#pragma unroll 1
                    for (int n = n0; n < n1; n++) {
                        f.acquire();
                        mbar_expect(f.bar, 16384);
                        tma_ld2(f.dst, m, (off + skip_own(n, mt)) * 64, row, f.bar);
                        PROF_FEED_A;
                        if (PF_ON && (n & 3) == ns) {
                            if (n < 8) tma_pf2(m, (off + n + 8) * 64, row);
                            else if (pm) tma_pf2(pm, (off + n - 8) * 64, row);
                        }
                        f.next();
                    }
                };
                if (!roleL) {
#pragma unroll 1
                    for (int i = NSLOT; i < 14; i++) {
                        f.acquire();
                        mbar_expect(f.bar, 16384);
                        tma_ld3(f.dst, &maps.m[M_XB], (i < 7 ? i : i - 7) * 64, mt * 64, 0, f.bar);
                        PROF_FEED_A;
                        if (PF_ON) {
                            if (i == 7) tma_pf2(&maps.m[M_CR + (ns >> 1)], ((ns & 1) * 16 + mt) * 64, row);
                            if (i == 8) tma_pf2(&maps.m[M_CR], ns * 64, row);
                            if (i == 9) tma_pf2(&maps.m[M_CR], (4 + ns) * 64, row);
                        }
                        f.next();
                    }
#pragma unroll 1
                    for (int i = 0; i < 4; i++) {
                        f.acquire();
                        mbar_expect(f.bar, 16384);
                        tma_ld2(f.dst, &maps.m[M_CR + (i >> 1)], ((i & 1) * 16 + mt) * 64, row, f.bar);
                        mbar_arrive(f.bar);
                        PROF_FEED_A;
                        f.next();
                    }
                    const unsigned ep = *epoch_ptr;
                    c_run(&maps.m[M_CR], 0, 0, 15, &maps.m[M_CI]);
                    if (PF_ON && ns == 3) tma_pf2(&maps.m[M_CI], 7 * 64, row);
                    c_run(&maps.m[M_CI], 0, 0, NBE, nullptr);
                    await(CNT_O + mt, (ep + 1) * 8, peek(CNT_O + mt));
                    PROF(146);
#pragma unroll 1
                    for (int i = 0; i < 7; i++) {
                        f.acquire();
                        mbar_expect(f.bar, 16384);
                        tma_ld2(f.dst, &maps.m[M_OLD], i * 64, row, f.bar);
                        PROF_FEED_A;
                        f.next();
                    }
                    *epoch_ptr = ep + 1;
                } else {
#pragma unroll 1
                    for (int i = NSLOT; i < 14; i++) {
                        f.acquire();
                        mbar_expect(f.bar, 8192);
                        tma_ld2(f.dst, &maps.m[M_XA32], par * 448 + i * 32, blk * 128, f.bar);
                        PROF_FEED_A;
                        f.next();
                    }
#pragma unroll 1
                    for (int i = 0; i < 7; i++) {
                        f.acquire();
                        mbar_expect(f.bar, 16384);
                        tma_ld2(f.dst, &maps.m[M_XA64], par * 448 + i * 64, blk * 128, f.bar);
                        PROF_FEED_A;
                        if (PF_ON) {
                            if (i == 0) tma_pf2(&maps.m[M_CR], (16 + ns) * 64, row);
                            if (i == 3) tma_pf2(&maps.m[M_CR], (20 + ns) * 64, row);
                        }
                        f.next();
                    }
                    c_run(&maps.m[M_CR], 16, 0, 15, &maps.m[M_CI]);
                    if (PF_ON && ns == 3) tma_pf2(&maps.m[M_CI], 23 * 64, row);
                    c_run(&maps.m[M_CI], 16, 0, 15, nullptr);
                    c_run(&maps.m[M_CI], 0, NBE, 15, nullptr);
                }
            }
        } else if (warp == 11) {
            if (elect()) {
                Feed f;
                f.init(BOFF);
                const unsigned target = (*epoch_ptr + 1) * 16;
                auto blob_run = [&](int quarter, int n0, int n1) {
                    const int cnt = CNT_A + (quarter >> 1) * 8 + ns * 2 + (quarter & 1);
                    const uint8_t* src = g_ab + (size_t)(quarter * 64 + ns) * BLOB;
                    await(cnt, target, peek(cnt));
                    PROF(150 + quarter);
#pragma unroll 1
                    for (int n = n0; n < n1; n++) {
                        f.acquire();
                        uint32_t dst = f.dst;
                        if (quarter == 0) {
                            if (n == 4) mbar_wait(base + BAR_OUT, 0);
                            if ((n >> 1) == 2) dst = base + STG + (n & 1) * BLOB;
                            if (n == 10) mbar_wait(base + BAR_OUT + 8, 0);
                        }
                        mbar_expect(f.bar, BLOB);
                        bulk_ld(dst, src + skip_own(n, mt) * (4 * BLOB), BLOB, f.bar);
                        PROF_FEED_B;
                        f.next();
                    }
                };
                auto warm = [&]() {
                    bulk_pf(maps.wi + bid * 3136, 3136);
                    bulk_pf(maps.xa + bid * 14336, 14336);
                    bulk_pf(maps.wqkv + bid * 9408, 9408);
                    bulk_pf(maps.wo + bid * 3136, 3136);
                };
                if (!roleL) {
#pragma unroll 1
                    for (int i = NSLOT; i < 14; i++) {
                        f.acquire();
                        mbar_expect(f.bar, BLOB);
                        tma_ld2(f.dst, &maps.m[i < 7 ? M_WR : M_WI], (i < 7 ? i : i - 7) * 64, col, f.bar);
                        if (i == NSLOT) warm();
                        PROF_FEED_B;
                        f.next();
                    }
#pragma unroll
                    for (int i = 0; i < 4; i++) {
                        PROF_FEED_B;
                        f.next();
                    }
                    blob_run(0, 0, 15);
                    blob_run(2, 0, NBE);
#pragma unroll 1
                    for (int i = 0; i < 7; i++) {
                        f.acquire();
                        mbar_expect(f.bar, 16384);
                        tma_ld2(f.dst, &maps.m[M_WO], col + 48, i * 64, f.bar);
                        tma_ld2(f.dst + 8192, &maps.m[M_WO], col, i * 64, f.bar);
                        PROF_FEED_B;
                        f.next();
                    }
                } else {
#pragma unroll 1
                    for (int i = NSLOT; i < 14; i++) {
                        f.acquire();
                        mbar_expect(f.bar, 16384);
                        tma_ld3(f.dst, &maps.m[M_WKV], col + 48, i * 32, 1, f.bar);
                        tma_ld3(f.dst + 8192, &maps.m[M_WKV], col, i * 32, 1, f.bar);
                        if (i == NSLOT) warm();
                        PROF_FEED_B;
                        f.next();
                    }
#pragma unroll 1
                    for (int i = 0; i < 7; i++) {
                        f.acquire();
                        mbar_expect(f.bar, 16384);
                        tma_ld2(f.dst, &maps.m[M_WQ], col + 48, i * 64, f.bar);
                        tma_ld2(f.dst + 8192, &maps.m[M_WQ], col, i * 64, f.bar);
                        PROF_FEED_B;
                        f.next();
                    }
                    blob_run(1, 0, 15);
                    blob_run(3, 0, 15);
                    if (NBE < 15) blob_run(2, NBE, 15);
                }
                *epoch_ptr = target >> 4;
            }
        } else {
            const int h = warp - 9;
            const uint32_t stg = base + STG + h * BLOB;
            if (!roleL) {
                if (elect()) {
                    mbar_wait(base + BAR_RDY + h * 8, 0);
                    PROF(130 + h);
                    fence_async_smem();
                    if (h) pause(AHI_DELAY);
                    bulk_st(g_ab + (size_t)((h * 16 + mt) * 4 + ns) * BLOB, stg, BLOB);
                    bulk_commit();
                    bulk_wait_all();
                    PROF(132 + h);
                    mbar_arrive(base + BAR_OUT);
                    signal(CNT_A + ns * 2 + h);
                    PROF(134 + h);

                    mbar_wait(base + BAR_RDY + 16 + h * 8, 0);
                    fence_async_smem();
                    PROF(136 + h);
#pragma unroll 1
                    for (int p = 0; p < 4; p++) {
                        if (p) pause(PACE_B);
                        bulk_st(g_ab + (size_t)((32 + h * 16 + mt) * 4 + ns) * BLOB + p * WSLOT,
                                base + (4 + h) * SLOT + BOFF + p * WSLOT, WSLOT);
                    }
                    bulk_commit();
                    bulk_wait_all();
                    mbar_arrive(base + BAR_OUT + 8);
                    signal(CNT_B + ns * 2 + h);
                    PROF(138 + h);

                    mbar_wait(base + BAR_RDY + 32 + h * 8, 0);
                    fence_async_smem();
                    mbar_wait(base + BAR_EMPTY + (POUT % NSLOT) * 8, (POUT / NSLOT) & 1);
                    PROF(140 + h);
#pragma unroll 1
                    for (int p = 0; p < 4; p++)
                        tma_red2(&maps.m[M_OUTB], 448 + col, mt * 128 + h * 64 + p * 16, stg + p * WSLOT);
                    bulk_commit();
                    bulk_wait_read();
                    mbar_arrive(base + BAR_FREE + h * 8);
                    PROF(142 + h);
                }
            } else {
                const unsigned tag = *epoch_ptr + 1;
                mbar_wait(base + BAR_FULL + 5 * 8, 0);
                {
                    uint8_t* dst = maps.out + (size_t)(mt * 128 + h * 64 + (lane >> 4)) * 1792 + 896 + ns * 224 + (lane & 15) * 16;
#pragma unroll 1
                    for (int i = 0; i < 8; i++) {
#pragma unroll
                        for (int k = 0; k < 4; k++)
                            if ((lane & 15) < 14) *reinterpret_cast<uint4*>(dst + (i * 4 + k) * 3584) = make_uint4(0, 0, 0, 0);
                        pause(PACE_Z);
                    }
                }
                if (lane == 0) PROF(130 + h);
                mbar_wait(base + BAR_PUB, 0);
                {
                    const uint32_t goff = h * 4096 + lane * 16, soff = base + STG + h * 2048 + lane * 16;
                    uint32_t v[16], t[16];
                    if (blk < 7) {
                        uint8_t* dst = g_halo + (size_t)(mt * 4 + ns) * (2 * WSLOT) + goff;
#pragma unroll
                        for (int i = 0; i < 4; i++)
                            if (i < 3 || h == 0) lds4(soff + 8 * WSLOT + i * 512, v[4 * i], v[4 * i + 1], v[4 * i + 2], v[4 * i + 3]);
#pragma unroll
                        for (int i = 0; i < 8; i++)
                            if (i < 6 || h == 0) st_tagged(dst + i * 512, v[2 * i], v[2 * i + 1], tag);
                    }
                    if (lane == 0) PROF(140 + h);
#pragma unroll
                    for (int i = 0; i < 16; i++) { v[i] = 0; t[i] = tag; }
                    if (blk > 0) {
                        const uint8_t* src = g_halo + (size_t)((mt - 1) * 4 + ns) * (2 * WSLOT) + goff;
                        pause(HALO_DELAY);
#pragma unroll 1
                        for (int n = 0; n < SPIN_LIMIT; n++) {
                            bool ok = true;
#pragma unroll
                            for (int i = 0; i < 8; i++)
                                if (i < 6 || h == 0) ld_tagged(src + i * 512, v[2 * i], t[2 * i], v[2 * i + 1], t[2 * i + 1]);
#pragma unroll
                            for (int i = 0; i < 16; i++) ok = ok && t[i] == tag;
                            if (__all_sync(0xffffffffu, ok)) break;
                        }
                    }
#pragma unroll
                    for (int i = 0; i < 4; i++)
                        if (i < 3 || h == 0) sts4(soff + i * 512, v[4 * i], v[4 * i + 1], v[4 * i + 2], v[4 * i + 3]);
                    warp_arrive(base + BAR_HALO);
                    if (lane == 0) PROF(138 + h);
                }
                __syncwarp();
                if (elect()) {
                    *epoch_ptr = tag;
                    mbar_wait(base + BAR_RDY + h * 8, 0);
                    PROF(132 + h);
                    fence_async_smem();
#pragma unroll 1
                    for (int p = 0; p < 4; p++) {
                        if (p) pause(PACE_O);
                        tma_st2(&maps.m[M_OST], col, mt * 128 + h * 64 + p * 16, stg + p * WSLOT);
                    }
                    bulk_commit();
                    bulk_wait_all();
                    PROF(134 + h);
                    signal(CNT_O + mt);
                    mbar_arrive(base + BAR_FREE + h * 8);
                    PROF(136 + h);
                }
            }
        }
    } else {
        asm volatile("setmaxnreg.inc.sync.aligned.u32 224;");
        Ring r;
        r.wg = warp >> 2;
        r.slot = 0;
        r.phase = 0;
        r.prev = 0;
        r.zero = blockIdx.y;
        r.leader = lane == 0;
        const int wg = warp >> 2;
        const uint32_t wslot = base + STG + warp * WSLOT;
        const uint32_t row_addr = wslot + (lane & 15) * 224 + (((lane >> 4) ^ (lane >> 2)) & 1) * 16;

        if (!roleL) {
            const uint32_t blob_off = ((lane >> 4) * 8 + (lane & 7)) * 128 +
                                      (((2 * (warp & 3) + ((lane >> 3) & 1)) ^ (lane & 7)) << 4);
            float x0[56], x1[56];
            r.stage_kk<1, true, false>(x0);
#pragma unroll 1
            for (int i = 1; i < 7; i++) r.stage_kk<1, false>(x0);

            r.stage_kk<-1, true>(x1);
            acc_fence(x0);
            store_blob(x0, base + STG + wg * BLOB + blob_off);
            warp_arrive(base + BAR_RDY + wg * 8);
#pragma unroll 1
            for (int i = 1; i < 7; i++) r.stage_kk<-1, false>(x1);

            mbar_wait(base + BAR_RDY, 0);
            mbar_wait(base + BAR_RDY + 8, 0);
            fence_async_smem();
            r.stage_kk<1, true>(x0, 0);
            acc_fence(x1);
            mbar_wait(base + BAR_EMPTY + (4 + wg) * 8, 1);
            store_blob(x1, base + (4 + wg) * SLOT + BOFF + blob_off);
            warp_arrive(base + BAR_RDY + 16 + wg * 8);
            r.stage_kk<1, false>(x0, 1);
            mbar_wait(base + BAR_RDY + 16, 0);
            mbar_wait(base + BAR_RDY + 24, 0);
            fence_async_smem();
#pragma unroll 1
            for (int i = 16; i < POUT; i++) r.stage_kk<1, false>(x0, (i >> 1) == 11 ? (i & 1) : -1);

            r.stage_kn<true>(x1);
            acc_fence(x0);
            store_rows<false>(x0, row_addr);
            warp_arrive(base + BAR_RDY + 32 + wg * 8);
#pragma unroll 1
            for (int i = 1; i < 7; i++) r.stage_kn<false>(x1);

            mbar_wait(base + BAR_FREE + wg * 8, 0);
            asm volatile("wgmma.wait_group.sync.aligned 0;" ::: "memory");
            acc_fence(x1);
            store_rows<true>(x1, row_addr);
            fence_async_smem();
            __syncwarp();
            if (elect()) {
                tma_st2(&maps.m[M_OUTA], par * 896 + col, blk * 128 + warp * 16, wslot);
                bulk_commit();
                bulk_wait_read();
            }
        } else {
            const int g = lane >> 2, tig = lane & 3;
            float y0[56], y1[56], y2[56];
            r.stage_kv<true>(y0, y1);
#pragma unroll 1
            for (int i = 1; i < 14; i++) r.stage_kv<false>(y0, y1);

            uint32_t kl[14], kh[14], vl[14], vh[14];
            r.stage_kn<true>(y2);
            acc_fence(y0);
            acc_fence(y1);
#pragma unroll
            for (int c = 0; c < 14; c++) {
                const int j = hw_tile(c);
                kh[c] = pack2(y0[4 * j + 2], y0[4 * j + 3]);
                vh[c] = movm(pack2(y1[4 * j + 2], y1[4 * j + 3]));
            }
            r.stage_kn<false>(y2);
            r.pin();
            {
                const uint32_t pub = wslot + WSLOT + lane * 16;
                sts4(pub, kh[0], kh[1], kh[2], kh[3]);
                sts4(pub + 512, kh[4], kh[5], kh[6], kh[7]);
                sts4(pub + 1024, kh[8], kh[9], kh[10], kh[11]);
                sts4(pub + 1536, kh[12], kh[13], vh[0], vh[1]);
                sts4(pub + 2048, vh[2], vh[3], vh[4], vh[5]);
                sts4(pub + 2560, vh[6], vh[7], vh[8], vh[9]);
                sts4(pub + 3072, vh[10], vh[11], vh[12], vh[13]);
                warp_arrive(base + BAR_HALO);
                if (threadIdx.x == 224) mbar_arrive(base + BAR_PUB);
            }
            r.stage_kn<false>(y2);
            r.stage_kn<false>(y2);
            r.pin();
#pragma unroll
            for (int c = 0; c < 14; c++) {
                const int j = hw_tile(c);
                kl[c] = pack2(y0[4 * j], y0[4 * j + 1]);
                vl[c] = movm(pack2(y1[4 * j], y1[4 * j + 1]));
            }
#pragma unroll 1
            for (int i = 4; i < 7; i++) r.stage_kn<false>(y2);

            r.stage_kk<1, true>(y0);
            acc_fence(y2);
            uint32_t ql[14], qh[14], kp[14], vp[14];
            mbar_wait(base + BAR_HALO, 0);
            const uint32_t sub = wslot + lane * 16;
            lds4(sub, kp[0], kp[1], kp[2], kp[3]);
            lds4(sub + 512, kp[4], kp[5], kp[6], kp[7]);
            lds4(sub + 1024, kp[8], kp[9], kp[10], kp[11]);
            lds4(sub + 1536, kp[12], kp[13], vp[0], vp[1]);
#pragma unroll
            for (int c = 0; c < 14; c++) {
                const int j = hw_tile(c);
                ql[c] = pack2(y2[4 * j], y2[4 * j + 1]);
                qh[c] = pack2(y2[4 * j + 2], y2[4 * j + 3]);
            }
            float s[8][4];
#pragma unroll
            for (int step = 0; step < 2; step++) {
#pragma unroll
                for (int i = 0; i < 8; i++) {
                    const int b = 1 - (i >> 2), h = i & 3;
                    const int c0 = 7 * (h >> 1) + 3 * (h & 1) + 2 * step;
                    const uint32_t* q = b ? qh : ql;
                    const uint32_t* kprev = b ? kl : kp;
                    const uint32_t* kcur = b ? kh : kl;
                    uint32_t q0 = q[c0], q1 = q[c0 + 1];
                    if ((h & 1) && step == 0) q0 = tig >= 2 ? q0 : 0u;
                    if (!(h & 1) && step == 1) q1 = tig < 2 ? q1 : 0u;
                    float (&d)[4] = s[2 * h + b];
                    if (step == 0) d[0] = d[1] = d[2] = d[3] = 0.f;
                    mma16816(d, kprev[c0], kcur[c0], kprev[c0 + 1], kcur[c0 + 1], q0, q1);
                }
            }
            r.stage_kk<1, false>(y0);
            r.pin();

            const uint32_t curmask = (2 * tig <= g ? 0x0000FFFFu : 0u) | (2 * tig + 1 <= g ? 0xFFFF0000u : 0u);
            uint32_t pr[8], mx[4];
            {
                const bool cur0 = g <= 2 * tig, cur1 = g <= 2 * tig + 1;
                const uint32_t keep = (blk == 0 && warp == 0) ? curmask : 0xFFFFFFFFu;
#pragma unroll
                for (int i = 0; i < 8; i++) pr[i] = movm(pack2(cur0 ? s[i][2] : s[i][0], cur1 ? s[i][3] : s[i][1]));
#pragma unroll
                for (int i = 0; i < 8; i++) {
                    pr[i] = pack2(bf_lo(pr[i]) * 0.18898223650461362f, bf_hi(pr[i]) * 0.18898223650461362f);
                    if ((i & 1) == 0) pr[i] = (pr[i] & keep) | (0xCE6ECE6Eu & ~keep);
                }
            }
            r.stage_kk<1, false>(y0);
            r.pin();
            float e0[8], e1[8];
#pragma unroll
            for (int i = 0; i < 4; i++) mx[i] = max2(__byte_perm(pr[2 * i], pr[2 * i + 1], 0x5410), __byte_perm(pr[2 * i], pr[2 * i + 1], 0x7632));
#pragma unroll
            for (int i = 0; i < 4; i++) mx[i] = max2(mx[i], __shfl_xor_sync(0xffffffffu, mx[i], 1));
#pragma unroll
            for (int i = 0; i < 4; i++) mx[i] = max2(mx[i], __shfl_xor_sync(0xffffffffu, mx[i], 2));
#pragma unroll
            for (int i = 0; i < 8; i++) {
                const float m = (i & 1) ? bf_hi(mx[i >> 1]) : bf_lo(mx[i >> 1]);
                e0[i] = bf_lo(pr[i]) - m;
                e1[i] = bf_hi(pr[i]) - m;
            }
            r.stage_kk<1, false>(y0);
            r.pin();
            float sm[8];
#pragma unroll
            for (int i = 0; i < 8; i++) {
                e0[i] = ex2(e0[i] * 1.4426950408889634f);
                e1[i] = ex2(e1[i] * 1.4426950408889634f);
                sm[i] = e0[i] + e1[i];
            }
#pragma unroll
            for (int i = 0; i < 8; i++) sm[i] += __shfl_xor_sync(0xffffffffu, sm[i], 1);
            r.stage_kk<1, false>(y0);
            r.pin();
#pragma unroll
            for (int i = 0; i < 8; i++) sm[i] += __shfl_xor_sync(0xffffffffu, sm[i], 2);
#pragma unroll
            for (int i = 0; i < 8; i++) {
                const float inv = rcp(sm[i]);
                pr[i] = pack2(e0[i] * inv, e1[i] * inv);
            }
            r.stage_kk<1, false>(y0);
            r.pin();
            lds4(sub + 2048, vp[2], vp[3], vp[4], vp[5]);
            lds4(sub + 2560, vp[6], vp[7], vp[8], vp[9]);
            lds4(sub + 3072, vp[10], vp[11], vp[12], vp[13]);
            float o[16][4];
#pragma unroll
            for (int ii = 0; ii < 16; ii++) {
                const int b = 1 - (ii >> 3), h = (ii >> 1) & 3, i = 4 * h + 2 * b + (ii & 1);
                const int c0 = 7 * (h >> 1) + 3 * (h & 1) + 2 * (i & 1);
                const uint32_t* vprev = b ? vl : vp;
                const uint32_t* vcur = b ? vh : vl;
                const uint32_t p = pr[2 * h + b];
                o[i][0] = o[i][1] = o[i][2] = o[i][3] = 0.f;
                mma16816(o[i], vprev[c0], vprev[c0 + 1], vcur[c0], vcur[c0 + 1], p & ~curmask, p & curmask);
            }
            r.stage_kk<1, false>(y0);
            r.pin();
            {
                uint32_t ot[2][14];
#pragma unroll
                for (int hp = 0; hp < 2; hp++) {
#pragma unroll
                    for (int b = 0; b < 2; b++) {
                        const int e = 8 * hp + 2 * b, d = e + 4, cb = 7 * hp;
                        ot[b][cb] = pack2(o[e][0], o[e][1]);
                        ot[b][cb + 1] = pack2(o[e][2], o[e][3]);
                        ot[b][cb + 2] = pack2(o[e + 1][0], o[e + 1][1]);
                        ot[b][cb + 3] = pack2(g < 4 ? o[e + 1][2] : o[d][0], g < 4 ? o[e + 1][3] : o[d][1]);
                        ot[b][cb + 4] = pack2(o[d][2], o[d][3]);
                        ot[b][cb + 5] = pack2(o[d + 1][0], o[d + 1][1]);
                        ot[b][cb + 6] = pack2(o[d + 1][2], o[d + 1][3]);
                    }
                }
#pragma unroll
                for (int c = 0; c < 14; c += 2)
                    store_pair<true>(row_addr + c * 16, tig >= 2, ot[0][c], ot[1][c], ot[0][c + 1], ot[1][c + 1]);
            }
            warp_arrive(base + BAR_RDY + wg * 8);

#pragma unroll 1
            for (int i = 7; i < 32 - E_EXTRA; i++) r.stage_kk<1, false>(y0);

            mbar_wait(base + BAR_FREE + wg * 8, 0);
            asm volatile("wgmma.wait_group.sync.aligned 0;" ::: "memory");
            acc_fence(y0);
            store_rows<false>(y0, row_addr);
            fence_async_smem();
            __syncwarp();
            if (elect()) {
                tma_red2(&maps.m[M_OUTB], 448 + col, mt * 128 + warp * 16, wslot);
                bulk_commit();
                bulk_wait_read();
            }
        }
    }
}

typedef CUresult (*EncodeFn)(CUtensorMap*, CUtensorMapDataType, cuuint32_t, void*, const cuuint64_t*, const cuuint64_t*,
                             const cuuint32_t*, const cuuint32_t*, CUtensorMapInterleave, CUtensorMapSwizzle,
                             CUtensorMapL2promotion, CUtensorMapFloatOOBfill);

void encode(EncodeFn fn, CUtensorMap* m, const void* ptr, int rank, uint64_t d0, uint64_t d1, uint64_t d2, uint64_t s1,
            uint64_t s2, uint32_t b0, uint32_t b1, uint32_t b2, CUtensorMapSwizzle sw) {
    const cuuint64_t dims[3] = {d0, d1, d2};
    const cuuint64_t strides[2] = {s1, s2};
    const cuuint32_t box[3] = {b0, b1, b2};
    const cuuint32_t es[3] = {1, 1, 1};
    fn(m, CU_TENSOR_MAP_DATA_TYPE_BFLOAT16, rank, const_cast<void*>(ptr), dims, strides, box, es,
       CU_TENSOR_MAP_INTERLEAVE_NONE, sw, CU_TENSOR_MAP_L2_PROMOTION_L2_128B, CU_TENSOR_MAP_FLOAT_OOB_FILL_NONE);
}

}

extern "C" void kernel_launch(void* const* d_in, const int* in_sizes, int n_in, void* d_out, int out_size) {
    (void)in_sizes; (void)n_in; (void)out_size;
    void* fnp = nullptr;
    cudaDriverEntryPointQueryResult st;
    cudaGetDriverEntryPoint("cuTensorMapEncodeTiled", &fnp, cudaEnableDefault, &st);
    EncodeFn fn = (EncodeFn)fnp;
    void* o_ptr = nullptr;
    cudaGetSymbolAddress(&o_ptr, g_o);
    cudaFuncSetAttribute(fused_kernel, cudaFuncAttributeMaxDynamicSharedMemorySize, SMEM_BYTES);

    const CUtensorMapSwizzle S128 = CU_TENSOR_MAP_SWIZZLE_128B, S64 = CU_TENSOR_MAP_SWIZZLE_64B, S0 = CU_TENSOR_MAP_SWIZZLE_NONE;
    Maps maps;
    encode(fn, &maps.m[M_XA32], d_in[0], 2, 896, 1024, 1, 1792, 0, 32, 128, 1, S64);
    encode(fn, &maps.m[M_XA64], d_in[0], 2, 896, 1024, 1, 1792, 0, 64, 128, 1, S128);
    encode(fn, &maps.m[M_WKV], d_in[1], 3, 448, 448, 3, 2688, 896, 64, 32, 2, S128);
    encode(fn, &maps.m[M_WQ], d_in[1], 2, 448, 448, 1, 2688, 0, 64, 64, 1, S128);
    encode(fn, &maps.m[M_WO], d_in[2], 2, 448, 448, 1, 896, 0, 64, 64, 1, S128);
    encode(fn, &maps.m[M_XB], d_in[3], 3, 448, 1024, 2, 896, 896 * 1024, 64, 64, 2, S128);
    encode(fn, &maps.m[M_CR], d_in[4], 2, 2048, 2048, 1, 4096, 0, 64, 128, 1, S128);
    encode(fn, &maps.m[M_CI], d_in[5], 2, 2048, 2048, 1, 4096, 0, 64, 128, 1, S128);
    encode(fn, &maps.m[M_WR], d_in[6], 2, 448, 448, 1, 896, 0, 64, 112, 1, S128);
    encode(fn, &maps.m[M_WI], d_in[7], 2, 448, 448, 1, 896, 0, 64, 112, 1, S128);
    encode(fn, &maps.m[M_OST], o_ptr, 2, 448, 2048, 1, 896, 0, 112, 16, 1, S0);
    encode(fn, &maps.m[M_OLD], o_ptr, 2, 448, 2048, 1, 896, 0, 64, 128, 1, S128);
    encode(fn, &maps.m[M_OUTA], d_out, 2, 1792, 1024, 1, 3584, 0, 112, 16, 1, S0);
    encode(fn, &maps.m[M_OUTB], d_out, 2, 896, 2048, 1, 1792, 0, 112, 16, 1, S0);

    maps.xa = (const uint8_t*)d_in[0];
    maps.wqkv = (const uint8_t*)d_in[1];
    maps.wo = (const uint8_t*)d_in[2];
    maps.wi = (const uint8_t*)d_in[7];
    maps.out = (uint8_t*)d_out;

    fused_kernel<<<128, 384, SMEM_BYTES>>>(maps);
}
```

```cpp
#include <cuda.h>
#include <cuda_bf16.h>
#include <cuda_runtime.h>
#include <stdint.h>

namespace {

constexpr int NA = 7;
constexpr int NB = 5;
constexpr uint32_t SLOT = 16384;
constexpr uint32_t BRING = NA * SLOT;
constexpr uint32_t STG = BRING + NB * SLOT;
constexpr uint32_t WSLOT = 3584;
constexpr uint32_t BLOB = 14336;
constexpr uint32_t BARS = STG + 9 * WSLOT;
constexpr uint32_t BAR_FULL = BARS;
constexpr uint32_t BAR_EMPTY = BARS + 64;
constexpr uint32_t BAR_HALO = BARS + 128;
constexpr uint32_t BAR_PUB = BARS + 136;
constexpr uint32_t BAR_OUT = BARS + 144;
constexpr uint32_t BAR_FREE = BARS + 160;
constexpr uint32_t BAR_RDY = BARS + 176;
constexpr uint32_t SMEM_BYTES = BARS + 256 + 1024;
constexpr uint32_t base = 1024;
constexpr int SPIN_LIMIT = 1 << 16;

#define E_EXTRA 0
#define AHI_DELAY 300
#define PACE_B 420
#define PACE_O 400
#define HALO_DELAY 400
#define MAPPING 0
#define SPARE0 0
constexpr int NBE = 13 + E_EXTRA;
constexpr int POUT = 33 + NBE;

enum { M_XA, M_WKV, M_WQ, M_WO, M_XB, M_WR, M_WI, M_CR, M_CI, M_OST, M_OLD, M_OUTA, M_OUTB, M_COUNT };
struct __align__(64) Maps {
    CUtensorMap m[M_COUNT];
    uint8_t* out;
};

constexpr int CNT_A = 0;
constexpr int CNT_B = 8;
constexpr int CNT_O = 16;
constexpr int CNT_COUNT = 32;

__device__ __align__(1024) uint8_t g_ab[2 * 32 * 4 * BLOB];
__device__ __align__(1024) __nv_bfloat16 g_o[2048 * 448];
__device__ __align__(1024) uint8_t g_halo[64 * 2 * WSLOT];
__device__ __align__(128) unsigned g_cnt[CNT_COUNT * 32];
__device__ __align__(128) unsigned g_epoch[128 * 4 * 8];

__device__ __forceinline__ unsigned clk32() { unsigned c; asm volatile("mov.u32 %0, %%clock;" : "=r"(c)); return c; }
__device__ __forceinline__ void pause_until(unsigned t0, unsigned cycles) {
    while (clk32() - t0 < cycles) {}
}

#define PROF(idx)

__device__ __forceinline__ void mbar_init(uint32_t bar, uint32_t cnt) {
    asm volatile("mbarrier.init.shared::cta.b64 [%0], %1;" ::"r"(bar), "r"(cnt) : "memory");
}
__device__ __forceinline__ void mbar_expect(uint32_t bar, uint32_t bytes) {
    asm volatile("mbarrier.arrive.expect_tx.shared::cta.b64 _, [%0], %1;" ::"r"(bar), "r"(bytes) : "memory");
}
__device__ __forceinline__ void mbar_arrive(uint32_t bar) {
    asm volatile("mbarrier.arrive.shared::cta.b64 _, [%0];" ::"r"(bar) : "memory");
}
__device__ __forceinline__ bool mbar_try(uint32_t bar, uint32_t parity) {
    uint32_t ok;
    asm volatile("{\n.reg .pred p;\nmbarrier.try_wait.parity.shared::cta.b64 p, [%1], %2;\nselp.u32 %0, 1, 0, p;\n}\n"
                 : "=r"(ok) : "r"(bar), "r"(parity) : "memory");
    return ok;
}
__device__ __forceinline__ void mbar_wait(uint32_t bar, uint32_t parity) {
#pragma unroll 1
    for (int n = 0; n < SPIN_LIMIT; n++)
        if (mbar_try(bar, parity)) break;
}
__device__ __forceinline__ bool elect() {
    uint32_t p;
    asm volatile("{\n.reg .pred p;\nelect.sync _|p, 0xffffffff;\nselp.u32 %0, 1, 0, p;\n}\n" : "=r"(p));
    return p;
}
__device__ __forceinline__ void nb_sync(int id, int n) { asm volatile("bar.sync %0, %1;" ::"r"(id), "r"(n) : "memory"); }
__device__ __forceinline__ void warp_arrive(uint32_t bar) {
    __syncwarp();
    if ((threadIdx.x & 31) == 0) mbar_arrive(bar);
}

__device__ __forceinline__ void tma_ld2(uint32_t dst, const CUtensorMap* m, int c0, int c1, uint32_t bar) {
    asm volatile("cp.async.bulk.tensor.2d.shared::cluster.global.mbarrier::complete_tx::bytes [%0], [%1, {%3, %4}], [%2];"
                 ::"r"(dst), "l"(m), "r"(bar), "r"(c0), "r"(c1) : "memory");
}
__device__ __forceinline__ void tma_ld3(uint32_t dst, const CUtensorMap* m, int c0, int c1, int c2, uint32_t bar) {
    asm volatile("cp.async.bulk.tensor.3d.shared::cluster.global.mbarrier::complete_tx::bytes [%0], [%1, {%3, %4, %5}], [%2];"
                 ::"r"(dst), "l"(m), "r"(bar), "r"(c0), "r"(c1), "r"(c2) : "memory");
}
__device__ __forceinline__ void tma_ld4(uint32_t dst, const CUtensorMap* m, int c0, int c1, int c2, int c3, uint32_t bar) {
    asm volatile("cp.async.bulk.tensor.4d.shared::cluster.global.mbarrier::complete_tx::bytes [%0], [%1, {%3, %4, %5, %6}], [%2];"
                 ::"r"(dst), "l"(m), "r"(bar), "r"(c0), "r"(c1), "r"(c2), "r"(c3) : "memory");
}
__device__ __forceinline__ void bulk_ld(uint32_t dst, const void* src, uint32_t bytes, uint32_t bar) {
    asm volatile("cp.async.bulk.shared::cluster.global.mbarrier::complete_tx::bytes [%0], [%1], %2, [%3];"
                 ::"r"(dst), "l"(src), "r"(bytes), "r"(bar) : "memory");
}
__device__ __forceinline__ void bulk_st(void* dst, uint32_t src, uint32_t bytes) {
    asm volatile("cp.async.bulk.global.shared::cta.bulk_group [%0], [%1], %2;" ::"l"(dst), "r"(src), "r"(bytes) : "memory");
}
__device__ __forceinline__ void tma_st2(const CUtensorMap* m, int c0, int c1, uint32_t src) {
    asm volatile("cp.async.bulk.tensor.2d.global.shared::cta.bulk_group [%0, {%1, %2}], [%3];"
                 ::"l"(m), "r"(c0), "r"(c1), "r"(src) : "memory");
}
__device__ __forceinline__ void tma_red2(const CUtensorMap* m, int c0, int c1, uint32_t src) {
    asm volatile("cp.reduce.async.bulk.tensor.2d.global.shared::cta.add.bulk_group [%0, {%1, %2}], [%3];"
                 ::"l"(m), "r"(c0), "r"(c1), "r"(src) : "memory");
}
__device__ __forceinline__ void bulk_commit() { asm volatile("cp.async.bulk.commit_group;" ::: "memory"); }
__device__ __forceinline__ void bulk_wait_all() { asm volatile("cp.async.bulk.wait_group 0;" ::: "memory"); }
__device__ __forceinline__ void bulk_wait_read() { asm volatile("cp.async.bulk.wait_group.read 0;" ::: "memory"); }
__device__ __forceinline__ void fence_async_smem() { asm volatile("fence.proxy.async.shared::cta;" ::: "memory"); }
__device__ __forceinline__ void fence_async_global() { asm volatile("fence.proxy.async.global;" ::: "memory"); }

__device__ __forceinline__ void signal(int idx) {
    fence_async_global();
    asm volatile("red.release.gpu.global.add.u32 [%0], 1;" ::"l"(&g_cnt[idx * 32]) : "memory");
}
__device__ __forceinline__ unsigned peek(int idx) {
    unsigned v;
    asm volatile("ld.relaxed.gpu.global.u32 %0, [%1];" : "=r"(v) : "l"(&g_cnt[idx * 32]) : "memory");
    return v;
}
__device__ __forceinline__ void await(int idx, unsigned target, unsigned v) {
#pragma unroll 1
    for (int n = 0; n < SPIN_LIMIT && (int)(v - target) < 0; n++) v = peek(idx);
    asm volatile("fence.acquire.gpu;" ::: "memory");
    fence_async_global();
}

#define WG_REGS                                                                                                     \
    "{%0,%1,%2,%3,%4,%5,%6,%7,%8,%9,%10,%11,%12,%13,%14,%15,%16,%17,%18,%19,%20,%21,%22,%23,%24,%25,%26,%27,"       \
    "%28,%29,%30,%31,%32,%33,%34,%35,%36,%37,%38,%39,%40,%41,%42,%43,%44,%45,%46,%47,%48,%49,%50,%51,%52,%53,%54,%55}"
#define WG_OPS(C)                                                                                                   \
    C(d[0]), C(d[1]), C(d[2]), C(d[3]), C(d[4]), C(d[5]), C(d[6]), C(d[7]), C(d[8]), C(d[9]), C(d[10]), C(d[11]),   \
    C(d[12]), C(d[13]), C(d[14]), C(d[15]), C(d[16]), C(d[17]), C(d[18]), C(d[19]), C(d[20]), C(d[21]), C(d[22]),   \
    C(d[23]), C(d[24]), C(d[25]), C(d[26]), C(d[27]), C(d[28]), C(d[29]), C(d[30]), C(d[31]), C(d[32]), C(d[33]),   \
    C(d[34]), C(d[35]), C(d[36]), C(d[37]), C(d[38]), C(d[39]), C(d[40]), C(d[41]), C(d[42]), C(d[43]), C(d[44]),   \
    C(d[45]), C(d[46]), C(d[47]), C(d[48]), C(d[49]), C(d[50]), C(d[51]), C(d[52]), C(d[53]), C(d[54]), C(d[55])

template <int TB, int SB, bool INIT>
__device__ __forceinline__ void wgmma112(float (&d)[56], uint64_t da, uint64_t db) {
    if (INIT) {
        asm volatile("{\n.reg .pred p;\nsetp.ne.b32 p, 0, 0;\n"
                     "wgmma.mma_async.sync.aligned.m64n112k16.f32.bf16.bf16 " WG_REGS ", %56, %57, p, 1, %59, 0, %58;\n}\n"
                     : WG_OPS("=f") : "l"(da), "l"(db), "n"(TB), "n"(SB));
    } else {
        asm volatile("{\n.reg .pred p;\nsetp.ne.b32 p, 1, 0;\n"
                     "wgmma.mma_async.sync.aligned.m64n112k16.f32.bf16.bf16 " WG_REGS ", %56, %57, p, 1, %59, 0, %58;\n}\n"
                     : WG_OPS("+f") : "l"(da), "l"(db), "n"(TB), "n"(SB));
    }
}
__device__ __forceinline__ void acc_fence(float (&d)[56]) {
#pragma unroll
    for (int i = 0; i < 56; i++) asm volatile("" : "+f"(d[i])::"memory");
}

__device__ __forceinline__ uint32_t pack2(float lo, float hi) {
    uint32_t r;
    asm volatile("cvt.rn.bf16x2.f32 %0, %1, %2;" : "=r"(r) : "f"(hi), "f"(lo));
    return r;
}
__device__ __forceinline__ uint32_t movm(uint32_t a) {
    uint32_t r;
    asm volatile("movmatrix.sync.aligned.m8n8.trans.b16 %0, %1;" : "=r"(r) : "r"(a));
    return r;
}
template <bool TRANS>
__device__ __forceinline__ void stsm4(uint32_t addr, uint32_t a, uint32_t b, uint32_t c, uint32_t d) {
    if (TRANS) asm volatile("stmatrix.sync.aligned.m8n8.x4.trans.shared.b16 [%0], {%1,%2,%3,%4};" ::"r"(addr), "r"(a), "r"(b), "r"(c), "r"(d) : "memory");
    else asm volatile("stmatrix.sync.aligned.m8n8.x4.shared.b16 [%0], {%1,%2,%3,%4};" ::"r"(addr), "r"(a), "r"(b), "r"(c), "r"(d) : "memory");
}
__device__ __forceinline__ void sts4(uint32_t addr, uint32_t a, uint32_t b, uint32_t c, uint32_t d) {
    asm volatile("st.shared.v4.b32 [%0], {%1,%2,%3,%4};" ::"r"(addr), "r"(a), "r"(b), "r"(c), "r"(d) : "memory");
}
__device__ __forceinline__ void lds4(uint32_t addr, uint32_t& a, uint32_t& b, uint32_t& c, uint32_t& d) {
    asm volatile("ld.shared.v4.b32 {%0,%1,%2,%3}, [%4];" : "=r"(a), "=r"(b), "=r"(c), "=r"(d) : "r"(addr) : "memory");
}
__device__ __forceinline__ void mma16816(float (&d)[4], uint32_t a0, uint32_t a1, uint32_t a2, uint32_t a3, uint32_t b0, uint32_t b1) {
    asm volatile("mma.sync.aligned.m16n8k16.row.col.f32.bf16.bf16.f32 {%0,%1,%2,%3}, {%4,%5,%6,%7}, {%8,%9}, {%0,%1,%2,%3};"
                 : "+f"(d[0]), "+f"(d[1]), "+f"(d[2]), "+f"(d[3]) : "r"(a0), "r"(a1), "r"(a2), "r"(a3), "r"(b0), "r"(b1));
}
__device__ __forceinline__ uint32_t max2(uint32_t a, uint32_t b) {
    uint32_t r;
    asm("max.bf16x2 %0, %1, %2;" : "=r"(r) : "r"(a), "r"(b));
    return r;
}
__device__ __forceinline__ void st_tagged(uint8_t* p, uint32_t a, uint32_t b, uint32_t tag) {
    asm volatile("{\n.reg .b64 x, y;\nmov.b64 x, {%1, %3};\nmov.b64 y, {%2, %3};\nst.relaxed.gpu.global.v2.b64 [%0], {x, y};\n}\n"
                 ::"l"(p), "r"(a), "r"(b), "r"(tag) : "memory");
}
__device__ __forceinline__ void ld_tagged(const uint8_t* p, uint32_t& a, uint32_t& ta, uint32_t& b, uint32_t& tb) {
    asm volatile("{\n.reg .b64 x, y;\nld.relaxed.gpu.global.v2.b64 {x, y}, [%4];\nmov.b64 {%0, %1}, x;\nmov.b64 {%2, %3}, y;\n}\n"
                 : "=r"(a), "=r"(ta), "=r"(b), "=r"(tb) : "l"(p) : "memory");
}
__device__ __forceinline__ float bf_lo(uint32_t v) { return __uint_as_float(v << 16); }
__device__ __forceinline__ float bf_hi(uint32_t v) { return __uint_as_float(v & 0xFFFF0000u); }
__device__ __forceinline__ float rcp(float x) { float r; asm("rcp.approx.ftz.f32 %0, %1;" : "=f"(r) : "f"(x)); return r; }
__device__ __forceinline__ float ex2(float x) { float r; asm volatile("ex2.approx.ftz.f32 %0, %1;" : "=f"(r) : "f"(x)); return r; }

__device__ __forceinline__ uint32_t full_bar(int stage) { return base + BAR_FULL + (stage & 7) * 8; }
__device__ __forceinline__ void wait_released(int j) { mbar_wait(base + BAR_EMPTY + (j & 7) * 8, (j >> 3) & 1); }

template <int N, uint32_t OFF>
struct Feed {
    int stage;
    uint32_t dst;
    __device__ __forceinline__ void seek(int i) { stage = i; dst = base + OFF + (i % N) * SLOT; }
    __device__ __forceinline__ uint32_t acquire() { wait_released(stage - N); return full_bar(stage); }
    __device__ __forceinline__ void next() {
        stage++;
        dst += SLOT;
        if (dst == base + OFF + N * SLOT) dst = base + OFF;
    }
};
__device__ __forceinline__ int skip_own(int n, int mt) { return n == mt ? 15 : n; }

constexpr uint64_t DESC_HI = (uint64_t)(64u | (1u << 30)) << 32;
constexpr uint32_t LBO_K = 1u << 16, LBO_N = 512u << 16;

struct Ring {
    int stage;
    uint32_t a, b;
    uint32_t awg;
    uint32_t zero;
    bool leader;
    __device__ __forceinline__ void seek(int i) {
        stage = i;
        a = (base + (i % NA) * SLOT) >> 4;
        b = (base + BRING + (i % NB) * SLOT) >> 4;
    }
    __device__ __forceinline__ void wait() {
        mbar_wait(full_bar(stage), (stage >> 3) & 1);
    }
    template <bool RELEASE>
    __device__ __forceinline__ void end() {
        asm volatile("wgmma.commit_group.sync.aligned;" ::: "memory");
        asm volatile("wgmma.wait_group.sync.aligned 1;" ::: "memory");
        if (RELEASE && leader) mbar_arrive(base + BAR_EMPTY + ((stage - 1) & 7) * 8);
        stage++;
        a += SLOT >> 4;
        if (a == (base + NA * SLOT) >> 4) a = base >> 4;
        b += SLOT >> 4;
        if (b == (base + BRING + NB * SLOT) >> 4) b = (base + BRING) >> 4;
    }
    __device__ __forceinline__ void pin() {
#pragma unroll 1
        for (uint32_t n = 0; n < zero; n++) asm volatile("nanosleep.u32 0;" ::: "memory");
    }
    template <int SB, bool INIT, bool RELEASE = true, bool WAIT = true>
    __device__ __forceinline__ void stage_kk(float (&d)[56], int stg = -1) {
        if (WAIT) wait();
        asm volatile("wgmma.fence.sync.aligned;" ::: "memory");
        const uint32_t sb = stg >= 0 ? (base + STG + stg * BLOB) >> 4 : b;
        const uint64_t da = DESC_HI | (a + awg + LBO_K), db = DESC_HI | (sb + LBO_K);
        wgmma112<0, SB, INIT>(d, da, db);
        wgmma112<0, SB, false>(d, da + 2, db + 2);
        wgmma112<0, SB, false>(d, da + 4, db + 4);
        wgmma112<0, SB, false>(d, da + 6, db + 6);
        end<RELEASE>();
    }
    template <bool INIT>
    __device__ __forceinline__ void stage_kn(float (&d)[56]) {
        wait();
        asm volatile("wgmma.fence.sync.aligned;" ::: "memory");
        const uint64_t da = DESC_HI | (a + awg + LBO_K), db = DESC_HI | (b + LBO_N);
        wgmma112<1, 1, INIT>(d, da, db);
        wgmma112<1, 1, false>(d, da + 2, db + 128);
        wgmma112<1, 1, false>(d, da + 4, db + 256);
        wgmma112<1, 1, false>(d, da + 6, db + 384);
        end<true>();
    }
    template <bool INIT>
    __device__ __forceinline__ void stage_kv(float (&dk)[56], float (&dv)[56]) {
        wait();
        asm volatile("wgmma.fence.sync.aligned;" ::: "memory");
        const uint32_t ax = (base >> 4) + (stage >> 1) * (SLOT >> 4) + (stage & 1) * 4;
        const uint64_t da = DESC_HI | (ax + awg + LBO_K), db = DESC_HI | (b + LBO_N);
        wgmma112<1, 1, INIT>(dk, da, db);
        wgmma112<1, 1, INIT>(dv, da, db + 256);
        wgmma112<1, 1, false>(dk, da + 2, db + 128);
        wgmma112<1, 1, false>(dv, da + 2, db + 384);
        end<!INIT>();
    }
};

template <bool TRANS>
__device__ __forceinline__ void store_pair(uint32_t addr, bool swap, uint32_t lo0, uint32_t hi0, uint32_t lo1, uint32_t hi1) {
    stsm4<TRANS>(addr, swap ? lo1 : lo0, swap ? hi1 : hi0, swap ? lo0 : lo1, swap ? hi0 : hi1);
}
__device__ __forceinline__ void store_rows(const float (&d)[56], uint32_t lane_addr) {
    const bool swap = threadIdx.x & 16;
#pragma unroll
    for (int j = 0; j < 14; j += 2) {
        store_pair<false>(lane_addr + j * 16, swap, pack2(d[4 * j], d[4 * j + 1]), pack2(d[4 * j + 2], d[4 * j + 3]),
                          pack2(d[4 * j + 4], d[4 * j + 5]), pack2(d[4 * j + 6], d[4 * j + 7]));
    }
}
__device__ __forceinline__ void store_blob(const float (&d)[56], uint32_t lane_addr) {
#pragma unroll
    for (int j = 0; j < 14; j += 2)
        stsm4<true>(lane_addr + j * 1024, pack2(d[4 * j], d[4 * j + 1]), pack2(d[4 * j + 2], d[4 * j + 3]),
                    pack2(d[4 * j + 4], d[4 * j + 5]), pack2(d[4 * j + 6], d[4 * j + 7]));
}

__global__ void __launch_bounds__(384, 1) fused_kernel(const __grid_constant__ Maps maps) {
    extern __shared__ uint8_t smem_raw[];
    if ((uint32_t)__cvta_generic_to_shared(smem_raw) != base) return;
    const int warp = __shfl_sync(0xffffffffu, threadIdx.x >> 5, 0);
    const int lane = threadIdx.x & 31;
    if (blockIdx.x - SPARE0 < 4u) {
        const int ns = blockIdx.x - SPARE0;
        if (threadIdx.x < 378) {
            const int r0 = threadIdx.x / 14;
            uint8_t* dst = maps.out + 896 + ns * 224 + (threadIdx.x - r0 * 14) * 16;
#pragma unroll 4
            for (int row = r0; row < 2048; row += 27) *reinterpret_cast<uint4*>(dst + (size_t)row * 1792) = make_uint4(0, 0, 0, 0);
        }
        __syncthreads();
        if (threadIdx.x < 17) {
            asm volatile("fence.acq_rel.gpu;" ::: "memory");
            const int idx = threadIdx.x < 16 ? CNT_O + threadIdx.x : CNT_B + ns * 2 + 1;
            asm volatile("red.relaxed.gpu.global.add.u32 [%0], 1;" ::"l"(&g_cnt[idx * 32]) : "memory");
        }
        return;
    }
    const int bid = blockIdx.x < SPARE0 ? blockIdx.x : blockIdx.x - 4;
    const int roleL = (bid >> 3) & 1;
    const int mt = ((bid >> 4) << 1) | ((bid >> 2) & 1);
    const int ns = bid & 3;
    const int par = mt >> 3, blk = mt & 7;

    if (warp == 8) {
        if (elect()) {
#pragma unroll
            for (int i = 0; i < 8; i++) mbar_init(base + BAR_FULL + i * 8, 2);
            asm volatile("fence.mbarrier_init.release.cluster;" ::: "memory");
        }
    } else if (warp == 9) {
        if (elect()) {
#pragma unroll
            for (int i = 0; i < 8; i++) mbar_init(base + BAR_EMPTY + i * 8, 8);
            asm volatile("fence.mbarrier_init.release.cluster;" ::: "memory");
        }
    } else if (warp == 10) {
        if (elect()) {
#pragma unroll
            for (int i = 0; i < 6; i++) mbar_init(base + BAR_RDY + i * 8, 4);
            asm volatile("fence.mbarrier_init.release.cluster;" ::: "memory");
        }
    } else if (warp == 11) {
        if (elect()) {
#pragma unroll
            for (int i = 0; i < 2; i++) {
                mbar_init(base + BAR_OUT + i * 8, 2);
                mbar_init(base + BAR_FREE + i * 8, 1);
            }
            mbar_init(base + BAR_HALO, 10);
            mbar_init(base + BAR_PUB, 1);
            asm volatile("fence.mbarrier_init.release.cluster;" ::: "memory");
        }
    }
    __syncthreads();

    const int col = ns * 112;
    if (warp == 8) {
        if (elect()) {
            if (roleL) {
#pragma unroll 1
                for (int i = 0; i < 4; i++) {
                    mbar_expect(full_bar(2 * i), SLOT);
                    tma_ld2(base + i * SLOT, &maps.m[M_XA], par * 448 + i * 64, blk * 128, full_bar(2 * i));
                }
            } else {
#pragma unroll 1
                for (int i = 0; i < NA; i++) {
                    mbar_expect(full_bar(i), SLOT);
                    tma_ld3(base + i * SLOT, &maps.m[M_XB], i * 64, mt * 64, 0, full_bar(i));
                }
            }
        }
    } else if (warp == 11) {
        if (elect()) {
#pragma unroll 1
            for (int i = 0; i < NB; i++) {
                const uint32_t dst = base + BRING + i * SLOT, bar = full_bar(i);
                mbar_expect(bar, roleL ? SLOT : BLOB);
                if (roleL) {
                    tma_ld4(dst, &maps.m[M_WKV], 0, i * 32, 1, ns, bar);
                    tma_ld4(dst + 8192, &maps.m[M_WKV], 64, i * 32, 1, ns, bar);
                    if (i & 1) mbar_arrive(bar);
                } else {
                    tma_ld2(dst, &maps.m[M_WR], i * 64, col, bar);
                }
            }
        }
    }

    if (warp >= 8) {
        asm volatile("setmaxnreg.dec.sync.aligned.u32 56;");
        unsigned* epoch_ptr = &g_epoch[(bid * 4 + (warp - 8)) * 8];
#define PROF_FEED_A
#define PROF_FEED_B
        if (warp == 8) {
            if (elect()) {
                Feed<NA, 0> f;
                const int row = mt * 128;
                auto c_run = [&](const CUtensorMap* m, int off, int n0, int n1) {
#pragma unroll 1
                    for (int n = n0; n < n1; n++) {
                        const uint32_t bar = f.acquire();
                        mbar_expect(bar, SLOT);
                        tma_ld2(f.dst, m, (off + skip_own(n, mt)) * 64, row, bar);
                        PROF_FEED_A;
                        f.next();
                    }
                };
                if (!roleL) {
                    const unsigned ep = *epoch_ptr;
                    f.seek(14);
#pragma unroll 1
                    for (int i = 0; i < 4; i++) {
                        const uint32_t bar = f.acquire();
                        mbar_expect(bar, SLOT);
                        tma_ld2(f.dst, &maps.m[M_CR + (i >> 1)], ((i & 1) * 16 + mt) * 64, row, bar);
                        mbar_arrive(bar);
                        PROF_FEED_A;
                        f.next();
                    }
                    c_run(&maps.m[M_CR], 0, 0, 15);
                    c_run(&maps.m[M_CI], 0, 0, NBE);
                    await(CNT_O + mt, (ep + 1) * 12, peek(CNT_O + mt));
                    PROF(146);
#pragma unroll 1
                    for (int i = 0; i < 7; i++) {
                        const uint32_t bar = f.acquire();
                        mbar_expect(bar, SLOT);
                        tma_ld2(f.dst, &maps.m[M_OLD], i * 64, row, bar);
                        PROF_FEED_A;
                        f.next();
                    }
                    *epoch_ptr = ep + 1;
                } else {
#pragma unroll 1
                    for (int i = 4; i < 7; i++) {
                        wait_released(2 * i - 8);
                        mbar_expect(full_bar(2 * i), SLOT);
                        tma_ld2(base + i * SLOT, &maps.m[M_XA], par * 448 + i * 64, blk * 128, full_bar(2 * i));
                    }
                    wait_released(7);
                    f.seek(21);
                    c_run(&maps.m[M_CR], 16, 0, 15);
                    c_run(&maps.m[M_CI], 16, 0, 15);
                    c_run(&maps.m[M_CI], 0, NBE, 15);
                }
            }
        } else if (warp == 11) {
            if (elect()) {
                Feed<NB, BRING> f;
                f.seek(NB);
                const unsigned ep = *epoch_ptr + 1;
                auto blob_run = [&](int quarter, int n0, int n1) {
                    const int cnt = CNT_A + (quarter >> 1) * 8 + ns * 2 + (quarter & 1);
                    const uint8_t* src = g_ab + (size_t)(quarter * 64 + ns) * BLOB;
                    await(cnt, ep * (quarter == 3 ? 17 : 16), peek(cnt));
                    PROF(150 + quarter);
#pragma unroll 1
                    for (int n = n0; n < n1; n++) {
                        const uint32_t bar = f.acquire();
                        uint32_t dst = f.dst;
                        if (quarter == 0) {
                            if (n == 3) mbar_wait(base + BAR_OUT, 0);
                            if (n == 3 || n == 4) dst = base + STG + (n - 3) * BLOB;
                            if (n == 8) mbar_wait(base + BAR_OUT + 8, 0);
                        }
                        mbar_expect(bar, BLOB);
                        bulk_ld(dst, src + skip_own(n, mt) * (4 * BLOB), BLOB, bar);
                        PROF_FEED_B;
                        f.next();
                    }
                };
                auto w_run = [&](const CUtensorMap* m, bool no_a) {
#pragma unroll 1
                    for (int i = 0; i < 7; i++) {
                        const uint32_t bar = f.acquire();
                        mbar_expect(bar, SLOT);
                        tma_ld3(f.dst, m, 0, i * 64, ns, bar);
                        tma_ld3(f.dst + 8192, m, 64, i * 64, ns, bar);
                        if (no_a) mbar_arrive(bar);
                        PROF_FEED_B;
                        f.next();
                    }
                };
                if (!roleL) {
#pragma unroll 1
                    for (int i = NB; i < 14; i++) {
                        const uint32_t bar = f.acquire();
                        mbar_expect(bar, BLOB);
                        tma_ld2(f.dst, &maps.m[i < 7 ? M_WR : M_WI], (i < 7 ? i : i - 7) * 64, col, bar);
                        if (i >= 7) mbar_arrive(bar);
                        PROF_FEED_B;
                        f.next();
                    }
                    f.seek(18);
                    blob_run(0, 0, 15);
                    blob_run(2, 0, NBE);
                    w_run(&maps.m[M_WO], false);
                } else {
#pragma unroll 1
                    for (int i = NB; i < 14; i++) {
                        const uint32_t bar = f.acquire();
                        mbar_expect(bar, SLOT);
                        tma_ld4(f.dst, &maps.m[M_WKV], 0, i * 32, 1, ns, bar);
                        tma_ld4(f.dst + 8192, &maps.m[M_WKV], 64, i * 32, 1, ns, bar);
                        if (i & 1) mbar_arrive(bar);
                        PROF_FEED_B;
                        f.next();
                    }
                    w_run(&maps.m[M_WQ], true);
                    blob_run(1, 0, 15);
                    blob_run(3, 0, 15);
                    if (NBE < 15) blob_run(2, NBE, 15);
                }
                *epoch_ptr = ep;
            }
        } else {
            const int h = warp - 9;
            const uint32_t stg = base + STG + h * BLOB;
            if (!roleL) {
                if (elect()) {
                    mbar_wait(base + BAR_RDY + h * 8, 0);
                    PROF(130 + h);
                    fence_async_smem();
                    if (h) pause_until(clk32(), AHI_DELAY);
                    bulk_st(g_ab + (size_t)((h * 16 + mt) * 4 + ns) * BLOB, stg, BLOB);
                    bulk_commit();
                    bulk_wait_all();
                    PROF(132 + h);
                    mbar_arrive(base + BAR_OUT);
                    signal(CNT_A + ns * 2 + h);
                    PROF(134 + h);

                    mbar_wait(base + BAR_RDY + 16 + h * 8, 0);
                    fence_async_smem();
                    PROF(136 + h);
                    const unsigned t0 = clk32();
#pragma unroll 1
                    for (int p = 0; p < 7; p++) {
                        pause_until(t0, p * PACE_B);
                        bulk_st(g_ab + (size_t)((32 + h * 16 + mt) * 4 + ns) * BLOB + p * 2048,
                                base + BRING + (1 + h) * SLOT + p * 2048, 2048);
                    }
                    bulk_commit();
                    bulk_wait_all();
                    mbar_arrive(base + BAR_OUT + 8);
                    signal(CNT_B + ns * 2 + h);
                    PROF(138 + h);

                    mbar_wait(base + BAR_RDY + 32 + h * 8, 0);
                    fence_async_smem();
                    wait_released(POUT + 1);
                    PROF(140 + h);
#pragma unroll 1
                    for (int p = 0; p < 4; p++)
                        tma_red2(&maps.m[M_OUTB], 448 + col, mt * 128 + h * 64 + p * 16, stg + p * WSLOT);
                    bulk_commit();
                    bulk_wait_read();
                    mbar_arrive(base + BAR_FREE + h * 8);
                    PROF(142 + h);
                }
            } else {
                const unsigned tag = *epoch_ptr + 1;
                mbar_wait(base + BAR_PUB, 0);
                {
                    const uint32_t goff = h * 4096 + lane * 16, soff = base + STG + h * 2048 + lane * 16;
                    uint32_t v[16], t[16];
                    if (blk < 7) {
                        uint8_t* dst = g_halo + (size_t)(mt * 4 + ns) * (2 * WSLOT) + goff;
#pragma unroll
                        for (int i = 0; i < 4; i++)
                            if (i < 3 || h == 0) lds4(soff + 8 * WSLOT + i * 512, v[4 * i], v[4 * i + 1], v[4 * i + 2], v[4 * i + 3]);
#pragma unroll
                        for (int i = 0; i < 8; i++)
                            if (i < 6 || h == 0) st_tagged(dst + i * 512, v[2 * i], v[2 * i + 1], tag);
                    }
                    if (lane == 0) PROF(140 + h);
#pragma unroll
                    for (int i = 0; i < 16; i++) { v[i] = 0; t[i] = tag; }
                    if (blk > 0) {
                        const uint8_t* src = g_halo + (size_t)((mt - 1) * 4 + ns) * (2 * WSLOT) + goff;
                        pause_until(clk32(), HALO_DELAY);
#pragma unroll 1
                        for (int n = 0; n < SPIN_LIMIT; n++) {
                            bool ok = true;
#pragma unroll
                            for (int i = 0; i < 8; i++)
                                if (i < 6 || h == 0) ld_tagged(src + i * 512, v[2 * i], t[2 * i], v[2 * i + 1], t[2 * i + 1]);
#pragma unroll
                            for (int i = 0; i < 16; i++) ok = ok && t[i] == tag;
                            if (__all_sync(0xffffffffu, ok)) break;
                        }
                    }
#pragma unroll
                    for (int i = 0; i < 4; i++)
                        if (i < 3 || h == 0) sts4(soff + i * 512, v[4 * i], v[4 * i + 1], v[4 * i + 2], v[4 * i + 3]);
                    warp_arrive(base + BAR_HALO);
                    if (lane == 0) PROF(138 + h);
                }
                __syncwarp();
                if (elect()) {
                    *epoch_ptr = tag;
                    mbar_wait(base + BAR_RDY + h * 8, 0);
                    PROF(132 + h);
                    fence_async_smem();
                    const unsigned t0 = clk32();
#pragma unroll 1
                    for (int p = 0; p < 4; p++) {
                        pause_until(t0, (2 * p + h) * PACE_O);
                        tma_st2(&maps.m[M_OST], col, mt * 128 + h * 64 + p * 16, stg + p * WSLOT);
                    }
                    bulk_commit();
                    bulk_wait_all();
                    PROF(134 + h);
                    mbar_arrive(base + BAR_FREE + h * 8);
                    signal(CNT_O + mt);
                    PROF(136 + h);
                }
            }
        }
    } else {
        asm volatile("setmaxnreg.inc.sync.aligned.u32 224;");
        Ring r;
        r.seek(0);
        r.awg = (warp >> 2) * 512;
        r.zero = blockIdx.y;
        r.leader = lane == 0;
        const int wg = warp >> 2;
        const uint32_t wslot = base + STG + warp * WSLOT;
        const uint32_t row_addr = wslot + (lane & 15) * 224 + (((lane >> 4) ^ (lane >> 2)) & 1) * 16;

        if (!roleL) {
            const uint32_t blob_off = ((lane >> 4) * 8 + (lane & 7)) * 128 +
                                      (((2 * (warp & 3) + ((lane >> 3) & 1)) ^ (lane & 7)) << 4);
            float x0[56], x1[56];
            r.stage_kk<1, true, false>(x0);
#pragma unroll 1
            for (int i = 1; i < 7; i++) r.stage_kk<1, false>(x0);

            r.seek(7);
            r.stage_kk<-1, true>(x1);
            acc_fence(x0);
            store_blob(x0, base + STG + wg * BLOB + blob_off);
            warp_arrive(base + BAR_RDY + wg * 8);
#pragma unroll 1
            for (int i = 1; i < 7; i++) r.stage_kk<-1, false>(x1);

            mbar_wait(base + BAR_RDY, 0);
            mbar_wait(base + BAR_RDY + 8, 0);
            fence_async_smem();
            r.seek(14);
            r.stage_kk<1, true>(x0, 0);
            acc_fence(x1);
            wait_released(12);
            store_blob(x1, base + BRING + (1 + wg) * SLOT + blob_off);
            warp_arrive(base + BAR_RDY + 16 + wg * 8);
            r.stage_kk<1, false>(x0, 1);
            mbar_wait(base + BAR_RDY + 16, 0);
            mbar_wait(base + BAR_RDY + 24, 0);
            fence_async_smem();
#pragma unroll 1
            for (int i = 16; i < POUT; i++) r.stage_kk<1, false>(x0, (i == 21 || i == 22) ? i - 21 : -1);

            r.seek(POUT);
            r.stage_kn<true>(x1);
            acc_fence(x0);
            store_rows(x0, row_addr);
            warp_arrive(base + BAR_RDY + 32 + wg * 8);
#pragma unroll 1
            for (int i = 1; i < 7; i++) r.stage_kn<false>(x1);

            mbar_wait(base + BAR_FREE + wg * 8, 0);
            asm volatile("wgmma.wait_group.sync.aligned 0;" ::: "memory");
            acc_fence(x1);
            store_rows(x1, row_addr);
            fence_async_smem();
            __syncwarp();
            if (elect()) {
                tma_st2(&maps.m[M_OUTA], par * 896 + col, blk * 128 + warp * 16, wslot);
                bulk_commit();
                bulk_wait_read();
            }
        } else {
            const int g = lane >> 2, tig = lane & 3;
            float y0[56], y1[56], y2[56];
            r.stage_kv<true>(y0, y1);
#pragma unroll 1
            for (int i = 1; i < 14; i++) r.stage_kv<false>(y0, y1);

            uint32_t kl[14], kh[14], vl[14], vh[14];
            r.seek(14);
            r.stage_kn<true>(y2);
            acc_fence(y0);
            acc_fence(y1);
#pragma unroll
            for (int c = 0; c < 14; c++) {
                kl[c] = pack2(y0[4 * c], y0[4 * c + 1]);
                kh[c] = pack2(y0[4 * c + 2], y0[4 * c + 3]);
                vh[c] = movm(pack2(y1[4 * c + 2], y1[4 * c + 3]));
            }
            r.stage_kn<false>(y2);
            r.pin();
            {
                const uint32_t pub = wslot + WSLOT + lane * 16;
                sts4(pub, kh[0], kh[1], kh[2], kh[3]);
                sts4(pub + 512, kh[4], kh[5], kh[6], kh[7]);
                sts4(pub + 1024, kh[8], kh[9], kh[10], kh[11]);
                sts4(pub + 1536, kh[12], kh[13], vh[0], vh[1]);
                sts4(pub + 2048, vh[2], vh[3], vh[4], vh[5]);
                sts4(pub + 2560, vh[6], vh[7], vh[8], vh[9]);
                sts4(pub + 3072, vh[10], vh[11], vh[12], vh[13]);
                warp_arrive(base + BAR_HALO);
                if (threadIdx.x == 224) mbar_arrive(base + BAR_PUB);
            }
            r.stage_kn<false>(y2);
            r.stage_kn<false>(y2);
            r.pin();
#pragma unroll
            for (int c = 0; c < 14; c++) {
                vl[c] = movm(pack2(y1[4 * c], y1[4 * c + 1]));
            }
#pragma unroll 1
            for (int i = 4; i < 7; i++) r.stage_kn<false>(y2);

            r.seek(21);
            r.stage_kk<1, true>(y0);
            acc_fence(y2);
            uint32_t ql[14], qh[14], kp[14], vp[14];
            mbar_wait(base + BAR_HALO, 0);
            const uint32_t sub = wslot + lane * 16;
            lds4(sub, kp[0], kp[1], kp[2], kp[3]);
            lds4(sub + 512, kp[4], kp[5], kp[6], kp[7]);
            lds4(sub + 1024, kp[8], kp[9], kp[10], kp[11]);
            lds4(sub + 1536, kp[12], kp[13], vp[0], vp[1]);
#pragma unroll
            for (int c = 0; c < 14; c++) {
                ql[c] = pack2(y2[4 * c], y2[4 * c + 1]);
                qh[c] = pack2(y2[4 * c + 2], y2[4 * c + 3]);
            }
            r.wait();
            float s[8][4];
#pragma unroll
            for (int step = 0; step < 2; step++) {
#pragma unroll
                for (int i = 0; i < 8; i++) {
                    const int b = 1 - (i >> 2), h = i & 3;
                    const int c0 = 7 * (h >> 1) + 3 * (h & 1) + 2 * step;
                    const uint32_t* q = b ? qh : ql;
                    const uint32_t* kprev = b ? kl : kp;
                    const uint32_t* kcur = b ? kh : kl;
                    uint32_t q0 = q[c0], q1 = q[c0 + 1];
                    if ((h & 1) && step == 0) q0 = tig >= 2 ? q0 : 0u;
                    if (!(h & 1) && step == 1) q1 = tig < 2 ? q1 : 0u;
                    float (&d)[4] = s[2 * h + b];
                    if (step == 0) d[0] = d[1] = d[2] = d[3] = 0.f;
                    mma16816(d, kprev[c0], kcur[c0], kprev[c0 + 1], kcur[c0 + 1], q0, q1);
                }
            }
            r.pin();
            r.stage_kk<1, false, true, false>(y0);
            r.pin();

            const uint32_t curmask = (2 * tig <= g ? 0x0000FFFFu : 0u) | (2 * tig + 1 <= g ? 0xFFFF0000u : 0u);
            uint32_t pr[8], mx[4];
            {
                const bool cur0 = g <= 2 * tig, cur1 = g <= 2 * tig + 1;
                const uint32_t keep = (blk == 0 && warp == 0) ? curmask : 0xFFFFFFFFu;
#pragma unroll
                for (int i = 0; i < 8; i++) pr[i] = movm(pack2(cur0 ? s[i][2] : s[i][0], cur1 ? s[i][3] : s[i][1]));
#pragma unroll
                for (int i = 0; i < 8; i++) {
                    pr[i] = pack2(bf_lo(pr[i]) * 0.18898223650461362f, bf_hi(pr[i]) * 0.18898223650461362f);
                    if ((i & 1) == 0) pr[i] = (pr[i] & keep) | (0xCE6ECE6Eu & ~keep);
                }
            }
            r.stage_kk<1, false>(y0);
            r.pin();
            float e0[8], e1[8];
#pragma unroll
            for (int i = 0; i < 4; i++) mx[i] = max2(__byte_perm(pr[2 * i], pr[2 * i + 1], 0x5410), __byte_perm(pr[2 * i], pr[2 * i + 1], 0x7632));
#pragma unroll
            for (int i = 0; i < 4; i++) mx[i] = max2(mx[i], __shfl_xor_sync(0xffffffffu, mx[i], 1));
#pragma unroll
            for (int i = 0; i < 4; i++) mx[i] = max2(mx[i], __shfl_xor_sync(0xffffffffu, mx[i], 2));
#pragma unroll
            for (int i = 0; i < 8; i++) {
                const float m = (i & 1) ? bf_hi(mx[i >> 1]) : bf_lo(mx[i >> 1]);
                e0[i] = bf_lo(pr[i]) - m;
                e1[i] = bf_hi(pr[i]) - m;
            }
            r.stage_kk<1, false>(y0);
            r.pin();
            float sm[8];
#pragma unroll
            for (int i = 0; i < 8; i++) {
                e0[i] = ex2(e0[i] * 1.4426950408889634f);
                e1[i] = ex2(e1[i] * 1.4426950408889634f);
                sm[i] = e0[i] + e1[i];
            }
#pragma unroll
            for (int i = 0; i < 8; i++) sm[i] += __shfl_xor_sync(0xffffffffu, sm[i], 1);
            r.stage_kk<1, false>(y0);
            r.pin();
#pragma unroll
            for (int i = 0; i < 8; i++) sm[i] += __shfl_xor_sync(0xffffffffu, sm[i], 2);
#pragma unroll
            for (int i = 0; i < 8; i++) {
                const float inv = rcp(sm[i]);
                pr[i] = pack2(e0[i] * inv, e1[i] * inv);
            }
            r.stage_kk<1, false>(y0);
            r.pin();
            lds4(sub + 2048, vp[2], vp[3], vp[4], vp[5]);
            lds4(sub + 2560, vp[6], vp[7], vp[8], vp[9]);
            lds4(sub + 3072, vp[10], vp[11], vp[12], vp[13]);
            r.wait();
            float o[16][4];
#pragma unroll
            for (int ii = 0; ii < 16; ii++) {
                const int b = 1 - (ii >> 3), h = (ii >> 1) & 3, i = 4 * h + 2 * b + (ii & 1);
                const int c0 = 7 * (h >> 1) + 3 * (h & 1) + 2 * (i & 1);
                const uint32_t* vprev = b ? vl : vp;
                const uint32_t* vcur = b ? vh : vl;
                const uint32_t p = pr[2 * h + b];
                o[i][0] = o[i][1] = o[i][2] = o[i][3] = 0.f;
                mma16816(o[i], vprev[c0], vprev[c0 + 1], vcur[c0], vcur[c0 + 1], p & ~curmask, p & curmask);
            }
            r.pin();
            r.stage_kk<1, false, true, false>(y0);
            r.pin();
            {
                uint32_t ot[2][14];
#pragma unroll
                for (int hp = 0; hp < 2; hp++) {
#pragma unroll
                    for (int b = 0; b < 2; b++) {
                        const int e = 8 * hp + 2 * b, d = e + 4, cb = 7 * hp;
                        ot[b][cb] = pack2(o[e][0], o[e][1]);
                        ot[b][cb + 1] = pack2(o[e][2], o[e][3]);
                        ot[b][cb + 2] = pack2(o[e + 1][0], o[e + 1][1]);
                        ot[b][cb + 3] = pack2(g < 4 ? o[e + 1][2] : o[d][0], g < 4 ? o[e + 1][3] : o[d][1]);
                        ot[b][cb + 4] = pack2(o[d][2], o[d][3]);
                        ot[b][cb + 5] = pack2(o[d + 1][0], o[d + 1][1]);
                        ot[b][cb + 6] = pack2(o[d + 1][2], o[d + 1][3]);
                    }
                }
#pragma unroll
                for (int c = 0; c < 14; c += 2)
                    store_pair<true>(row_addr + c * 16, tig >= 2, ot[0][c], ot[1][c], ot[0][c + 1], ot[1][c + 1]);
            }
            warp_arrive(base + BAR_RDY + wg * 8);

#pragma unroll 1
            for (int i = 7; i < 32 - E_EXTRA; i++) r.stage_kk<1, false>(y0);

            mbar_wait(base + BAR_FREE + wg * 8, 0);
            asm volatile("wgmma.wait_group.sync.aligned 0;" ::: "memory");
            acc_fence(y0);
            store_rows(y0, row_addr);
            fence_async_smem();
            __syncwarp();
            if (elect()) {
                tma_red2(&maps.m[M_OUTB], 448 + col, mt * 128 + warp * 16, wslot);
                bulk_commit();
                bulk_wait_read();
            }
        }
    }
}

typedef CUresult (*EncodeFn)(CUtensorMap*, CUtensorMapDataType, cuuint32_t, void*, const cuuint64_t*, const cuuint64_t*,
                             const cuuint32_t*, const cuuint32_t*, CUtensorMapInterleave, CUtensorMapSwizzle,
                             CUtensorMapL2promotion, CUtensorMapFloatOOBfill);

struct Dim { uint64_t size, stride; uint32_t box; };
void encode(EncodeFn fn, CUtensorMap* m, const void* ptr, CUtensorMapSwizzle sw, Dim d0, Dim d1, Dim d2 = {0, 0, 0}, Dim d3 = {0, 0, 0}) {
    const cuuint64_t dims[4] = {d0.size, d1.size, d2.size, d3.size};
    const cuuint64_t strides[3] = {d1.stride, d2.stride, d3.stride};
    const cuuint32_t box[4] = {d0.box, d1.box, d2.box, d3.box};
    const cuuint32_t es[4] = {1, 1, 1, 1};
    fn(m, CU_TENSOR_MAP_DATA_TYPE_BFLOAT16, d3.size ? 4 : d2.size ? 3 : 2, const_cast<void*>(ptr), dims, strides, box, es,
       CU_TENSOR_MAP_INTERLEAVE_NONE, sw, CU_TENSOR_MAP_L2_PROMOTION_L2_128B, CU_TENSOR_MAP_FLOAT_OOB_FILL_NONE);
}

}

extern "C" void kernel_launch(void* const* d_in, const int* in_sizes, int n_in, void* d_out, int out_size) {
    (void)in_sizes; (void)n_in; (void)out_size;
    void* fnp = nullptr;
    cudaDriverEntryPointQueryResult st;
    cudaGetDriverEntryPoint("cuTensorMapEncodeTiled", &fnp, cudaEnableDefault, &st);
    EncodeFn fn = (EncodeFn)fnp;
    void* o_ptr = nullptr;
    cudaGetSymbolAddress(&o_ptr, g_o);
    cudaFuncSetAttribute(fused_kernel, cudaFuncAttributeMaxDynamicSharedMemorySize, SMEM_BYTES);

    const CUtensorMapSwizzle S128 = CU_TENSOR_MAP_SWIZZLE_128B, S0 = CU_TENSOR_MAP_SWIZZLE_NONE;
    Maps maps;
    encode(fn, &maps.m[M_XA], d_in[0], S128, {896, 2, 64}, {1024, 1792, 128});
    encode(fn, &maps.m[M_WKV], d_in[1], S128, {112, 2, 64}, {448, 2688, 32}, {3, 896, 2}, {4, 224, 1});
    encode(fn, &maps.m[M_WQ], d_in[1], S128, {112, 2, 64}, {448, 2688, 64}, {4, 224, 1});
    encode(fn, &maps.m[M_WO], d_in[2], S128, {112, 2, 64}, {448, 896, 64}, {4, 224, 1});
    encode(fn, &maps.m[M_XB], d_in[3], S128, {448, 2, 64}, {1024, 896, 64}, {2, 896 * 1024, 2});
    encode(fn, &maps.m[M_CR], d_in[4], S128, {2048, 2, 64}, {2048, 4096, 128});
    encode(fn, &maps.m[M_CI], d_in[5], S128, {2048, 2, 64}, {2048, 4096, 128});
    encode(fn, &maps.m[M_WR], d_in[6], S128, {448, 2, 64}, {448, 896, 112});
    encode(fn, &maps.m[M_WI], d_in[7], S128, {448, 2, 64}, {448, 896, 112});
    encode(fn, &maps.m[M_OST], o_ptr, S0, {448, 2, 112}, {2048, 896, 16});
    encode(fn, &maps.m[M_OLD], o_ptr, S128, {448, 2, 64}, {2048, 896, 128});
    encode(fn, &maps.m[M_OUTA], d_out, S0, {1792, 2, 112}, {1024, 3584, 16});
    encode(fn, &maps.m[M_OUTB], d_out, S0, {896, 2, 112}, {2048, 1792, 16});
    maps.out = (uint8_t*)d_out;

    fused_kernel<<<132, 384, SMEM_BYTES>>>(maps);
}
```

```cpp
#include <cuda.h>
#include <cuda_bf16.h>
#include <cuda_runtime.h>
#include <stdint.h>

namespace {

constexpr int NA = 7;
constexpr int NB = 5;
constexpr uint32_t SLOT = 16384;
constexpr uint32_t BRING = NA * SLOT;
constexpr uint32_t STG = BRING + NB * SLOT;
constexpr uint32_t WSLOT = 3584;
constexpr uint32_t BLOB = 14336;
constexpr uint32_t BARS = STG + 9 * WSLOT;
constexpr uint32_t BAR_FULL = BARS;
constexpr uint32_t BAR_EMPTY = BARS + 64;
constexpr uint32_t BAR_HALO = BARS + 128;
constexpr uint32_t BAR_PUB = BARS + 136;
constexpr uint32_t BAR_OUT = BARS + 144;
constexpr uint32_t BAR_FREE = BARS + 160;
constexpr uint32_t BAR_RDY = BARS + 176;
constexpr uint32_t SMEM_BYTES = BARS + 256 + 1024;
constexpr uint32_t base = 1024;
constexpr int SPIN_LIMIT = 1 << 16;

#define E_EXTRA 0
#define PACE_A 0
#define PACE_B 360
#define PACE_O 300
#define HALO_DELAY 400
#define MAPPING 0
#define SPARE0 12
constexpr int NBE = 13 + E_EXTRA;
constexpr int POUT = 33 + NBE;

enum { M_XA, M_WKV, M_WQ, M_WO, M_XB, M_WR, M_WI, M_CR, M_CI, M_OST, M_OLD, M_OUTA, M_OUTB, M_COUNT };
struct __align__(64) Maps {
    CUtensorMap m[M_COUNT];
    uint8_t* out;
};

constexpr int CNT_A = 0;
constexpr int CNT_B = 4;
constexpr int CNT_Z = 8;
constexpr int CNT_O = 16;
constexpr int CNT_COUNT = 32;

__device__ __align__(1024) uint8_t g_ab[2 * 32 * 4 * BLOB];
__device__ __align__(1024) __nv_bfloat16 g_o[2048 * 448];
__device__ __align__(1024) uint8_t g_halo[64 * 2 * WSLOT];
__device__ __align__(128) unsigned g_cnt[CNT_COUNT * 32];
__device__ __align__(128) unsigned g_epoch[128 * 4 * 8];

__device__ __forceinline__ unsigned clk32() { unsigned c; asm volatile("mov.u32 %0, %%clock;" : "=r"(c)); return c; }
__device__ __forceinline__ void pause_until(unsigned t0, unsigned cycles) {
    while (clk32() - t0 < cycles) {}
}

#define PROF(idx)

__device__ __forceinline__ void mbar_init(uint32_t bar, uint32_t cnt) {
    asm volatile("mbarrier.init.shared::cta.b64 [%0], %1;" ::"r"(bar), "r"(cnt) : "memory");
}
__device__ __forceinline__ void mbar_expect(uint32_t bar, uint32_t bytes) {
    asm volatile("mbarrier.arrive.expect_tx.shared::cta.b64 _, [%0], %1;" ::"r"(bar), "r"(bytes) : "memory");
}
__device__ __forceinline__ void mbar_arrive(uint32_t bar) {
    asm volatile("mbarrier.arrive.shared::cta.b64 _, [%0];" ::"r"(bar) : "memory");
}
__device__ __forceinline__ bool mbar_try(uint32_t bar, uint32_t parity) {
    uint32_t ok;
    asm volatile("{\n.reg .pred p;\nmbarrier.try_wait.parity.shared::cta.b64 p, [%1], %2;\nselp.u32 %0, 1, 0, p;\n}\n"
                 : "=r"(ok) : "r"(bar), "r"(parity) : "memory");
    return ok;
}
__device__ __forceinline__ void mbar_wait(uint32_t bar, uint32_t parity) {
#pragma unroll 1
    for (int n = 0; n < SPIN_LIMIT; n++)
        if (mbar_try(bar, parity)) break;
}
__device__ __forceinline__ bool elect() {
    uint32_t p;
    asm volatile("{\n.reg .pred p;\nelect.sync _|p, 0xffffffff;\nselp.u32 %0, 1, 0, p;\n}\n" : "=r"(p));
    return p;
}
__device__ __forceinline__ void nb_sync(int id, int n) { asm volatile("bar.sync %0, %1;" ::"r"(id), "r"(n) : "memory"); }
__device__ __forceinline__ void warp_arrive(uint32_t bar) {
    __syncwarp();
    if ((threadIdx.x & 31) == 0) mbar_arrive(bar);
}

__device__ __forceinline__ void tma_ld2(uint32_t dst, const CUtensorMap* m, int c0, int c1, uint32_t bar) {
    asm volatile("cp.async.bulk.tensor.2d.shared::cluster.global.mbarrier::complete_tx::bytes [%0], [%1, {%3, %4}], [%2];"
                 ::"r"(dst), "l"(m), "r"(bar), "r"(c0), "r"(c1) : "memory");
}
__device__ __forceinline__ void tma_ld3(uint32_t dst, const CUtensorMap* m, int c0, int c1, int c2, uint32_t bar) {
    asm volatile("cp.async.bulk.tensor.3d.shared::cluster.global.mbarrier::complete_tx::bytes [%0], [%1, {%3, %4, %5}], [%2];"
                 ::"r"(dst), "l"(m), "r"(bar), "r"(c0), "r"(c1), "r"(c2) : "memory");
}
__device__ __forceinline__ void tma_ld4(uint32_t dst, const CUtensorMap* m, int c0, int c1, int c2, int c3, uint32_t bar) {
    asm volatile("cp.async.bulk.tensor.4d.shared::cluster.global.mbarrier::complete_tx::bytes [%0], [%1, {%3, %4, %5, %6}], [%2];"
                 ::"r"(dst), "l"(m), "r"(bar), "r"(c0), "r"(c1), "r"(c2), "r"(c3) : "memory");
}
__device__ __forceinline__ void bulk_ld(uint32_t dst, const void* src, uint32_t bytes, uint32_t bar) {
    asm volatile("cp.async.bulk.shared::cluster.global.mbarrier::complete_tx::bytes [%0], [%1], %2, [%3];"
                 ::"r"(dst), "l"(src), "r"(bytes), "r"(bar) : "memory");
}
__device__ __forceinline__ void bulk_st(void* dst, uint32_t src, uint32_t bytes) {
    asm volatile("cp.async.bulk.global.shared::cta.bulk_group [%0], [%1], %2;" ::"l"(dst), "r"(src), "r"(bytes) : "memory");
}
__device__ __forceinline__ void tma_st2(const CUtensorMap* m, int c0, int c1, uint32_t src) {
    asm volatile("cp.async.bulk.tensor.2d.global.shared::cta.bulk_group [%0, {%1, %2}], [%3];"
                 ::"l"(m), "r"(c0), "r"(c1), "r"(src) : "memory");
}
__device__ __forceinline__ void tma_red2(const CUtensorMap* m, int c0, int c1, uint32_t src) {
    asm volatile("cp.reduce.async.bulk.tensor.2d.global.shared::cta.add.bulk_group [%0, {%1, %2}], [%3];"
                 ::"l"(m), "r"(c0), "r"(c1), "r"(src) : "memory");
}
__device__ __forceinline__ void bulk_commit() { asm volatile("cp.async.bulk.commit_group;" ::: "memory"); }
__device__ __forceinline__ void bulk_wait_all() { asm volatile("cp.async.bulk.wait_group 0;" ::: "memory"); }
__device__ __forceinline__ void bulk_wait_read() { asm volatile("cp.async.bulk.wait_group.read 0;" ::: "memory"); }
__device__ __forceinline__ void fence_async_smem() { asm volatile("fence.proxy.async.shared::cta;" ::: "memory"); }
__device__ __forceinline__ void fence_async_global() { asm volatile("fence.proxy.async.global;" ::: "memory"); }

__device__ __forceinline__ void signal(int idx) {
    fence_async_global();
    asm volatile("red.release.gpu.global.add.u32 [%0], 1;" ::"l"(&g_cnt[idx * 32]) : "memory");
}
__device__ __forceinline__ unsigned peek(int idx) {
    unsigned v;
    asm volatile("ld.relaxed.gpu.global.u32 %0, [%1];" : "=r"(v) : "l"(&g_cnt[idx * 32]) : "memory");
    return v;
}
__device__ __forceinline__ void await(int idx, unsigned target, unsigned v) {
#pragma unroll 1
    for (int n = 0; n < SPIN_LIMIT && (int)(v - target) < 0; n++) v = peek(idx);
    asm volatile("fence.acquire.gpu;" ::: "memory");
    fence_async_global();
}

#define WG_REGS                                                                                                     \
    "{%0,%1,%2,%3,%4,%5,%6,%7,%8,%9,%10,%11,%12,%13,%14,%15,%16,%17,%18,%19,%20,%21,%22,%23,%24,%25,%26,%27,"       \
    "%28,%29,%30,%31,%32,%33,%34,%35,%36,%37,%38,%39,%40,%41,%42,%43,%44,%45,%46,%47,%48,%49,%50,%51,%52,%53,%54,%55}"
#define WG_OPS(C)                                                                                                   \
    C(d[0]), C(d[1]), C(d[2]), C(d[3]), C(d[4]), C(d[5]), C(d[6]), C(d[7]), C(d[8]), C(d[9]), C(d[10]), C(d[11]),   \
    C(d[12]), C(d[13]), C(d[14]), C(d[15]), C(d[16]), C(d[17]), C(d[18]), C(d[19]), C(d[20]), C(d[21]), C(d[22]),   \
    C(d[23]), C(d[24]), C(d[25]), C(d[26]), C(d[27]), C(d[28]), C(d[29]), C(d[30]), C(d[31]), C(d[32]), C(d[33]),   \
    C(d[34]), C(d[35]), C(d[36]), C(d[37]), C(d[38]), C(d[39]), C(d[40]), C(d[41]), C(d[42]), C(d[43]), C(d[44]),   \
    C(d[45]), C(d[46]), C(d[47]), C(d[48]), C(d[49]), C(d[50]), C(d[51]), C(d[52]), C(d[53]), C(d[54]), C(d[55])

template <int TB, int SB, bool INIT>
__device__ __forceinline__ void wgmma112(float (&d)[56], uint64_t da, uint64_t db) {
    if (INIT) {
        asm volatile("{\n.reg .pred p;\nsetp.ne.b32 p, 0, 0;\n"
                     "wgmma.mma_async.sync.aligned.m64n112k16.f32.bf16.bf16 " WG_REGS ", %56, %57, p, 1, %59, 0, %58;\n}\n"
                     : WG_OPS("=f") : "l"(da), "l"(db), "n"(TB), "n"(SB));
    } else {
        asm volatile("{\n.reg .pred p;\nsetp.ne.b32 p, 1, 0;\n"
                     "wgmma.mma_async.sync.aligned.m64n112k16.f32.bf16.bf16 " WG_REGS ", %56, %57, p, 1, %59, 0, %58;\n}\n"
                     : WG_OPS("+f") : "l"(da), "l"(db), "n"(TB), "n"(SB));
    }
}
__device__ __forceinline__ void acc_fence(float (&d)[56]) {
#pragma unroll
    for (int i = 0; i < 56; i++) asm volatile("" : "+f"(d[i])::"memory");
}

__device__ __forceinline__ uint32_t pack2(float lo, float hi) {
    uint32_t r;
    asm volatile("cvt.rn.bf16x2.f32 %0, %1, %2;" : "=r"(r) : "f"(hi), "f"(lo));
    return r;
}
__device__ __forceinline__ uint32_t movm(uint32_t a) {
    uint32_t r;
    asm volatile("movmatrix.sync.aligned.m8n8.trans.b16 %0, %1;" : "=r"(r) : "r"(a));
    return r;
}
template <bool TRANS>
__device__ __forceinline__ void stsm4(uint32_t addr, uint32_t a, uint32_t b, uint32_t c, uint32_t d) {
    if (TRANS) asm volatile("stmatrix.sync.aligned.m8n8.x4.trans.shared.b16 [%0], {%1,%2,%3,%4};" ::"r"(addr), "r"(a), "r"(b), "r"(c), "r"(d) : "memory");
    else asm volatile("stmatrix.sync.aligned.m8n8.x4.shared.b16 [%0], {%1,%2,%3,%4};" ::"r"(addr), "r"(a), "r"(b), "r"(c), "r"(d) : "memory");
}
__device__ __forceinline__ void sts4(uint32_t addr, uint32_t a, uint32_t b, uint32_t c, uint32_t d) {
    asm volatile("st.shared.v4.b32 [%0], {%1,%2,%3,%4};" ::"r"(addr), "r"(a), "r"(b), "r"(c), "r"(d) : "memory");
}
__device__ __forceinline__ void lds4(uint32_t addr, uint32_t& a, uint32_t& b, uint32_t& c, uint32_t& d) {
    asm volatile("ld.shared.v4.b32 {%0,%1,%2,%3}, [%4];" : "=r"(a), "=r"(b), "=r"(c), "=r"(d) : "r"(addr) : "memory");
}
__device__ __forceinline__ void mma16816(float (&d)[4], uint32_t a0, uint32_t a1, uint32_t a2, uint32_t a3, uint32_t b0, uint32_t b1) {
    asm volatile("mma.sync.aligned.m16n8k16.row.col.f32.bf16.bf16.f32 {%0,%1,%2,%3}, {%4,%5,%6,%7}, {%8,%9}, {%0,%1,%2,%3};"
                 : "+f"(d[0]), "+f"(d[1]), "+f"(d[2]), "+f"(d[3]) : "r"(a0), "r"(a1), "r"(a2), "r"(a3), "r"(b0), "r"(b1));
}
__device__ __forceinline__ uint32_t max2(uint32_t a, uint32_t b) {
    uint32_t r;
    asm("max.bf16x2 %0, %1, %2;" : "=r"(r) : "r"(a), "r"(b));
    return r;
}
__device__ __forceinline__ void st_tagged(uint8_t* p, uint32_t a, uint32_t b, uint32_t tag) {
    asm volatile("{\n.reg .b64 x, y;\nmov.b64 x, {%1, %3};\nmov.b64 y, {%2, %3};\nst.relaxed.gpu.global.v2.b64 [%0], {x, y};\n}\n"
                 ::"l"(p), "r"(a), "r"(b), "r"(tag) : "memory");
}
__device__ __forceinline__ void ld_tagged(const uint8_t* p, uint32_t& a, uint32_t& ta, uint32_t& b, uint32_t& tb) {
    asm volatile("{\n.reg .b64 x, y;\nld.relaxed.gpu.global.v2.b64 {x, y}, [%4];\nmov.b64 {%0, %1}, x;\nmov.b64 {%2, %3}, y;\n}\n"
                 : "=r"(a), "=r"(ta), "=r"(b), "=r"(tb) : "l"(p) : "memory");
}
__device__ __forceinline__ float bf_lo(uint32_t v) { return __uint_as_float(v << 16); }
__device__ __forceinline__ float bf_hi(uint32_t v) { return __uint_as_float(v & 0xFFFF0000u); }
__device__ __forceinline__ float rcp(float x) { float r; asm("rcp.approx.ftz.f32 %0, %1;" : "=f"(r) : "f"(x)); return r; }
__device__ __forceinline__ float ex2(float x) { float r; asm volatile("ex2.approx.ftz.f32 %0, %1;" : "=f"(r) : "f"(x)); return r; }

__device__ __forceinline__ uint32_t full_bar(int stage) { return base + BAR_FULL + (stage & 7) * 8; }
__device__ __forceinline__ void wait_released(int j) { mbar_wait(base + BAR_EMPTY + (j & 7) * 8, (j >> 3) & 1); }

template <int N, uint32_t OFF>
struct Feed {
    int stage;
    uint32_t dst;
    __device__ __forceinline__ void seek(int i) { stage = i; dst = base + OFF + (i % N) * SLOT; }
    __device__ __forceinline__ uint32_t acquire() { wait_released(stage - N); return full_bar(stage); }
    __device__ __forceinline__ void next() {
        stage++;
        dst += SLOT;
        if (dst == base + OFF + N * SLOT) dst = base + OFF;
    }
};
__device__ __forceinline__ int skip_own(int n, int mt) { return n == mt ? 15 : n; }

constexpr uint64_t DESC_HI = (uint64_t)(64u | (1u << 30)) << 32;
constexpr uint32_t LBO_K = 1u << 16, LBO_N = 512u << 16;

struct Ring {
    int stage;
    uint32_t a, b;
    uint32_t awg;
    uint32_t zero;
    bool leader;
    __device__ __forceinline__ void seek(int i) {
        stage = i;
        a = (base + (i % NA) * SLOT) >> 4;
        b = (base + BRING + (i % NB) * SLOT) >> 4;
    }
    __device__ __forceinline__ void wait() {
        mbar_wait(full_bar(stage), (stage >> 3) & 1);
    }
    template <bool RELEASE>
    __device__ __forceinline__ void end() {
        asm volatile("wgmma.commit_group.sync.aligned;" ::: "memory");
        asm volatile("wgmma.wait_group.sync.aligned 1;" ::: "memory");
        if (RELEASE && leader) mbar_arrive(base + BAR_EMPTY + ((stage - 1) & 7) * 8);
        stage++;
        a += SLOT >> 4;
        if (a == (base + NA * SLOT) >> 4) a = base >> 4;
        b += SLOT >> 4;
        if (b == (base + BRING + NB * SLOT) >> 4) b = (base + BRING) >> 4;
    }
    __device__ __forceinline__ void pin() {
#pragma unroll 1
        for (uint32_t n = 0; n < zero; n++) asm volatile("nanosleep.u32 0;" ::: "memory");
    }
    template <int SB, bool INIT, bool RELEASE = true, bool WAIT = true>
    __device__ __forceinline__ void stage_kk(float (&d)[56], int stg = -1) {
        if (WAIT) wait();
        asm volatile("wgmma.fence.sync.aligned;" ::: "memory");
        const uint32_t sb = stg >= 0 ? (base + STG + stg * BLOB) >> 4 : b;
        const uint64_t da = DESC_HI | (a + awg + LBO_K), db = DESC_HI | (sb + LBO_K);
        wgmma112<0, SB, INIT>(d, da, db);
        wgmma112<0, SB, false>(d, da + 2, db + 2);
        wgmma112<0, SB, false>(d, da + 4, db + 4);
        wgmma112<0, SB, false>(d, da + 6, db + 6);
        end<RELEASE>();
    }
    template <bool INIT>
    __device__ __forceinline__ void stage_kn(float (&d)[56]) {
        wait();
        asm volatile("wgmma.fence.sync.aligned;" ::: "memory");
        const uint64_t da = DESC_HI | (a + awg + LBO_K), db = DESC_HI | (b + LBO_N);
        wgmma112<1, 1, INIT>(d, da, db);
        wgmma112<1, 1, false>(d, da + 2, db + 128);
        wgmma112<1, 1, false>(d, da + 4, db + 256);
        wgmma112<1, 1, false>(d, da + 6, db + 384);
        end<true>();
    }
    template <bool INIT>
    __device__ __forceinline__ void stage_kv(float (&dk)[56], float (&dv)[56]) {
        wait();
        asm volatile("wgmma.fence.sync.aligned;" ::: "memory");
        const uint32_t ax = (base >> 4) + (stage >> 1) * (SLOT >> 4) + (stage & 1) * 4;
        const uint64_t da = DESC_HI | (ax + awg + LBO_K), db = DESC_HI | (b + LBO_N);
        wgmma112<1, 1, INIT>(dk, da, db);
        wgmma112<1, 1, INIT>(dv, da, db + 256);
        wgmma112<1, 1, false>(dk, da + 2, db + 128);
        wgmma112<1, 1, false>(dv, da + 2, db + 384);
        end<!INIT>();
    }
};

template <bool TRANS>
__device__ __forceinline__ void store_pair(uint32_t addr, bool swap, uint32_t lo0, uint32_t hi0, uint32_t lo1, uint32_t hi1) {
    stsm4<TRANS>(addr, swap ? lo1 : lo0, swap ? hi1 : hi0, swap ? lo0 : lo1, swap ? hi0 : hi1);
}
__device__ __forceinline__ void store_rows(const float (&d)[56], uint32_t lane_addr) {
    const bool swap = threadIdx.x & 16;
#pragma unroll
    for (int j = 0; j < 14; j += 2) {
        store_pair<false>(lane_addr + j * 16, swap, pack2(d[4 * j], d[4 * j + 1]), pack2(d[4 * j + 2], d[4 * j + 3]),
                          pack2(d[4 * j + 4], d[4 * j + 5]), pack2(d[4 * j + 6], d[4 * j + 7]));
    }
}
__device__ __forceinline__ void store_blob(const float (&d)[56], uint32_t lane_addr) {
#pragma unroll
    for (int j = 0; j < 14; j += 2)
        stsm4<true>(lane_addr + j * 1024, pack2(d[4 * j], d[4 * j + 1]), pack2(d[4 * j + 2], d[4 * j + 3]),
                    pack2(d[4 * j + 4], d[4 * j + 5]), pack2(d[4 * j + 6], d[4 * j + 7]));
}

__global__ void __launch_bounds__(384, 1) fused_kernel(const __grid_constant__ Maps maps) {
    extern __shared__ uint8_t smem_raw[];
    if ((uint32_t)__cvta_generic_to_shared(smem_raw) != base) return;
    const int warp = __shfl_sync(0xffffffffu, threadIdx.x >> 5, 0);
    const int lane = threadIdx.x & 31;
    if ((blockIdx.x >> 1) == SPARE0 || blockIdx.x >= 130) {
        const int ns = blockIdx.x >= 130 ? blockIdx.x - 128 : blockIdx.x & 1;
        if (threadIdx.x < 378) {
            const int r0 = threadIdx.x / 14;
            uint8_t* dst = maps.out + 896 + ns * 224 + (threadIdx.x - r0 * 14) * 16;
#pragma unroll 4
            for (int row = r0; row < 2048; row += 27) *reinterpret_cast<uint4*>(dst + (size_t)row * 1792) = make_uint4(0, 0, 0, 0);
        }
        __syncthreads();
        if (threadIdx.x < 17) {
            asm volatile("fence.acq_rel.gpu;" ::: "memory");
            const int idx = threadIdx.x < 16 ? CNT_O + threadIdx.x : CNT_Z + ns;
            asm volatile("red.relaxed.gpu.global.add.u32 [%0], 1;" ::"l"(&g_cnt[idx * 32]) : "memory");
        }
        return;
    }
    const int bid = blockIdx.x < 2 * SPARE0 ? blockIdx.x : blockIdx.x - 2;
    const int roleL = (bid >> 3) & 1;
    const int mt = ((bid >> 4) << 1) | ((bid >> 2) & 1);
    const int ns = bid & 3;
    const int par = mt >> 3, blk = mt & 7;

    if (warp == 8) {
        if (elect()) {
#pragma unroll
            for (int i = 0; i < 8; i++) mbar_init(base + BAR_FULL + i * 8, 2);
            asm volatile("fence.mbarrier_init.release.cluster;" ::: "memory");
        }
    } else if (warp == 9) {
        if (elect()) {
#pragma unroll
            for (int i = 0; i < 8; i++) mbar_init(base + BAR_EMPTY + i * 8, 8);
            asm volatile("fence.mbarrier_init.release.cluster;" ::: "memory");
        }
    } else if (warp == 10) {
        if (elect()) {
#pragma unroll
            for (int i = 0; i < 6; i++) mbar_init(base + BAR_RDY + i * 8, 4);
            asm volatile("fence.mbarrier_init.release.cluster;" ::: "memory");
        }
    } else if (warp == 11) {
        if (elect()) {
#pragma unroll
            for (int i = 0; i < 2; i++) {
                mbar_init(base + BAR_OUT + i * 8, 1);
                mbar_init(base + BAR_FREE + i * 8, 1);
            }
            mbar_init(base + BAR_HALO, 10);
            mbar_init(base + BAR_PUB, 1);
            asm volatile("fence.mbarrier_init.release.cluster;" ::: "memory");
        }
    }
    __syncthreads();

    const int col = ns * 112;
    if (warp == 8) {
        if (elect()) {
            if (roleL) {
#pragma unroll 1
                for (int i = 0; i < 4; i++) {
                    mbar_expect(full_bar(2 * i), SLOT);
                    tma_ld2(base + i * SLOT, &maps.m[M_XA], par * 448 + i * 64, blk * 128, full_bar(2 * i));
                }
            } else {
#pragma unroll 1
                for (int i = 0; i < NA; i++) {
                    mbar_expect(full_bar(i), SLOT);
                    tma_ld3(base + i * SLOT, &maps.m[M_XB], i * 64, mt * 64, 0, full_bar(i));
                }
            }
        }
    } else if (warp == 11) {
        if (elect()) {
#pragma unroll 1
            for (int i = 0; i < NB; i++) {
                const uint32_t dst = base + BRING + i * SLOT, bar = full_bar(i);
                mbar_expect(bar, roleL ? SLOT : BLOB);
                if (roleL) {
                    tma_ld4(dst, &maps.m[M_WKV], 0, i * 32, 1, ns, bar);
                    tma_ld4(dst + 8192, &maps.m[M_WKV], 64, i * 32, 1, ns, bar);
                    if (i & 1) mbar_arrive(bar);
                } else {
                    tma_ld2(dst, &maps.m[M_WR], i * 64, col, bar);
                }
            }
        }
    }

    if (warp >= 8) {
        asm volatile("setmaxnreg.dec.sync.aligned.u32 56;");
        unsigned* epoch_ptr = &g_epoch[(bid * 4 + (warp - 8)) * 8];
#define PROF_FEED_A
#define PROF_FEED_B
        if (warp == 8) {
            if (elect()) {
                Feed<NA, 0> f;
                const int row = mt * 128;
                auto c_run = [&](const CUtensorMap* m, int off, int n0, int n1) {
#pragma unroll 1
                    for (int n = n0; n < n1; n++) {
                        const uint32_t bar = f.acquire();
                        mbar_expect(bar, SLOT);
                        tma_ld2(f.dst, m, (off + skip_own(n, mt)) * 64, row, bar);
                        PROF_FEED_A;
                        f.next();
                    }
                };
                if (!roleL) {
                    const unsigned ep = *epoch_ptr;
                    f.seek(14);
#pragma unroll 1
                    for (int i = 0; i < 4; i++) {
                        const uint32_t bar = f.acquire();
                        mbar_expect(bar, SLOT);
                        tma_ld2(f.dst, &maps.m[M_CR + (i >> 1)], ((i & 1) * 16 + mt) * 64, row, bar);
                        mbar_arrive(bar);
                        PROF_FEED_A;
                        f.next();
                    }
                    c_run(&maps.m[M_CR], 0, 0, 15);
                    c_run(&maps.m[M_CI], 0, 0, NBE);
                    await(CNT_O + mt, (ep + 1) * 8, peek(CNT_O + mt));
                    PROF(146);
#pragma unroll 1
                    for (int i = 0; i < 7; i++) {
                        const uint32_t bar = f.acquire();
                        mbar_expect(bar, SLOT);
                        tma_ld2(f.dst, &maps.m[M_OLD], i * 64, row, bar);
                        PROF_FEED_A;
                        f.next();
                    }
                    *epoch_ptr = ep + 1;
                } else {
#pragma unroll 1
                    for (int i = 4; i < 7; i++) {
                        wait_released(2 * i - 8);
                        mbar_expect(full_bar(2 * i), SLOT);
                        tma_ld2(base + i * SLOT, &maps.m[M_XA], par * 448 + i * 64, blk * 128, full_bar(2 * i));
                    }
                    wait_released(7);
                    f.seek(21);
                    c_run(&maps.m[M_CR], 16, 0, 15);
                    c_run(&maps.m[M_CI], 16, 0, 15);
                    c_run(&maps.m[M_CI], 0, NBE, 15);
                }
            }
        } else if (warp == 11) {
            if (elect()) {
                Feed<NB, BRING> f;
                f.seek(NB);
                const unsigned ep = *epoch_ptr + 1;
                auto blob_run = [&](int quarter, int n0, int n1) {
                    const int cnt = CNT_A + (quarter >> 1) * 4 + ns;
                    const uint8_t* src = g_ab + (size_t)(quarter * 64 + ns) * BLOB;
                    if (n0 == 0) await(cnt, ep * 16, peek(cnt));
                    PROF(150 + quarter);
#pragma unroll 1
                    for (int n = n0; n < n1; n++) {
                        const uint32_t bar = f.acquire();
                        uint32_t dst = f.dst;
                        if (quarter == 0) {
                            if (n == 3) mbar_wait(base + BAR_OUT, 0);
                            if (n == 3 || n == 4) dst = base + STG + (n - 3) * BLOB;
                            if (n == 8) mbar_wait(base + BAR_OUT + 8, 0);
                        }
                        mbar_expect(bar, BLOB);
                        bulk_ld(dst, src + skip_own(n, mt) * (4 * BLOB), BLOB, bar);
                        PROF_FEED_B;
                        f.next();
                    }
                };
                auto w_run = [&](const CUtensorMap* m, bool no_a) {
#pragma unroll 1
                    for (int i = 0; i < 7; i++) {
                        const uint32_t bar = f.acquire();
                        mbar_expect(bar, SLOT);
                        tma_ld3(f.dst, m, 0, i * 64, ns, bar);
                        tma_ld3(f.dst + 8192, m, 64, i * 64, ns, bar);
                        if (no_a) mbar_arrive(bar);
                        PROF_FEED_B;
                        f.next();
                    }
                };
                if (!roleL) {
#pragma unroll 1
                    for (int i = NB; i < 14; i++) {
                        const uint32_t bar = f.acquire();
                        mbar_expect(bar, BLOB);
                        tma_ld2(f.dst, &maps.m[i < 7 ? M_WR : M_WI], (i < 7 ? i : i - 7) * 64, col, bar);
                        if (i >= 7) mbar_arrive(bar);
                        PROF_FEED_B;
                        f.next();
                    }
                    f.seek(18);
                    blob_run(0, 0, 15);
                    blob_run(2, 0, NBE);
                    w_run(&maps.m[M_WO], false);
                } else {
#pragma unroll 1
                    for (int i = NB; i < 14; i++) {
                        const uint32_t bar = f.acquire();
                        mbar_expect(bar, SLOT);
                        tma_ld4(f.dst, &maps.m[M_WKV], 0, i * 32, 1, ns, bar);
                        tma_ld4(f.dst + 8192, &maps.m[M_WKV], 64, i * 32, 1, ns, bar);
                        if (i & 1) mbar_arrive(bar);
                        PROF_FEED_B;
                        f.next();
                    }
                    w_run(&maps.m[M_WQ], true);
                    blob_run(1, 0, 15);
                    blob_run(3, 0, 15);
                    if (NBE < 15) blob_run(2, NBE, 15);
                }
                *epoch_ptr = ep;
            }
        } else {
            const int h = warp - 9;
            const uint32_t stg = base + STG + h * BLOB;
            if (!roleL) {
                if (elect()) {
                    uint8_t* dst = g_ab + (size_t)((h * 32 + mt) * 4 + ns) * BLOB;
                    mbar_wait(base + BAR_RDY + h * 16, 0);
                    mbar_wait(base + BAR_RDY + h * 16 + 8, 0);
                    PROF(130 + h);
                    fence_async_smem();
                    const unsigned t0 = clk32();
                    const uint32_t src = h ? base + BRING + SLOT : base + STG, pitch = h ? SLOT : BLOB;
#pragma unroll 1
                    for (int p = 0; p < 8; p++) {
                        pause_until(t0, p * (h ? PACE_B : PACE_A));
                        bulk_st(dst + (p >> 2) * (64 * BLOB) + (p & 3) * WSLOT, src + (p >> 2) * pitch + (p & 3) * WSLOT, WSLOT);
                    }
                    bulk_commit();
                    bulk_wait_all();
                    PROF(132 + h);
                    mbar_arrive(base + BAR_OUT + h * 8);
                    signal(CNT_A + h * 4 + ns);
                    PROF(134 + h);

                    mbar_wait(base + BAR_RDY + 32 + h * 8, 0);
                    fence_async_smem();
                    wait_released(POUT + 1);
                    PROF(140 + h);
#pragma unroll 1
                    for (int p = 0; p < 4; p++)
                        tma_red2(&maps.m[M_OUTB], 448 + col, mt * 128 + h * 64 + p * 16, stg + p * WSLOT);
                    bulk_commit();
                    bulk_wait_read();
                    mbar_arrive(base + BAR_FREE + h * 8);
                    PROF(142 + h);
                }
            } else {
                const unsigned tag = *epoch_ptr + 1;
                mbar_wait(base + BAR_PUB, 0);
                {
                    const uint32_t goff = h * 4096 + lane * 16, soff = base + STG + h * 2048 + lane * 16;
                    uint32_t v[16], t[16];
                    if (blk < 7) {
                        uint8_t* dst = g_halo + (size_t)(mt * 4 + ns) * (2 * WSLOT) + goff;
#pragma unroll
                        for (int i = 0; i < 4; i++)
                            if (i < 3 || h == 0) lds4(soff + 8 * WSLOT + i * 512, v[4 * i], v[4 * i + 1], v[4 * i + 2], v[4 * i + 3]);
#pragma unroll
                        for (int i = 0; i < 8; i++)
                            if (i < 6 || h == 0) st_tagged(dst + i * 512, v[2 * i], v[2 * i + 1], tag);
                    }
                    if (lane == 0) PROF(140 + h);
#pragma unroll
                    for (int i = 0; i < 16; i++) { v[i] = 0; t[i] = tag; }
                    if (blk > 0) {
                        const uint8_t* src = g_halo + (size_t)((mt - 1) * 4 + ns) * (2 * WSLOT) + goff;
                        pause_until(clk32(), HALO_DELAY);
#pragma unroll 1
                        for (int n = 0; n < SPIN_LIMIT; n++) {
                            bool ok = true;
#pragma unroll
                            for (int i = 0; i < 8; i++)
                                if (i < 6 || h == 0) ld_tagged(src + i * 512, v[2 * i], t[2 * i], v[2 * i + 1], t[2 * i + 1]);
#pragma unroll
                            for (int i = 0; i < 16; i++) ok = ok && t[i] == tag;
                            if (__all_sync(0xffffffffu, ok)) break;
                        }
                    }
#pragma unroll
                    for (int i = 0; i < 4; i++)
                        if (i < 3 || h == 0) sts4(soff + i * 512, v[4 * i], v[4 * i + 1], v[4 * i + 2], v[4 * i + 3]);
                    warp_arrive(base + BAR_HALO);
                    if (lane == 0) PROF(138 + h);
                }
                __syncwarp();
                if (elect()) {
                    *epoch_ptr = tag;
                    if (h == 0) {
                        mbar_wait(base + BAR_RDY, 0);
                        mbar_wait(base + BAR_RDY + 8, 0);
                        PROF(132);
                        fence_async_smem();
                        const unsigned t0 = clk32();
#pragma unroll 1
                        for (int p = 0; p < 8; p++) {
                            pause_until(t0, p * PACE_O);
                            tma_st2(&maps.m[M_OST], col, mt * 128 + p * 16, stg + p * WSLOT);
                        }
                        bulk_commit();
                        bulk_wait_all();
                        PROF(134);
                        mbar_arrive(base + BAR_FREE);
                        signal(CNT_O + mt);
                        PROF(136);
                    } else {
                        mbar_wait(base + BAR_RDY, 0);
                        await(CNT_Z + ns, tag, peek(CNT_Z + ns));
                        mbar_arrive(base + BAR_FREE + 8);
                    }
                }
            }
        }
    } else {
        asm volatile("setmaxnreg.inc.sync.aligned.u32 224;");
        Ring r;
        r.seek(0);
        r.awg = (warp >> 2) * 512;
        r.zero = blockIdx.y;
        r.leader = lane == 0;
        const int wg = warp >> 2;
        const uint32_t wslot = base + STG + warp * WSLOT;
        const uint32_t row_addr = wslot + (lane & 15) * 224 + (((lane >> 4) ^ (lane >> 2)) & 1) * 16;

        if (!roleL) {
            const uint32_t blob_off = ((lane >> 4) * 8 + (lane & 7)) * 128 +
                                      (((2 * (warp & 3) + ((lane >> 3) & 1)) ^ (lane & 7)) << 4);
            float x0[56], x1[56];
            r.stage_kk<1, true, false>(x0);
#pragma unroll 1
            for (int i = 1; i < 7; i++) r.stage_kk<1, false>(x0);

            r.seek(7);
            r.stage_kk<-1, true>(x1);
            acc_fence(x0);
            store_blob(x0, base + STG + wg * BLOB + blob_off);
            warp_arrive(base + BAR_RDY + wg * 8);
#pragma unroll 1
            for (int i = 1; i < 7; i++) r.stage_kk<-1, false>(x1);

            mbar_wait(base + BAR_RDY, 0);
            mbar_wait(base + BAR_RDY + 8, 0);
            fence_async_smem();
            r.seek(14);
            r.stage_kk<1, true>(x0, 0);
            acc_fence(x1);
            wait_released(12);
            store_blob(x1, base + BRING + (1 + wg) * SLOT + blob_off);
            warp_arrive(base + BAR_RDY + 16 + wg * 8);
            r.stage_kk<1, false>(x0, 1);
            mbar_wait(base + BAR_RDY + 16, 0);
            mbar_wait(base + BAR_RDY + 24, 0);
            fence_async_smem();
#pragma unroll 1
            for (int i = 16; i < POUT; i++) r.stage_kk<1, false>(x0, (i == 21 || i == 22) ? i - 21 : -1);

            r.seek(POUT);
            r.stage_kn<true>(x1);
            acc_fence(x0);
            store_rows(x0, row_addr);
            warp_arrive(base + BAR_RDY + 32 + wg * 8);
#pragma unroll 1
            for (int i = 1; i < 7; i++) r.stage_kn<false>(x1);

            mbar_wait(base + BAR_FREE + wg * 8, 0);
            asm volatile("wgmma.wait_group.sync.aligned 0;" ::: "memory");
            acc_fence(x1);
            store_rows(x1, row_addr);
            fence_async_smem();
            __syncwarp();
            if (elect()) {
                tma_st2(&maps.m[M_OUTA], par * 896 + col, blk * 128 + warp * 16, wslot);
                bulk_commit();
                bulk_wait_read();
            }
        } else {
            const int g = lane >> 2, tig = lane & 3;
            float y0[56], y1[56], y2[56];
            r.stage_kv<true>(y0, y1);
#pragma unroll 1
            for (int i = 1; i < 14; i++) r.stage_kv<false>(y0, y1);

            uint32_t kl[14], kh[14], vl[14], vh[14];
            r.seek(14);
            r.stage_kn<true>(y2);
            acc_fence(y0);
            acc_fence(y1);
#pragma unroll
            for (int c = 0; c < 14; c++) {
                kl[c] = pack2(y0[4 * c], y0[4 * c + 1]);
                kh[c] = pack2(y0[4 * c + 2], y0[4 * c + 3]);
                vh[c] = movm(pack2(y1[4 * c + 2], y1[4 * c + 3]));
            }
            r.stage_kn<false>(y2);
            r.pin();
            {
                const uint32_t pub = wslot + WSLOT + lane * 16;
                sts4(pub, kh[0], kh[1], kh[2], kh[3]);
                sts4(pub + 512, kh[4], kh[5], kh[6], kh[7]);
                sts4(pub + 1024, kh[8], kh[9], kh[10], kh[11]);
                sts4(pub + 1536, kh[12], kh[13], vh[0], vh[1]);
                sts4(pub + 2048, vh[2], vh[3], vh[4], vh[5]);
                sts4(pub + 2560, vh[6], vh[7], vh[8], vh[9]);
                sts4(pub + 3072, vh[10], vh[11], vh[12], vh[13]);
                warp_arrive(base + BAR_HALO);
                if (threadIdx.x == 224) mbar_arrive(base + BAR_PUB);
            }
            r.stage_kn<false>(y2);
            r.stage_kn<false>(y2);
            r.pin();
#pragma unroll
            for (int c = 0; c < 14; c++) {
                vl[c] = movm(pack2(y1[4 * c], y1[4 * c + 1]));
            }
#pragma unroll 1
            for (int i = 4; i < 7; i++) r.stage_kn<false>(y2);

            r.seek(21);
            r.stage_kk<1, true>(y0);
            acc_fence(y2);
            uint32_t ql[14], qh[14], kp[14], vp[14];
            mbar_wait(base + BAR_HALO, 0);
            const uint32_t sub = wslot + lane * 16;
            lds4(sub, kp[0], kp[1], kp[2], kp[3]);
            lds4(sub + 512, kp[4], kp[5], kp[6], kp[7]);
            lds4(sub + 1024, kp[8], kp[9], kp[10], kp[11]);
            lds4(sub + 1536, kp[12], kp[13], vp[0], vp[1]);
#pragma unroll
            for (int c = 0; c < 14; c++) {
                ql[c] = pack2(y2[4 * c], y2[4 * c + 1]);
                qh[c] = pack2(y2[4 * c + 2], y2[4 * c + 3]);
            }
            r.wait();
            float s[8][4];
#pragma unroll
            for (int step = 0; step < 2; step++) {
#pragma unroll
                for (int i = 0; i < 8; i++) {
                    const int b = 1 - (i >> 2), h = i & 3;
                    const int c0 = 7 * (h >> 1) + 3 * (h & 1) + 2 * step;
                    const uint32_t* q = b ? qh : ql;
                    const uint32_t* kprev = b ? kl : kp;
                    const uint32_t* kcur = b ? kh : kl;
                    uint32_t q0 = q[c0], q1 = q[c0 + 1];
                    if ((h & 1) && step == 0) q0 = tig >= 2 ? q0 : 0u;
                    if (!(h & 1) && step == 1) q1 = tig < 2 ? q1 : 0u;
                    float (&d)[4] = s[2 * h + b];
                    if (step == 0) d[0] = d[1] = d[2] = d[3] = 0.f;
                    mma16816(d, kprev[c0], kcur[c0], kprev[c0 + 1], kcur[c0 + 1], q0, q1);
                }
            }
            r.pin();
            r.stage_kk<1, false, true, false>(y0);
            r.pin();

            const uint32_t curmask = (2 * tig <= g ? 0x0000FFFFu : 0u) | (2 * tig + 1 <= g ? 0xFFFF0000u : 0u);
            uint32_t pr[8], mx[4];
            {
                const bool cur0 = g <= 2 * tig, cur1 = g <= 2 * tig + 1;
                const uint32_t keep = (blk == 0 && warp == 0) ? curmask : 0xFFFFFFFFu;
#pragma unroll
                for (int i = 0; i < 8; i++) pr[i] = movm(pack2(cur0 ? s[i][2] : s[i][0], cur1 ? s[i][3] : s[i][1]));
#pragma unroll
                for (int i = 0; i < 8; i++) {
                    pr[i] = pack2(bf_lo(pr[i]) * 0.18898223650461362f, bf_hi(pr[i]) * 0.18898223650461362f);
                    if ((i & 1) == 0) pr[i] = (pr[i] & keep) | (0xCE6ECE6Eu & ~keep);
                }
            }
            r.stage_kk<1, false>(y0);
            r.pin();
            float e0[8], e1[8];
#pragma unroll
            for (int i = 0; i < 4; i++) mx[i] = max2(__byte_perm(pr[2 * i], pr[2 * i + 1], 0x5410), __byte_perm(pr[2 * i], pr[2 * i + 1], 0x7632));
#pragma unroll
            for (int i = 0; i < 4; i++) mx[i] = max2(mx[i], __shfl_xor_sync(0xffffffffu, mx[i], 1));
#pragma unroll
            for (int i = 0; i < 4; i++) mx[i] = max2(mx[i], __shfl_xor_sync(0xffffffffu, mx[i], 2));
#pragma unroll
            for (int i = 0; i < 8; i++) {
                const float m = (i & 1) ? bf_hi(mx[i >> 1]) : bf_lo(mx[i >> 1]);
                e0[i] = bf_lo(pr[i]) - m;
                e1[i] = bf_hi(pr[i]) - m;
            }
            r.stage_kk<1, false>(y0);
            r.pin();
            float sm[8];
#pragma unroll
            for (int i = 0; i < 8; i++) {
                e0[i] = ex2(e0[i] * 1.4426950408889634f);
                e1[i] = ex2(e1[i] * 1.4426950408889634f);
                sm[i] = e0[i] + e1[i];
            }
#pragma unroll
            for (int i = 0; i < 8; i++) sm[i] += __shfl_xor_sync(0xffffffffu, sm[i], 1);
            r.stage_kk<1, false>(y0);
            r.pin();
#pragma unroll
            for (int i = 0; i < 8; i++) sm[i] += __shfl_xor_sync(0xffffffffu, sm[i], 2);
#pragma unroll
            for (int i = 0; i < 8; i++) {
                const float inv = rcp(sm[i]);
                pr[i] = pack2(e0[i] * inv, e1[i] * inv);
            }
            r.stage_kk<1, false>(y0);
            r.pin();
            lds4(sub + 2048, vp[2], vp[3], vp[4], vp[5]);
            lds4(sub + 2560, vp[6], vp[7], vp[8], vp[9]);
            lds4(sub + 3072, vp[10], vp[11], vp[12], vp[13]);
            r.wait();
            float o[16][4];
#pragma unroll
            for (int ii = 0; ii < 16; ii++) {
                const int b = 1 - (ii >> 3), h = (ii >> 1) & 3, i = 4 * h + 2 * b + (ii & 1);
                const int c0 = 7 * (h >> 1) + 3 * (h & 1) + 2 * (i & 1);
                const uint32_t* vprev = b ? vl : vp;
                const uint32_t* vcur = b ? vh : vl;
                const uint32_t p = pr[2 * h + b];
                o[i][0] = o[i][1] = o[i][2] = o[i][3] = 0.f;
                mma16816(o[i], vprev[c0], vprev[c0 + 1], vcur[c0], vcur[c0 + 1], p & ~curmask, p & curmask);
            }
            r.pin();
            r.stage_kk<1, false, true, false>(y0);
            r.pin();
            {
                uint32_t ot[2][14];
#pragma unroll
                for (int hp = 0; hp < 2; hp++) {
#pragma unroll
                    for (int b = 0; b < 2; b++) {
                        const int e = 8 * hp + 2 * b, d = e + 4, cb = 7 * hp;
                        ot[b][cb] = pack2(o[e][0], o[e][1]);
                        ot[b][cb + 1] = pack2(o[e][2], o[e][3]);
                        ot[b][cb + 2] = pack2(o[e + 1][0], o[e + 1][1]);
                        ot[b][cb + 3] = pack2(g < 4 ? o[e + 1][2] : o[d][0], g < 4 ? o[e + 1][3] : o[d][1]);
                        ot[b][cb + 4] = pack2(o[d][2], o[d][3]);
                        ot[b][cb + 5] = pack2(o[d + 1][0], o[d + 1][1]);
                        ot[b][cb + 6] = pack2(o[d + 1][2], o[d + 1][3]);
                    }
                }
#pragma unroll
                for (int c = 0; c < 14; c += 2)
                    store_pair<true>(row_addr + c * 16, tig >= 2, ot[0][c], ot[1][c], ot[0][c + 1], ot[1][c + 1]);
            }
            warp_arrive(base + BAR_RDY + wg * 8);

#pragma unroll 1
            for (int i = 7; i < 32 - E_EXTRA; i++) r.stage_kk<1, false>(y0);

            mbar_wait(base + BAR_FREE, 0);
            mbar_wait(base + BAR_FREE + 8, 0);
            asm volatile("wgmma.wait_group.sync.aligned 0;" ::: "memory");
            acc_fence(y0);
            store_rows(y0, row_addr);
            fence_async_smem();
            __syncwarp();
            if (elect()) {
                tma_red2(&maps.m[M_OUTB], 448 + col, mt * 128 + warp * 16, wslot);
                bulk_commit();
                bulk_wait_read();
            }
        }
    }
}

typedef CUresult (*EncodeFn)(CUtensorMap*, CUtensorMapDataType, cuuint32_t, void*, const cuuint64_t*, const cuuint64_t*,
                             const cuuint32_t*, const cuuint32_t*, CUtensorMapInterleave, CUtensorMapSwizzle,
                             CUtensorMapL2promotion, CUtensorMapFloatOOBfill);

struct Dim { uint64_t size, stride; uint32_t box; };
void encode(EncodeFn fn, CUtensorMap* m, const void* ptr, CUtensorMapSwizzle sw, Dim d0, Dim d1, Dim d2 = {0, 0, 0}, Dim d3 = {0, 0, 0}) {
    const cuuint64_t dims[4] = {d0.size, d1.size, d2.size, d3.size};
    const cuuint64_t strides[3] = {d1.stride, d2.stride, d3.stride};
    const cuuint32_t box[4] = {d0.box, d1.box, d2.box, d3.box};
    const cuuint32_t es[4] = {1, 1, 1, 1};
    fn(m, CU_TENSOR_MAP_DATA_TYPE_BFLOAT16, d3.size ? 4 : d2.size ? 3 : 2, const_cast<void*>(ptr), dims, strides, box, es,
       CU_TENSOR_MAP_INTERLEAVE_NONE, sw, CU_TENSOR_MAP_L2_PROMOTION_L2_128B, CU_TENSOR_MAP_FLOAT_OOB_FILL_NONE);
}

}

extern "C" void kernel_launch(void* const* d_in, const int* in_sizes, int n_in, void* d_out, int out_size) {
    (void)in_sizes; (void)n_in; (void)out_size;
    void* fnp = nullptr;
    cudaDriverEntryPointQueryResult st;
    cudaGetDriverEntryPoint("cuTensorMapEncodeTiled", &fnp, cudaEnableDefault, &st);
    EncodeFn fn = (EncodeFn)fnp;
    void* o_ptr = nullptr;
    cudaGetSymbolAddress(&o_ptr, g_o);
    cudaFuncSetAttribute(fused_kernel, cudaFuncAttributeMaxDynamicSharedMemorySize, SMEM_BYTES);

    const CUtensorMapSwizzle S128 = CU_TENSOR_MAP_SWIZZLE_128B, S0 = CU_TENSOR_MAP_SWIZZLE_NONE;
    Maps maps;
    encode(fn, &maps.m[M_XA], d_in[0], S128, {896, 2, 64}, {1024, 1792, 128});
    encode(fn, &maps.m[M_WKV], d_in[1], S128, {112, 2, 64}, {448, 2688, 32}, {3, 896, 2}, {4, 224, 1});
    encode(fn, &maps.m[M_WQ], d_in[1], S128, {112, 2, 64}, {448, 2688, 64}, {4, 224, 1});
    encode(fn, &maps.m[M_WO], d_in[2], S128, {112, 2, 64}, {448, 896, 64}, {4, 224, 1});
    encode(fn, &maps.m[M_XB], d_in[3], S128, {448, 2, 64}, {1024, 896, 64}, {2, 896 * 1024, 2});
    encode(fn, &maps.m[M_CR], d_in[4], S128, {2048, 2, 64}, {2048, 4096, 128});
    encode(fn, &maps.m[M_CI], d_in[5], S128, {2048, 2, 64}, {2048, 4096, 128});
    encode(fn, &maps.m[M_WR], d_in[6], S128, {448, 2, 64}, {448, 896, 112});
    encode(fn, &maps.m[M_WI], d_in[7], S128, {448, 2, 64}, {448, 896, 112});
    encode(fn, &maps.m[M_OST], o_ptr, S0, {448, 2, 112}, {2048, 896, 16});
    encode(fn, &maps.m[M_OLD], o_ptr, S128, {448, 2, 64}, {2048, 896, 128});
    encode(fn, &maps.m[M_OUTA], d_out, S0, {1792, 2, 112}, {1024, 3584, 16});
    encode(fn, &maps.m[M_OUTB], d_out, S0, {896, 2, 112}, {2048, 1792, 16});
    maps.out = (uint8_t*)d_out;

    fused_kernel<<<132, 384, SMEM_BYTES>>>(maps);
}
```

```cpp
#include <cuda.h>
#include <cuda_bf16.h>
#include <cuda_runtime.h>
#include <stdint.h>

namespace {

constexpr uint32_t SLOT = 16384;
constexpr int NA = 7;
constexpr uint32_t BRING = NA * SLOT;
constexpr uint32_t HALO = BRING + 6 * SLOT;
constexpr uint32_t HSLOT = 1792;
constexpr uint32_t WSLOT = 3584;
constexpr uint32_t BLOB = 14336;
constexpr uint32_t BARS = 14 * SLOT;
constexpr uint32_t BAR_FULL = BARS;
constexpr uint32_t BAR_EMPTY = BARS + 64;
constexpr uint32_t BAR_RDY = BARS + 128;
constexpr uint32_t BAR_DEP = BARS + 160;
constexpr uint32_t BAR_HALO = BARS + 192;
constexpr uint32_t BAR_PUB = BARS + 208;
constexpr uint32_t SMEM_BYTES = BARS + 256 + 1024;
constexpr uint32_t base = 1024;
constexpr int SPIN_LIMIT = 1 << 16;
constexpr uint32_t SENTINEL = 0xFFFFFFFFu;

#define E_EXTRA 0
#define HALO_DELAY 300
#define MAPPING 0
#define SPARE0 12
constexpr int NBE = 13 + E_EXTRA;
constexpr int POUT = 33 + NBE;
constexpr int ELAST = POUT + 6;
constexpr int LLAST = 52 - E_EXTRA;

enum { M_XA, M_WQK, M_WV, M_WO, M_XB, M_WR, M_WI, M_CR, M_CI, M_OUTA, M_OUTB, M_COUNT };
struct __align__(64) Maps { CUtensorMap m[M_COUNT]; };

constexpr int CNT_A = 0;
constexpr int CNT_B = 4;
constexpr int CNT_Z = 8;
constexpr int CNT_O = 16;
constexpr int CNT_COUNT = 32;

__device__ __align__(1024) uint8_t g_ab[64 * 4 * BLOB];
__device__ __align__(1024) uint8_t g_o[16 * 7 * SLOT];
__device__ __align__(1024) uint8_t g_part[64 * 2 * BLOB];
__device__ __align__(1024) uint8_t g_halo[64 * 2 * 2 * HSLOT];
__device__ __align__(128) unsigned g_cnt[CNT_COUNT * 32];
__device__ __align__(128) unsigned g_epoch[128 * 4 * 8];

__device__ __forceinline__ unsigned clk32() { unsigned c; asm volatile("mov.u32 %0, %%clock;" : "=r"(c)); return c; }
__device__ __forceinline__ void pause_until(unsigned t0, unsigned cycles) {
    while (clk32() - t0 < cycles) {}
}

#define PROF(idx)

__device__ __forceinline__ void mbar_init(uint32_t bar, uint32_t cnt) {
    asm volatile("mbarrier.init.shared::cta.b64 [%0], %1;" ::"r"(bar), "r"(cnt) : "memory");
}
__device__ __forceinline__ void mbar_expect(uint32_t bar, uint32_t bytes) {
    asm volatile("mbarrier.arrive.expect_tx.shared::cta.b64 _, [%0], %1;" ::"r"(bar), "r"(bytes) : "memory");
}
__device__ __forceinline__ void mbar_arrive(uint32_t bar) {
    asm volatile("mbarrier.arrive.shared::cta.b64 _, [%0];" ::"r"(bar) : "memory");
}
__device__ __forceinline__ bool mbar_try(uint32_t bar, uint32_t parity) {
    uint32_t ok;
    asm volatile("{\n.reg .pred p;\nmbarrier.try_wait.parity.shared::cta.b64 p, [%1], %2;\nselp.u32 %0, 1, 0, p;\n}\n"
                 : "=r"(ok) : "r"(bar), "r"(parity) : "memory");
    return ok;
}
__device__ __forceinline__ void mbar_wait(uint32_t bar, uint32_t parity) {
#pragma unroll 1
    for (int n = 0; n < SPIN_LIMIT; n++)
        if (mbar_try(bar, parity)) break;
}
__device__ __forceinline__ bool elect() {
    uint32_t p;
    asm volatile("{\n.reg .pred p;\nelect.sync _|p, 0xffffffff;\nselp.u32 %0, 1, 0, p;\n}\n" : "=r"(p));
    return p;
}
__device__ __forceinline__ void nb_sync(int id, int n) { asm volatile("bar.sync %0, %1;" ::"r"(id), "r"(n) : "memory"); }
__device__ __forceinline__ void warp_arrive(uint32_t bar) {
    __syncwarp();
    if ((threadIdx.x & 31) == 0) mbar_arrive(bar);
}

__device__ __forceinline__ void tma_ld2(uint32_t dst, const CUtensorMap* m, int c0, int c1, uint32_t bar) {
    asm volatile("cp.async.bulk.tensor.2d.shared::cluster.global.mbarrier::complete_tx::bytes [%0], [%1, {%3, %4}], [%2];"
                 ::"r"(dst), "l"(m), "r"(bar), "r"(c0), "r"(c1) : "memory");
}
__device__ __forceinline__ void tma_ld3(uint32_t dst, const CUtensorMap* m, int c0, int c1, int c2, uint32_t bar) {
    asm volatile("cp.async.bulk.tensor.3d.shared::cluster.global.mbarrier::complete_tx::bytes [%0], [%1, {%3, %4, %5}], [%2];"
                 ::"r"(dst), "l"(m), "r"(bar), "r"(c0), "r"(c1), "r"(c2) : "memory");
}
__device__ __forceinline__ void tma_ld4(uint32_t dst, const CUtensorMap* m, int c0, int c1, int c2, int c3, uint32_t bar) {
    asm volatile("cp.async.bulk.tensor.4d.shared::cluster.global.mbarrier::complete_tx::bytes [%0], [%1, {%3, %4, %5, %6}], [%2];"
                 ::"r"(dst), "l"(m), "r"(bar), "r"(c0), "r"(c1), "r"(c2), "r"(c3) : "memory");
}
__device__ __forceinline__ void bulk_ld(uint32_t dst, const void* src, uint32_t bytes, uint32_t bar) {
    asm volatile("cp.async.bulk.shared::cluster.global.mbarrier::complete_tx::bytes [%0], [%1], %2, [%3];"
                 ::"r"(dst), "l"(src), "r"(bytes), "r"(bar) : "memory");
}
__device__ __forceinline__ void tma_st2(const CUtensorMap* m, int c0, int c1, uint32_t src) {
    asm volatile("cp.async.bulk.tensor.2d.global.shared::cta.bulk_group [%0, {%1, %2}], [%3];"
                 ::"l"(m), "r"(c0), "r"(c1), "r"(src) : "memory");
}
__device__ __forceinline__ void bulk_commit() { asm volatile("cp.async.bulk.commit_group;" ::: "memory"); }
__device__ __forceinline__ void bulk_wait_read() { asm volatile("cp.async.bulk.wait_group.read 0;" ::: "memory"); }
__device__ __forceinline__ void fence_async_smem() { asm volatile("fence.proxy.async.shared::cta;" ::: "memory"); }
__device__ __forceinline__ void fence_async_global() { asm volatile("fence.proxy.async.global;" ::: "memory"); }

__device__ __forceinline__ void signal(int idx) {
    asm volatile("red.release.gpu.global.add.u32 [%0], 1;" ::"l"(&g_cnt[idx * 32]) : "memory");
}
__device__ __forceinline__ void await(int idx, unsigned target) {
#pragma unroll 1
    for (int n = 0; n < SPIN_LIMIT; n++) {
        unsigned v;
        asm volatile("ld.relaxed.gpu.global.u32 %0, [%1];" : "=r"(v) : "l"(&g_cnt[idx * 32]) : "memory");
        if ((int)(v - target) >= 0) break;
    }
    asm volatile("fence.acquire.gpu;" ::: "memory");
}
__device__ __forceinline__ void wait_dep(int k) {
    mbar_wait(base + BAR_DEP + k * 8, 0);
    fence_async_global();
}

#define WG_REGS                                                                                                     \
    "{%0,%1,%2,%3,%4,%5,%6,%7,%8,%9,%10,%11,%12,%13,%14,%15,%16,%17,%18,%19,%20,%21,%22,%23,%24,%25,%26,%27,"       \
    "%28,%29,%30,%31,%32,%33,%34,%35,%36,%37,%38,%39,%40,%41,%42,%43,%44,%45,%46,%47,%48,%49,%50,%51,%52,%53,%54,%55}"
#define WG_OPS(C)                                                                                                   \
    C(d[0]), C(d[1]), C(d[2]), C(d[3]), C(d[4]), C(d[5]), C(d[6]), C(d[7]), C(d[8]), C(d[9]), C(d[10]), C(d[11]),   \
    C(d[12]), C(d[13]), C(d[14]), C(d[15]), C(d[16]), C(d[17]), C(d[18]), C(d[19]), C(d[20]), C(d[21]), C(d[22]),   \
    C(d[23]), C(d[24]), C(d[25]), C(d[26]), C(d[27]), C(d[28]), C(d[29]), C(d[30]), C(d[31]), C(d[32]), C(d[33]),   \
    C(d[34]), C(d[35]), C(d[36]), C(d[37]), C(d[38]), C(d[39]), C(d[40]), C(d[41]), C(d[42]), C(d[43]), C(d[44]),   \
    C(d[45]), C(d[46]), C(d[47]), C(d[48]), C(d[49]), C(d[50]), C(d[51]), C(d[52]), C(d[53]), C(d[54]), C(d[55])

template <int TA, int TB, int SB, bool INIT>
__device__ __forceinline__ void wgmma112(float (&d)[56], uint64_t da, uint64_t db) {
    if (INIT) {
        asm volatile("{\n.reg .pred p;\nsetp.ne.b32 p, 0, 0;\n"
                     "wgmma.mma_async.sync.aligned.m64n112k16.f32.bf16.bf16 " WG_REGS ", %56, %57, p, 1, %59, %60, %58;\n}\n"
                     : WG_OPS("=f") : "l"(da), "l"(db), "n"(TB), "n"(SB), "n"(TA));
    } else {
        asm volatile("{\n.reg .pred p;\nsetp.ne.b32 p, 1, 0;\n"
                     "wgmma.mma_async.sync.aligned.m64n112k16.f32.bf16.bf16 " WG_REGS ", %56, %57, p, 1, %59, %60, %58;\n}\n"
                     : WG_OPS("+f") : "l"(da), "l"(db), "n"(TB), "n"(SB), "n"(TA));
    }
}
__device__ __forceinline__ void acc_fence(float (&d)[56]) {
#pragma unroll
    for (int i = 0; i < 56; i++) asm volatile("" : "+f"(d[i])::"memory");
}

__device__ __forceinline__ uint32_t pack2(float lo, float hi) {
    uint32_t r;
    asm volatile("cvt.rn.bf16x2.f32 %0, %1, %2;" : "=r"(r) : "f"(hi), "f"(lo));
    return r;
}
__device__ __forceinline__ uint32_t movm(uint32_t a) {
    uint32_t r;
    asm volatile("movmatrix.sync.aligned.m8n8.trans.b16 %0, %1;" : "=r"(r) : "r"(a));
    return r;
}
__device__ __forceinline__ void stsm4(uint32_t addr, uint32_t a, uint32_t b, uint32_t c, uint32_t d) {
    asm volatile("stmatrix.sync.aligned.m8n8.x4.shared.b16 [%0], {%1,%2,%3,%4};" ::"r"(addr), "r"(a), "r"(b), "r"(c), "r"(d) : "memory");
}
__device__ __forceinline__ void sts1(uint32_t addr, uint32_t a) { asm volatile("st.shared.b32 [%0], %1;" ::"r"(addr), "r"(a) : "memory"); }
__device__ __forceinline__ uint32_t lds1(uint32_t addr) {
    uint32_t a;
    asm volatile("ld.shared.b32 %0, [%1];" : "=r"(a) : "r"(addr) : "memory");
    return a;
}
__device__ __forceinline__ void stg1(uint8_t* p, uint32_t a) { asm volatile("st.global.b32 [%0], %1;" ::"l"(p), "r"(a) : "memory"); }
__device__ __forceinline__ void st_part(uint8_t* p, const uint32_t* v) {
    asm volatile("st.relaxed.gpu.global.v4.b32 [%0], {%1,%2,%3,%4};" ::"l"(p), "r"(v[0]), "r"(v[1]), "r"(v[2]), "r"(v[3]) : "memory");
}
__device__ __forceinline__ void ld_part(const uint8_t* p, uint32_t* v) {
    asm volatile("ld.relaxed.gpu.global.v4.b32 {%0,%1,%2,%3}, [%4];" : "=r"(v[0]), "=r"(v[1]), "=r"(v[2]), "=r"(v[3]) : "l"(p) : "memory");
}
__device__ __forceinline__ void mma16816(float (&d)[4], const uint32_t (&a)[4], uint32_t b0, uint32_t b1) {
    asm volatile("mma.sync.aligned.m16n8k16.row.col.f32.bf16.bf16.f32 {%0,%1,%2,%3}, {%4,%5,%6,%7}, {%8,%9}, {%0,%1,%2,%3};"
                 : "+f"(d[0]), "+f"(d[1]), "+f"(d[2]), "+f"(d[3]) : "r"(a[0]), "r"(a[1]), "r"(a[2]), "r"(a[3]), "r"(b0), "r"(b1));
}
__device__ __forceinline__ uint32_t max2(uint32_t a, uint32_t b) {
    uint32_t r;
    asm("max.bf16x2 %0, %1, %2;" : "=r"(r) : "r"(a), "r"(b));
    return r;
}
__device__ __forceinline__ void st_tagged(uint8_t* p, uint32_t a, uint32_t b, uint32_t tag) {
    asm volatile("{\n.reg .b64 x, y;\nmov.b64 x, {%1, %3};\nmov.b64 y, {%2, %3};\nst.relaxed.gpu.global.v2.b64 [%0], {x, y};\n}\n"
                 ::"l"(p), "r"(a), "r"(b), "r"(tag) : "memory");
}
__device__ __forceinline__ void ld_tagged(const uint8_t* p, uint32_t& a, uint32_t& ta, uint32_t& b, uint32_t& tb) {
    asm volatile("{\n.reg .b64 x, y;\nld.relaxed.gpu.global.v2.b64 {x, y}, [%4];\nmov.b64 {%0, %1}, x;\nmov.b64 {%2, %3}, y;\n}\n"
                 : "=r"(a), "=r"(ta), "=r"(b), "=r"(tb) : "l"(p) : "memory");
}
__device__ __forceinline__ float bf_lo(uint32_t v) { return __uint_as_float(v << 16); }
__device__ __forceinline__ float bf_hi(uint32_t v) { return __uint_as_float(v & 0xFFFF0000u); }
__device__ __forceinline__ float rcp(float x) { float r; asm("rcp.approx.ftz.f32 %0, %1;" : "=f"(r) : "f"(x)); return r; }
__device__ __forceinline__ float ex2(float x) { float r; asm volatile("ex2.approx.ftz.f32 %0, %1;" : "=f"(r) : "f"(x)); return r; }

__device__ __forceinline__ uint32_t full_bar(int stage) { return base + BAR_FULL + (stage & 7) * 8; }
__device__ __forceinline__ void wait_released(int j) { mbar_wait(base + BAR_EMPTY + (j & 7) * 8, (j >> 3) & 1); }

template <int V>
struct Int { static constexpr int value = V; };

__host__ __device__ constexpr int bslot_e(int i) { return (i < 2 || i >= 14) ? (i + 5) % 7 : (i + 1) % 5; }
__host__ __device__ constexpr int bslot_l(int i) { return i % 6; }

template <uint32_t OFF>
struct Feed {
    int stage;
    uint32_t dst;
    __device__ __forceinline__ void seek(int i, int slot) { stage = i; dst = base + OFF + slot * SLOT; }
    template <int N>
    __device__ __forceinline__ uint32_t acquire() { wait_released(stage - N); return full_bar(stage); }
    template <int N>
    __device__ __forceinline__ void next() {
        stage++;
        dst += SLOT;
        if (dst == base + OFF + N * SLOT) dst = base + OFF;
    }
};
__device__ __forceinline__ int skip_own(int n, int mt) { return n == mt ? 15 : n; }

__host__ __device__ constexpr uint64_t desc_const(uint32_t lbo, uint32_t sbo, uint32_t mode) {
    return ((uint64_t)((sbo >> 4) | (mode << 30)) << 32) | ((lbo >> 4) << 16);
}
constexpr uint64_t D_K128 = desc_const(16, 1024, 1);
constexpr uint64_t D_N128 = desc_const(8192, 1024, 1);
constexpr uint64_t D_BLOB = desc_const(128, 256, 0);
constexpr uint64_t D_OT = desc_const(2048, 128, 0);

enum Kind { XW, XWN, QK, BIG, OUT };

struct Ring {
    int stage;
    uint32_t a, b;
    uint32_t wg;
    uint32_t zero;
    bool leader;
    __device__ __forceinline__ void seek(int i, int bslot) {
        stage = i;
        a = (base + (i % NA) * SLOT) >> 4;
        b = (base + BRING + bslot * SLOT) >> 4;
    }
    __device__ __forceinline__ void wait() {
        mbar_wait(full_bar(stage), (stage >> 3) & 1);
    }
    __device__ __forceinline__ void pin() {
        uint32_t n = 0;
#pragma unroll 1
        do {
            asm volatile("pmevent 7;" ::: "memory");
        } while (n++ < zero);
    }
    template <Kind K, int NBS, bool INIT, int SB = 1, bool WAIT = true>
    __device__ __forceinline__ void run(float (&d)[56], float (&e)[56]) {
        if (WAIT) wait();
        asm volatile("wgmma.fence.sync.aligned;" ::: "memory");
        if (K == QK) {
            const uint64_t da = D_K128 + ((base >> 4) + (stage >> 1) * (SLOT >> 4) + (stage & 1) * 4 + wg * 512), db = D_N128 + b;
            wgmma112<0, 1, 1, INIT>(d, da, db);
            wgmma112<0, 1, 1, INIT>(e, da, db + 256);
            wgmma112<0, 1, 1, false>(d, da + 2, db + 128);
            wgmma112<0, 1, 1, false>(e, da + 2, db + 384);
        } else {
            constexpr int TA = K == OUT, TB = K != XW;
            constexpr uint32_t sa = K == OUT ? 256 : 2, sb = K == XW ? 2 : K == BIG ? 224 : 128;
            const uint64_t da = (K == OUT ? D_OT : D_K128) + (a + wg * (K == OUT ? 64 : 512));
            const uint64_t db = (K == XW ? D_K128 : K == BIG ? D_BLOB : D_N128) + b;
            wgmma112<TA, TB, SB, INIT>(d, da, db);
            wgmma112<TA, TB, SB, false>(d, da + sa, db + sb);
            wgmma112<TA, TB, SB, false>(d, da + 2 * sa, db + 2 * sb);
            wgmma112<TA, TB, SB, false>(d, da + 3 * sa, db + 3 * sb);
        }
        asm volatile("wgmma.commit_group.sync.aligned;" ::: "memory");
        asm volatile("wgmma.wait_group.sync.aligned 1;" ::: "memory");
        if (leader && stage > 0) mbar_arrive(base + BAR_EMPTY + ((stage - 1) & 7) * 8);
        stage++;
        a += SLOT >> 4;
        if (a == (base + NA * SLOT) >> 4) a = base >> 4;
        b += SLOT >> 4;
        if (b == (base + BRING + NBS * SLOT) >> 4) b = (base + BRING) >> 4;
    }
    template <Kind K, int NBS, bool INIT, int SB = 1, bool WAIT = true>
    __device__ __forceinline__ void run(float (&d)[56]) { run<K, NBS, INIT, SB, WAIT>(d, d); }
};

__device__ __forceinline__ void pack_all(const float (&d)[56], uint32_t (&p)[28]) {
#pragma unroll
    for (int i = 0; i < 28; i++) p[i] = pack2(d[2 * i], d[2 * i + 1]);
}
template <int I0, int I1>
__device__ __forceinline__ void store_frags(uint8_t* dst, const uint32_t (&p)[28]) {
#pragma unroll
    for (int i = I0; i < I1; i++) stg1(dst + i * 128, p[i]);
}
__device__ __forceinline__ void stage_frags(uint32_t lane_addr, const uint32_t (&p)[28]) {
#pragma unroll
    for (int i = 0; i < 28; i += 4) stsm4(lane_addr + i * 128, p[i], p[i + 1], p[i + 2], p[i + 3]);
}
__device__ __forceinline__ void store_out(const uint32_t (&p)[28], uint32_t slab, const CUtensorMap* m, int c0, int c1) {
    const int lane = threadIdx.x & 31;
    const bool swap = lane & 16;
    const uint32_t addr = slab + (lane & 15) * 224 + (((lane >> 4) ^ (lane >> 2)) & 1) * 16;
#pragma unroll
    for (int i = 0; i < 28; i += 4)
        stsm4(addr + i * 8, swap ? p[i + 2] : p[i], swap ? p[i + 3] : p[i + 1], swap ? p[i] : p[i + 2], swap ? p[i + 1] : p[i + 3]);
    fence_async_smem();
    __syncwarp();
    if (elect()) {
        tma_st2(m, c0, c1, slab);
        bulk_commit();
        bulk_wait_read();
    }
}
__host__ __device__ constexpr int tile_of(int t) { return 7 * (t >> 2) + 3 * ((t >> 1) & 1) + 2 * (t & 1); }

__global__ void __launch_bounds__(384, 1) fused_kernel(const __grid_constant__ Maps maps) {
    extern __shared__ uint8_t smem_raw[];
    if ((uint32_t)__cvta_generic_to_shared(smem_raw) != base) return;
    const int warp = __shfl_sync(0xffffffffu, threadIdx.x >> 5, 0);
    const int lane = threadIdx.x & 31;
    if ((blockIdx.x >> 1) == SPARE0 || blockIdx.x >= 130) {
        const int ns = blockIdx.x >= 130 ? blockIdx.x - 128 : blockIdx.x & 1;
        uint4* dst = reinterpret_cast<uint4*>(g_part + (size_t)ns * 32 * BLOB);
#pragma unroll 4
        for (int i = threadIdx.x; i < 2 * BLOB; i += 384) dst[i] = make_uint4(SENTINEL, SENTINEL, SENTINEL, SENTINEL);
        __syncthreads();
        if (threadIdx.x < 17) signal(threadIdx.x < 16 ? CNT_O + threadIdx.x : CNT_Z + ns);
        return;
    }
    const int bid = blockIdx.x < 2 * SPARE0 ? blockIdx.x : blockIdx.x - 2;
    const int roleL = (bid >> 3) & 1;
    const int mt = ((bid >> 4) << 1) | ((bid >> 2) & 1);
    const int ns = bid & 3;
    const int par = mt >> 3, blk = mt & 7;

    if (warp == 8) {
        if (elect()) {
#pragma unroll
            for (int i = 0; i < 8; i++) mbar_init(base + BAR_FULL + i * 8, 2);
            asm volatile("fence.mbarrier_init.release.cluster;" ::: "memory");
        }
    } else if (warp == 9) {
        if (elect()) {
#pragma unroll
            for (int i = 0; i < 8; i++) mbar_init(base + BAR_EMPTY + i * 8, 8);
            asm volatile("fence.mbarrier_init.release.cluster;" ::: "memory");
        }
    } else if (warp == 10) {
        if (elect()) {
#pragma unroll
            for (int i = 0; i < 4; i++) mbar_init(base + BAR_RDY + i * 8, 8);
#pragma unroll
            for (int i = 0; i < 2; i++) mbar_init(base + BAR_HALO + i * 8, 8);
            asm volatile("fence.mbarrier_init.release.cluster;" ::: "memory");
        }
    } else if (warp == 11) {
        if (elect()) {
#pragma unroll
            for (int i = 0; i < 3; i++) mbar_init(base + BAR_DEP + i * 8, 1);
#pragma unroll
            for (int i = 0; i < 2; i++) mbar_init(base + BAR_PUB + i * 8, 1);
            asm volatile("fence.mbarrier_init.release.cluster;" ::: "memory");
        }
    }
    __syncthreads();

    const int col = ns * 112;
    if (warp == 8) {
        if (elect()) {
            if (roleL) {
#pragma unroll 1
                for (int i = 0; i < 4; i++) {
                    mbar_expect(full_bar(2 * i), SLOT);
                    tma_ld2(base + i * SLOT, &maps.m[M_XA], par * 448 + i * 64, blk * 128, full_bar(2 * i));
                }
            } else {
#pragma unroll 1
                for (int i = 0; i < NA; i++) {
                    mbar_expect(full_bar(i), SLOT);
                    tma_ld3(base + i * SLOT, &maps.m[M_XB], i * 64, mt * 64, 0, full_bar(i));
                }
            }
        }
    } else if (warp == 11) {
        if (elect()) {
            if (roleL) {
#pragma unroll 1
                for (int i = 0; i < 6; i++) {
                    const uint32_t dst = base + BRING + i * SLOT, bar = full_bar(i);
                    mbar_expect(bar, SLOT);
                    tma_ld4(dst, &maps.m[M_WQK], 0, i * 32, 0, ns, bar);
                    tma_ld4(dst + 8192, &maps.m[M_WQK], 64, i * 32, 0, ns, bar);
                    if (i & 1) mbar_arrive(bar);
                }
            } else {
#pragma unroll
                for (int i = 0; i < 7; i++) {
                    mbar_expect(full_bar(i), BLOB);
                    tma_ld2(base + BRING + bslot_e(i) * SLOT, &maps.m[M_WR], i * 64, col, full_bar(i));
                }
            }
        }
    }

    if (warp >= 8) {
        asm volatile("setmaxnreg.dec.sync.aligned.u32 56;");
        unsigned* epoch_ptr = &g_epoch[(bid * 4 + (warp - 8)) * 8];
#define PROF_FEED_A
#define PROF_FEED_B
        if (warp == 8) {
            if (elect()) {
                Feed<0> f;
                const int row = mt * 128;
                auto c_run = [&](const CUtensorMap* m, int off, int n0, int n1) {
#pragma unroll 1
                    for (int n = n0; n < n1; n++) {
                        const uint32_t bar = f.acquire<NA>();
                        mbar_expect(bar, SLOT);
                        tma_ld2(f.dst, m, (off + skip_own(n, mt)) * 64, row, bar);
                        PROF_FEED_A;
                        f.next<NA>();
                    }
                };
                if (!roleL) {
                    f.seek(14, 0);
#pragma unroll 1
                    for (int i = 0; i < 4; i++) {
                        const uint32_t bar = f.acquire<NA>();
                        mbar_expect(bar, SLOT);
                        tma_ld2(f.dst, &maps.m[M_CR + (i >> 1)], ((i & 1) * 16 + mt) * 64, row, bar);
                        mbar_arrive(bar);
                        PROF_FEED_A;
                        f.next<NA>();
                    }
                    c_run(&maps.m[M_CR], 0, 0, 15);
                    c_run(&maps.m[M_CI], 0, 0, NBE);
                    wait_dep(2);
#pragma unroll 1
                    for (int i = 0; i < 7; i++) {
                        const uint32_t bar = f.acquire<NA>();
                        mbar_expect(bar, SLOT);
                        bulk_ld(f.dst, g_o + (size_t)(mt * 7 + i) * SLOT, SLOT, bar);
                        PROF_FEED_A;
                        f.next<NA>();
                    }
                } else {
#pragma unroll 1
                    for (int i = 4; i < 7; i++) {
                        wait_released(2 * i - 8);
                        mbar_expect(full_bar(2 * i), SLOT);
                        tma_ld2(base + i * SLOT, &maps.m[M_XA], par * 448 + i * 64, blk * 128, full_bar(2 * i));
                    }
                    wait_released(7);
                    f.seek(21, 0);
                    c_run(&maps.m[M_CR], 16, 0, 15);
                    c_run(&maps.m[M_CI], 16, 0, 15);
                    c_run(&maps.m[M_CI], 0, NBE, 15);
                }
            }
        } else if (warp == 11) {
            if (elect()) {
                Feed<BRING> f;
                auto blob_run = [&](auto nbs, int quarter, int n0, int n1) {
                    constexpr int N = decltype(nbs)::value;
                    const uint8_t* src = g_ab + (size_t)(quarter * 64 + ns) * BLOB;
#pragma unroll 1
                    for (int n = n0; n < n1; n++) {
                        const uint32_t bar = f.template acquire<N>();
                        mbar_expect(bar, BLOB);
                        bulk_ld(f.dst, src + skip_own(n, mt) * (4 * BLOB), BLOB, bar);
                        PROF_FEED_B;
                        f.template next<N>();
                    }
                };
                auto w_run = [&](auto nbs, const CUtensorMap* m, bool no_a) {
                    constexpr int N = decltype(nbs)::value;
#pragma unroll 1
                    for (int i = 0; i < 7; i++) {
                        const uint32_t bar = f.template acquire<N>();
                        mbar_expect(bar, SLOT);
                        tma_ld3(f.dst, m, 0, i * 64, ns, bar);
                        tma_ld3(f.dst + 8192, m, 64, i * 64, ns, bar);
                        if (no_a) mbar_arrive(bar);
                        PROF_FEED_B;
                        f.template next<N>();
                    }
                };
                if (!roleL) {
                    f.seek(7, bslot_e(7));
#pragma unroll 1
                    for (int i = 0; i < 7; i++) {
                        const uint32_t bar = f.acquire<5>();
                        mbar_expect(bar, BLOB);
                        tma_ld2(f.dst, &maps.m[M_WI], i * 64, col, bar);
                        mbar_arrive(bar);
                        PROF_FEED_B;
                        f.next<5>();
                    }
                    f.seek(18, bslot_e(18));
                    wait_dep(0);
                    blob_run(Int<7>(), 0, 0, 15);
                    wait_dep(1);
                    blob_run(Int<7>(), 2, 0, NBE);
                    w_run(Int<7>(), &maps.m[M_WO], false);
                } else {
                    f.seek(6, 0);
#pragma unroll 1
                    for (int i = 6; i < 14; i++) {
                        const uint32_t bar = f.acquire<6>();
                        mbar_expect(bar, SLOT);
                        tma_ld4(f.dst, &maps.m[M_WQK], 0, i * 32, 0, ns, bar);
                        tma_ld4(f.dst + 8192, &maps.m[M_WQK], 64, i * 32, 0, ns, bar);
                        if (i & 1) mbar_arrive(bar);
                        PROF_FEED_B;
                        f.next<6>();
                    }
                    w_run(Int<6>(), &maps.m[M_WV], true);
                    wait_dep(0);
                    blob_run(Int<6>(), 1, 0, 15);
                    wait_dep(1);
                    blob_run(Int<6>(), 3, 0, 15);
                    blob_run(Int<6>(), 2, NBE, 15);
                }
            }
        } else if (warp == 10) {
            if (elect()) {
                const unsigned ep = *epoch_ptr + 1;
                await(CNT_A + ns, ep * 16);
                mbar_arrive(base + BAR_DEP);
                PROF(150);
                await(CNT_B + ns, ep * 16);
                mbar_arrive(base + BAR_DEP + 8);
                PROF(151);
                if (roleL) await(CNT_Z + ns, ep);
                else await(CNT_O + mt, ep * 8);
                mbar_arrive(base + BAR_DEP + 16);
                PROF(152);
                *epoch_ptr = ep;
            }
        } else if (!roleL) {
            if (elect()) {
                mbar_wait(base + BAR_RDY, 0);
                PROF(130);
                signal(CNT_A + ns);
                PROF(131);
                mbar_wait(base + BAR_RDY + 24, 0);
                PROF(132);
                signal(CNT_B + ns);
                PROF(133);
            }
        } else {
            const unsigned tag = *epoch_ptr + 1;
#pragma unroll 1
            for (int kv = 0; kv < 2; kv++) {
                uint32_t v[14], t[14];
#pragma unroll
                for (int i = 0; i < 14; i++) v[i] = 0;
                mbar_wait(base + BAR_PUB + kv * 8, 0);
                if (lane == 0) PROF(140 + kv);
                if (blk > 0) {
                    const uint8_t* src = g_halo + (size_t)(((mt - 1) * 4 + ns) * 2 + kv) * (2 * HSLOT) + lane * 16;
                    pause_until(clk32(), HALO_DELAY);
#pragma unroll 1
                    for (int n = 0; n < SPIN_LIMIT; n++) {
                        bool ok = true;
#pragma unroll
                        for (int i = 0; i < 7; i++) ld_tagged(src + i * 512, v[2 * i], t[2 * i], v[2 * i + 1], t[2 * i + 1]);
#pragma unroll
                        for (int i = 0; i < 14; i++) ok = ok && t[i] == tag;
                        if (__all_sync(0xffffffffu, ok)) break;
                    }
                }
#pragma unroll
                for (int i = 0; i < 14; i++) sts1(base + HALO + i * 128 + lane * 4, v[i]);
                warp_arrive(base + BAR_HALO + kv * 8);
                if (lane == 0) PROF(142 + kv);
            }
            if (elect()) {
                mbar_wait(base + BAR_RDY, 0);
                PROF(130);
                signal(CNT_O + mt);
                PROF(131);
                *epoch_ptr = tag;
            }
        }
    } else {
        asm volatile("setmaxnreg.inc.sync.aligned.u32 224;");
        Ring r;
        r.wg = warp >> 2;
        r.zero = blockIdx.y;
        r.leader = lane == 0;
        const int wg = warp >> 2;
        uint8_t* part = g_part + (size_t)(ns * 16 + mt) * (2 * BLOB) + threadIdx.x * 16;
        uint32_t p[28];

        if (!roleL) {
            uint8_t* blob = g_ab + (size_t)((wg * 16 + mt) * 4 + ns) * BLOB + (warp & 3) * WSLOT + lane * 4;
            const uint32_t own = base + BRING + wg * SLOT + (warp & 3) * WSLOT + lane * 16;
            float x0[56], x1[56];
            r.seek(0, bslot_e(0));
            r.run<XW, 7, true>(x0);
            r.run<XW, 7, false>(x0);
            r.seek(2, bslot_e(2));
#pragma unroll 1
            for (int i = 2; i < 7; i++) r.run<XW, 5, false>(x0);

            r.seek(7, bslot_e(7));
            r.run<XW, 5, true, -1>(x1);
            acc_fence(x0);
            pack_all(x0, p);
            store_frags<0, 14>(blob, p);
            r.run<XW, 5, false, -1>(x1);
            store_frags<14, 28>(blob, p);
            warp_arrive(base + BAR_RDY);
            r.run<XW, 5, false, -1>(x1);
            stage_frags(own + 5 * SLOT, p);
            warp_arrive(base + BAR_RDY + 8);
#pragma unroll 1
            for (int i = 10; i < 14; i++) r.run<XW, 5, false, -1>(x1);

            mbar_wait(base + BAR_RDY + 8, 0);
            fence_async_smem();
            r.seek(14, bslot_e(14));
            r.run<BIG, 7, true>(x0);
            acc_fence(x1);
            pack_all(x1, p);
            wait_released(10);
            stage_frags(own, p);
            warp_arrive(base + BAR_RDY + 16);
            r.run<BIG, 7, false>(x0);
            mbar_wait(base + BAR_RDY + 16, 0);
            fence_async_smem();
            blob += (size_t)128 * BLOB;
            r.run<BIG, 7, false>(x0);
            store_frags<0, 7>(blob, p);
            r.run<BIG, 7, false>(x0);
            store_frags<7, 14>(blob, p);
            r.run<BIG, 7, false>(x0);
            store_frags<14, 21>(blob, p);
            r.run<BIG, 7, false>(x0);
            store_frags<21, 28>(blob, p);
            warp_arrive(base + BAR_RDY + 24);
#pragma unroll 1
            for (int i = 20; i < POUT; i++) r.run<BIG, 7, false>(x0);

            r.seek(POUT, bslot_e(POUT));
            r.run<OUT, 7, true>(x1);
            acc_fence(x0);
            pack_all(x0, p);
#pragma unroll
            for (int i = 0; i < 3; i++) st_part(part + i * 4096, p + 4 * i);
            r.run<OUT, 7, false>(x1);
#pragma unroll
            for (int i = 3; i < 7; i++) st_part(part + i * 4096, p + 4 * i);
#pragma unroll 1
            for (int i = 2; i < 7; i++) r.run<OUT, 7, false>(x1);

            wait_released(ELAST - 6);
            asm volatile("wgmma.wait_group.sync.aligned 0;" ::: "memory");
            acc_fence(x1);
            pack_all(x1, p);
            const uint32_t slab = base + (wg ? BRING + bslot_e(ELAST - 6) * SLOT : ((ELAST - 6) % NA) * SLOT) + (warp & 3) * WSLOT;
            store_out(p, slab, &maps.m[M_OUTA], par * 896 + col, blk * 128 + warp * 16);
        } else {
            const int g = lane >> 2, tig = lane & 3;
            const unsigned tag = g_epoch[(bid * 4 + 1) * 8] + 1;
            const uint32_t hin = base + HALO + warp * HSLOT + lane * 4;
            uint8_t* hout = g_halo + (size_t)((mt * 4 + ns) * 2) * (2 * HSLOT) + lane * 16;
            auto publish = [&](const uint32_t (&h)[14], int kv) {
                if (warp < 7) {
#pragma unroll
                    for (int c = 0; c < 14; c++) sts1(hin + HSLOT + c * 128, h[c]);
                    warp_arrive(base + BAR_HALO + kv * 8);
                } else {
                    if (blk < 7) {
#pragma unroll
                        for (int i = 0; i < 7; i++) st_tagged(hout + kv * (2 * HSLOT) + i * 512, h[2 * i], h[2 * i + 1], tag);
                    }
                    warp_arrive(base + BAR_PUB + kv * 8);
                }
            };
            float y0[56], y1[56], y2[56];
            r.seek(0, 0);
            r.run<QK, 6, true>(y0, y1);
#pragma unroll 1
            for (int i = 1; i < 14; i++) r.run<QK, 6, false>(y0, y1);

            uint32_t m1[8][4], m0[8][4];
            r.seek(14, bslot_l(14));
            r.run<XWN, 6, true>(y2);
            acc_fence(y0);
            acc_fence(y1);
            {
                uint32_t lo[14], hi[14];
#pragma unroll
                for (int c = 0; c < 14; c++) {
                    lo[c] = pack2(y1[4 * c], y1[4 * c + 1]);
                    hi[c] = pack2(y1[4 * c + 2], y1[4 * c + 3]);
                }
                publish(hi, 0);
#pragma unroll
                for (int t = 0; t < 8; t++) {
                    const int c = tile_of(t);
                    const uint32_t dup = (t & 3) == 2 ? r.zero : 0u;
                    m1[t][0] = lo[c] ^ dup;
                    m1[t][1] = hi[c] ^ dup;
                    m1[t][2] = lo[c + 1];
                    m1[t][3] = hi[c + 1];
                    m0[t][0] = lo[c] + r.zero + dup;
                    m0[t][2] = lo[c + 1] + r.zero;
                }
            }
            r.run<XWN, 6, false>(y2);
            r.pin();
            uint32_t q[2][8][2];
#pragma unroll
            for (int b = 0; b < 2; b++) {
                uint32_t v[14];
#pragma unroll
                for (int c = 0; c < 14; c++) v[c] = pack2(y0[4 * c + 2 * b], y0[4 * c + 2 * b + 1]);
#pragma unroll
                for (int t = 0; t < 8; t++) {
                    const int c = tile_of(t);
                    q[b][t][0] = (t & 3) == 2 ? (tig >= 2 ? v[c] : 0u) : v[c];
                    q[b][t][1] = (t & 3) == 1 ? (tig < 2 ? v[c + 1] : 0u) : v[c + 1];
                }
            }
            r.run<XWN, 6, false>(y2);
            r.run<XWN, 6, false>(y2);
            r.run<XWN, 6, false>(y2);
            mbar_wait(base + BAR_HALO, 0);
#pragma unroll
            for (int t = 0; t < 8; t++) {
                m0[t][1] = lds1(hin + tile_of(t) * 128);
                m0[t][3] = lds1(hin + tile_of(t) * 128 + 128);
            }
            r.wait();
            float s[8][4];
#pragma unroll
            for (int step = 0; step < 2; step++) {
#pragma unroll
                for (int i = 0; i < 8; i++) {
                    const int b = 1 - (i >> 2), h = i & 3, t = 2 * h + step;
                    float (&d)[4] = s[2 * h + b];
                    if (step == 0) d[0] = d[1] = d[2] = d[3] = 0.f;
                    mma16816(d, b ? m1[t] : m0[t], q[b][t][0], q[b][t][1]);
                }
            }
            r.pin();
            r.run<XWN, 6, false, 1, false>(y2);
            r.pin();

            uint32_t pr[8], mx[4];
            {
                const bool cur0 = g <= 2 * tig, cur1 = g <= 2 * tig + 1;
#pragma unroll
                for (int i = 0; i < 8; i++) {
                    const int c = (i & 1) ? 2 : 0;
                    pr[i] = movm(pack2(cur0 ? s[i][c] : s[i][2 - c], cur1 ? s[i][c + 1] : s[i][3 - c]));
                }
            }
            r.run<XWN, 6, false>(y2);
            r.pin();
            const uint32_t curmask = (2 * tig <= g ? 0x0000FFFFu : 0u) | (2 * tig + 1 <= g ? 0xFFFF0000u : 0u);
            uint32_t mx1[4];
            {
                const uint32_t keep = (blk == 0 && warp == 0) ? curmask : 0xFFFFFFFFu;
#pragma unroll
                for (int i = 0; i < 8; i++) {
                    pr[i] = pack2(bf_lo(pr[i]) * 0.18898223650461362f, bf_hi(pr[i]) * 0.18898223650461362f);
                    if ((i & 1) == 0) pr[i] = (pr[i] & keep) | (0xCE6ECE6Eu & ~keep);
                }
#pragma unroll
                for (int i = 0; i < 4; i++) {
                    mx[i] = max2(__byte_perm(pr[2 * i], pr[2 * i + 1], 0x5410), __byte_perm(pr[2 * i], pr[2 * i + 1], 0x7632));
                    mx1[i] = __shfl_xor_sync(0xffffffffu, mx[i], 1);
                }
            }

            r.seek(21, bslot_l(21));
            r.run<BIG, 6, true>(y0);
            acc_fence(y2);
            uint32_t vh[14];
#pragma unroll
            for (int c = 0; c < 14; c++) vh[c] = movm(pack2(y2[4 * c + 2], y2[4 * c + 3]));
            r.run<BIG, 6, false>(y0);
            wait_released(19);
            publish(vh, 1);
            r.run<BIG, 6, false>(y0);
            r.pin();
            uint32_t vl[14];
#pragma unroll
            for (int c = 0; c < 14; c++) vl[c] = movm(pack2(y2[4 * c], y2[4 * c + 1]));
#pragma unroll
            for (int i = 0; i < 4; i++) {
                mx[i] = max2(mx[i], mx1[i]);
                mx1[i] = __shfl_xor_sync(0xffffffffu, mx[i], 2);
            }
            r.run<BIG, 6, false>(y0);
            r.pin();
            float e0[8], e1[8], sm[8], sm1[8];
#pragma unroll
            for (int i = 0; i < 8; i++) {
                const uint32_t m2 = max2(mx[i >> 1], mx1[i >> 1]);
                const float m = ((i & 1) ? bf_hi(m2) : bf_lo(m2)) * -1.4426950408889634f;
                e0[i] = ex2(fmaf(bf_lo(pr[i]), 1.4426950408889634f, m));
                e1[i] = ex2(fmaf(bf_hi(pr[i]), 1.4426950408889634f, m));
                sm[i] = e0[i] + e1[i];
                sm1[i] = __shfl_xor_sync(0xffffffffu, sm[i], 1);
            }
            r.run<BIG, 6, false>(y0);
            r.pin();
#pragma unroll
            for (int i = 0; i < 8; i++) {
                sm[i] += sm1[i];
                sm1[i] = __shfl_xor_sync(0xffffffffu, sm[i], 2);
            }
#pragma unroll
            for (int t = 0; t < 8; t++) {
                const int c = tile_of(t);
                const uint32_t dup = (t & 3) == 2 ? r.zero : 0u;
                m1[t][0] = vl[c] ^ dup;
                m1[t][1] = vl[c + 1];
                m1[t][2] = vh[c] ^ dup;
                m1[t][3] = vh[c + 1];
                m0[t][0] = vl[c] + r.zero + dup;
                m0[t][1] = vl[c + 1] + r.zero;
            }
            r.run<BIG, 6, false>(y0);
            mbar_wait(base + BAR_HALO + 8, 0);
#pragma unroll
            for (int t = 0; t < 8; t++) {
                m0[t][2] = lds1(hin + tile_of(t) * 128);
                m0[t][3] = lds1(hin + tile_of(t) * 128 + 128);
            }
            uint32_t pb[8][2];
#pragma unroll
            for (int i = 0; i < 8; i++) {
                const float inv = rcp(sm[i] + sm1[i]);
                const uint32_t w = pack2(e0[i] * inv, e1[i] * inv);
                pb[i][i & 1] = w & curmask;
                pb[i][1 - (i & 1)] = w & ~curmask;
            }
            r.wait();
            float o[2][8][4];
#pragma unroll
            for (int i = 0; i < 16; i++) {
                const int b = 1 - (i >> 3), t = i & 7;
                float (&d)[4] = o[b][t];
                d[0] = d[1] = d[2] = d[3] = 0.f;
                mma16816(d, b ? m1[t] : m0[t], pb[(t & 6) + b][0], pb[(t & 6) + b][1]);
            }
            r.pin();
            r.run<BIG, 6, false, 1, false>(y0);
            r.pin();
            uint8_t* odst = g_o + (size_t)mt * 7 * SLOT + ns * (14 * 2048) + warp * 256 + lane * 4;
#pragma unroll
            for (int hp = 0; hp < 2; hp++) {
#pragma unroll
                for (int b = 0; b < 2; b++) {
                    const float (&u)[8][4] = o[b];
                    const int t = 4 * hp;
                    uint8_t* dst = odst + hp * (7 * 2048) + b * 128;
                    stg1(dst, pack2(u[t][0], u[t][1]));
                    stg1(dst + 2048, pack2(u[t][2], u[t][3]));
                    stg1(dst + 2 * 2048, pack2(u[t + 1][0], u[t + 1][1]));
                    stg1(dst + 3 * 2048, pack2(g < 4 ? u[t + 1][2] : u[t + 2][0], g < 4 ? u[t + 1][3] : u[t + 2][1]));
                    stg1(dst + 4 * 2048, pack2(u[t + 2][2], u[t + 2][3]));
                    stg1(dst + 5 * 2048, pack2(u[t + 3][0], u[t + 3][1]));
                    stg1(dst + 6 * 2048, pack2(u[t + 3][2], u[t + 3][3]));
                    if (hp + b < 2) {
                        r.run<BIG, 6, false>(y0);
                        r.pin();
                    }
                }
            }
            warp_arrive(base + BAR_RDY);

#pragma unroll 1
            for (int i = 31; i < LLAST; i++) r.run<BIG, 6, false>(y0);
            mbar_wait(base + BAR_DEP + 16, 0);
#pragma unroll
            for (int i = 0; i < 7; i++) ld_part(part + i * 4096, p + 4 * i);
            r.seek(LLAST, bslot_l(LLAST));
            r.run<BIG, 6, false>(y0);
            wait_released(LLAST - 6);
#pragma unroll 1
            for (int n = 0; n < SPIN_LIMIT; n++) {
                bool ok = true;
#pragma unroll
                for (int i = 0; i < 28; i++) ok = ok && p[i] != SENTINEL;
                if (__all_sync(0xffffffffu, ok)) break;
#pragma unroll
                for (int i = 0; i < 7; i++) ld_part(part + i * 4096, p + 4 * i);
            }
            asm volatile("wgmma.wait_group.sync.aligned 0;" ::: "memory");
            acc_fence(y0);
#pragma unroll
            for (int i = 0; i < 28; i++) p[i] = pack2(y0[2 * i] + bf_lo(p[i]), y0[2 * i + 1] + bf_hi(p[i]));
            const uint32_t slab = base + (wg ? HALO : ((LLAST - 6) % NA) * SLOT) + (warp & 3) * WSLOT;
            store_out(p, slab, &maps.m[M_OUTB], 448 + col, mt * 128 + warp * 16);
        }
    }
}

typedef CUresult (*EncodeFn)(CUtensorMap*, CUtensorMapDataType, cuuint32_t, void*, const cuuint64_t*, const cuuint64_t*,
                             const cuuint32_t*, const cuuint32_t*, CUtensorMapInterleave, CUtensorMapSwizzle,
                             CUtensorMapL2promotion, CUtensorMapFloatOOBfill);

struct Dim { uint64_t size, stride; uint32_t box; };
void encode(EncodeFn fn, CUtensorMap* m, const void* ptr, CUtensorMapSwizzle sw, Dim d0, Dim d1, Dim d2 = {0, 0, 0}, Dim d3 = {0, 0, 0}) {
    const cuuint64_t dims[4] = {d0.size, d1.size, d2.size, d3.size};
    const cuuint64_t strides[3] = {d1.stride, d2.stride, d3.stride};
    const cuuint32_t box[4] = {d0.box, d1.box, d2.box, d3.box};
    const cuuint32_t es[4] = {1, 1, 1, 1};
    fn(m, CU_TENSOR_MAP_DATA_TYPE_BFLOAT16, d3.size ? 4 : d2.size ? 3 : 2, const_cast<void*>(ptr), dims, strides, box, es,
       CU_TENSOR_MAP_INTERLEAVE_NONE, sw, CU_TENSOR_MAP_L2_PROMOTION_L2_128B, CU_TENSOR_MAP_FLOAT_OOB_FILL_NONE);
}

}

extern "C" void kernel_launch(void* const* d_in, const int* in_sizes, int n_in, void* d_out, int out_size) {
    (void)in_sizes; (void)n_in; (void)out_size;
    void* fnp = nullptr;
    cudaDriverEntryPointQueryResult st;
    cudaGetDriverEntryPoint("cuTensorMapEncodeTiled", &fnp, cudaEnableDefault, &st);
    EncodeFn fn = (EncodeFn)fnp;
    cudaFuncSetAttribute(fused_kernel, cudaFuncAttributeMaxDynamicSharedMemorySize, SMEM_BYTES);

    const CUtensorMapSwizzle S128 = CU_TENSOR_MAP_SWIZZLE_128B, S0 = CU_TENSOR_MAP_SWIZZLE_NONE;
    Maps maps;
    encode(fn, &maps.m[M_XA], d_in[0], S128, {896, 2, 64}, {1024, 1792, 128});
    encode(fn, &maps.m[M_WQK], d_in[1], S128, {112, 2, 64}, {448, 2688, 32}, {3, 896, 2}, {4, 224, 1});
    encode(fn, &maps.m[M_WV], (const uint8_t*)d_in[1] + 1792, S128, {112, 2, 64}, {448, 2688, 64}, {4, 224, 1});
    encode(fn, &maps.m[M_WO], d_in[2], S128, {112, 2, 64}, {448, 896, 64}, {4, 224, 1});
    encode(fn, &maps.m[M_XB], d_in[3], S128, {448, 2, 64}, {1024, 896, 64}, {2, 896 * 1024, 2});
    encode(fn, &maps.m[M_CR], d_in[4], S128, {2048, 2, 64}, {2048, 4096, 128});
    encode(fn, &maps.m[M_CI], d_in[5], S128, {2048, 2, 64}, {2048, 4096, 128});
    encode(fn, &maps.m[M_WR], d_in[6], S128, {448, 2, 64}, {448, 896, 112});
    encode(fn, &maps.m[M_WI], d_in[7], S128, {448, 2, 64}, {448, 896, 112});
    encode(fn, &maps.m[M_OUTA], d_out, S0, {1792, 2, 112}, {1024, 3584, 16});
    encode(fn, &maps.m[M_OUTB], d_out, S0, {896, 2, 112}, {2048, 1792, 16});

    fused_kernel<<<132, 384, SMEM_BYTES>>>(maps);
}
```

```cpp
#include <cuda.h>
#include <cuda_bf16.h>
#include <cuda_runtime.h>
#include <stdint.h>

namespace {

constexpr uint32_t SLOT = 16384;
constexpr int NA = 7;
constexpr uint32_t BRING = NA * SLOT;
constexpr uint32_t HALO = BRING + 6 * SLOT;
constexpr uint32_t HSLOT = 1792;
constexpr uint32_t WSLOT = 3584;
constexpr uint32_t BLOB = 14336;
constexpr uint32_t BARS = 14 * SLOT;
constexpr uint32_t BAR_FULL = BARS;
constexpr uint32_t BAR_EMPTY = BARS + 64;
constexpr uint32_t BAR_RDY = BARS + 128;
constexpr uint32_t BAR_DEP = BARS + 160;
constexpr uint32_t BAR_HALO = BARS + 192;
constexpr uint32_t BAR_PUB = BARS + 208;
constexpr uint32_t SMEM_BYTES = BARS + 256 + 1024;
constexpr uint32_t base = 1024;
constexpr int SPIN_LIMIT = 1 << 16;
constexpr uint32_t SENTINEL = 0xFFFFFFFFu;

#define E_EXTRA 0
#define HALO_DELAY 300
#define PACE_0 0
#define MAPPING 0
#define SPARE0 12
constexpr int NBE = 13 + E_EXTRA;
constexpr int POUT = 33 + NBE;
constexpr int ELAST = POUT + 6;
constexpr int LLAST = 52 - E_EXTRA;

enum { M_XA, M_WQK, M_WV, M_WO, M_XB, M_WR, M_WI, M_CR, M_CI, M_OUTA, M_OUTB, M_COUNT };
struct __align__(64) Maps { CUtensorMap m[M_COUNT]; };

constexpr int CNT_A = 0;
constexpr int CNT_B = 4;
constexpr int CNT_Z = 8;
constexpr int CNT_O = 16;
constexpr int CNT_COUNT = 32;

__device__ __align__(1024) uint8_t g_ab[64 * 4 * BLOB];
__device__ __align__(1024) uint8_t g_o[16 * 7 * SLOT];
__device__ __align__(1024) uint8_t g_part[64 * 2 * BLOB];
__device__ __align__(1024) uint8_t g_halo[64 * 2 * 2 * HSLOT];
__device__ __align__(128) unsigned g_cnt[CNT_COUNT * 32];
__device__ __align__(128) unsigned g_epoch[128 * 4 * 8];

__device__ __forceinline__ unsigned clk32() { unsigned c; asm volatile("mov.u32 %0, %%clock;" : "=r"(c)); return c; }
__device__ __forceinline__ void pause_until(unsigned t0, unsigned cycles) {
    while (clk32() - t0 < cycles) {}
}

#define PROF(idx)

__device__ __forceinline__ void mbar_init(uint32_t bar, uint32_t cnt) {
    asm volatile("mbarrier.init.shared::cta.b64 [%0], %1;" ::"r"(bar), "r"(cnt) : "memory");
}
__device__ __forceinline__ void mbar_expect(uint32_t bar, uint32_t bytes) {
    asm volatile("mbarrier.arrive.expect_tx.shared::cta.b64 _, [%0], %1;" ::"r"(bar), "r"(bytes) : "memory");
}
__device__ __forceinline__ void mbar_arrive(uint32_t bar) {
    asm volatile("mbarrier.arrive.shared::cta.b64 _, [%0];" ::"r"(bar) : "memory");
}
__device__ __forceinline__ bool mbar_try(uint32_t bar, uint32_t parity) {
    uint32_t ok;
    asm volatile("{\n.reg .pred p;\nmbarrier.try_wait.parity.shared::cta.b64 p, [%1], %2;\nselp.u32 %0, 1, 0, p;\n}\n"
                 : "=r"(ok) : "r"(bar), "r"(parity) : "memory");
    return ok;
}
__device__ __forceinline__ void mbar_wait(uint32_t bar, uint32_t parity) {
#pragma unroll 1
    for (int n = 0; n < SPIN_LIMIT; n++)
        if (mbar_try(bar, parity)) break;
}
__device__ __forceinline__ bool elect() {
    uint32_t p;
    asm volatile("{\n.reg .pred p;\nelect.sync _|p, 0xffffffff;\nselp.u32 %0, 1, 0, p;\n}\n" : "=r"(p));
    return p;
}
__device__ __forceinline__ void nb_sync(int id, int n) { asm volatile("bar.sync %0, %1;" ::"r"(id), "r"(n) : "memory"); }
__device__ __forceinline__ void warp_arrive(uint32_t bar) {
    __syncwarp();
    if ((threadIdx.x & 31) == 0) mbar_arrive(bar);
}

__device__ __forceinline__ void tma_ld2(uint32_t dst, const CUtensorMap* m, int c0, int c1, uint32_t bar) {
    asm volatile("cp.async.bulk.tensor.2d.shared::cluster.global.mbarrier::complete_tx::bytes [%0], [%1, {%3, %4}], [%2];"
                 ::"r"(dst), "l"(m), "r"(bar), "r"(c0), "r"(c1) : "memory");
}
__device__ __forceinline__ void tma_ld3(uint32_t dst, const CUtensorMap* m, int c0, int c1, int c2, uint32_t bar) {
    asm volatile("cp.async.bulk.tensor.3d.shared::cluster.global.mbarrier::complete_tx::bytes [%0], [%1, {%3, %4, %5}], [%2];"
                 ::"r"(dst), "l"(m), "r"(bar), "r"(c0), "r"(c1), "r"(c2) : "memory");
}
__device__ __forceinline__ void tma_ld4(uint32_t dst, const CUtensorMap* m, int c0, int c1, int c2, int c3, uint32_t bar) {
    asm volatile("cp.async.bulk.tensor.4d.shared::cluster.global.mbarrier::complete_tx::bytes [%0], [%1, {%3, %4, %5, %6}], [%2];"
                 ::"r"(dst), "l"(m), "r"(bar), "r"(c0), "r"(c1), "r"(c2), "r"(c3) : "memory");
}
__device__ __forceinline__ void bulk_ld(uint32_t dst, const void* src, uint32_t bytes, uint32_t bar) {
    asm volatile("cp.async.bulk.shared::cluster.global.mbarrier::complete_tx::bytes [%0], [%1], %2, [%3];"
                 ::"r"(dst), "l"(src), "r"(bytes), "r"(bar) : "memory");
}
__device__ __forceinline__ void tma_st2(const CUtensorMap* m, int c0, int c1, uint32_t src) {
    asm volatile("cp.async.bulk.tensor.2d.global.shared::cta.bulk_group [%0, {%1, %2}], [%3];"
                 ::"l"(m), "r"(c0), "r"(c1), "r"(src) : "memory");
}
__device__ __forceinline__ void bulk_commit() { asm volatile("cp.async.bulk.commit_group;" ::: "memory"); }
__device__ __forceinline__ void bulk_wait_read() { asm volatile("cp.async.bulk.wait_group.read 0;" ::: "memory"); }
__device__ __forceinline__ void fence_async_smem() { asm volatile("fence.proxy.async.shared::cta;" ::: "memory"); }
__device__ __forceinline__ void fence_async_global() { asm volatile("fence.proxy.async.global;" ::: "memory"); }

__device__ __forceinline__ void signal(int idx) {
    asm volatile("fence.proxy.async;\nred.relaxed.gpu.global.add.u32 [%0], 1;" ::"l"(&g_cnt[idx * 32]) : "memory");
}
__device__ __forceinline__ void await(int idx, unsigned target) {
#pragma unroll 1
    for (int n = 0; n < SPIN_LIMIT; n++) {
        unsigned v;
        asm volatile("ld.relaxed.gpu.global.u32 %0, [%1];" : "=r"(v) : "l"(&g_cnt[idx * 32]) : "memory");
        if ((int)(v - target) >= 0) break;
    }
    asm volatile("fence.acquire.gpu;" ::: "memory");
}
__device__ __forceinline__ void wait_dep(int k) {
    mbar_wait(base + BAR_DEP + k * 8, 0);
    fence_async_global();
}

#define WG_REGS                                                                                                     \
    "{%0,%1,%2,%3,%4,%5,%6,%7,%8,%9,%10,%11,%12,%13,%14,%15,%16,%17,%18,%19,%20,%21,%22,%23,%24,%25,%26,%27,"       \
    "%28,%29,%30,%31,%32,%33,%34,%35,%36,%37,%38,%39,%40,%41,%42,%43,%44,%45,%46,%47,%48,%49,%50,%51,%52,%53,%54,%55}"
#define WG_OPS(C)                                                                                                   \
    C(d[0]), C(d[1]), C(d[2]), C(d[3]), C(d[4]), C(d[5]), C(d[6]), C(d[7]), C(d[8]), C(d[9]), C(d[10]), C(d[11]),   \
    C(d[12]), C(d[13]), C(d[14]), C(d[15]), C(d[16]), C(d[17]), C(d[18]), C(d[19]), C(d[20]), C(d[21]), C(d[22]),   \
    C(d[23]), C(d[24]), C(d[25]), C(d[26]), C(d[27]), C(d[28]), C(d[29]), C(d[30]), C(d[31]), C(d[32]), C(d[33]),   \
    C(d[34]), C(d[35]), C(d[36]), C(d[37]), C(d[38]), C(d[39]), C(d[40]), C(d[41]), C(d[42]), C(d[43]), C(d[44]),   \
    C(d[45]), C(d[46]), C(d[47]), C(d[48]), C(d[49]), C(d[50]), C(d[51]), C(d[52]), C(d[53]), C(d[54]), C(d[55])

template <int TA, int TB, int SB, bool INIT>
__device__ __forceinline__ void wgmma112(float (&d)[56], uint64_t da, uint64_t db) {
    if (INIT) {
        asm volatile("{\n.reg .pred p;\nsetp.ne.b32 p, 0, 0;\n"
                     "wgmma.mma_async.sync.aligned.m64n112k16.f32.bf16.bf16 " WG_REGS ", %56, %57, p, 1, %59, %60, %58;\n}\n"
                     : WG_OPS("=f") : "l"(da), "l"(db), "n"(TB), "n"(SB), "n"(TA));
    } else {
        asm volatile("{\n.reg .pred p;\nsetp.ne.b32 p, 1, 0;\n"
                     "wgmma.mma_async.sync.aligned.m64n112k16.f32.bf16.bf16 " WG_REGS ", %56, %57, p, 1, %59, %60, %58;\n}\n"
                     : WG_OPS("+f") : "l"(da), "l"(db), "n"(TB), "n"(SB), "n"(TA));
    }
}
__device__ __forceinline__ void acc_fence(float (&d)[56]) {
#pragma unroll
    for (int i = 0; i < 56; i++) asm volatile("" : "+f"(d[i])::"memory");
}

__device__ __forceinline__ uint32_t pack2(float lo, float hi) {
    uint32_t r;
    asm volatile("cvt.rn.bf16x2.f32 %0, %1, %2;" : "=r"(r) : "f"(hi), "f"(lo));
    return r;
}
__device__ __forceinline__ uint32_t movm(uint32_t a) {
    uint32_t r;
    asm volatile("movmatrix.sync.aligned.m8n8.trans.b16 %0, %1;" : "=r"(r) : "r"(a));
    return r;
}
__device__ __forceinline__ void stsm4(uint32_t addr, uint32_t a, uint32_t b, uint32_t c, uint32_t d) {
    asm volatile("stmatrix.sync.aligned.m8n8.x4.shared.b16 [%0], {%1,%2,%3,%4};" ::"r"(addr), "r"(a), "r"(b), "r"(c), "r"(d) : "memory");
}
__device__ __forceinline__ void sts1(uint32_t addr, uint32_t a) { asm volatile("st.shared.b32 [%0], %1;" ::"r"(addr), "r"(a) : "memory"); }
__device__ __forceinline__ uint32_t lds1(uint32_t addr) {
    uint32_t a;
    asm volatile("ld.shared.b32 %0, [%1];" : "=r"(a) : "r"(addr) : "memory");
    return a;
}
__device__ __forceinline__ void stg1(uint8_t* p, uint32_t a) { asm volatile("st.global.b32 [%0], %1;" ::"l"(p), "r"(a) : "memory"); }
__device__ __forceinline__ void st_part(uint8_t* p, const uint32_t* v) {
    asm volatile("st.relaxed.gpu.global.v4.b32 [%0], {%1,%2,%3,%4};" ::"l"(p), "r"(v[0]), "r"(v[1]), "r"(v[2]), "r"(v[3]) : "memory");
}
__device__ __forceinline__ void ld_part(const uint8_t* p, uint32_t* v) {
    asm volatile("ld.relaxed.gpu.global.v4.b32 {%0,%1,%2,%3}, [%4];" : "=r"(v[0]), "=r"(v[1]), "=r"(v[2]), "=r"(v[3]) : "l"(p) : "memory");
}
__device__ __forceinline__ void mma16816(float (&d)[4], const uint32_t (&a)[4], uint32_t b0, uint32_t b1) {
    asm volatile("mma.sync.aligned.m16n8k16.row.col.f32.bf16.bf16.f32 {%0,%1,%2,%3}, {%4,%5,%6,%7}, {%8,%9}, {%0,%1,%2,%3};"
                 : "+f"(d[0]), "+f"(d[1]), "+f"(d[2]), "+f"(d[3]) : "r"(a[0]), "r"(a[1]), "r"(a[2]), "r"(a[3]), "r"(b0), "r"(b1));
}
__device__ __forceinline__ uint32_t max2(uint32_t a, uint32_t b) {
    uint32_t r;
    asm("max.bf16x2 %0, %1, %2;" : "=r"(r) : "r"(a), "r"(b));
    return r;
}
__device__ __forceinline__ void st_tagged(uint8_t* p, uint32_t a, uint32_t b, uint32_t tag) {
    asm volatile("{\n.reg .b64 x, y;\nmov.b64 x, {%1, %3};\nmov.b64 y, {%2, %3};\nst.relaxed.gpu.global.v2.b64 [%0], {x, y};\n}\n"
                 ::"l"(p), "r"(a), "r"(b), "r"(tag) : "memory");
}
__device__ __forceinline__ void ld_tagged(const uint8_t* p, uint32_t& a, uint32_t& ta, uint32_t& b, uint32_t& tb) {
    asm volatile("{\n.reg .b64 x, y;\nld.relaxed.gpu.global.v2.b64 {x, y}, [%4];\nmov.b64 {%0, %1}, x;\nmov.b64 {%2, %3}, y;\n}\n"
                 : "=r"(a), "=r"(ta), "=r"(b), "=r"(tb) : "l"(p) : "memory");
}
__device__ __forceinline__ float bf_lo(uint32_t v) { return __uint_as_float(v << 16); }
__device__ __forceinline__ float bf_hi(uint32_t v) { return __uint_as_float(v & 0xFFFF0000u); }
__device__ __forceinline__ float rcp(float x) { float r; asm("rcp.approx.ftz.f32 %0, %1;" : "=f"(r) : "f"(x)); return r; }
__device__ __forceinline__ float ex2(float x) { float r; asm volatile("ex2.approx.ftz.f32 %0, %1;" : "=f"(r) : "f"(x)); return r; }

__device__ __forceinline__ uint32_t full_bar(int stage) { return base + BAR_FULL + (stage & 7) * 8; }
__device__ __forceinline__ void wait_released(int j) { mbar_wait(base + BAR_EMPTY + (j & 7) * 8, (j >> 3) & 1); }

template <int V>
struct Int { static constexpr int value = V; };

__host__ __device__ constexpr int bslot_e(int i) { return (i < 2 || i >= 14) ? (i + 5) % 7 : (i + 1) % 5; }
__host__ __device__ constexpr int bslot_l(int i) { return i % 6; }

template <uint32_t OFF>
struct Feed {
    int stage;
    uint32_t dst;
    __device__ __forceinline__ void seek(int i, int slot) { stage = i; dst = base + OFF + slot * SLOT; }
    template <int N>
    __device__ __forceinline__ uint32_t acquire() { wait_released(stage - N); return full_bar(stage); }
    template <int N>
    __device__ __forceinline__ void next() {
        stage++;
        dst += SLOT;
        if (dst == base + OFF + N * SLOT) dst = base + OFF;
    }
};
__device__ __forceinline__ int skip_own(int n, int mt) { return n == mt ? 15 : n; }

__host__ __device__ constexpr uint64_t desc_const(uint32_t lbo, uint32_t sbo, uint32_t mode) {
    return ((uint64_t)((sbo >> 4) | (mode << 30)) << 32) | ((lbo >> 4) << 16);
}
constexpr uint64_t D_K128 = desc_const(16, 1024, 1);
constexpr uint64_t D_N128 = desc_const(8192, 1024, 1);
constexpr uint64_t D_BLOB = desc_const(128, 256, 0);
constexpr uint64_t D_OT = desc_const(2048, 128, 0);

enum Kind { XW, XWN, QK, BIG, OUT };

struct Ring {
    int stage;
    uint32_t a, b;
    uint32_t wg;
    uint32_t zero;
    bool leader;
    __device__ __forceinline__ void seek(int i, int bslot) {
        stage = i;
        a = (base + (i % NA) * SLOT) >> 4;
        b = (base + BRING + bslot * SLOT) >> 4;
    }
    __device__ __forceinline__ void wait() {
        mbar_wait(full_bar(stage), (stage >> 3) & 1);
    }
    __device__ __forceinline__ void pin() {
        uint32_t n = 0;
#pragma unroll 1
        do {
            asm volatile("pmevent 7;" ::: "memory");
        } while (n++ < zero);
    }
    template <Kind K, int NBS, bool INIT, int SB = 1, bool WAIT = true>
    __device__ __forceinline__ void run(float (&d)[56], float (&e)[56]) {
        if (WAIT) wait();
        asm volatile("wgmma.fence.sync.aligned;" ::: "memory");
        if (K == QK) {
            const uint64_t da = D_K128 + ((base >> 4) + (stage >> 1) * (SLOT >> 4) + (stage & 1) * 4 + wg * 512), db = D_N128 + b;
            wgmma112<0, 1, 1, INIT>(d, da, db);
            wgmma112<0, 1, 1, INIT>(e, da, db + 256);
            wgmma112<0, 1, 1, false>(d, da + 2, db + 128);
            wgmma112<0, 1, 1, false>(e, da + 2, db + 384);
        } else {
            constexpr int TA = K == OUT, TB = K != XW;
            constexpr uint32_t sa = K == OUT ? 256 : 2, sb = K == XW ? 2 : K == BIG ? 224 : 128;
            const uint64_t da = (K == OUT ? D_OT : D_K128) + (a + wg * (K == OUT ? 64 : 512));
            const uint64_t db = (K == XW ? D_K128 : K == BIG ? D_BLOB : D_N128) + b;
            wgmma112<TA, TB, SB, INIT>(d, da, db);
            wgmma112<TA, TB, SB, false>(d, da + sa, db + sb);
            wgmma112<TA, TB, SB, false>(d, da + 2 * sa, db + 2 * sb);
            wgmma112<TA, TB, SB, false>(d, da + 3 * sa, db + 3 * sb);
        }
        asm volatile("wgmma.commit_group.sync.aligned;" ::: "memory");
        asm volatile("wgmma.wait_group.sync.aligned 1;" ::: "memory");
        if (leader && stage > 0) mbar_arrive(base + BAR_EMPTY + ((stage - 1) & 7) * 8);
        stage++;
        a += SLOT >> 4;
        if (a == (base + NA * SLOT) >> 4) a = base >> 4;
        b += SLOT >> 4;
        if (b == (base + BRING + NBS * SLOT) >> 4) b = (base + BRING) >> 4;
    }
    template <Kind K, int NBS, bool INIT, int SB = 1, bool WAIT = true>
    __device__ __forceinline__ void run(float (&d)[56]) { run<K, NBS, INIT, SB, WAIT>(d, d); }
};

__device__ __forceinline__ void pack_all(const float (&d)[56], uint32_t (&p)[28]) {
#pragma unroll
    for (int i = 0; i < 28; i++) p[i] = pack2(d[2 * i], d[2 * i + 1]);
}
template <int I0, int I1>
__device__ __forceinline__ void store_frags(uint8_t* dst, const uint32_t (&p)[28]) {
#pragma unroll
    for (int i = I0; i < I1; i++) stg1(dst + i * 128, p[i]);
}
__device__ __forceinline__ void stage_frags(uint32_t lane_addr, const uint32_t (&p)[28]) {
#pragma unroll
    for (int i = 0; i < 28; i += 4) stsm4(lane_addr + i * 128, p[i], p[i + 1], p[i + 2], p[i + 3]);
}
__device__ __forceinline__ void store_out(const uint32_t (&p)[28], uint32_t slab, const CUtensorMap* m, int c0, int c1) {
    const int lane = threadIdx.x & 31;
    const bool swap = lane & 16;
    const uint32_t addr = slab + (lane & 15) * 224 + (((lane >> 4) ^ (lane >> 2)) & 1) * 16;
#pragma unroll
    for (int i = 0; i < 28; i += 4)
        stsm4(addr + i * 8, swap ? p[i + 2] : p[i], swap ? p[i + 3] : p[i + 1], swap ? p[i] : p[i + 2], swap ? p[i + 1] : p[i + 3]);
    fence_async_smem();
    __syncwarp();
    if (elect()) {
        tma_st2(m, c0, c1, slab);
        bulk_commit();
        bulk_wait_read();
    }
}
__host__ __device__ constexpr int tile_of(int t) { return 7 * (t >> 2) + 3 * ((t >> 1) & 1) + 2 * (t & 1); }

__global__ void __launch_bounds__(384, 1) fused_kernel(const __grid_constant__ Maps maps) {
    extern __shared__ uint8_t smem_raw[];
    if ((uint32_t)__cvta_generic_to_shared(smem_raw) != base) return;
    const int warp = __shfl_sync(0xffffffffu, threadIdx.x >> 5, 0);
    const int lane = threadIdx.x & 31;
    const int bid = blockIdx.x < 2 * SPARE0 ? blockIdx.x : blockIdx.x - 2;
    if ((blockIdx.x >> 1) == SPARE0 || blockIdx.x >= 130) {
        const int ns = blockIdx.x >= 130 ? blockIdx.x - 128 : blockIdx.x & 1;
        uint4* dst = reinterpret_cast<uint4*>(g_part + (size_t)ns * 32 * BLOB);
#pragma unroll 4
        for (int i = threadIdx.x; i < 2 * BLOB; i += 384) dst[i] = make_uint4(SENTINEL, SENTINEL, SENTINEL, SENTINEL);
        __syncthreads();
        if (threadIdx.x < 17) {
            const int idx = threadIdx.x < 16 ? CNT_O + threadIdx.x : CNT_Z + ns;
            asm volatile("red.release.gpu.global.add.u32 [%0], 1;" ::"l"(&g_cnt[idx * 32]) : "memory");
        }
        return;
    }
    const int roleL = (bid >> 3) & 1;
    const int mt = ((bid >> 4) << 1) | ((bid >> 2) & 1);
    const int ns = bid & 3;
    const int par = mt >> 3, blk = mt & 7;

    if (warp == 8) {
        if (elect()) {
#pragma unroll
            for (int i = 0; i < 8; i++) mbar_init(base + BAR_FULL + i * 8, 2);
            asm volatile("fence.mbarrier_init.release.cluster;" ::: "memory");
        }
    } else if (warp == 9) {
        if (elect()) {
#pragma unroll
            for (int i = 0; i < 8; i++) mbar_init(base + BAR_EMPTY + i * 8, 8);
            asm volatile("fence.mbarrier_init.release.cluster;" ::: "memory");
        }
    } else if (warp == 10) {
        if (elect()) {
#pragma unroll
            for (int i = 0; i < 4; i++) mbar_init(base + BAR_RDY + i * 8, 8);
#pragma unroll
            for (int i = 0; i < 2; i++) mbar_init(base + BAR_HALO + i * 8, 8);
            asm volatile("fence.mbarrier_init.release.cluster;" ::: "memory");
        }
    } else if (warp == 11) {
        if (elect()) {
#pragma unroll
            for (int i = 0; i < 3; i++) mbar_init(base + BAR_DEP + i * 8, 1);
#pragma unroll
            for (int i = 0; i < 2; i++) mbar_init(base + BAR_PUB + i * 8, 1);
            asm volatile("fence.mbarrier_init.release.cluster;" ::: "memory");
        }
    }
    __syncthreads();

    const int col = ns * 112;
    const unsigned t_fill = clk32();
    if (warp == 8) {
        if (elect()) {
            if (roleL) {
#pragma unroll 1
                for (int i = 0; i < 4; i++) {
                    mbar_expect(full_bar(2 * i), SLOT);
                    tma_ld2(base + i * SLOT, &maps.m[M_XA], par * 448 + i * 64, blk * 128, full_bar(2 * i));
                    if (PACE_0) pause_until(t_fill, (i + 1) * 2 * PACE_0);
                }
            } else {
#pragma unroll 1
                for (int i = 0; i < NA; i++) {
                    mbar_expect(full_bar(i), SLOT);
                    tma_ld3(base + i * SLOT, &maps.m[M_XB], i * 64, mt * 64, 0, full_bar(i));
                    if (PACE_0) pause_until(t_fill, (i + 1) * PACE_0);
                }
            }
        }
    } else if (warp == 11) {
        if (elect()) {
            if (roleL) {
#pragma unroll 1
                for (int i = 0; i < 6; i++) {
                    const uint32_t dst = base + BRING + i * SLOT, bar = full_bar(i);
                    mbar_expect(bar, SLOT);
                    tma_ld4(dst, &maps.m[M_WQK], 0, i * 32, 0, ns, bar);
                    tma_ld4(dst + 8192, &maps.m[M_WQK], 64, i * 32, 0, ns, bar);
                    if (i & 1) mbar_arrive(bar);
                    if (PACE_0) pause_until(t_fill, (i + 1) * PACE_0);
                }
            } else {
#pragma unroll
                for (int i = 0; i < 7; i++) {
                    mbar_expect(full_bar(i), BLOB);
                    tma_ld2(base + BRING + bslot_e(i) * SLOT, &maps.m[M_WR], i * 64, col, full_bar(i));
                    if (PACE_0) pause_until(t_fill, (i + 1) * PACE_0);
                }
            }
        }
    }

    if (warp >= 8) {
        asm volatile("setmaxnreg.dec.sync.aligned.u32 56;");
        unsigned* epoch_ptr = &g_epoch[(bid * 4 + (warp - 8)) * 8];
#define PROF_FEED_A
#define PROF_FEED_B
        if (warp == 8) {
            if (elect()) {
                Feed<0> f;
                const int row = mt * 128;
                auto c_run = [&](const CUtensorMap* m, int off, int n0, int n1) {
#pragma unroll 1
                    for (int n = n0; n < n1; n++) {
                        const uint32_t bar = f.acquire<NA>();
                        mbar_expect(bar, SLOT);
                        tma_ld2(f.dst, m, (off + skip_own(n, mt)) * 64, row, bar);
                        PROF_FEED_A;
                        f.next<NA>();
                    }
                };
                if (!roleL) {
                    f.seek(14, 0);
#pragma unroll 1
                    for (int i = 0; i < 4; i++) {
                        const uint32_t bar = f.acquire<NA>();
                        mbar_expect(bar, SLOT);
                        tma_ld2(f.dst, &maps.m[M_CR + (i >> 1)], ((i & 1) * 16 + mt) * 64, row, bar);
                        mbar_arrive(bar);
                        PROF_FEED_A;
                        f.next<NA>();
                    }
                    c_run(&maps.m[M_CR], 0, 0, 15);
                    c_run(&maps.m[M_CI], 0, 0, NBE);
                    wait_dep(2);
#pragma unroll 1
                    for (int i = 0; i < 7; i++) {
                        const uint32_t bar = f.acquire<NA>();
                        mbar_expect(bar, SLOT);
                        bulk_ld(f.dst, g_o + (size_t)(mt * 7 + i) * SLOT, SLOT, bar);
                        PROF_FEED_A;
                        f.next<NA>();
                    }
                } else {
#pragma unroll 1
                    for (int i = 4; i < 7; i++) {
                        wait_released(2 * i - 8);
                        mbar_expect(full_bar(2 * i), SLOT);
                        tma_ld2(base + i * SLOT, &maps.m[M_XA], par * 448 + i * 64, blk * 128, full_bar(2 * i));
                    }
                    wait_released(7);
                    f.seek(21, 0);
                    c_run(&maps.m[M_CR], 16, 0, 15);
                    c_run(&maps.m[M_CI], 16, 0, 15);
                    c_run(&maps.m[M_CI], 0, NBE, 15);
                }
            }
        } else if (warp == 11) {
            if (elect()) {
                Feed<BRING> f;
                auto blob_run = [&](auto nbs, int quarter, int n0, int n1) {
                    constexpr int N = decltype(nbs)::value;
                    const uint8_t* src = g_ab + (size_t)(quarter * 64 + ns) * BLOB;
#pragma unroll 1
                    for (int n = n0; n < n1; n++) {
                        const uint32_t bar = f.template acquire<N>();
                        mbar_expect(bar, BLOB);
                        bulk_ld(f.dst, src + skip_own(n, mt) * (4 * BLOB), BLOB, bar);
                        PROF_FEED_B;
                        f.template next<N>();
                    }
                };
                auto w_run = [&](auto nbs, const CUtensorMap* m, bool no_a) {
                    constexpr int N = decltype(nbs)::value;
#pragma unroll 1
                    for (int i = 0; i < 7; i++) {
                        const uint32_t bar = f.template acquire<N>();
                        mbar_expect(bar, SLOT);
                        tma_ld3(f.dst, m, 0, i * 64, ns, bar);
                        tma_ld3(f.dst + 8192, m, 64, i * 64, ns, bar);
                        if (no_a) mbar_arrive(bar);
                        PROF_FEED_B;
                        f.template next<N>();
                    }
                };
                if (!roleL) {
                    f.seek(7, bslot_e(7));
#pragma unroll 1
                    for (int i = 0; i < 7; i++) {
                        const uint32_t bar = f.acquire<5>();
                        mbar_expect(bar, BLOB);
                        tma_ld2(f.dst, &maps.m[M_WI], i * 64, col, bar);
                        mbar_arrive(bar);
                        PROF_FEED_B;
                        f.next<5>();
                    }
                    f.seek(18, bslot_e(18));
                    wait_dep(0);
                    blob_run(Int<7>(), 0, 0, 15);
                    wait_dep(1);
                    blob_run(Int<7>(), 2, 0, NBE);
                    w_run(Int<7>(), &maps.m[M_WO], false);
                } else {
                    f.seek(6, 0);
#pragma unroll 1
                    for (int i = 6; i < 14; i++) {
                        const uint32_t bar = f.acquire<6>();
                        mbar_expect(bar, SLOT);
                        tma_ld4(f.dst, &maps.m[M_WQK], 0, i * 32, 0, ns, bar);
                        tma_ld4(f.dst + 8192, &maps.m[M_WQK], 64, i * 32, 0, ns, bar);
                        if (i & 1) mbar_arrive(bar);
                        PROF_FEED_B;
                        f.next<6>();
                    }
                    w_run(Int<6>(), &maps.m[M_WV], true);
                    wait_dep(0);
                    blob_run(Int<6>(), 1, 0, 15);
                    wait_dep(1);
                    blob_run(Int<6>(), 3, 0, 15);
                    blob_run(Int<6>(), 2, NBE, 15);
                }
            }
        } else if (warp == 10) {
            if (elect()) {
                const unsigned ep = *epoch_ptr + 1;
                await(CNT_A + ns, ep * 16);
                mbar_arrive(base + BAR_DEP);
                PROF(150);
                await(CNT_B + ns, ep * 16);
                mbar_arrive(base + BAR_DEP + 8);
                PROF(151);
                if (roleL) await(CNT_Z + ns, ep);
                else await(CNT_O + mt, ep * 8);
                mbar_arrive(base + BAR_DEP + 16);
                PROF(152);
                *epoch_ptr = ep;
            }
        } else if (!roleL) {
            if (elect()) {
                mbar_wait(base + BAR_RDY, 0);
                PROF(130);
                signal(CNT_A + ns);
                PROF(131);
                mbar_wait(base + BAR_RDY + 24, 0);
                PROF(132);
                signal(CNT_B + ns);
                PROF(133);
            }
        } else {
            const unsigned tag = *epoch_ptr + 1;
#pragma unroll 1
            for (int kv = 0; kv < 2; kv++) {
                uint32_t v[14], t[14];
#pragma unroll
                for (int i = 0; i < 14; i++) v[i] = 0;
                mbar_wait(base + BAR_PUB + kv * 8, 0);
                if (lane == 0) PROF(140 + kv);
                if (blk > 0) {
                    const uint8_t* src = g_halo + (size_t)(((mt - 1) * 4 + ns) * 2 + kv) * (2 * HSLOT) + lane * 16;
                    pause_until(clk32(), HALO_DELAY);
#pragma unroll 1
                    for (int n = 0; n < SPIN_LIMIT; n++) {
                        bool ok = true;
#pragma unroll
                        for (int i = 0; i < 7; i++) ld_tagged(src + i * 512, v[2 * i], t[2 * i], v[2 * i + 1], t[2 * i + 1]);
#pragma unroll
                        for (int i = 0; i < 14; i++) ok = ok && t[i] == tag;
                        if (__all_sync(0xffffffffu, ok)) break;
                    }
                }
#pragma unroll
                for (int i = 0; i < 14; i++) sts1(base + HALO + i * 128 + lane * 4, v[i]);
                warp_arrive(base + BAR_HALO + kv * 8);
                if (lane == 0) PROF(142 + kv);
            }
            if (elect()) {
                mbar_wait(base + BAR_RDY, 0);
                PROF(130);
                signal(CNT_O + mt);
                PROF(131);
                *epoch_ptr = tag;
            }
        }
    } else {
        asm volatile("setmaxnreg.inc.sync.aligned.u32 224;");
        Ring r;
        r.wg = warp >> 2;
        r.zero = blockIdx.y;
        r.leader = lane == 0;
        const int wg = warp >> 2;
        uint8_t* part = g_part + (size_t)(ns * 16 + mt) * (2 * BLOB) + threadIdx.x * 16;
        uint32_t p[28];

        if (!roleL) {
            uint8_t* blob = g_ab + (size_t)((wg * 16 + mt) * 4 + ns) * BLOB + (warp & 3) * WSLOT + lane * 4;
            const uint32_t own = base + BRING + wg * SLOT + (warp & 3) * WSLOT + lane * 16;
            float x0[56], x1[56];
            r.seek(0, bslot_e(0));
            r.run<XW, 7, true>(x0);
            r.run<XW, 7, false>(x0);
            r.seek(2, bslot_e(2));
#pragma unroll 1
            for (int i = 2; i < 7; i++) r.run<XW, 5, false>(x0);

            r.seek(7, bslot_e(7));
            r.run<XW, 5, true, -1>(x1);
            acc_fence(x0);
            pack_all(x0, p);
            store_frags<0, 14>(blob, p);
            r.run<XW, 5, false, -1>(x1);
            store_frags<14, 28>(blob, p);
            warp_arrive(base + BAR_RDY);
            r.run<XW, 5, false, -1>(x1);
            stage_frags(own + 5 * SLOT, p);
            warp_arrive(base + BAR_RDY + 8);
#pragma unroll 1
            for (int i = 10; i < 14; i++) r.run<XW, 5, false, -1>(x1);

            mbar_wait(base + BAR_RDY + 8, 0);
            fence_async_smem();
            r.seek(14, bslot_e(14));
            r.run<BIG, 7, true>(x0);
            acc_fence(x1);
            pack_all(x1, p);
            wait_released(10);
            stage_frags(own, p);
            warp_arrive(base + BAR_RDY + 16);
            r.run<BIG, 7, false>(x0);
            mbar_wait(base + BAR_RDY + 16, 0);
            fence_async_smem();
            blob += (size_t)128 * BLOB;
            r.run<BIG, 7, false>(x0);
            store_frags<0, 7>(blob, p);
            r.run<BIG, 7, false>(x0);
            store_frags<7, 14>(blob, p);
            r.run<BIG, 7, false>(x0);
            store_frags<14, 21>(blob, p);
            r.run<BIG, 7, false>(x0);
            store_frags<21, 28>(blob, p);
            warp_arrive(base + BAR_RDY + 24);
#pragma unroll 1
            for (int i = 20; i < POUT; i++) r.run<BIG, 7, false>(x0);

            r.seek(POUT, bslot_e(POUT));
            r.run<OUT, 7, true>(x1);
            acc_fence(x0);
            pack_all(x0, p);
#pragma unroll
            for (int i = 0; i < 3; i++) st_part(part + i * 4096, p + 4 * i);
            r.run<OUT, 7, false>(x1);
#pragma unroll
            for (int i = 3; i < 7; i++) st_part(part + i * 4096, p + 4 * i);
#pragma unroll 1
            for (int i = 2; i < 7; i++) r.run<OUT, 7, false>(x1);

            wait_released(ELAST - 6);
            asm volatile("wgmma.wait_group.sync.aligned 0;" ::: "memory");
            acc_fence(x1);
            pack_all(x1, p);
            const uint32_t slab = base + (wg ? BRING + bslot_e(ELAST - 6) * SLOT : ((ELAST - 6) % NA) * SLOT) + (warp & 3) * WSLOT;
            store_out(p, slab, &maps.m[M_OUTA], par * 896 + col, blk * 128 + warp * 16);
        } else {
            const int g = lane >> 2, tig = lane & 3;
            const unsigned tag = g_epoch[(bid * 4 + 1) * 8] + 1;
            const uint32_t hin = base + HALO + warp * HSLOT + lane * 4;
            uint8_t* hout = g_halo + (size_t)((mt * 4 + ns) * 2) * (2 * HSLOT) + lane * 16;
            auto publish = [&](const uint32_t (&h)[14], int kv) {
                if (warp < 7) {
#pragma unroll
                    for (int c = 0; c < 14; c++) sts1(hin + HSLOT + c * 128, h[c]);
                    warp_arrive(base + BAR_HALO + kv * 8);
                } else {
                    if (blk < 7) {
#pragma unroll
                        for (int i = 0; i < 7; i++) st_tagged(hout + kv * (2 * HSLOT) + i * 512, h[2 * i], h[2 * i + 1], tag);
                    }
                    warp_arrive(base + BAR_PUB + kv * 8);
                }
            };
            float y0[56], y1[56], y2[56];
            r.seek(0, 0);
            r.run<QK, 6, true>(y0, y1);
#pragma unroll 1
            for (int i = 1; i < 14; i++) r.run<QK, 6, false>(y0, y1);

            uint32_t m1[8][4], m0[8][4];
            r.seek(14, bslot_l(14));
            r.run<XWN, 6, true>(y2);
            acc_fence(y0);
            acc_fence(y1);
            {
                uint32_t lo[14], hi[14];
#pragma unroll
                for (int c = 0; c < 14; c++) {
                    lo[c] = pack2(y1[4 * c], y1[4 * c + 1]);
                    hi[c] = pack2(y1[4 * c + 2], y1[4 * c + 3]);
                }
                publish(hi, 0);
#pragma unroll
                for (int t = 0; t < 8; t++) {
                    const int c = tile_of(t);
                    const uint32_t dup = (t & 3) == 2 ? r.zero : 0u;
                    m1[t][0] = lo[c] ^ dup;
                    m1[t][1] = hi[c] ^ dup;
                    m1[t][2] = lo[c + 1];
                    m1[t][3] = hi[c + 1];
                    m0[t][0] = lo[c] + r.zero + dup;
                    m0[t][2] = lo[c + 1] + r.zero;
                }
            }
            r.run<XWN, 6, false>(y2);
            r.pin();
            uint32_t q[2][8][2];
#pragma unroll
            for (int b = 0; b < 2; b++) {
                uint32_t v[14];
#pragma unroll
                for (int c = 0; c < 14; c++) v[c] = pack2(y0[4 * c + 2 * b], y0[4 * c + 2 * b + 1]);
#pragma unroll
                for (int t = 0; t < 8; t++) {
                    const int c = tile_of(t);
                    q[b][t][0] = (t & 3) == 2 ? (tig >= 2 ? v[c] : 0u) : v[c];
                    q[b][t][1] = (t & 3) == 1 ? (tig < 2 ? v[c + 1] : 0u) : v[c + 1];
                }
            }
            r.run<XWN, 6, false>(y2);
            r.run<XWN, 6, false>(y2);
            r.run<XWN, 6, false>(y2);
            mbar_wait(base + BAR_HALO, 0);
#pragma unroll
            for (int t = 0; t < 8; t++) {
                m0[t][1] = lds1(hin + tile_of(t) * 128);
                m0[t][3] = lds1(hin + tile_of(t) * 128 + 128);
            }
            r.wait();
            float s[8][4];
#pragma unroll
            for (int step = 0; step < 2; step++) {
#pragma unroll
                for (int i = 0; i < 8; i++) {
                    const int b = 1 - (i >> 2), h = i & 3, t = 2 * h + step;
                    float (&d)[4] = s[2 * h + b];
                    if (step == 0) d[0] = d[1] = d[2] = d[3] = 0.f;
                    mma16816(d, b ? m1[t] : m0[t], q[b][t][0], q[b][t][1]);
                }
            }
            r.pin();
            r.run<XWN, 6, false, 1, false>(y2);
            r.pin();

            uint32_t pr[8], mx[4];
            {
                const bool cur0 = g <= 2 * tig, cur1 = g <= 2 * tig + 1;
#pragma unroll
                for (int i = 0; i < 8; i++) {
                    const int c = (i & 1) ? 2 : 0;
                    pr[i] = movm(pack2(cur0 ? s[i][c] : s[i][2 - c], cur1 ? s[i][c + 1] : s[i][3 - c]));
                }
            }
            r.run<XWN, 6, false>(y2);
            r.pin();
            const uint32_t curmask = (2 * tig <= g ? 0x0000FFFFu : 0u) | (2 * tig + 1 <= g ? 0xFFFF0000u : 0u);
            uint32_t mx1[4];
            {
                const uint32_t keep = (blk == 0 && warp == 0) ? curmask : 0xFFFFFFFFu;
#pragma unroll
                for (int i = 0; i < 8; i++) {
                    pr[i] = pack2(bf_lo(pr[i]) * 0.18898223650461362f, bf_hi(pr[i]) * 0.18898223650461362f);
                    if ((i & 1) == 0) pr[i] = (pr[i] & keep) | (0xCE6ECE6Eu & ~keep);
                }
#pragma unroll
                for (int i = 0; i < 4; i++) {
                    mx[i] = max2(__byte_perm(pr[2 * i], pr[2 * i + 1], 0x5410), __byte_perm(pr[2 * i], pr[2 * i + 1], 0x7632));
                    mx1[i] = __shfl_xor_sync(0xffffffffu, mx[i], 1);
                }
            }

            r.seek(21, bslot_l(21));
            r.run<BIG, 6, true>(y0);
            acc_fence(y2);
            uint32_t vh[14];
#pragma unroll
            for (int c = 0; c < 14; c++) vh[c] = movm(pack2(y2[4 * c + 2], y2[4 * c + 3]));
            r.run<BIG, 6, false>(y0);
            wait_released(19);
            publish(vh, 1);
            r.run<BIG, 6, false>(y0);
            r.pin();
            uint32_t vl[14];
#pragma unroll
            for (int c = 0; c < 14; c++) vl[c] = movm(pack2(y2[4 * c], y2[4 * c + 1]));
#pragma unroll
            for (int i = 0; i < 4; i++) {
                mx[i] = max2(mx[i], mx1[i]);
                mx1[i] = __shfl_xor_sync(0xffffffffu, mx[i], 2);
            }
            r.run<BIG, 6, false>(y0);
            r.pin();
            float e0[8], e1[8], sm[8], sm1[8];
#pragma unroll
            for (int i = 0; i < 8; i++) {
                const uint32_t m2 = max2(mx[i >> 1], mx1[i >> 1]);
                const float m = ((i & 1) ? bf_hi(m2) : bf_lo(m2)) * -1.4426950408889634f;
                e0[i] = ex2(fmaf(bf_lo(pr[i]), 1.4426950408889634f, m));
                e1[i] = ex2(fmaf(bf_hi(pr[i]), 1.4426950408889634f, m));
                sm[i] = e0[i] + e1[i];
                sm1[i] = __shfl_xor_sync(0xffffffffu, sm[i], 1);
            }
            r.run<BIG, 6, false>(y0);
            r.pin();
#pragma unroll
            for (int i = 0; i < 8; i++) {
                sm[i] += sm1[i];
                sm1[i] = __shfl_xor_sync(0xffffffffu, sm[i], 2);
            }
#pragma unroll
            for (int t = 0; t < 8; t++) {
                const int c = tile_of(t);
                const uint32_t dup = (t & 3) == 2 ? r.zero : 0u;
                m1[t][0] = vl[c] ^ dup;
                m1[t][1] = vl[c + 1];
                m1[t][2] = vh[c] ^ dup;
                m1[t][3] = vh[c + 1];
                m0[t][0] = vl[c] + r.zero + dup;
                m0[t][1] = vl[c + 1] + r.zero;
            }
            r.run<BIG, 6, false>(y0);
            mbar_wait(base + BAR_HALO + 8, 0);
#pragma unroll
            for (int t = 0; t < 8; t++) {
                m0[t][2] = lds1(hin + tile_of(t) * 128);
                m0[t][3] = lds1(hin + tile_of(t) * 128 + 128);
            }
            uint32_t pb[8][2];
#pragma unroll
            for (int i = 0; i < 8; i++) {
                const float inv = rcp(sm[i] + sm1[i]);
                const uint32_t w = pack2(e0[i] * inv, e1[i] * inv);
                pb[i][i & 1] = w & curmask;
                pb[i][1 - (i & 1)] = w & ~curmask;
            }
            r.wait();
            float o[2][8][4];
#pragma unroll
            for (int i = 0; i < 16; i++) {
                const int b = 1 - (i >> 3), t = i & 7;
                float (&d)[4] = o[b][t];
                d[0] = d[1] = d[2] = d[3] = 0.f;
                mma16816(d, b ? m1[t] : m0[t], pb[(t & 6) + b][0], pb[(t & 6) + b][1]);
            }
            r.pin();
            r.run<BIG, 6, false, 1, false>(y0);
            r.pin();
            uint8_t* odst = g_o + (size_t)mt * 7 * SLOT + ns * (14 * 2048) + warp * 256 + lane * 4;
#pragma unroll
            for (int hp = 0; hp < 2; hp++) {
#pragma unroll
                for (int b = 0; b < 2; b++) {
                    const float (&u)[8][4] = o[b];
                    const int t = 4 * hp;
                    uint8_t* dst = odst + hp * (7 * 2048) + b * 128;
                    stg1(dst, pack2(u[t][0], u[t][1]));
                    stg1(dst + 2048, pack2(u[t][2], u[t][3]));
                    stg1(dst + 2 * 2048, pack2(u[t + 1][0], u[t + 1][1]));
                    stg1(dst + 3 * 2048, pack2(g < 4 ? u[t + 1][2] : u[t + 2][0], g < 4 ? u[t + 1][3] : u[t + 2][1]));
                    stg1(dst + 4 * 2048, pack2(u[t + 2][2], u[t + 2][3]));
                    stg1(dst + 5 * 2048, pack2(u[t + 3][0], u[t + 3][1]));
                    stg1(dst + 6 * 2048, pack2(u[t + 3][2], u[t + 3][3]));
                    if (hp + b < 2) {
                        r.run<BIG, 6, false>(y0);
                        r.pin();
                    }
                }
            }
            warp_arrive(base + BAR_RDY);

#pragma unroll 1
            for (int i = 31; i < LLAST; i++) r.run<BIG, 6, false>(y0);
            mbar_wait(base + BAR_DEP + 16, 0);
#pragma unroll
            for (int i = 0; i < 7; i++) ld_part(part + i * 4096, p + 4 * i);
            r.seek(LLAST, bslot_l(LLAST));
            r.run<BIG, 6, false>(y0);
            wait_released(LLAST - 6);
#pragma unroll 1
            for (int n = 0; n < SPIN_LIMIT; n++) {
                bool ok = true;
#pragma unroll
                for (int i = 0; i < 28; i++) ok = ok && p[i] != SENTINEL;
                if (__all_sync(0xffffffffu, ok)) break;
#pragma unroll
                for (int i = 0; i < 7; i++) ld_part(part + i * 4096, p + 4 * i);
            }
            asm volatile("wgmma.wait_group.sync.aligned 0;" ::: "memory");
            acc_fence(y0);
#pragma unroll
            for (int i = 0; i < 28; i++) p[i] = pack2(y0[2 * i] + bf_lo(p[i]), y0[2 * i + 1] + bf_hi(p[i]));
            const uint32_t slab = base + (wg ? HALO : ((LLAST - 6) % NA) * SLOT) + (warp & 3) * WSLOT;
            store_out(p, slab, &maps.m[M_OUTB], 448 + col, mt * 128 + warp * 16);
        }
    }
}

typedef CUresult (*EncodeFn)(CUtensorMap*, CUtensorMapDataType, cuuint32_t, void*, const cuuint64_t*, const cuuint64_t*,
                             const cuuint32_t*, const cuuint32_t*, CUtensorMapInterleave, CUtensorMapSwizzle,
                             CUtensorMapL2promotion, CUtensorMapFloatOOBfill);

struct Dim { uint64_t size, stride; uint32_t box; };
void encode(EncodeFn fn, CUtensorMap* m, const void* ptr, CUtensorMapSwizzle sw, Dim d0, Dim d1, Dim d2 = {0, 0, 0}, Dim d3 = {0, 0, 0}) {
    const cuuint64_t dims[4] = {d0.size, d1.size, d2.size, d3.size};
    const cuuint64_t strides[3] = {d1.stride, d2.stride, d3.stride};
    const cuuint32_t box[4] = {d0.box, d1.box, d2.box, d3.box};
    const cuuint32_t es[4] = {1, 1, 1, 1};
    fn(m, CU_TENSOR_MAP_DATA_TYPE_BFLOAT16, d3.size ? 4 : d2.size ? 3 : 2, const_cast<void*>(ptr), dims, strides, box, es,
       CU_TENSOR_MAP_INTERLEAVE_NONE, sw, CU_TENSOR_MAP_L2_PROMOTION_L2_128B, CU_TENSOR_MAP_FLOAT_OOB_FILL_NONE);
}

}

extern "C" void kernel_launch(void* const* d_in, const int* in_sizes, int n_in, void* d_out, int out_size) {
    (void)in_sizes; (void)n_in; (void)out_size;
    void* fnp = nullptr;
    cudaDriverEntryPointQueryResult st;
    cudaGetDriverEntryPoint("cuTensorMapEncodeTiled", &fnp, cudaEnableDefault, &st);
    EncodeFn fn = (EncodeFn)fnp;
    cudaFuncSetAttribute(fused_kernel, cudaFuncAttributeMaxDynamicSharedMemorySize, SMEM_BYTES);

    const CUtensorMapSwizzle S128 = CU_TENSOR_MAP_SWIZZLE_128B, S0 = CU_TENSOR_MAP_SWIZZLE_NONE;
    Maps maps;
    encode(fn, &maps.m[M_XA], d_in[0], S128, {896, 2, 64}, {1024, 1792, 128});
    encode(fn, &maps.m[M_WQK], d_in[1], S128, {112, 2, 64}, {448, 2688, 32}, {3, 896, 2}, {4, 224, 1});
    encode(fn, &maps.m[M_WV], (const uint8_t*)d_in[1] + 1792, S128, {112, 2, 64}, {448, 2688, 64}, {4, 224, 1});
    encode(fn, &maps.m[M_WO], d_in[2], S128, {112, 2, 64}, {448, 896, 64}, {4, 224, 1});
    encode(fn, &maps.m[M_XB], d_in[3], S128, {448, 2, 64}, {1024, 896, 64}, {2, 896 * 1024, 2});
    encode(fn, &maps.m[M_CR], d_in[4], S128, {2048, 2, 64}, {2048, 4096, 128});
    encode(fn, &maps.m[M_CI], d_in[5], S128, {2048, 2, 64}, {2048, 4096, 128});
    encode(fn, &maps.m[M_WR], d_in[6], S128, {448, 2, 64}, {448, 896, 112});
    encode(fn, &maps.m[M_WI], d_in[7], S128, {448, 2, 64}, {448, 896, 112});
    encode(fn, &maps.m[M_OUTA], d_out, S0, {1792, 2, 112}, {1024, 3584, 16});
    encode(fn, &maps.m[M_OUTB], d_out, S0, {896, 2, 112}, {2048, 1792, 16});

    fused_kernel<<<132, 384, SMEM_BYTES>>>(maps);
}
```

```cpp
#include <cuda.h>
#include <cuda_bf16.h>
#include <cuda_runtime.h>
#include <stdint.h>

namespace {

constexpr uint32_t SLOT = 16384;
constexpr int NA = 7;
constexpr uint32_t BRING = NA * SLOT;
constexpr uint32_t HALO = BRING + 6 * SLOT;
constexpr uint32_t HSLOT = 1792;
constexpr uint32_t WSLOT = 3584;
constexpr uint32_t BLOB = 14336;
constexpr uint32_t BARS = 14 * SLOT;
constexpr uint32_t BAR_FULL = BARS;
constexpr uint32_t BAR_EMPTY = BARS + 64;
constexpr uint32_t BAR_RDY = BARS + 128;
constexpr uint32_t BAR_DEP = BARS + 160;
constexpr uint32_t BAR_HALO = BARS + 192;
constexpr uint32_t SMEM_BYTES = BARS + 256 + 1024;
constexpr uint32_t base = 1024;
constexpr int SPIN_LIMIT = 1 << 16;

#define E_EXTRA 0
#define HALO_DELAY 6000
#define PACE_0 0
#define O_SLICE 5
#define MAPPING 0
#define SPARE0 12
constexpr int NBE = 13 + E_EXTRA;
constexpr int POUT = 33 + NBE;
constexpr int ELAST = POUT + 6;
constexpr int LLAST = 52 - E_EXTRA;

enum { M_XA, M_XH, M_WQK, M_WV, M_WO, M_XB, M_WR, M_WI, M_CR, M_CI, M_OUTA, M_OUTB, M_COUNT };
struct __align__(64) Maps { CUtensorMap m[M_COUNT]; };

constexpr int CNT_A = 0;
constexpr int CNT_B = 4;
constexpr int CNT_O = 16;
constexpr int CNT_COUNT = 32;

__device__ __align__(1024) uint8_t g_ab[64 * 4 * BLOB];
__device__ __align__(1024) uint8_t g_o[16 * 7 * SLOT];
__device__ __align__(1024) uint8_t g_part[64 * 2 * BLOB];
__device__ __align__(1024) uint8_t g_halo[64 * 2 * 2 * HSLOT];
__device__ __align__(128) unsigned g_cnt[CNT_COUNT * 32];
__device__ __align__(128) unsigned g_epoch[132 * 4 * 8];

__device__ __forceinline__ unsigned clk32() { unsigned c; asm volatile("mov.u32 %0, %%clock;" : "=r"(c)); return c; }
__device__ __forceinline__ void pause_until(unsigned t0, unsigned cycles) {
    while (clk32() - t0 < cycles) {}
}

#define PROF(idx)

__device__ __forceinline__ void mbar_init(uint32_t bar, uint32_t cnt) {
    asm volatile("mbarrier.init.shared::cta.b64 [%0], %1;" ::"r"(bar), "r"(cnt) : "memory");
}
__device__ __forceinline__ void mbar_expect(uint32_t bar, uint32_t bytes) {
    asm volatile("mbarrier.arrive.expect_tx.shared::cta.b64 _, [%0], %1;" ::"r"(bar), "r"(bytes) : "memory");
}
__device__ __forceinline__ void mbar_arrive(uint32_t bar) {
    asm volatile("mbarrier.arrive.shared::cta.b64 _, [%0];" ::"r"(bar) : "memory");
}
__device__ __forceinline__ bool mbar_try(uint32_t bar, uint32_t parity) {
    uint32_t ok;
    asm volatile("{\n.reg .pred p;\nmbarrier.try_wait.parity.shared::cta.b64 p, [%1], %2;\nselp.u32 %0, 1, 0, p;\n}\n"
                 : "=r"(ok) : "r"(bar), "r"(parity) : "memory");
    return ok;
}
__device__ __forceinline__ void mbar_wait(uint32_t bar, uint32_t parity) {
#pragma unroll 1
    for (int n = 0; n < SPIN_LIMIT; n++)
        if (mbar_try(bar, parity)) break;
}
__device__ __forceinline__ bool elect() {
    uint32_t p;
    asm volatile("{\n.reg .pred p;\nelect.sync _|p, 0xffffffff;\nselp.u32 %0, 1, 0, p;\n}\n" : "=r"(p));
    return p;
}
__device__ __forceinline__ void nb_sync(int id, int n) { asm volatile("bar.sync %0, %1;" ::"r"(id), "r"(n) : "memory"); }
__device__ __forceinline__ void warp_arrive(uint32_t bar) {
    __syncwarp();
    if ((threadIdx.x & 31) == 0) mbar_arrive(bar);
}

__device__ __forceinline__ void tma_ld2(uint32_t dst, const CUtensorMap* m, int c0, int c1, uint32_t bar) {
    asm volatile("cp.async.bulk.tensor.2d.shared::cluster.global.mbarrier::complete_tx::bytes [%0], [%1, {%3, %4}], [%2];"
                 ::"r"(dst), "l"(m), "r"(bar), "r"(c0), "r"(c1) : "memory");
}
__device__ __forceinline__ void tma_ld3(uint32_t dst, const CUtensorMap* m, int c0, int c1, int c2, uint32_t bar) {
    asm volatile("cp.async.bulk.tensor.3d.shared::cluster.global.mbarrier::complete_tx::bytes [%0], [%1, {%3, %4, %5}], [%2];"
                 ::"r"(dst), "l"(m), "r"(bar), "r"(c0), "r"(c1), "r"(c2) : "memory");
}
__device__ __forceinline__ void tma_ld4(uint32_t dst, const CUtensorMap* m, int c0, int c1, int c2, int c3, uint32_t bar) {
    asm volatile("cp.async.bulk.tensor.4d.shared::cluster.global.mbarrier::complete_tx::bytes [%0], [%1, {%3, %4, %5, %6}], [%2];"
                 ::"r"(dst), "l"(m), "r"(bar), "r"(c0), "r"(c1), "r"(c2), "r"(c3) : "memory");
}
__device__ __forceinline__ void bulk_ld(uint32_t dst, const void* src, uint32_t bytes, uint32_t bar) {
    asm volatile("cp.async.bulk.shared::cluster.global.mbarrier::complete_tx::bytes [%0], [%1], %2, [%3];"
                 ::"r"(dst), "l"(src), "r"(bytes), "r"(bar) : "memory");
}
__device__ __forceinline__ void tma_st2(const CUtensorMap* m, int c0, int c1, uint32_t src) {
    asm volatile("cp.async.bulk.tensor.2d.global.shared::cta.bulk_group [%0, {%1, %2}], [%3];"
                 ::"l"(m), "r"(c0), "r"(c1), "r"(src) : "memory");
}
__device__ __forceinline__ void bulk_commit() { asm volatile("cp.async.bulk.commit_group;" ::: "memory"); }
__device__ __forceinline__ void bulk_wait_read() { asm volatile("cp.async.bulk.wait_group.read 0;" ::: "memory"); }
__device__ __forceinline__ void fence_async_smem() { asm volatile("fence.proxy.async.shared::cta;" ::: "memory"); }
__device__ __forceinline__ void fence_async_global() { asm volatile("fence.proxy.async.global;" ::: "memory"); }

__device__ __forceinline__ void signal(int idx) {
    asm volatile("fence.proxy.async;\nred.relaxed.gpu.global.add.u32 [%0], 1;" ::"l"(&g_cnt[idx * 32]) : "memory");
}
__device__ __forceinline__ void await(int idx, unsigned target) {
#pragma unroll 1
    for (int n = 0; n < SPIN_LIMIT; n++) {
        unsigned v;
        asm volatile("ld.relaxed.gpu.global.u32 %0, [%1];" : "=r"(v) : "l"(&g_cnt[idx * 32]) : "memory");
        if ((int)(v - target) >= 0) break;
    }
    asm volatile("fence.acquire.gpu;" ::: "memory");
}
__device__ __forceinline__ void wait_dep(int k) {
    mbar_wait(base + BAR_DEP + k * 8, 0);
    fence_async_global();
}

#define WG_REGS                                                                                                     \
    "{%0,%1,%2,%3,%4,%5,%6,%7,%8,%9,%10,%11,%12,%13,%14,%15,%16,%17,%18,%19,%20,%21,%22,%23,%24,%25,%26,%27,"       \
    "%28,%29,%30,%31,%32,%33,%34,%35,%36,%37,%38,%39,%40,%41,%42,%43,%44,%45,%46,%47,%48,%49,%50,%51,%52,%53,%54,%55}"
#define WG_OPS(C)                                                                                                   \
    C(d[0]), C(d[1]), C(d[2]), C(d[3]), C(d[4]), C(d[5]), C(d[6]), C(d[7]), C(d[8]), C(d[9]), C(d[10]), C(d[11]),   \
    C(d[12]), C(d[13]), C(d[14]), C(d[15]), C(d[16]), C(d[17]), C(d[18]), C(d[19]), C(d[20]), C(d[21]), C(d[22]),   \
    C(d[23]), C(d[24]), C(d[25]), C(d[26]), C(d[27]), C(d[28]), C(d[29]), C(d[30]), C(d[31]), C(d[32]), C(d[33]),   \
    C(d[34]), C(d[35]), C(d[36]), C(d[37]), C(d[38]), C(d[39]), C(d[40]), C(d[41]), C(d[42]), C(d[43]), C(d[44]),   \
    C(d[45]), C(d[46]), C(d[47]), C(d[48]), C(d[49]), C(d[50]), C(d[51]), C(d[52]), C(d[53]), C(d[54]), C(d[55])

template <int TA, int TB, int SB, bool INIT>
__device__ __forceinline__ void wgmma112(float (&d)[56], uint64_t da, uint64_t db) {
    if (INIT) {
        asm volatile("{\n.reg .pred p;\nsetp.ne.b32 p, 0, 0;\n"
                     "wgmma.mma_async.sync.aligned.m64n112k16.f32.bf16.bf16 " WG_REGS ", %56, %57, p, 1, %59, %60, %58;\n}\n"
                     : WG_OPS("=f") : "l"(da), "l"(db), "n"(TB), "n"(SB), "n"(TA));
    } else {
        asm volatile("{\n.reg .pred p;\nsetp.ne.b32 p, 1, 0;\n"
                     "wgmma.mma_async.sync.aligned.m64n112k16.f32.bf16.bf16 " WG_REGS ", %56, %57, p, 1, %59, %60, %58;\n}\n"
                     : WG_OPS("+f") : "l"(da), "l"(db), "n"(TB), "n"(SB), "n"(TA));
    }
}
__device__ __forceinline__ void acc_fence(float (&d)[56]) {
#pragma unroll
    for (int i = 0; i < 56; i++) asm volatile("" : "+f"(d[i])::"memory");
}

__device__ __forceinline__ uint32_t pack2(float lo, float hi) {
    uint32_t r;
    asm volatile("cvt.rn.bf16x2.f32 %0, %1, %2;" : "=r"(r) : "f"(hi), "f"(lo));
    return r;
}
__device__ __forceinline__ uint32_t movm(uint32_t a) {
    uint32_t r;
    asm volatile("movmatrix.sync.aligned.m8n8.trans.b16 %0, %1;" : "=r"(r) : "r"(a));
    return r;
}
__device__ __forceinline__ void stsm4(uint32_t addr, uint32_t a, uint32_t b, uint32_t c, uint32_t d) {
    asm volatile("stmatrix.sync.aligned.m8n8.x4.shared.b16 [%0], {%1,%2,%3,%4};" ::"r"(addr), "r"(a), "r"(b), "r"(c), "r"(d) : "memory");
}
__device__ __forceinline__ void sts1(uint32_t addr, uint32_t a) { asm volatile("st.shared.b32 [%0], %1;" ::"r"(addr), "r"(a) : "memory"); }
__device__ __forceinline__ uint32_t lds1(uint32_t addr) {
    uint32_t a;
    asm volatile("ld.shared.b32 %0, [%1];" : "=r"(a) : "r"(addr) : "memory");
    return a;
}
__device__ __forceinline__ void stg1(uint8_t* p, uint32_t a) { asm volatile("st.global.b32 [%0], %1;" ::"l"(p), "r"(a) : "memory"); }
__device__ __forceinline__ void st_part(uint8_t* p, const uint32_t* v, uint32_t parity) {
    asm volatile("{\n.reg .b64 x, y;\nmov.b64 x, {%1, %2};\nmov.b64 y, {%3, %4};\nst.relaxed.gpu.global.v2.b64 [%0], {x, y};\n}\n"
                 ::"l"(p), "r"((v[0] & ~1u) | parity), "r"(v[1]), "r"((v[2] & ~1u) | parity), "r"(v[3]) : "memory");
}
__device__ __forceinline__ void mma16816(float (&d)[4], const uint32_t (&a)[4], uint32_t b0, uint32_t b1) {
    asm volatile("mma.sync.aligned.m16n8k16.row.col.f32.bf16.bf16.f32 {%0,%1,%2,%3}, {%4,%5,%6,%7}, {%8,%9}, {%0,%1,%2,%3};"
                 : "+f"(d[0]), "+f"(d[1]), "+f"(d[2]), "+f"(d[3]) : "r"(a[0]), "r"(a[1]), "r"(a[2]), "r"(a[3]), "r"(b0), "r"(b1));
}
__device__ __forceinline__ uint32_t max2(uint32_t a, uint32_t b) {
    uint32_t r;
    asm("max.bf16x2 %0, %1, %2;" : "=r"(r) : "r"(a), "r"(b));
    return r;
}
__device__ __forceinline__ void st_tagged(uint8_t* p, uint32_t a, uint32_t b, uint32_t tag) {
    asm volatile("{\n.reg .b64 x, y;\nmov.b64 x, {%1, %3};\nmov.b64 y, {%2, %3};\nst.relaxed.gpu.global.v2.b64 [%0], {x, y};\n}\n"
                 ::"l"(p), "r"(a), "r"(b), "r"(tag) : "memory");
}
__device__ __forceinline__ void ld_tagged(const uint8_t* p, uint32_t& a, uint32_t& ta, uint32_t& b, uint32_t& tb) {
    asm volatile("{\n.reg .b64 x, y;\nld.relaxed.gpu.global.v2.b64 {x, y}, [%4];\nmov.b64 {%0, %1}, x;\nmov.b64 {%2, %3}, y;\n}\n"
                 : "=r"(a), "=r"(ta), "=r"(b), "=r"(tb) : "l"(p) : "memory");
}
__device__ __forceinline__ float bf_lo(uint32_t v) { return __uint_as_float(v << 16); }
__device__ __forceinline__ float bf_hi(uint32_t v) { return __uint_as_float(v & 0xFFFF0000u); }
__device__ __forceinline__ float rcp(float x) { float r; asm("rcp.approx.ftz.f32 %0, %1;" : "=f"(r) : "f"(x)); return r; }
__device__ __forceinline__ float ex2(float x) { float r; asm volatile("ex2.approx.ftz.f32 %0, %1;" : "=f"(r) : "f"(x)); return r; }

__device__ __forceinline__ uint32_t full_bar(int stage) { return base + BAR_FULL + (stage & 7) * 8; }
__device__ __forceinline__ void wait_released(int j) { mbar_wait(base + BAR_EMPTY + (j & 7) * 8, (j >> 3) & 1); }

template <int V>
struct Int { static constexpr int value = V; };

__host__ __device__ constexpr int bslot_e(int i) { return (i < 2 || i >= 14) ? (i + 5) % 7 : (i + 1) % 5; }
__host__ __device__ constexpr int bslot_l(int i) { return i % 6; }

template <uint32_t OFF>
struct Feed {
    int stage;
    uint32_t dst;
    __device__ __forceinline__ void seek(int i, int slot) { stage = i; dst = base + OFF + slot * SLOT; }
    template <int N>
    __device__ __forceinline__ uint32_t acquire() { wait_released(stage - N); return full_bar(stage); }
    template <int N>
    __device__ __forceinline__ void next() {
        stage++;
        dst += SLOT;
        if (dst == base + OFF + N * SLOT) dst = base + OFF;
    }
};
__device__ __forceinline__ int skip_own(int n, int mt) { return n == mt ? 15 : n; }

__host__ __device__ constexpr uint64_t desc_const(uint32_t lbo, uint32_t sbo, uint32_t mode) {
    return ((uint64_t)((sbo >> 4) | (mode << 30)) << 32) | ((lbo >> 4) << 16);
}
constexpr uint64_t D_K128 = desc_const(16, 1024, 1);
constexpr uint64_t D_N128 = desc_const(8192, 1024, 1);
constexpr uint64_t D_BLOB = desc_const(128, 256, 0);
constexpr uint64_t D_OT = desc_const(2048, 128, 0);

enum Kind { XW, XWN, QK, BIG, OUT };

struct Ring {
    int stage;
    uint32_t a, b;
    uint32_t wg;
    uint32_t zero;
    bool leader;
    __device__ __forceinline__ void seek(int i, int bslot) {
        stage = i;
        a = (base + (i % NA) * SLOT) >> 4;
        b = (base + BRING + bslot * SLOT) >> 4;
    }
    __device__ __forceinline__ void wait() {
        mbar_wait(full_bar(stage), (stage >> 3) & 1);
    }
    __device__ __forceinline__ void pin() {
        uint32_t n = 0;
#pragma unroll 1
        do {
            asm volatile("pmevent 7;" ::: "memory");
        } while (n++ < zero);
    }
    template <Kind K, int NBS, bool INIT, int SB = 1, bool WAIT = true>
    __device__ __forceinline__ void run(float (&d)[56], float (&e)[56]) {
        if (WAIT) wait();
        asm volatile("wgmma.fence.sync.aligned;" ::: "memory");
        if (K == QK) {
            const uint64_t da = D_K128 + ((base >> 4) + (stage >> 1) * (SLOT >> 4) + (stage & 1) * 4 + wg * 512), db = D_N128 + b;
            wgmma112<0, 1, 1, INIT>(d, da, db);
            wgmma112<0, 1, 1, INIT>(e, da, db + 256);
            wgmma112<0, 1, 1, false>(d, da + 2, db + 128);
            wgmma112<0, 1, 1, false>(e, da + 2, db + 384);
        } else {
            constexpr int TA = K == OUT, TB = K != XW;
            constexpr uint32_t sa = K == OUT ? 256 : 2, sb = K == XW ? 2 : K == BIG ? 224 : 128;
            const uint64_t da = (K == OUT ? D_OT : D_K128) + (a + wg * (K == OUT ? 64 : 512));
            const uint64_t db = (K == XW ? D_K128 : K == BIG ? D_BLOB : D_N128) + b;
            wgmma112<TA, TB, SB, INIT>(d, da, db);
            wgmma112<TA, TB, SB, false>(d, da + sa, db + sb);
            wgmma112<TA, TB, SB, false>(d, da + 2 * sa, db + 2 * sb);
            wgmma112<TA, TB, SB, false>(d, da + 3 * sa, db + 3 * sb);
        }
        asm volatile("wgmma.commit_group.sync.aligned;" ::: "memory");
        asm volatile("wgmma.wait_group.sync.aligned 1;" ::: "memory");
        if (leader && stage > 0) mbar_arrive(base + BAR_EMPTY + ((stage - 1) & 7) * 8);
        stage++;
        a += SLOT >> 4;
        if (a == (base + NA * SLOT) >> 4) a = base >> 4;
        b += SLOT >> 4;
        if (b == (base + BRING + NBS * SLOT) >> 4) b = (base + BRING) >> 4;
    }
    template <Kind K, int NBS, bool INIT, int SB = 1, bool WAIT = true>
    __device__ __forceinline__ void run(float (&d)[56]) { run<K, NBS, INIT, SB, WAIT>(d, d); }
};

__device__ __forceinline__ void pack_all(const float (&d)[56], uint32_t (&p)[28]) {
#pragma unroll
    for (int i = 0; i < 28; i++) p[i] = pack2(d[2 * i], d[2 * i + 1]);
}
template <int I0, int I1>
__device__ __forceinline__ void store_frags(uint8_t* dst, const uint32_t (&p)[28]) {
#pragma unroll
    for (int i = I0; i < I1; i++) stg1(dst + i * 128, p[i]);
}
__device__ __forceinline__ void stage_frags(uint32_t lane_addr, const uint32_t (&p)[28]) {
#pragma unroll
    for (int i = 0; i < 28; i += 4) stsm4(lane_addr + i * 128, p[i], p[i + 1], p[i + 2], p[i + 3]);
}
__device__ __forceinline__ void store_out(const uint32_t (&p)[28], uint32_t slab, const CUtensorMap* m, int c0, int c1) {
    const int lane = threadIdx.x & 31;
    const bool swap = lane & 16;
    const uint32_t addr = slab + (lane & 15) * 224 + (((lane >> 4) ^ (lane >> 2)) & 1) * 16;
#pragma unroll
    for (int i = 0; i < 28; i += 4)
        stsm4(addr + i * 8, swap ? p[i + 2] : p[i], swap ? p[i + 3] : p[i + 1], swap ? p[i] : p[i + 2], swap ? p[i + 1] : p[i + 3]);
    fence_async_smem();
    __syncwarp();
    if (elect()) {
        tma_st2(m, c0, c1, slab);
        bulk_commit();
        bulk_wait_read();
    }
}
__host__ __device__ constexpr int tile_of(int t) { return 7 * (t >> 2) + 3 * ((t >> 1) & 1) + 2 * (t & 1); }

__global__ void __launch_bounds__(384, 1) fused_kernel(const __grid_constant__ Maps maps) {
    extern __shared__ uint8_t smem_raw[];
    if ((uint32_t)__cvta_generic_to_shared(smem_raw) != base) return;
    const int warp = __shfl_sync(0xffffffffu, threadIdx.x >> 5, 0);
    const int lane = threadIdx.x & 31;
    const int bid = blockIdx.x < 2 * SPARE0 || blockIdx.x >= 130 ? blockIdx.x
                    : (blockIdx.x >> 1) == SPARE0                ? 128 + (blockIdx.x & 1)
                                                                 : blockIdx.x - 2;
    const bool roleH = bid >= 128;
    const int roleL = (bid >> 3) & 1;
    const int mt = ((bid >> 4) << 1) | ((bid >> 2) & 1);
    const int ns = bid & 3;
    const int par = mt >> 3, blk = mt & 7;

    if (warp == 8) {
        if (elect()) {
#pragma unroll
            for (int i = 0; i < 8; i++) mbar_init(base + BAR_FULL + i * 8, 2);
            asm volatile("fence.mbarrier_init.release.cluster;" ::: "memory");
        }
    } else if (warp == 9) {
        if (elect()) {
#pragma unroll
            for (int i = 0; i < 8; i++) mbar_init(base + BAR_EMPTY + i * 8, 8);
            asm volatile("fence.mbarrier_init.release.cluster;" ::: "memory");
        }
    } else if (warp == 10) {
        if (elect()) {
#pragma unroll
            for (int i = 0; i < 4; i++) mbar_init(base + BAR_RDY + i * 8, 8);
#pragma unroll
            for (int i = 0; i < 2; i++) mbar_init(base + BAR_HALO + i * 8, 8);
            asm volatile("fence.mbarrier_init.release.cluster;" ::: "memory");
        }
    } else if (warp == 11) {
        if (elect()) {
#pragma unroll
            for (int i = 0; i < 3; i++) mbar_init(base + BAR_DEP + i * 8, 1);
            asm volatile("fence.mbarrier_init.release.cluster;" ::: "memory");
        }
    }
    __syncthreads();

    const int col = ns * 112;
    const unsigned t_fill = clk32();
    if (warp == 8) {
        if (elect()) {
            if (roleL) {
#pragma unroll 1
                for (int i = 0; i < 4; i++) {
                    mbar_expect(full_bar(2 * i), SLOT);
                    tma_ld2(base + i * SLOT, &maps.m[M_XA], par * 448 + i * 64, blk * 128, full_bar(2 * i));
                    if (PACE_0) pause_until(t_fill, (i + 1) * 2 * PACE_0);
                }
            } else {
#pragma unroll 1
                for (int i = 0; i < NA; i++) {
                    mbar_expect(full_bar(i), SLOT);
                    if (roleH) tma_ld4(base + i * SLOT, &maps.m[M_XH], i * 64, 120, 0, 0, full_bar(i));
                    else tma_ld3(base + i * SLOT, &maps.m[M_XB], i * 64, mt * 64, 0, full_bar(i));
                    if (PACE_0) pause_until(t_fill, (i + 1) * PACE_0);
                }
            }
        }
    } else if (warp == 11) {
        if (elect()) {
            if (roleL) {
#pragma unroll 1
                for (int i = 0; i < 6; i++) {
                    const uint32_t dst = base + BRING + i * SLOT, bar = full_bar(i);
                    mbar_expect(bar, SLOT);
                    tma_ld4(dst, &maps.m[M_WQK], 0, i * 32, 0, ns, bar);
                    tma_ld4(dst + 8192, &maps.m[M_WQK], 64, i * 32, 0, ns, bar);
                    if (i & 1) mbar_arrive(bar);
                    if (PACE_0) pause_until(t_fill, (i + 1) * PACE_0);
                }
            } else if (!roleH) {
#pragma unroll
                for (int i = 0; i < 7; i++) {
                    mbar_expect(full_bar(i), BLOB);
                    tma_ld2(base + BRING + bslot_e(i) * SLOT, &maps.m[M_WR], i * 64, col, full_bar(i));
                    if (PACE_0) pause_until(t_fill, (i + 1) * PACE_0);
                }
            }
        }
    }

    if (warp >= 8) {
        asm volatile("setmaxnreg.dec.sync.aligned.u32 56;");
        unsigned* epoch_ptr = &g_epoch[(bid * 4 + (warp - 8)) * 8];
#define PROF_FEED_A
#define PROF_FEED_B
        if (warp == 8) {
            if (!roleH && elect()) {
                Feed<0> f;
                const int row = mt * 128;
                auto c_run = [&](const CUtensorMap* m, int off, int n0, int n1) {
#pragma unroll 1
                    for (int n = n0; n < n1; n++) {
                        const uint32_t bar = f.acquire<NA>();
                        mbar_expect(bar, SLOT);
                        tma_ld2(f.dst, m, (off + skip_own(n, mt)) * 64, row, bar);
                        PROF_FEED_A;
                        f.next<NA>();
                    }
                };
                if (!roleL) {
                    f.seek(14, 0);
                    mbar_wait(base + BAR_RDY, 0);
#pragma unroll 1
                    for (int i = 0; i < 4; i++) {
                        const uint32_t bar = f.acquire<NA>();
                        mbar_expect(bar, SLOT);
                        tma_ld2(f.dst, &maps.m[M_CR + (i >> 1)], ((i & 1) * 16 + mt) * 64, row, bar);
                        mbar_arrive(bar);
                        PROF_FEED_A;
                        f.next<NA>();
                    }
                    c_run(&maps.m[M_CR], 0, 0, 15);
                    c_run(&maps.m[M_CI], 0, 0, NBE);
                    wait_dep(2);
#pragma unroll 1
                    for (int i = 0; i < 7; i++) {
                        const uint32_t bar = f.acquire<NA>();
                        mbar_expect(bar, SLOT);
                        bulk_ld(f.dst, g_o + (size_t)(mt * 7 + i) * SLOT, SLOT, bar);
                        PROF_FEED_A;
                        f.next<NA>();
                    }
                } else {
#pragma unroll 1
                    for (int i = 4; i < 7; i++) {
                        wait_released(2 * i - 8);
                        mbar_expect(full_bar(2 * i), SLOT);
                        tma_ld2(base + i * SLOT, &maps.m[M_XA], par * 448 + i * 64, blk * 128, full_bar(2 * i));
                    }
                    wait_released(7);
                    f.seek(21, 0);
                    c_run(&maps.m[M_CR], 16, 0, 15);
                    c_run(&maps.m[M_CI], 16, 0, 15);
                    c_run(&maps.m[M_CI], 0, NBE, 15);
                }
            }
        } else if (warp == 11) {
            if (elect()) {
                Feed<BRING> f;
                auto blob_run = [&](auto nbs, int quarter, int n0, int n1) {
                    constexpr int N = decltype(nbs)::value;
                    const uint8_t* src = g_ab + (size_t)(quarter * 64 + ns) * BLOB;
#pragma unroll 1
                    for (int n = n0; n < n1; n++) {
                        const uint32_t bar = f.template acquire<N>();
                        mbar_expect(bar, BLOB);
                        bulk_ld(f.dst, src + skip_own(n, mt) * (4 * BLOB), BLOB, bar);
                        PROF_FEED_B;
                        f.template next<N>();
                    }
                };
                auto w_run = [&](auto nbs, const CUtensorMap* m, int slice, bool no_a) {
                    constexpr int N = decltype(nbs)::value;
#pragma unroll 1
                    for (int i = 0; i < 7; i++) {
                        const uint32_t bar = f.stage < N ? full_bar(f.stage) : f.template acquire<N>();
                        mbar_expect(bar, SLOT);
                        tma_ld3(f.dst, m, 0, i * 64, slice, bar);
                        tma_ld3(f.dst + 8192, m, 64, i * 64, slice, bar);
                        if (no_a) mbar_arrive(bar);
                        PROF_FEED_B;
                        f.template next<N>();
                    }
                };
                if (roleH) {
                    f.seek(0, 0);
                    w_run(Int<7>(), &maps.m[M_WV], 4 + ns, false);
                    w_run(Int<7>(), &maps.m[M_WV], 8 + ns, true);
                } else if (!roleL) {
                    f.seek(7, bslot_e(7));
#pragma unroll 1
                    for (int i = 0; i < 7; i++) {
                        const uint32_t bar = f.acquire<5>();
                        mbar_expect(bar, BLOB);
                        tma_ld2(f.dst, &maps.m[M_WI], i * 64, col, bar);
                        mbar_arrive(bar);
                        PROF_FEED_B;
                        f.next<5>();
                    }
                    f.seek(18, bslot_e(18));
                    wait_dep(0);
                    blob_run(Int<7>(), 0, 0, 15);
                    wait_dep(1);
                    blob_run(Int<7>(), 2, 0, NBE);
                    w_run(Int<7>(), &maps.m[M_WO], ns, false);
                } else {
                    f.seek(6, 0);
#pragma unroll 1
                    for (int i = 6; i < 14; i++) {
                        const uint32_t bar = f.acquire<6>();
                        mbar_expect(bar, SLOT);
                        tma_ld4(f.dst, &maps.m[M_WQK], 0, i * 32, 0, ns, bar);
                        tma_ld4(f.dst + 8192, &maps.m[M_WQK], 64, i * 32, 0, ns, bar);
                        if (i & 1) mbar_arrive(bar);
                        PROF_FEED_B;
                        f.next<6>();
                    }
                    w_run(Int<6>(), &maps.m[M_WV], 8 + ns, true);
                    wait_dep(0);
                    blob_run(Int<6>(), 1, 0, 15);
                    wait_dep(1);
                    blob_run(Int<6>(), 3, 0, 15);
                    blob_run(Int<6>(), 2, NBE, 15);
                }
            }
        } else if (roleH) {
        } else if (warp == 10) {
            if (elect()) {
                const unsigned ep = *epoch_ptr + 1;
                await(CNT_A + ns, ep * 16);
                mbar_arrive(base + BAR_DEP);
                PROF(150);
                await(CNT_B + ns, ep * 16);
                mbar_arrive(base + BAR_DEP + 8);
                PROF(151);
                if (!roleL) {
                    await(CNT_O + mt, ep * 4);
                    mbar_arrive(base + BAR_DEP + 16);
                }
                PROF(152);
                *epoch_ptr = ep;
            }
        } else if (!roleL) {
            if (elect()) {
                mbar_wait(base + BAR_RDY, 0);
                PROF(130);
                signal(CNT_A + ns);
                PROF(131);
                mbar_wait(base + BAR_RDY + 24, 0);
                PROF(132);
                signal(CNT_B + ns);
                PROF(133);
            }
        } else {
            const unsigned tag = *epoch_ptr + 1;
#pragma unroll 1
            for (int kv = 0; kv < 2; kv++) {
                uint32_t v[14], t[14];
#pragma unroll
                for (int i = 0; i < 14; i++) v[i] = 0;

                if (blk > 0) {
                    const uint8_t* src = g_halo + (size_t)(((mt - 1) * 4 + ns) * 2 + kv) * (2 * HSLOT) + lane * 16;
                    pause_until(t_fill, HALO_DELAY + kv * 3200);
#pragma unroll 1
                    for (int n = 0; n < SPIN_LIMIT; n++) {
                        bool ok = true;
#pragma unroll
                        for (int i = 0; i < 7; i++) ld_tagged(src + i * 512, v[2 * i], t[2 * i], v[2 * i + 1], t[2 * i + 1]);
#pragma unroll
                        for (int i = 0; i < 14; i++) ok = ok && t[i] == tag;
                        if (__all_sync(0xffffffffu, ok)) break;
                    }
                }
#pragma unroll
                for (int i = 0; i < 14; i++) sts1(base + HALO + kv * (8 * HSLOT) + i * 128 + lane * 4, v[i]);
                warp_arrive(base + BAR_HALO + kv * 8);
                if (lane == 0) PROF(142 + kv);
            }
            if (elect()) {
                mbar_wait(base + BAR_RDY, 0);
                PROF(130);
                signal(CNT_O + mt);
                PROF(131);
                *epoch_ptr = tag;
            }
        }
    } else {
        asm volatile("setmaxnreg.inc.sync.aligned.u32 224;");
        Ring r;
        r.wg = warp >> 2;
        r.zero = blockIdx.y;
        r.leader = lane == 0;
        const int wg = warp >> 2;
        uint8_t* part = g_part + (size_t)(ns * 16 + mt) * (2 * BLOB) + threadIdx.x * 16;
        uint32_t p[28];
        unsigned* epoch_ptr = &g_epoch[bid * 4 * 8];
        const unsigned tag = *epoch_ptr + 1;

        if (roleH) {
            uint8_t* hout = g_halo + (size_t)((warp * 8 + ns) * 2) * (2 * HSLOT) + lane * 16;
            float x0[56], x1[56];
            r.seek(0, 0);
            r.run<XWN, 7, true>(x0);
#pragma unroll 1
            for (int i = 1; i < 7; i++) r.run<XWN, 7, false>(x0);
            r.run<XWN, 7, true>(x1);
            acc_fence(x0);
            pack_all(x0, p);
#pragma unroll
            for (int i = 0; i < 14; i++) st_tagged(hout + (i & 1) * (16 * HSLOT) + (i >> 1) * 512, p[(i >> 1) * 4 + (i & 1)], p[(i >> 1) * 4 + (i & 1) + 2], tag);
#pragma unroll 1
            for (int i = 1; i < 7; i++) r.run<XWN, 7, false>(x1);
            asm volatile("wgmma.wait_group.sync.aligned 0;" ::: "memory");
            acc_fence(x1);
            pack_all(x1, p);
#pragma unroll
            for (int i = 0; i < 28; i++) p[i] = movm(p[i]);
#pragma unroll
            for (int i = 0; i < 14; i++)
                st_tagged(hout + 2 * HSLOT + (i & 1) * (16 * HSLOT) + (i >> 1) * 512, p[(i >> 1) * 4 + (i & 1)], p[(i >> 1) * 4 + (i & 1) + 2], tag);
        } else if (!roleL) {
            uint8_t* blob = g_ab + (size_t)((wg * 16 + mt) * 4 + ns) * BLOB + (warp & 3) * WSLOT + lane * 4;
            const uint32_t own = base + BRING + wg * SLOT + (warp & 3) * WSLOT + lane * 16;
            float x0[56], x1[56];
            r.seek(0, bslot_e(0));
            r.run<XW, 7, true>(x0);
            r.run<XW, 7, false>(x0);
            r.seek(2, bslot_e(2));
#pragma unroll 1
            for (int i = 2; i < 7; i++) r.run<XW, 5, false>(x0);

            r.seek(7, bslot_e(7));
            r.run<XW, 5, true, -1>(x1);
            acc_fence(x0);
            pack_all(x0, p);
            store_frags<0, 9>(blob, p);
            r.run<XW, 5, false, -1>(x1);
            store_frags<9, 18>(blob, p);
            r.run<XW, 5, false, -1>(x1);
            store_frags<18, 28>(blob, p);
            warp_arrive(base + BAR_RDY);
            r.run<XW, 5, false, -1>(x1);
            stage_frags(own + 5 * SLOT, p);
            warp_arrive(base + BAR_RDY + 8);
#pragma unroll 1
            for (int i = 11; i < 14; i++) r.run<XW, 5, false, -1>(x1);

            mbar_wait(base + BAR_RDY + 8, 0);
            fence_async_smem();
            r.seek(14, bslot_e(14));
            r.run<BIG, 7, true>(x0);
            acc_fence(x1);
            pack_all(x1, p);
            wait_released(10);
            stage_frags(own, p);
            warp_arrive(base + BAR_RDY + 16);
            r.run<BIG, 7, false>(x0);
            mbar_wait(base + BAR_RDY + 16, 0);
            fence_async_smem();
            blob += (size_t)128 * BLOB;
            store_frags<0, 4>(blob, p);
            r.run<BIG, 7, false>(x0);
            store_frags<4, 8>(blob, p);
            r.run<BIG, 7, false>(x0);
            store_frags<8, 12>(blob, p);
            r.run<BIG, 7, false>(x0);
            store_frags<12, 16>(blob, p);
            r.run<BIG, 7, false>(x0);
            store_frags<16, 20>(blob, p);
            r.run<BIG, 7, false>(x0);
            store_frags<20, 24>(blob, p);
            r.run<BIG, 7, false>(x0);
            store_frags<24, 28>(blob, p);
            warp_arrive(base + BAR_RDY + 24);
#pragma unroll 1
            for (int i = 22; i < POUT; i++) r.run<BIG, 7, false>(x0);

            r.seek(POUT, bslot_e(POUT));
            r.run<OUT, 7, true>(x1);
            acc_fence(x0);
            pack_all(x0, p);
            st_part(part, p, tag & 1);
#pragma unroll
            for (int i = 0; i < 3; i++) {
                r.run<OUT, 7, false>(x1);
                st_part(part + (2 * i + 1) * 4096, p + 8 * i + 4, tag & 1);
                st_part(part + (2 * i + 2) * 4096, p + 8 * i + 8, tag & 1);
            }
#pragma unroll 1
            for (int i = 4; i < 7; i++) r.run<OUT, 7, false>(x1);

            wait_released(ELAST - 6);
            asm volatile("wgmma.wait_group.sync.aligned 0;" ::: "memory");
            acc_fence(x1);
            pack_all(x1, p);
            const uint32_t slab = base + (wg ? BRING + bslot_e(ELAST - 6) * SLOT : ((ELAST - 6) % NA) * SLOT) + (warp & 3) * WSLOT;
            store_out(p, slab, &maps.m[M_OUTA], par * 896 + col, blk * 128 + warp * 16);
        } else {
            const int g = lane >> 2, tig = lane & 3;
            const uint32_t hin = base + HALO + warp * HSLOT + lane * 4;
            auto publish = [&](const uint32_t (&h)[14], int kv) {
                if (warp < 7) {
#pragma unroll
                    for (int c = 0; c < 14; c++) sts1(hin + HSLOT + c * 128, h[c]);
                    warp_arrive(base + BAR_HALO + kv * 8);
                }
            };
            float y0[56], y1[56], y2[56];
            r.seek(0, 0);
            r.run<QK, 6, true>(y0, y1);
#pragma unroll 1
            for (int i = 1; i < 14; i++) r.run<QK, 6, false>(y0, y1);

            uint32_t m1[8][4], m0[8][4];
            r.seek(14, bslot_l(14));
            r.run<XWN, 6, true>(y2);
            acc_fence(y0);
            acc_fence(y1);
            {
                uint32_t lo[14], hi[14];
#pragma unroll
                for (int c = 0; c < 14; c++) {
                    lo[c] = pack2(y1[4 * c], y1[4 * c + 1]);
                    hi[c] = pack2(y1[4 * c + 2], y1[4 * c + 3]);
                }
                publish(hi, 0);
#pragma unroll
                for (int t = 0; t < 8; t++) {
                    const int c = tile_of(t);
                    const uint32_t dup = (t & 3) == 2 ? r.zero : 0u;
                    m1[t][0] = lo[c] ^ dup;
                    m1[t][1] = hi[c] ^ dup;
                    m1[t][2] = lo[c + 1];
                    m1[t][3] = hi[c + 1];
                    m0[t][0] = lo[c] + r.zero + dup;
                    m0[t][2] = lo[c + 1] + r.zero;
                }
            }
            r.run<XWN, 6, false>(y2);
            r.pin();
            uint32_t q[2][8][2];
#pragma unroll
            for (int b = 0; b < 2; b++) {
                uint32_t v[14];
#pragma unroll
                for (int c = 0; c < 14; c++) v[c] = pack2(y0[4 * c + 2 * b], y0[4 * c + 2 * b + 1]);
#pragma unroll
                for (int t = 0; t < 8; t++) {
                    const int c = tile_of(t);
                    q[b][t][0] = (t & 3) == 2 ? (tig >= 2 ? v[c] : 0u) : v[c];
                    q[b][t][1] = (t & 3) == 1 ? (tig < 2 ? v[c + 1] : 0u) : v[c + 1];
                }
            }
            r.run<XWN, 6, false>(y2);
            r.run<XWN, 6, false>(y2);
            r.run<XWN, 6, false>(y2);
            mbar_wait(base + BAR_HALO, 0);
#pragma unroll
            for (int t = 0; t < 8; t++) {
                m0[t][1] = lds1(hin + tile_of(t) * 128);
                m0[t][3] = lds1(hin + tile_of(t) * 128 + 128);
            }
            r.wait();
            float s[8][4];
#pragma unroll
            for (int step = 0; step < 2; step++) {
#pragma unroll
                for (int i = 0; i < 8; i++) {
                    const int b = 1 - (i >> 2), h = i & 3, t = 2 * h + step;
                    float (&d)[4] = s[2 * h + b];
                    if (step == 0) d[0] = d[1] = d[2] = d[3] = 0.f;
                    mma16816(d, b ? m1[t] : m0[t], q[b][t][0], q[b][t][1]);
                }
            }
            r.pin();
            r.run<XWN, 6, false, 1, false>(y2);
            r.pin();

            uint32_t pr[8], mx[4];
            {
                const bool cur0 = g <= 2 * tig, cur1 = g <= 2 * tig + 1;
#pragma unroll
                for (int i = 0; i < 8; i++) {
                    const int c = (i & 1) ? 2 : 0;
                    pr[i] = movm(pack2(cur0 ? s[i][c] : s[i][2 - c], cur1 ? s[i][c + 1] : s[i][3 - c]));
                }
            }
            r.run<XWN, 6, false>(y2);
            r.pin();
            const uint32_t curmask = (2 * tig <= g ? 0x0000FFFFu : 0u) | (2 * tig + 1 <= g ? 0xFFFF0000u : 0u);
            uint32_t mx1[4];
            {
                const uint32_t keep = (blk == 0 && warp == 0) ? curmask : 0xFFFFFFFFu;
#pragma unroll
                for (int i = 0; i < 8; i++) {
                    pr[i] = pack2(bf_lo(pr[i]) * 0.18898223650461362f, bf_hi(pr[i]) * 0.18898223650461362f);
                    if ((i & 1) == 0) pr[i] = (pr[i] & keep) | (0xCE6ECE6Eu & ~keep);
                }
#pragma unroll
                for (int i = 0; i < 4; i++) {
                    mx[i] = max2(__byte_perm(pr[2 * i], pr[2 * i + 1], 0x5410), __byte_perm(pr[2 * i], pr[2 * i + 1], 0x7632));
                    mx1[i] = __shfl_xor_sync(0xffffffffu, mx[i], 1);
                }
            }

            r.seek(21, bslot_l(21));
            r.run<BIG, 6, true>(y0);
            acc_fence(y2);
            uint32_t vh[14];
#pragma unroll
            for (int c = 0; c < 14; c++) vh[c] = movm(pack2(y2[4 * c + 2], y2[4 * c + 3]));
            r.run<BIG, 6, false>(y0);
            wait_released(19);
            publish(vh, 1);
            r.run<BIG, 6, false>(y0);
            r.pin();
            uint32_t vl[14];
#pragma unroll
            for (int c = 0; c < 14; c++) vl[c] = movm(pack2(y2[4 * c], y2[4 * c + 1]));
#pragma unroll
            for (int i = 0; i < 4; i++) {
                mx[i] = max2(mx[i], mx1[i]);
                mx1[i] = __shfl_xor_sync(0xffffffffu, mx[i], 2);
            }
            r.run<BIG, 6, false>(y0);
            r.pin();
            float e0[8], e1[8], sm[8], sm1[8];
#pragma unroll
            for (int i = 0; i < 8; i++) {
                const uint32_t m2 = max2(mx[i >> 1], mx1[i >> 1]);
                const float m = ((i & 1) ? bf_hi(m2) : bf_lo(m2)) * -1.4426950408889634f;
                e0[i] = ex2(fmaf(bf_lo(pr[i]), 1.4426950408889634f, m));
                e1[i] = ex2(fmaf(bf_hi(pr[i]), 1.4426950408889634f, m));
                sm[i] = e0[i] + e1[i];
                sm1[i] = __shfl_xor_sync(0xffffffffu, sm[i], 1);
            }
            r.run<BIG, 6, false>(y0);
            r.pin();
#pragma unroll
            for (int i = 0; i < 8; i++) {
                sm[i] += sm1[i];
                sm1[i] = __shfl_xor_sync(0xffffffffu, sm[i], 2);
            }
#pragma unroll
            for (int t = 0; t < 8; t++) {
                const int c = tile_of(t);
                const uint32_t dup = (t & 3) == 2 ? r.zero : 0u;
                m1[t][0] = vl[c] ^ dup;
                m1[t][1] = vl[c + 1];
                m1[t][2] = vh[c] ^ dup;
                m1[t][3] = vh[c + 1];
                m0[t][0] = vl[c] + r.zero + dup;
                m0[t][1] = vl[c + 1] + r.zero;
            }
            r.run<BIG, 6, false>(y0);
            mbar_wait(base + BAR_HALO + 8, 0);
            const uint32_t vin = warp ? hin : hin + 8 * HSLOT;
#pragma unroll
            for (int t = 0; t < 8; t++) {
                m0[t][2] = lds1(vin + tile_of(t) * 128);
                m0[t][3] = lds1(vin + tile_of(t) * 128 + 128);
            }
            uint32_t pb[8][2];
#pragma unroll
            for (int i = 0; i < 8; i++) {
                const float inv = rcp(sm[i] + sm1[i]);
                const uint32_t w = pack2(e0[i] * inv, e1[i] * inv);
                pb[i][i & 1] = w & curmask;
                pb[i][1 - (i & 1)] = w & ~curmask;
            }
            r.wait();
            float o[2][8][4];
#pragma unroll
            for (int i = 0; i < 16; i++) {
                const int b = 1 - (i >> 3), t = i & 7;
                float (&d)[4] = o[b][t];
                d[0] = d[1] = d[2] = d[3] = 0.f;
                mma16816(d, b ? m1[t] : m0[t], pb[(t & 6) + b][0], pb[(t & 6) + b][1]);
            }
            r.pin();
            r.run<BIG, 6, false, 1, false>(y0);
            r.pin();
            uint8_t* odst = g_o + (size_t)mt * 7 * SLOT + ns * (14 * 2048) + warp * 256 + lane * 4;
#pragma unroll
            for (int hp = 0; hp < 2; hp++) {
#pragma unroll
                for (int b = 0; b < 2; b++) {
                    const float (&u)[8][4] = o[b];
                    const int t = 4 * hp;
                    uint32_t* w = p + 14 * hp + b;
                    w[0] = pack2(u[t][0], u[t][1]);
                    w[2] = pack2(u[t][2], u[t][3]);
                    w[4] = pack2(u[t + 1][0], u[t + 1][1]);
                    w[6] = pack2(g < 4 ? u[t + 1][2] : u[t + 2][0], g < 4 ? u[t + 1][3] : u[t + 2][1]);
                    w[8] = pack2(u[t + 2][2], u[t + 2][3]);
                    w[10] = pack2(u[t + 3][0], u[t + 3][1]);
                    w[12] = pack2(u[t + 3][2], u[t + 3][3]);
                }
            }
#pragma unroll
            for (int i = 0; i < 28; i++) {
                if (i && i % O_SLICE == 0) r.run<BIG, 6, false>(y0);
                stg1(odst + (i >> 1) * 2048 + (i & 1) * 128, p[i]);
            }
            warp_arrive(base + BAR_RDY);

#pragma unroll 1
            for (int i = 28 + 27 / O_SLICE; i < LLAST; i++) r.run<BIG, 6, false>(y0);
#pragma unroll
            for (int i = 0; i < 7; i++) ld_tagged(part + i * 4096, p[4 * i], p[4 * i + 1], p[4 * i + 2], p[4 * i + 3]);
            r.seek(LLAST, bslot_l(LLAST));
            r.run<BIG, 6, false>(y0);
            wait_released(LLAST - 6);
#pragma unroll 1
            for (int n = 0; n < SPIN_LIMIT; n++) {
                uint32_t stale = 0;
#pragma unroll
                for (int i = 0; i < 28; i += 2) stale |= p[i] ^ tag;
                if (__all_sync(0xffffffffu, !(stale & 1))) break;
#pragma unroll
                for (int i = 0; i < 7; i++) ld_tagged(part + i * 4096, p[4 * i], p[4 * i + 1], p[4 * i + 2], p[4 * i + 3]);
            }
            asm volatile("wgmma.wait_group.sync.aligned 0;" ::: "memory");
            acc_fence(y0);
#pragma unroll
            for (int i = 0; i < 28; i++) p[i] = pack2(y0[2 * i] + bf_lo(p[i]), y0[2 * i + 1] + bf_hi(p[i]));
            const uint32_t slab = base + (wg ? HALO : ((LLAST - 6) % NA) * SLOT) + (warp & 3) * WSLOT;
            store_out(p, slab, &maps.m[M_OUTB], 448 + col, mt * 128 + warp * 16);
        }
        if (threadIdx.x == 32) *epoch_ptr = tag;
    }
}

typedef CUresult (*EncodeFn)(CUtensorMap*, CUtensorMapDataType, cuuint32_t, void*, const cuuint64_t*, const cuuint64_t*,
                             const cuuint32_t*, const cuuint32_t*, CUtensorMapInterleave, CUtensorMapSwizzle,
                             CUtensorMapL2promotion, CUtensorMapFloatOOBfill);

struct Dim { uint64_t size, stride; uint32_t box; };
void encode(EncodeFn fn, CUtensorMap* m, const void* ptr, CUtensorMapSwizzle sw, Dim d0, Dim d1, Dim d2 = {0, 0, 0}, Dim d3 = {0, 0, 0}) {
    const cuuint64_t dims[4] = {d0.size, d1.size, d2.size, d3.size};
    const cuuint64_t strides[3] = {d1.stride, d2.stride, d3.stride};
    const cuuint32_t box[4] = {d0.box, d1.box, d2.box, d3.box};
    const cuuint32_t es[4] = {1, 1, 1, 1};
    fn(m, CU_TENSOR_MAP_DATA_TYPE_BFLOAT16, d3.size ? 4 : d2.size ? 3 : 2, const_cast<void*>(ptr), dims, strides, box, es,
       CU_TENSOR_MAP_INTERLEAVE_NONE, sw, CU_TENSOR_MAP_L2_PROMOTION_L2_128B, CU_TENSOR_MAP_FLOAT_OOB_FILL_NONE);
}

}

extern "C" void kernel_launch(void* const* d_in, const int* in_sizes, int n_in, void* d_out, int out_size) {
    (void)in_sizes; (void)n_in; (void)out_size;
    void* fnp = nullptr;
    cudaDriverEntryPointQueryResult st;
    cudaGetDriverEntryPoint("cuTensorMapEncodeTiled", &fnp, cudaEnableDefault, &st);
    EncodeFn fn = (EncodeFn)fnp;
    cudaFuncSetAttribute(fused_kernel, cudaFuncAttributeMaxDynamicSharedMemorySize, SMEM_BYTES);

    const CUtensorMapSwizzle S128 = CU_TENSOR_MAP_SWIZZLE_128B, S0 = CU_TENSOR_MAP_SWIZZLE_NONE;
    Maps maps;
    encode(fn, &maps.m[M_XA], d_in[0], S128, {896, 2, 64}, {1024, 1792, 128});
    encode(fn, &maps.m[M_WQK], d_in[1], S128, {112, 2, 64}, {448, 2688, 32}, {3, 896, 2}, {4, 224, 1});
    encode(fn, &maps.m[M_WV], d_in[1], S128, {112, 2, 64}, {448, 2688, 64}, {12, 224, 1});
    encode(fn, &maps.m[M_XH], d_in[0], S128, {448, 2, 64}, {128, 1792, 8}, {8, 128 * 1792, 8}, {2, 896, 2});
    encode(fn, &maps.m[M_WO], d_in[2], S128, {112, 2, 64}, {448, 896, 64}, {4, 224, 1});
    encode(fn, &maps.m[M_XB], d_in[3], S128, {448, 2, 64}, {1024, 896, 64}, {2, 896 * 1024, 2});
    encode(fn, &maps.m[M_CR], d_in[4], S128, {2048, 2, 64}, {2048, 4096, 128});
    encode(fn, &maps.m[M_CI], d_in[5], S128, {2048, 2, 64}, {2048, 4096, 128});
    encode(fn, &maps.m[M_WR], d_in[6], S128, {448, 2, 64}, {448, 896, 112});
    encode(fn, &maps.m[M_WI], d_in[7], S128, {448, 2, 64}, {448, 896, 112});
    encode(fn, &maps.m[M_OUTA], d_out, S0, {1792, 2, 112}, {1024, 3584, 16});
    encode(fn, &maps.m[M_OUTB], d_out, S0, {896, 2, 112}, {2048, 1792, 16});

    fused_kernel<<<132, 384, SMEM_BYTES>>>(maps);
}
```

```cpp
#include <cuda.h>
#include <cuda_bf16.h>
#include <cuda_runtime.h>
#include <stdint.h>

namespace {

constexpr uint32_t SLOT = 16384;
constexpr int NA = 7;
constexpr uint32_t BRING = NA * SLOT;
constexpr uint32_t HALO = BRING + 6 * SLOT;
constexpr uint32_t HSLOT = 1792;
constexpr uint32_t WSLOT = 3584;
constexpr uint32_t BLOB = 14336;
constexpr uint32_t BARS = 14 * SLOT;
constexpr uint32_t BAR_FULL = BARS;
constexpr uint32_t BAR_EMPTY = BARS + 64;
constexpr uint32_t BAR_RDY = BARS + 128;
constexpr uint32_t BAR_DEP = BARS + 160;
constexpr uint32_t BAR_HALO = BARS + 192;
constexpr uint32_t TAG = BARS + 208;
constexpr uint32_t SMEM_BYTES = BARS + 256 + 1024;
constexpr uint32_t base = 1024;
constexpr int SPIN_LIMIT = 1 << 16;

#define E_EXTRA 0
#define HALO_DELAY 6000
#define PACE_0 0
#define O_SLICE 5
#define B_SLICE 5
#define MAPPING 2
#define SPARE0 12
constexpr int NBE = 13 + E_EXTRA;
constexpr int POUT = 33 + NBE;
constexpr int ELAST = POUT + 6;
constexpr int LLAST = 52 - E_EXTRA;

enum { M_XA, M_XH, M_WQK, M_WV, M_WO, M_XB, M_WR, M_WI, M_CR, M_CI, M_OUTA, M_OUTB, M_COUNT };
struct __align__(64) Maps { CUtensorMap m[M_COUNT]; };

constexpr int CNT_A = 0;
constexpr int CNT_B = 4;
constexpr int CNT_O = 16;
constexpr int CNT_COUNT = 32;

__device__ __align__(1024) uint8_t g_ab[64 * 4 * BLOB];
__device__ __align__(1024) uint8_t g_o[16 * 7 * SLOT];
__device__ __align__(1024) uint8_t g_part[64 * 2 * BLOB];
__device__ __align__(1024) uint8_t g_halo[64 * 2 * 2 * HSLOT];
__device__ __align__(128) unsigned g_cnt[CNT_COUNT * 32];
__device__ __align__(128) unsigned g_epoch[132 * 4 * 8];

__device__ __forceinline__ unsigned clk32() { unsigned c; asm volatile("mov.u32 %0, %%clock;" : "=r"(c)); return c; }
__device__ __forceinline__ void pause_until(unsigned t0, unsigned cycles) {
    while (clk32() - t0 < cycles) {}
}

#define PROF(idx)

__device__ __forceinline__ void mbar_init(uint32_t bar, uint32_t cnt) {
    asm volatile("mbarrier.init.shared::cta.b64 [%0], %1;" ::"r"(bar), "r"(cnt) : "memory");
}
__device__ __forceinline__ void mbar_expect(uint32_t bar, uint32_t bytes) {
    asm volatile("mbarrier.arrive.expect_tx.shared::cta.b64 _, [%0], %1;" ::"r"(bar), "r"(bytes) : "memory");
}
__device__ __forceinline__ void mbar_arrive(uint32_t bar) {
    asm volatile("mbarrier.arrive.shared::cta.b64 _, [%0];" ::"r"(bar) : "memory");
}
__device__ __forceinline__ bool mbar_try(uint32_t bar, uint32_t parity) {
    uint32_t ok;
    asm volatile("{\n.reg .pred p;\nmbarrier.try_wait.parity.shared::cta.b64 p, [%1], %2;\nselp.u32 %0, 1, 0, p;\n}\n"
                 : "=r"(ok) : "r"(bar), "r"(parity) : "memory");
    return ok;
}
__device__ __forceinline__ void mbar_wait(uint32_t bar, uint32_t parity) {
#pragma unroll 1
    for (int n = 0; n < SPIN_LIMIT; n++)
        if (mbar_try(bar, parity)) break;
}
__device__ __forceinline__ bool elect() {
    uint32_t p;
    asm volatile("{\n.reg .pred p;\nelect.sync _|p, 0xffffffff;\nselp.u32 %0, 1, 0, p;\n}\n" : "=r"(p));
    return p;
}
__device__ __forceinline__ void nb_sync(int id, int n) { asm volatile("bar.sync %0, %1;" ::"r"(id), "r"(n) : "memory"); }
__device__ __forceinline__ void warp_arrive(uint32_t bar) {
    __syncwarp();
    if (elect()) mbar_arrive(bar);
}
__device__ __forceinline__ uint32_t band(uint32_t x, uint32_t m) {
    uint32_t r;
    asm volatile("and.b32 %0, %1, %2;" : "=r"(r) : "r"(x), "r"(m));
    return r;
}
__device__ __forceinline__ float fmul(float x, float y) {
    float r;
    asm volatile("mul.f32 %0, %1, %2;" : "=f"(r) : "f"(x), "f"(y));
    return r;
}
__device__ __forceinline__ uint32_t dup(uint32_t x, uint32_t zero) {
    uint32_t r;
    asm volatile("xor.b32 %0, %1, %2;" : "=r"(r) : "r"(x), "r"(zero));
    return r;
}

__device__ __forceinline__ void tma_ld2(uint32_t dst, const CUtensorMap* m, int c0, int c1, uint32_t bar) {
    asm volatile("cp.async.bulk.tensor.2d.shared::cluster.global.mbarrier::complete_tx::bytes [%0], [%1, {%3, %4}], [%2];"
                 ::"r"(dst), "l"(m), "r"(bar), "r"(c0), "r"(c1) : "memory");
}
__device__ __forceinline__ void tma_ld3(uint32_t dst, const CUtensorMap* m, int c0, int c1, int c2, uint32_t bar) {
    asm volatile("cp.async.bulk.tensor.3d.shared::cluster.global.mbarrier::complete_tx::bytes [%0], [%1, {%3, %4, %5}], [%2];"
                 ::"r"(dst), "l"(m), "r"(bar), "r"(c0), "r"(c1), "r"(c2) : "memory");
}
__device__ __forceinline__ void tma_ld4(uint32_t dst, const CUtensorMap* m, int c0, int c1, int c2, int c3, uint32_t bar) {
    asm volatile("cp.async.bulk.tensor.4d.shared::cluster.global.mbarrier::complete_tx::bytes [%0], [%1, {%3, %4, %5, %6}], [%2];"
                 ::"r"(dst), "l"(m), "r"(bar), "r"(c0), "r"(c1), "r"(c2), "r"(c3) : "memory");
}
__device__ __forceinline__ void bulk_ld(uint32_t dst, const void* src, uint32_t bytes, uint32_t bar) {
    asm volatile("cp.async.bulk.shared::cluster.global.mbarrier::complete_tx::bytes [%0], [%1], %2, [%3];"
                 ::"r"(dst), "l"(src), "r"(bytes), "r"(bar) : "memory");
}
__device__ __forceinline__ void tma_st2(const CUtensorMap* m, int c0, int c1, uint32_t src) {
    asm volatile("cp.async.bulk.tensor.2d.global.shared::cta.bulk_group [%0, {%1, %2}], [%3];"
                 ::"l"(m), "r"(c0), "r"(c1), "r"(src) : "memory");
}
__device__ __forceinline__ void bulk_commit() { asm volatile("cp.async.bulk.commit_group;" ::: "memory"); }
__device__ __forceinline__ void bulk_wait_read() { asm volatile("cp.async.bulk.wait_group.read 0;" ::: "memory"); }
__device__ __forceinline__ void fence_async_smem() { asm volatile("fence.proxy.async.shared::cta;" ::: "memory"); }
__device__ __forceinline__ void fence_async_global() { asm volatile("fence.proxy.async.global;" ::: "memory"); }

__device__ __forceinline__ void signal(int idx) {
    asm volatile("fence.proxy.async;\nred.relaxed.gpu.global.add.u32 [%0], 1;" ::"l"(&g_cnt[idx * 32]) : "memory");
}
__device__ __forceinline__ void await(int idx, unsigned target) {
#pragma unroll 1
    for (int n = 0; n < SPIN_LIMIT; n++) {
        unsigned v;
        asm volatile("ld.relaxed.gpu.global.u32 %0, [%1];" : "=r"(v) : "l"(&g_cnt[idx * 32]) : "memory");
        if ((int)(v - target) >= 0) break;
    }
    asm volatile("fence.acquire.gpu;" ::: "memory");
}
__device__ __forceinline__ void wait_dep(int k) {
    mbar_wait(base + BAR_DEP + k * 8, 0);
    fence_async_global();
}

#define WG_REGS                                                                                                     \
    "{%0,%1,%2,%3,%4,%5,%6,%7,%8,%9,%10,%11,%12,%13,%14,%15,%16,%17,%18,%19,%20,%21,%22,%23,%24,%25,%26,%27,"       \
    "%28,%29,%30,%31,%32,%33,%34,%35,%36,%37,%38,%39,%40,%41,%42,%43,%44,%45,%46,%47,%48,%49,%50,%51,%52,%53,%54,%55}"
#define WG_OPS(C)                                                                                                   \
    C(d[0]), C(d[1]), C(d[2]), C(d[3]), C(d[4]), C(d[5]), C(d[6]), C(d[7]), C(d[8]), C(d[9]), C(d[10]), C(d[11]),   \
    C(d[12]), C(d[13]), C(d[14]), C(d[15]), C(d[16]), C(d[17]), C(d[18]), C(d[19]), C(d[20]), C(d[21]), C(d[22]),   \
    C(d[23]), C(d[24]), C(d[25]), C(d[26]), C(d[27]), C(d[28]), C(d[29]), C(d[30]), C(d[31]), C(d[32]), C(d[33]),   \
    C(d[34]), C(d[35]), C(d[36]), C(d[37]), C(d[38]), C(d[39]), C(d[40]), C(d[41]), C(d[42]), C(d[43]), C(d[44]),   \
    C(d[45]), C(d[46]), C(d[47]), C(d[48]), C(d[49]), C(d[50]), C(d[51]), C(d[52]), C(d[53]), C(d[54]), C(d[55])

template <int TA, int TB, int SB, bool INIT>
__device__ __forceinline__ void wgmma112(float (&d)[56], uint64_t da, uint64_t db) {
    if (INIT) {
        asm volatile("{\n.reg .pred p;\nsetp.ne.b32 p, 0, 0;\n"
                     "wgmma.mma_async.sync.aligned.m64n112k16.f32.bf16.bf16 " WG_REGS ", %56, %57, p, 1, %59, %60, %58;\n}\n"
                     : WG_OPS("=f") : "l"(da), "l"(db), "n"(TB), "n"(SB), "n"(TA));
    } else {
        asm volatile("{\n.reg .pred p;\nsetp.ne.b32 p, 1, 0;\n"
                     "wgmma.mma_async.sync.aligned.m64n112k16.f32.bf16.bf16 " WG_REGS ", %56, %57, p, 1, %59, %60, %58;\n}\n"
                     : WG_OPS("+f") : "l"(da), "l"(db), "n"(TB), "n"(SB), "n"(TA));
    }
}
__device__ __forceinline__ void acc_fence(float (&d)[56]) {
#pragma unroll
    for (int i = 0; i < 56; i++) asm volatile("" : "+f"(d[i])::"memory");
}

__device__ __forceinline__ uint32_t pack2(float lo, float hi) {
    uint32_t r;
    asm volatile("cvt.rn.bf16x2.f32 %0, %1, %2;" : "=r"(r) : "f"(hi), "f"(lo));
    return r;
}
__device__ __forceinline__ uint32_t movm(uint32_t a) {
    uint32_t r;
    asm volatile("movmatrix.sync.aligned.m8n8.trans.b16 %0, %1;" : "=r"(r) : "r"(a));
    return r;
}
__device__ __forceinline__ void stsm4(uint32_t addr, uint32_t a, uint32_t b, uint32_t c, uint32_t d) {
    asm volatile("stmatrix.sync.aligned.m8n8.x4.shared.b16 [%0], {%1,%2,%3,%4};" ::"r"(addr), "r"(a), "r"(b), "r"(c), "r"(d) : "memory");
}
__device__ __forceinline__ void sts1(uint32_t addr, uint32_t a) { asm volatile("st.shared.b32 [%0], %1;" ::"r"(addr), "r"(a) : "memory"); }
__device__ __forceinline__ uint32_t lds1(uint32_t addr) {
    uint32_t a;
    asm volatile("ld.shared.b32 %0, [%1];" : "=r"(a) : "r"(addr) : "memory");
    return a;
}
__device__ __forceinline__ void stg1(uint8_t* p, uint32_t a) { asm volatile("st.global.b32 [%0], %1;" ::"l"(p), "r"(a) : "memory"); }
__device__ __forceinline__ void st_part(uint8_t* p, const uint32_t* v, uint32_t parity) {
    asm volatile("{\n.reg .b64 x, y;\nmov.b64 x, {%1, %2};\nmov.b64 y, {%3, %4};\nst.relaxed.gpu.global.v2.b64 [%0], {x, y};\n}\n"
                 ::"l"(p), "r"((v[0] & ~1u) | parity), "r"(v[1]), "r"((v[2] & ~1u) | parity), "r"(v[3]) : "memory");
}
__device__ __forceinline__ void mma16816(float (&d)[4], const uint32_t (&a)[4], uint32_t b0, uint32_t b1) {
    asm volatile("mma.sync.aligned.m16n8k16.row.col.f32.bf16.bf16.f32 {%0,%1,%2,%3}, {%4,%5,%6,%7}, {%8,%9}, {%0,%1,%2,%3};"
                 : "+f"(d[0]), "+f"(d[1]), "+f"(d[2]), "+f"(d[3]) : "r"(a[0]), "r"(a[1]), "r"(a[2]), "r"(a[3]), "r"(b0), "r"(b1));
}
__device__ __forceinline__ uint32_t max2(uint32_t a, uint32_t b) {
    uint32_t r;
    asm("max.bf16x2 %0, %1, %2;" : "=r"(r) : "r"(a), "r"(b));
    return r;
}
__device__ __forceinline__ void st_tagged(uint8_t* p, uint32_t a, uint32_t b, uint32_t tag) {
    asm volatile("{\n.reg .b64 x, y;\nmov.b64 x, {%1, %3};\nmov.b64 y, {%2, %3};\nst.relaxed.gpu.global.v2.b64 [%0], {x, y};\n}\n"
                 ::"l"(p), "r"(a), "r"(b), "r"(tag) : "memory");
}
__device__ __forceinline__ void ld_tagged(const uint8_t* p, uint32_t& a, uint32_t& ta, uint32_t& b, uint32_t& tb) {
    asm volatile("{\n.reg .b64 x, y;\nld.relaxed.gpu.global.v2.b64 {x, y}, [%4];\nmov.b64 {%0, %1}, x;\nmov.b64 {%2, %3}, y;\n}\n"
                 : "=r"(a), "=r"(ta), "=r"(b), "=r"(tb) : "l"(p) : "memory");
}
__device__ __forceinline__ float bf_lo(uint32_t v) { return __uint_as_float(v << 16); }
__device__ __forceinline__ float bf_hi(uint32_t v) { return __uint_as_float(v & 0xFFFF0000u); }
__device__ __forceinline__ float rcp(float x) { float r; asm("rcp.approx.ftz.f32 %0, %1;" : "=f"(r) : "f"(x)); return r; }
__device__ __forceinline__ float ex2(float x) { float r; asm volatile("ex2.approx.ftz.f32 %0, %1;" : "=f"(r) : "f"(x)); return r; }

__device__ __forceinline__ uint32_t full_bar(int stage) { return base + BAR_FULL + (stage & 7) * 8; }
__device__ __forceinline__ void wait_released(int j) { mbar_wait(base + BAR_EMPTY + (j & 7) * 8, (j >> 3) & 1); }

template <int V>
struct Int { static constexpr int value = V; };

__host__ __device__ constexpr int bslot_e(int i) { return (i < 2 || i >= 14) ? (i + 5) % 7 : (i + 1) % 5; }
__host__ __device__ constexpr int bslot_l(int i) { return i % 6; }

template <uint32_t OFF>
struct Feed {
    int stage;
    uint32_t dst;
    __device__ __forceinline__ void seek(int i, int slot) { stage = i; dst = base + OFF + slot * SLOT; }
    template <int N>
    __device__ __forceinline__ uint32_t acquire() { wait_released(stage - N); return full_bar(stage); }
    template <int N>
    __device__ __forceinline__ void next() {
        stage++;
        dst += SLOT;
        if (dst == base + OFF + N * SLOT) dst = base + OFF;
    }
};
__device__ __forceinline__ int skip_own(int n, int mt) { return n == mt ? 15 : n; }

__host__ __device__ constexpr uint64_t desc_const(uint32_t lbo, uint32_t sbo, uint32_t mode) {
    return ((uint64_t)((sbo >> 4) | (mode << 30)) << 32) | ((lbo >> 4) << 16);
}
constexpr uint64_t D_K128 = desc_const(16, 1024, 1);
constexpr uint64_t D_N128 = desc_const(8192, 1024, 1);
constexpr uint64_t D_BLOB = desc_const(128, 256, 0);
constexpr uint64_t D_OT = desc_const(2048, 128, 0);

enum Kind { XW, XWN, QK, BIG, OUT };

struct Ring {
    int stage;
    uint32_t a, b;
    uint32_t wg;
    uint32_t zero;
    __device__ __forceinline__ void seek(int i, int bslot) {
        stage = i;
        a = (base + (i % NA) * SLOT) >> 4;
        b = (base + BRING + bslot * SLOT) >> 4;
    }
    __device__ __forceinline__ void wait() {
        mbar_wait(full_bar(stage), (stage >> 3) & 1);
    }
    __device__ __forceinline__ void pin() {
        uint32_t n = 0;
#pragma unroll 1
        do {
            asm volatile("pmevent 7;" ::: "memory");
        } while (n++ < zero);
    }
    template <Kind K, int NBS, bool INIT, int SB = 1, bool WAIT = true>
    __device__ __forceinline__ void run(float (&d)[56], float (&e)[56]) {
        if (WAIT) wait();
        asm volatile("wgmma.fence.sync.aligned;" ::: "memory");
        if (K == QK) {
            const uint64_t da = D_K128 + ((base >> 4) + (stage >> 1) * (SLOT >> 4) + (stage & 1) * 4 + wg * 512), db = D_N128 + b;
            wgmma112<0, 1, 1, INIT>(d, da, db);
            wgmma112<0, 1, 1, INIT>(e, da, db + 256);
            wgmma112<0, 1, 1, false>(d, da + 2, db + 128);
            wgmma112<0, 1, 1, false>(e, da + 2, db + 384);
        } else {
            constexpr int TA = K == OUT, TB = K != XW;
            constexpr uint32_t sa = K == OUT ? 256 : 2, sb = K == XW ? 2 : K == BIG ? 224 : 128;
            const uint64_t da = (K == OUT ? D_OT : D_K128) + (a + wg * (K == OUT ? 64 : 512));
            const uint64_t db = (K == XW ? D_K128 : K == BIG ? D_BLOB : D_N128) + b;
            wgmma112<TA, TB, SB, INIT>(d, da, db);
            wgmma112<TA, TB, SB, false>(d, da + sa, db + sb);
            wgmma112<TA, TB, SB, false>(d, da + 2 * sa, db + 2 * sb);
            wgmma112<TA, TB, SB, false>(d, da + 3 * sa, db + 3 * sb);
        }
        asm volatile("wgmma.commit_group.sync.aligned;" ::: "memory");
        asm volatile("wgmma.wait_group.sync.aligned 1;" ::: "memory");
        if (stage > 0 && elect()) mbar_arrive(base + BAR_EMPTY + ((stage - 1) & 7) * 8);
        stage++;
        a += SLOT >> 4;
        if (a == (base + NA * SLOT) >> 4) a = base >> 4;
        b += SLOT >> 4;
        if (b == (base + BRING + NBS * SLOT) >> 4) b = (base + BRING) >> 4;
    }
    template <Kind K, int NBS, bool INIT, int SB = 1, bool WAIT = true>
    __device__ __forceinline__ void run(float (&d)[56]) { run<K, NBS, INIT, SB, WAIT>(d, d); }
};

__device__ __forceinline__ void pack_all(const float (&d)[56], uint32_t (&p)[28]) {
#pragma unroll
    for (int i = 0; i < 28; i++) p[i] = pack2(d[2 * i], d[2 * i + 1]);
}
template <int I0, int I1>
__device__ __forceinline__ void store_frags(uint8_t* dst, const uint32_t (&p)[28]) {
#pragma unroll
    for (int i = I0; i < I1; i++) stg1(dst + i * 128, p[i]);
}
template <int I0, int I1>
__device__ __forceinline__ void stage_frags(uint32_t lane_addr, const uint32_t (&p)[28]) {
#pragma unroll
    for (int i = I0; i < I1; i += 4) stsm4(lane_addr + i * 128, p[i], p[i + 1], p[i + 2], p[i + 3]);
}
__device__ __forceinline__ void store_out(const uint32_t (&p)[28], int lane, uint32_t slab, const CUtensorMap* m, int c0, int c1) {
    const bool swap = lane & 16;
    const uint32_t addr = slab + (lane & 15) * 224 + (((lane >> 4) ^ (lane >> 2)) & 1) * 16;
#pragma unroll
    for (int i = 0; i < 28; i += 4)
        stsm4(addr + i * 8, swap ? p[i + 2] : p[i], swap ? p[i + 3] : p[i + 1], swap ? p[i] : p[i + 2], swap ? p[i + 1] : p[i + 3]);
    fence_async_smem();
    __syncwarp();
    if (elect()) {
        tma_st2(m, c0, c1, slab);
        bulk_commit();
        bulk_wait_read();
    }
}
__host__ __device__ constexpr int tile_of(int t) { return 7 * (t >> 2) + 3 * ((t >> 1) & 1) + 2 * (t & 1); }

__global__ void __launch_bounds__(384, 1) fused_kernel(const __grid_constant__ Maps maps) {
    extern __shared__ uint8_t smem_raw[];
    if ((uint32_t)__cvta_generic_to_shared(smem_raw) != base) return;
    const int warp = __shfl_sync(0xffffffffu, threadIdx.x >> 5, 0);
    int lane = threadIdx.x & 31;
    asm volatile("" : "+r"(lane));
    const int bid = blockIdx.x < 2 * SPARE0 || blockIdx.x >= 130 ? blockIdx.x
                    : (blockIdx.x >> 1) == SPARE0                ? 128 + (blockIdx.x & 1)
                                                                 : blockIdx.x - 2;
    const bool roleH = bid >= 128;
    const int roleL = (bid >> 4) & 1;
    const int mt = ((bid >> 5) << 2) | ((bid >> 2) & 3);
    const int ns = bid & 3;
    const int par = mt >> 3, blk = mt & 7;

    if (warp == 8) {
        if (elect()) {
#pragma unroll
            for (int i = 0; i < 8; i++) mbar_init(base + BAR_FULL + i * 8, 2);
            asm volatile("fence.mbarrier_init.release.cluster;" ::: "memory");
        }
    } else if (warp == 9) {
        if (elect()) {
#pragma unroll
            for (int i = 0; i < 8; i++) mbar_init(base + BAR_EMPTY + i * 8, 8);
            asm volatile("fence.mbarrier_init.release.cluster;" ::: "memory");
        }
    } else if (warp == 10) {
        if (elect()) {
#pragma unroll
            for (int i = 0; i < 4; i++) mbar_init(base + BAR_RDY + i * 8, 8);
#pragma unroll
            for (int i = 0; i < 2; i++) mbar_init(base + BAR_HALO + i * 8, 8);
            asm volatile("fence.mbarrier_init.release.cluster;" ::: "memory");
        }
    } else if (warp == 11) {
        if (elect()) {
#pragma unroll
            for (int i = 0; i < 3; i++) mbar_init(base + BAR_DEP + i * 8, 1);
            asm volatile("fence.mbarrier_init.release.cluster;" ::: "memory");
        }
    }
    __syncthreads();

    const int col = ns * 112;
    const unsigned t_fill = clk32();
    if (warp == 8) {
        if (elect()) {
            if (roleL) {
#pragma unroll 1
                for (int i = 0; i < 4; i++) {
                    mbar_expect(full_bar(2 * i), SLOT);
                    tma_ld2(base + i * SLOT, &maps.m[M_XA], par * 448 + i * 64, blk * 128, full_bar(2 * i));
                    if (PACE_0) pause_until(t_fill, (i + 1) * 2 * PACE_0);
                }
            } else {
#pragma unroll 1
                for (int i = 0; i < NA; i++) {
                    mbar_expect(full_bar(i), SLOT);
                    if (roleH) tma_ld4(base + i * SLOT, &maps.m[M_XH], i * 64, 120, 0, 0, full_bar(i));
                    else tma_ld3(base + i * SLOT, &maps.m[M_XB], i * 64, mt * 64, 0, full_bar(i));
                    if (PACE_0) pause_until(t_fill, (i + 1) * PACE_0);
                }
            }
        }
    } else if (warp == 11) {
        if (elect()) {
            if (roleL) {
#pragma unroll 1
                for (int i = 0; i < 6; i++) {
                    const uint32_t dst = base + BRING + i * SLOT, bar = full_bar(i);
                    mbar_expect(bar, SLOT);
                    tma_ld4(dst, &maps.m[M_WQK], 0, i * 32, 0, ns, bar);
                    tma_ld4(dst + 8192, &maps.m[M_WQK], 64, i * 32, 0, ns, bar);
                    if (i & 1) mbar_arrive(bar);
                    if (PACE_0) pause_until(t_fill, (i + 1) * PACE_0);
                }
            } else if (!roleH) {
#pragma unroll
                for (int i = 0; i < 7; i++) {
                    mbar_expect(full_bar(i), BLOB);
                    tma_ld2(base + BRING + bslot_e(i) * SLOT, &maps.m[M_WR], i * 64, col, full_bar(i));
                    if (PACE_0) pause_until(t_fill, (i + 1) * PACE_0);
                }
            }
        }
    }

    if (warp >= 8) {
        asm volatile("setmaxnreg.dec.sync.aligned.u32 56;");
        unsigned* epoch_ptr = &g_epoch[(bid * 4 + (warp - 8)) * 8];
#define PROF_FEED_A
#define PROF_FEED_B
        if (warp == 8) {
            if (!roleH && elect()) {
                Feed<0> f;
                const int row = mt * 128;
                auto c_run = [&](const CUtensorMap* m, int off, int n0, int n1) {
#pragma unroll 1
                    for (int n = n0; n < n1; n++) {
                        const uint32_t bar = f.acquire<NA>();
                        mbar_expect(bar, SLOT);
                        tma_ld2(f.dst, m, (off + skip_own(n, mt)) * 64, row, bar);
                        PROF_FEED_A;
                        f.next<NA>();
                    }
                };
                if (!roleL) {
                    f.seek(14, 0);
                    mbar_wait(base + BAR_RDY, 0);
#pragma unroll 1
                    for (int i = 0; i < 4; i++) {
                        const uint32_t bar = f.acquire<NA>();
                        mbar_expect(bar, SLOT);
                        tma_ld2(f.dst, &maps.m[M_CR + (i >> 1)], ((i & 1) * 16 + mt) * 64, row, bar);
                        mbar_arrive(bar);
                        PROF_FEED_A;
                        f.next<NA>();
                    }
                    c_run(&maps.m[M_CR], 0, 0, 15);
                    c_run(&maps.m[M_CI], 0, 0, NBE);
                    wait_dep(2);
#pragma unroll 1
                    for (int i = 0; i < 7; i++) {
                        const uint32_t bar = f.acquire<NA>();
                        mbar_expect(bar, SLOT);
                        bulk_ld(f.dst, g_o + (size_t)(mt * 7 + i) * SLOT, SLOT, bar);
                        PROF_FEED_A;
                        f.next<NA>();
                    }
                } else {
#pragma unroll 1
                    for (int i = 4; i < 7; i++) {
                        wait_released(2 * i - 8);
                        mbar_expect(full_bar(2 * i), SLOT);
                        tma_ld2(base + i * SLOT, &maps.m[M_XA], par * 448 + i * 64, blk * 128, full_bar(2 * i));
                    }
                    wait_released(7);
                    f.seek(21, 0);
                    c_run(&maps.m[M_CR], 16, 0, 15);
                    c_run(&maps.m[M_CI], 16, 0, 15);
                    c_run(&maps.m[M_CI], 0, NBE, 15);
                }
            }
        } else if (warp == 11) {
            if (elect()) {
                Feed<BRING> f;
                auto blob_run = [&](auto nbs, int quarter, int n0, int n1) {
                    constexpr int N = decltype(nbs)::value;
                    const uint8_t* src = g_ab + (size_t)(quarter * 64 + ns) * BLOB;
#pragma unroll 1
                    for (int n = n0; n < n1; n++) {
                        const uint32_t bar = f.template acquire<N>();
                        mbar_expect(bar, BLOB);
                        bulk_ld(f.dst, src + skip_own(n, mt) * (4 * BLOB), BLOB, bar);
                        PROF_FEED_B;
                        f.template next<N>();
                    }
                };
                auto w_run = [&](auto nbs, const CUtensorMap* m, int slice, bool no_a) {
                    constexpr int N = decltype(nbs)::value;
#pragma unroll 1
                    for (int i = 0; i < 7; i++) {
                        const uint32_t bar = f.stage < N ? full_bar(f.stage) : f.template acquire<N>();
                        mbar_expect(bar, SLOT);
                        tma_ld3(f.dst, m, 0, i * 64, slice, bar);
                        tma_ld3(f.dst + 8192, m, 64, i * 64, slice, bar);
                        if (no_a) mbar_arrive(bar);
                        PROF_FEED_B;
                        f.template next<N>();
                    }
                };
                if (roleH) {
                    f.seek(0, 0);
                    w_run(Int<7>(), &maps.m[M_WV], 4 + ns, false);
                    w_run(Int<7>(), &maps.m[M_WV], 8 + ns, true);
                } else if (!roleL) {
                    f.seek(7, bslot_e(7));
#pragma unroll 1
                    for (int i = 0; i < 7; i++) {
                        const uint32_t bar = f.acquire<5>();
                        mbar_expect(bar, BLOB);
                        tma_ld2(f.dst, &maps.m[M_WI], i * 64, col, bar);
                        mbar_arrive(bar);
                        PROF_FEED_B;
                        f.next<5>();
                    }
                    f.seek(18, bslot_e(18));
                    wait_dep(0);
                    blob_run(Int<7>(), 0, 0, 15);
                    wait_dep(1);
                    blob_run(Int<7>(), 2, 0, NBE);
                    w_run(Int<7>(), &maps.m[M_WO], ns, false);
                } else {
                    f.seek(6, 0);
#pragma unroll 1
                    for (int i = 6; i < 14; i++) {
                        const uint32_t bar = f.acquire<6>();
                        mbar_expect(bar, SLOT);
                        tma_ld4(f.dst, &maps.m[M_WQK], 0, i * 32, 0, ns, bar);
                        tma_ld4(f.dst + 8192, &maps.m[M_WQK], 64, i * 32, 0, ns, bar);
                        if (i & 1) mbar_arrive(bar);
                        PROF_FEED_B;
                        f.next<6>();
                    }
                    w_run(Int<6>(), &maps.m[M_WV], 8 + ns, true);
                    wait_dep(0);
                    blob_run(Int<6>(), 1, 0, 15);
                    wait_dep(1);
                    blob_run(Int<6>(), 3, 0, 15);
                    blob_run(Int<6>(), 2, NBE, 15);
                }
            }
        } else if (roleH) {
        } else if (warp == 10) {
            if (elect()) {
                const unsigned ep = *epoch_ptr + 1;
                sts1(base + TAG, ep);
                await(CNT_A + ns, ep * 16);
                mbar_arrive(base + BAR_DEP);
                PROF(150);
                await(CNT_B + ns, ep * 16);
                mbar_arrive(base + BAR_DEP + 8);
                PROF(151);
                if (!roleL) {
                    await(CNT_O + mt, ep * 4);
                    mbar_arrive(base + BAR_DEP + 16);
                }
                PROF(152);
                *epoch_ptr = ep;
            }
        } else if (!roleL) {
            if (elect()) {
                mbar_wait(base + BAR_RDY, 0);
                PROF(130);
                signal(CNT_A + ns);
                PROF(131);
                mbar_wait(base + BAR_RDY + 24, 0);
                PROF(132);
                signal(CNT_B + ns);
                PROF(133);
            }
        } else {
            const unsigned tag = *epoch_ptr + 1;
#pragma unroll 1
            for (int kv = 0; kv < 2; kv++) {
                uint32_t v[14], t[14];
#pragma unroll
                for (int i = 0; i < 14; i++) v[i] = 0;

                if (blk > 0) {
                    const uint8_t* src = g_halo + (size_t)(((mt - 1) * 4 + ns) * 2 + kv) * (2 * HSLOT) + lane * 16;
                    pause_until(t_fill, HALO_DELAY + kv * 3200);
#pragma unroll 1
                    for (int n = 0; n < SPIN_LIMIT; n++) {
                        bool ok = true;
#pragma unroll
                        for (int i = 0; i < 7; i++) ld_tagged(src + i * 512, v[2 * i], t[2 * i], v[2 * i + 1], t[2 * i + 1]);
#pragma unroll
                        for (int i = 0; i < 14; i++) ok = ok && t[i] == tag;
                        if (__all_sync(0xffffffffu, ok)) break;
                    }
                }
#pragma unroll
                for (int i = 0; i < 14; i++) sts1(base + HALO + kv * (8 * HSLOT) + i * 128 + lane * 4, v[i]);
                warp_arrive(base + BAR_HALO + kv * 8);
                if (lane == 0) PROF(142 + kv);
            }
            if (elect()) {
                mbar_wait(base + BAR_RDY, 0);
                PROF(130);
                signal(CNT_O + mt);
                PROF(131);
                *epoch_ptr = tag;
            }
        }
    } else {
        asm volatile("setmaxnreg.inc.sync.aligned.u32 224;");
        Ring r;
        r.wg = warp >> 2;
        r.zero = blockIdx.y;
        const int wg = warp >> 2;
        uint8_t* part = g_part + (size_t)(ns * 16 + mt) * (2 * BLOB) + warp * 512 + lane * 16;
        uint32_t p[28];

        if (roleH) {
            unsigned* epoch_ptr = &g_epoch[bid * 4 * 8];
            const unsigned tag = *epoch_ptr + 1;
            uint8_t* hout = g_halo + (size_t)((warp * 8 + ns) * 2) * (2 * HSLOT) + lane * 16;
            float x0[56], x1[56];
            r.seek(0, 0);
            r.run<XWN, 7, true>(x0);
#pragma unroll 1
            for (int i = 1; i < 7; i++) r.run<XWN, 7, false>(x0);
            r.run<XWN, 7, true>(x1);
            acc_fence(x0);
            pack_all(x0, p);
#pragma unroll
            for (int i = 0; i < 14; i++) st_tagged(hout + (i & 1) * (16 * HSLOT) + (i >> 1) * 512, p[(i >> 1) * 4 + (i & 1)], p[(i >> 1) * 4 + (i & 1) + 2], tag);
#pragma unroll 1
            for (int i = 1; i < 7; i++) r.run<XWN, 7, false>(x1);
            asm volatile("wgmma.wait_group.sync.aligned 0;" ::: "memory");
            acc_fence(x1);
            pack_all(x1, p);
#pragma unroll
            for (int i = 0; i < 28; i++) p[i] = movm(p[i]);
#pragma unroll
            for (int i = 0; i < 14; i++)
                st_tagged(hout + 2 * HSLOT + (i & 1) * (16 * HSLOT) + (i >> 1) * 512, p[(i >> 1) * 4 + (i & 1)], p[(i >> 1) * 4 + (i & 1) + 2], tag);
            if (threadIdx.x == 0) *epoch_ptr = tag;
        } else if (!roleL) {
            uint8_t* blob = g_ab + (size_t)((wg * 16 + mt) * 4 + ns) * BLOB + (warp & 3) * WSLOT + lane * 4;
            const uint32_t own = base + BRING + wg * SLOT + (warp & 3) * WSLOT + lane * 16;
            float x0[56], x1[56];
            r.seek(0, bslot_e(0));
            r.run<XW, 7, true>(x0);
            r.run<XW, 7, false>(x0);
            r.seek(2, bslot_e(2));
#pragma unroll 1
            for (int i = 2; i < 7; i++) r.run<XW, 5, false>(x0);

            r.seek(7, bslot_e(7));
            r.run<XW, 5, true, -1>(x1);
            acc_fence(x0);
            pack_all(x0, p);
            store_frags<0, 9>(blob, p);
            r.run<XW, 5, false, -1>(x1);
            store_frags<9, 18>(blob, p);
            r.run<XW, 5, false, -1>(x1);
            store_frags<18, 28>(blob, p);
            warp_arrive(base + BAR_RDY);
            r.run<XW, 5, false, -1>(x1);
            stage_frags<0, 8>(own + 5 * SLOT, p);
            r.run<XW, 5, false, -1>(x1);
            stage_frags<8, 20>(own + 5 * SLOT, p);
            r.run<XW, 5, false, -1>(x1);
            stage_frags<20, 28>(own + 5 * SLOT, p);
            warp_arrive(base + BAR_RDY + 8);
            r.run<XW, 5, false, -1>(x1);

            mbar_wait(base + BAR_RDY + 8, 0);
            fence_async_smem();
            r.seek(14, bslot_e(14));
            r.run<BIG, 7, true>(x0);
            acc_fence(x1);
            pack_all(x1, p);
            wait_released(10);
            stage_frags<0, 28>(own, p);
            warp_arrive(base + BAR_RDY + 16);
            r.run<BIG, 7, false>(x0);
            mbar_wait(base + BAR_RDY + 16, 0);
            fence_async_smem();
            blob += (size_t)128 * BLOB;
#pragma unroll
            for (int i = 0; i < 28; i++) {
                if (i % B_SLICE == 0) r.run<BIG, 7, false>(x0);
                stg1(blob + i * 128, p[i]);
            }
            warp_arrive(base + BAR_RDY + 24);
#pragma unroll 1
            for (int i = 17 + 27 / B_SLICE; i < POUT; i++) r.run<BIG, 7, false>(x0);

            const uint32_t tag = lds1(base + TAG);
            r.seek(POUT, bslot_e(POUT));
            r.run<OUT, 7, true>(x1);
            acc_fence(x0);
            pack_all(x0, p);
            st_part(part, p, tag & 1);
#pragma unroll
            for (int i = 0; i < 3; i++) {
                r.run<OUT, 7, false>(x1);
                st_part(part + (2 * i + 1) * 4096, p + 8 * i + 4, tag & 1);
                st_part(part + (2 * i + 2) * 4096, p + 8 * i + 8, tag & 1);
            }
#pragma unroll 1
            for (int i = 4; i < 7; i++) r.run<OUT, 7, false>(x1);

            wait_released(ELAST - 6);
            asm volatile("wgmma.wait_group.sync.aligned 0;" ::: "memory");
            acc_fence(x1);
            pack_all(x1, p);
            const uint32_t slab = base + (wg ? BRING + bslot_e(ELAST - 6) * SLOT : ((ELAST - 6) % NA) * SLOT) + (warp & 3) * WSLOT;
            store_out(p, lane, slab, &maps.m[M_OUTA], par * 896 + col, blk * 128 + warp * 16);
        } else {
            const int g = lane >> 2, tig = lane & 3;
            const uint32_t hin = base + HALO + warp * HSLOT + lane * 4;
            auto publish = [&](const uint32_t (&h)[14], int kv) {
                if (warp < 7) {
#pragma unroll
                    for (int c = 0; c < 14; c++) sts1(hin + HSLOT + c * 128, h[c]);
                    warp_arrive(base + BAR_HALO + kv * 8);
                }
            };
            float y0[56], y1[56], y2[56];
            r.seek(0, 0);
            r.run<QK, 6, true>(y0, y1);
#pragma unroll 1
            for (int i = 1; i < 14; i++) r.run<QK, 6, false>(y0, y1);

            uint32_t m1[8][4], m0[8][4], lo[14], hi[14];
            r.seek(14, bslot_l(14));
            r.run<XWN, 6, true>(y2);
            acc_fence(y0);
            acc_fence(y1);
#pragma unroll
            for (int c = 0; c < 14; c++) hi[c] = pack2(y1[4 * c + 2], y1[4 * c + 3]);
            publish(hi, 0);
            r.run<XWN, 6, false>(y2);
            r.pin();
#pragma unroll
            for (int c = 0; c < 14; c++) lo[c] = pack2(y1[4 * c], y1[4 * c + 1]);
#pragma unroll
            for (int t = 0; t < 8; t++) {
                const int c = tile_of(t);
                const bool shared = (t & 3) == 2;
                m1[t][0] = shared ? dup(lo[c], r.zero) : lo[c];
                m1[t][1] = shared ? dup(hi[c], r.zero) : hi[c];
                m1[t][2] = lo[c + 1];
                m1[t][3] = hi[c + 1];
                m0[t][0] = dup(m1[t][0], r.zero);
                m0[t][2] = dup(lo[c + 1], 2 * r.zero);
            }
            r.run<XWN, 6, false>(y2);
            r.pin();
            uint32_t q[2][8][2];
#pragma unroll
            for (int b = 0; b < 2; b++) {
                uint32_t v[14];
#pragma unroll
                for (int c = 0; c < 14; c++) v[c] = pack2(y0[4 * c + 2 * b], y0[4 * c + 2 * b + 1]);
#pragma unroll
                for (int t = 0; t < 8; t++) {
                    const int c = tile_of(t);
                    q[b][t][0] = (t & 3) == 2 ? (tig >= 2 ? v[c] : 0u) : v[c];
                    q[b][t][1] = (t & 3) == 1 ? (tig < 2 ? v[c + 1] : 0u) : v[c + 1];
                }
            }
            r.run<XWN, 6, false>(y2);
            mbar_wait(base + BAR_HALO, 0);
#pragma unroll
            for (int t = 0; t < 8; t++) {
                m0[t][1] = lds1(hin + tile_of(t) * 128 + ((t & 3) == 2 ? r.zero : 0u));
                m0[t][3] = lds1(hin + tile_of(t) * 128 + 128);
            }
            r.wait();
            float s[8][4];
#pragma unroll
            for (int step = 0; step < 2; step++) {
#pragma unroll
                for (int i = 0; i < 8; i++) {
                    const int b = 1 - (i >> 2), h = i & 3, t = 2 * h + step;
                    float (&d)[4] = s[2 * h + b];
                    if (step == 0) d[0] = d[1] = d[2] = d[3] = 0.f;
                    mma16816(d, b ? m1[t] : m0[t], q[b][t][0], q[b][t][1]);
                }
            }
            r.pin();
            r.run<XWN, 6, false, 1, false>(y2);
            r.pin();

            uint32_t pr[8], mx[4], mx1[4];
            {
                const bool cur0 = g <= 2 * tig, cur1 = g <= 2 * tig + 1;
#pragma unroll
                for (int i = 0; i < 8; i++) {
                    const int c = (i & 1) ? 2 : 0;
                    pr[i] = movm(pack2(cur0 ? s[i][c] : s[i][2 - c], cur1 ? s[i][c + 1] : s[i][3 - c]));
                }
            }
            r.run<XWN, 6, false>(y2);
            r.pin();
            const uint32_t curmask = (2 * tig <= g ? 0x0000FFFFu : 0u) | (2 * tig + 1 <= g ? 0xFFFF0000u : 0u);
#pragma unroll
            for (int i = 0; i < 8; i++) pr[i] = pack2(bf_lo(pr[i]) * 0.18898223650461362f, bf_hi(pr[i]) * 0.18898223650461362f);
            r.run<XWN, 6, false>(y2);
            r.pin();
            {
                const uint32_t keep = (blk == 0 && warp == 0) ? curmask : 0xFFFFFFFFu;
#pragma unroll
                for (int i = 0; i < 4; i++) {
                    pr[2 * i] = (pr[2 * i] & keep) | (0xCE6ECE6Eu & ~keep);
                    mx[i] = max2(__byte_perm(pr[2 * i], pr[2 * i + 1], 0x5410), __byte_perm(pr[2 * i], pr[2 * i + 1], 0x7632));
                }
#pragma unroll
                for (int i = 0; i < 4; i++) mx[i] = max2(mx[i], __shfl_xor_sync(0xffffffffu, mx[i], 1));
#pragma unroll
                for (int i = 0; i < 4; i++) mx1[i] = __shfl_xor_sync(0xffffffffu, mx[i], 2);
            }

            r.seek(21, bslot_l(21));
            r.run<BIG, 6, true>(y0);
            acc_fence(y2);
#pragma unroll
            for (int c = 0; c < 14; c++) hi[c] = movm(pack2(y2[4 * c + 2], y2[4 * c + 3]));
            r.run<BIG, 6, false>(y0);
            wait_released(18);
            publish(hi, 1);
            float e0[8], e1[8], sm[8], sm1[8];
#pragma unroll
            for (int i = 0; i < 8; i++) {
                const uint32_t m2 = max2(mx[i >> 1], mx1[i >> 1]);
                sm[i] = fmul(((i & 1) ? bf_hi(m2) : bf_lo(m2)), -1.4426950408889634f);
            }
            r.run<BIG, 6, false>(y0);
            r.pin();
#pragma unroll
            for (int c = 0; c < 14; c++) lo[c] = movm(pack2(y2[4 * c], y2[4 * c + 1]));
            r.run<BIG, 6, false>(y0);
            r.pin();
#pragma unroll
            for (int i = 0; i < 8; i++) {
                e0[i] = ex2(fmaf(bf_lo(pr[i]), 1.4426950408889634f, sm[i]));
                e1[i] = ex2(fmaf(bf_hi(pr[i]), 1.4426950408889634f, sm[i]));
            }
            r.run<BIG, 6, false>(y0);
            r.pin();
#pragma unroll
            for (int i = 0; i < 8; i++) {
                sm[i] = e0[i] + e1[i];
                sm1[i] = __shfl_xor_sync(0xffffffffu, sm[i], 1);
            }
#pragma unroll
            for (int t = 0; t < 8; t++) {
                const int c = tile_of(t);
                const bool shared = (t & 3) == 2;
                m1[t][0] = shared ? dup(lo[c], r.zero) : lo[c];
                m1[t][1] = lo[c + 1];
                m1[t][2] = shared ? dup(hi[c], r.zero) : hi[c];
                m1[t][3] = hi[c + 1];
                m0[t][0] = dup(m1[t][0], r.zero);
                m0[t][1] = dup(lo[c + 1], 2 * r.zero);
            }
            r.run<BIG, 6, false>(y0);
            r.pin();
#pragma unroll
            for (int i = 0; i < 8; i++) sm[i] += sm1[i];
#pragma unroll
            for (int i = 0; i < 8; i++) {
                const float inv = rcp(sm[i] + __shfl_xor_sync(0xffffffffu, sm[i], 2));
                pr[i] = pack2(e0[i] * inv, e1[i] * inv);
            }
            r.run<BIG, 6, false>(y0);
            mbar_wait(base + BAR_HALO + 8, 0);
            const uint32_t vin = warp ? hin : hin + 8 * HSLOT;
#pragma unroll
            for (int t = 0; t < 8; t++) {
                m0[t][2] = lds1(vin + tile_of(t) * 128 + ((t & 3) == 2 ? r.zero : 0u));
                m0[t][3] = lds1(vin + tile_of(t) * 128 + 128);
            }
            uint32_t pb[8][2];
#pragma unroll
            for (int i = 0; i < 8; i++) {
                pb[i][i & 1] = band(pr[i], curmask);
                pb[i][1 - (i & 1)] = band(pr[i], ~curmask);
            }
            r.wait();
            float o[2][8][4];
#pragma unroll
            for (int i = 0; i < 16; i++) {
                const int b = 1 - (i >> 3), t = i & 7;
                float (&d)[4] = o[b][t];
                d[0] = d[1] = d[2] = d[3] = 0.f;
                mma16816(d, b ? m1[t] : m0[t], pb[(t & 6) + b][0], pb[(t & 6) + b][1]);
            }
            r.pin();
            r.run<BIG, 6, false, 1, false>(y0);
            r.pin();
            uint8_t* odst = g_o + (size_t)mt * 7 * SLOT + ns * (14 * 2048) + warp * 256 + lane * 4;
#pragma unroll
            for (int hp = 0; hp < 2; hp++) {
#pragma unroll
                for (int b = 0; b < 2; b++) {
                    const float (&u)[8][4] = o[b];
                    const int t = 4 * hp;
                    uint32_t* w = p + 14 * hp + b;
                    w[0] = pack2(u[t][0], u[t][1]);
                    w[2] = pack2(u[t][2], u[t][3]);
                    w[4] = pack2(u[t + 1][0], u[t + 1][1]);
                    w[6] = pack2(g < 4 ? u[t + 1][2] : u[t + 2][0], g < 4 ? u[t + 1][3] : u[t + 2][1]);
                    w[8] = pack2(u[t + 2][2], u[t + 2][3]);
                    w[10] = pack2(u[t + 3][0], u[t + 3][1]);
                    w[12] = pack2(u[t + 3][2], u[t + 3][3]);
                }
            }
#pragma unroll
            for (int i = 0; i < 28; i++) {
                if (i && i % O_SLICE == 0) r.run<BIG, 6, false>(y0);
                stg1(odst + (i >> 1) * 2048 + (i & 1) * 128, p[i]);
            }
            warp_arrive(base + BAR_RDY);

#pragma unroll 1
            for (int i = 29 + 27 / O_SLICE; i < LLAST; i++) r.run<BIG, 6, false>(y0);
#pragma unroll
            for (int i = 0; i < 7; i++) ld_tagged(part + i * 4096, p[4 * i], p[4 * i + 1], p[4 * i + 2], p[4 * i + 3]);
            const uint32_t tag = lds1(base + TAG);
            r.seek(LLAST, bslot_l(LLAST));
            r.run<BIG, 6, false>(y0);
            wait_released(LLAST - 6);
#pragma unroll 1
            for (int n = 0; n < SPIN_LIMIT; n++) {
                uint32_t stale = 0;
#pragma unroll
                for (int i = 0; i < 28; i += 2) stale |= p[i] ^ tag;
                if (__all_sync(0xffffffffu, !(stale & 1))) break;
#pragma unroll
                for (int i = 0; i < 7; i++) ld_tagged(part + i * 4096, p[4 * i], p[4 * i + 1], p[4 * i + 2], p[4 * i + 3]);
            }
            asm volatile("wgmma.wait_group.sync.aligned 0;" ::: "memory");
            acc_fence(y0);
#pragma unroll
            for (int i = 0; i < 28; i++) p[i] = pack2(y0[2 * i] + bf_lo(p[i]), y0[2 * i + 1] + bf_hi(p[i]));
            const uint32_t slab = base + (wg ? HALO : ((LLAST - 6) % NA) * SLOT) + (warp & 3) * WSLOT;
            store_out(p, lane, slab, &maps.m[M_OUTB], 448 + col, mt * 128 + warp * 16);
        }
    }
}

typedef CUresult (*EncodeFn)(CUtensorMap*, CUtensorMapDataType, cuuint32_t, void*, const cuuint64_t*, const cuuint64_t*,
                             const cuuint32_t*, const cuuint32_t*, CUtensorMapInterleave, CUtensorMapSwizzle,
                             CUtensorMapL2promotion, CUtensorMapFloatOOBfill);

struct Dim { uint64_t size, stride; uint32_t box; };
void encode(EncodeFn fn, CUtensorMap* m, const void* ptr, CUtensorMapSwizzle sw, Dim d0, Dim d1, Dim d2 = {0, 0, 0}, Dim d3 = {0, 0, 0}) {
    const cuuint64_t dims[4] = {d0.size, d1.size, d2.size, d3.size};
    const cuuint64_t strides[3] = {d1.stride, d2.stride, d3.stride};
    const cuuint32_t box[4] = {d0.box, d1.box, d2.box, d3.box};
    const cuuint32_t es[4] = {1, 1, 1, 1};
    fn(m, CU_TENSOR_MAP_DATA_TYPE_BFLOAT16, d3.size ? 4 : d2.size ? 3 : 2, const_cast<void*>(ptr), dims, strides, box, es,
       CU_TENSOR_MAP_INTERLEAVE_NONE, sw, CU_TENSOR_MAP_L2_PROMOTION_L2_128B, CU_TENSOR_MAP_FLOAT_OOB_FILL_NONE);
}

}

extern "C" void kernel_launch(void* const* d_in, const int* in_sizes, int n_in, void* d_out, int out_size) {
    (void)in_sizes; (void)n_in; (void)out_size;
    void* fnp = nullptr;
    cudaDriverEntryPointQueryResult st;
    cudaGetDriverEntryPoint("cuTensorMapEncodeTiled", &fnp, cudaEnableDefault, &st);
    EncodeFn fn = (EncodeFn)fnp;
    cudaFuncSetAttribute(fused_kernel, cudaFuncAttributeMaxDynamicSharedMemorySize, SMEM_BYTES);

    const CUtensorMapSwizzle S128 = CU_TENSOR_MAP_SWIZZLE_128B, S0 = CU_TENSOR_MAP_SWIZZLE_NONE;
    Maps maps;
    encode(fn, &maps.m[M_XA], d_in[0], S128, {896, 2, 64}, {1024, 1792, 128});
    encode(fn, &maps.m[M_WQK], d_in[1], S128, {112, 2, 64}, {448, 2688, 32}, {3, 896, 2}, {4, 224, 1});
    encode(fn, &maps.m[M_WV], d_in[1], S128, {112, 2, 64}, {448, 2688, 64}, {12, 224, 1});
    encode(fn, &maps.m[M_XH], d_in[0], S128, {448, 2, 64}, {128, 1792, 8}, {8, 128 * 1792, 8}, {2, 896, 2});
    encode(fn, &maps.m[M_WO], d_in[2], S128, {112, 2, 64}, {448, 896, 64}, {4, 224, 1});
    encode(fn, &maps.m[M_XB], d_in[3], S128, {448, 2, 64}, {1024, 896, 64}, {2, 896 * 1024, 2});
    encode(fn, &maps.m[M_CR], d_in[4], S128, {2048, 2, 64}, {2048, 4096, 128});
    encode(fn, &maps.m[M_CI], d_in[5], S128, {2048, 2, 64}, {2048, 4096, 128});
    encode(fn, &maps.m[M_WR], d_in[6], S128, {448, 2, 64}, {448, 896, 112});
    encode(fn, &maps.m[M_WI], d_in[7], S128, {448, 2, 64}, {448, 896, 112});
    encode(fn, &maps.m[M_OUTA], d_out, S0, {1792, 2, 112}, {1024, 3584, 16});
    encode(fn, &maps.m[M_OUTB], d_out, S0, {896, 2, 112}, {2048, 1792, 16});

    fused_kernel<<<132, 384, SMEM_BYTES>>>(maps);
}
```

```cpp
#include <cuda.h>
#include <cuda_bf16.h>
#include <cuda_runtime.h>
#include <stdint.h>

namespace {

constexpr uint32_t SLOT = 16384;
constexpr int NA = 7;
constexpr uint32_t BRING = NA * SLOT;
constexpr uint32_t HALO = BRING + 6 * SLOT;
constexpr uint32_t HSLOT = 1792;
constexpr uint32_t WSLOT = 3584;
constexpr uint32_t BLOB = 14336;
constexpr uint32_t BARS = 14 * SLOT;
constexpr uint32_t BAR_FULL = BARS;
constexpr uint32_t BAR_EMPTY = BARS + 64;
constexpr uint32_t BAR_RDY = BARS + 128;
constexpr uint32_t BAR_DEP = BARS + 160;
constexpr uint32_t BAR_HALO = BARS + 192;
constexpr uint32_t TAG = BARS + 208;
constexpr uint32_t SMEM_BYTES = BARS + 256 + 1024;
constexpr uint32_t base = 1024;
constexpr int SPIN_LIMIT = 1 << 16;

#define E_EXTRA 0
#define HALO_DELAY 7000
#define O_SLICE 5
#define B_SLICE 5
#define LEAD 2
#define MAPPING 2
#define SPARE0 12
constexpr int NBE = 13 + E_EXTRA;
constexpr int POUT = 33 + NBE;
constexpr int ELAST = POUT + 6;
constexpr int LLAST = 52 - E_EXTRA;

enum { M_XA, M_XH, M_WQK, M_WV, M_WO, M_XB, M_WR, M_WI, M_CR, M_CI, M_OUTA, M_OUTB, M_COUNT };
struct __align__(64) Maps { CUtensorMap m[M_COUNT]; };

constexpr int CNT_A = 0;
constexpr int CNT_B = 4;
constexpr int CNT_O = 16;
constexpr int CNT_COUNT = 32;

struct Scratch {
    uint8_t ab[64 * 4 * BLOB];
    uint8_t o[16 * 7 * SLOT];
    uint8_t part[64 * 2 * BLOB];
    uint8_t halo[64 * 2 * 2 * HSLOT];
    unsigned cnt[CNT_COUNT * 32];
    unsigned epoch[132 * 4 * 8];
};
__device__ __align__(1024) Scratch g_scratch;

__device__ __forceinline__ unsigned clk32() { unsigned c; asm volatile("mov.u32 %0, %%clock;" : "=r"(c)); return c; }
__device__ __forceinline__ void pause_until(unsigned t0, unsigned cycles) {
    while (clk32() - t0 < cycles) {}
}

#define PROF(idx)

__device__ __forceinline__ void mbar_init(uint32_t bar, uint32_t cnt) {
    asm volatile("mbarrier.init.shared::cta.b64 [%0], %1;" ::"r"(bar), "r"(cnt) : "memory");
}
__device__ __forceinline__ void mbar_expect(uint32_t bar, uint32_t bytes) {
    asm volatile("mbarrier.arrive.expect_tx.shared::cta.b64 _, [%0], %1;" ::"r"(bar), "r"(bytes) : "memory");
}
__device__ __forceinline__ void mbar_arrive(uint32_t bar) {
    asm volatile("mbarrier.arrive.shared::cta.b64 _, [%0];" ::"r"(bar) : "memory");
}
__device__ __forceinline__ bool mbar_try(uint32_t bar, uint32_t parity) {
    uint32_t ok;
    asm volatile("{\n.reg .pred p;\nmbarrier.try_wait.parity.shared::cta.b64 p, [%1], %2;\nselp.u32 %0, 1, 0, p;\n}\n"
                 : "=r"(ok) : "r"(bar), "r"(parity) : "memory");
    return ok;
}
__device__ __forceinline__ void mbar_wait(uint32_t bar, uint32_t parity) {
#pragma unroll 1
    for (int n = 0; n < SPIN_LIMIT; n++)
        if (mbar_try(bar, parity)) break;
}
__device__ __forceinline__ bool elect() {
    uint32_t p;
    asm volatile("{\n.reg .pred p;\nelect.sync _|p, 0xffffffff;\nselp.u32 %0, 1, 0, p;\n}\n" : "=r"(p));
    return p;
}
__device__ __forceinline__ void nb_sync(int id, int n) { asm volatile("bar.sync %0, %1;" ::"r"(id), "r"(n) : "memory"); }
__device__ __forceinline__ void warp_arrive(uint32_t bar) {
    __syncwarp();
    if (elect()) mbar_arrive(bar);
}
__device__ __forceinline__ uint32_t band(uint32_t x, uint32_t m) {
    uint32_t r;
    asm volatile("and.b32 %0, %1, %2;" : "=r"(r) : "r"(x), "r"(m));
    return r;
}
__device__ __forceinline__ float fmul(float x, float y) {
    float r;
    asm volatile("mul.f32 %0, %1, %2;" : "=f"(r) : "f"(x), "f"(y));
    return r;
}
__device__ __forceinline__ uint32_t dup(uint32_t x, uint32_t zero) {
    uint32_t r;
    asm volatile("xor.b32 %0, %1, %2;" : "=r"(r) : "r"(x), "r"(zero));
    return r;
}

__device__ __forceinline__ void tma_ld2(uint32_t dst, const CUtensorMap* m, int c0, int c1, uint32_t bar) {
    asm volatile("cp.async.bulk.tensor.2d.shared::cluster.global.mbarrier::complete_tx::bytes [%0], [%1, {%3, %4}], [%2];"
                 ::"r"(dst), "l"(m), "r"(bar), "r"(c0), "r"(c1) : "memory");
}
__device__ __forceinline__ void tma_ld3(uint32_t dst, const CUtensorMap* m, int c0, int c1, int c2, uint32_t bar) {
    asm volatile("cp.async.bulk.tensor.3d.shared::cluster.global.mbarrier::complete_tx::bytes [%0], [%1, {%3, %4, %5}], [%2];"
                 ::"r"(dst), "l"(m), "r"(bar), "r"(c0), "r"(c1), "r"(c2) : "memory");
}
__device__ __forceinline__ void tma_ld4(uint32_t dst, const CUtensorMap* m, int c0, int c1, int c2, int c3, uint32_t bar) {
    asm volatile("cp.async.bulk.tensor.4d.shared::cluster.global.mbarrier::complete_tx::bytes [%0], [%1, {%3, %4, %5, %6}], [%2];"
                 ::"r"(dst), "l"(m), "r"(bar), "r"(c0), "r"(c1), "r"(c2), "r"(c3) : "memory");
}
__device__ __forceinline__ void bulk_ld(uint32_t dst, const void* src, uint32_t bytes, uint32_t bar) {
    asm volatile("cp.async.bulk.shared::cluster.global.mbarrier::complete_tx::bytes [%0], [%1], %2, [%3];"
                 ::"r"(dst), "l"(src), "r"(bytes), "r"(bar) : "memory");
}
__device__ __forceinline__ void tma_st2(const CUtensorMap* m, int c0, int c1, uint32_t src) {
    asm volatile("cp.async.bulk.tensor.2d.global.shared::cta.bulk_group [%0, {%1, %2}], [%3];"
                 ::"l"(m), "r"(c0), "r"(c1), "r"(src) : "memory");
}
__device__ __forceinline__ void bulk_commit() { asm volatile("cp.async.bulk.commit_group;" ::: "memory"); }
__device__ __forceinline__ void bulk_wait_read() { asm volatile("cp.async.bulk.wait_group.read 0;" ::: "memory"); }
__device__ __forceinline__ void fence_async_smem() { asm volatile("fence.proxy.async.shared::cta;" ::: "memory"); }
__device__ __forceinline__ void fence_async_global() { asm volatile("fence.proxy.async.global;" ::: "memory"); }

__device__ __forceinline__ void signal(Scratch* sc, int idx) {
    asm volatile("fence.proxy.async;\nred.relaxed.gpu.global.add.u32 [%0], 1;" ::"l"(&sc->cnt[idx * 32]) : "memory");
}
__device__ __forceinline__ void await(Scratch* sc, int idx, unsigned target) {
#pragma unroll 1
    for (int n = 0; n < SPIN_LIMIT; n++) {
        unsigned v;
        asm volatile("ld.relaxed.gpu.global.u32 %0, [%1];" : "=r"(v) : "l"(&sc->cnt[idx * 32]) : "memory");
        if ((int)(v - target) >= 0) break;
    }
    asm volatile("fence.acquire.gpu;" ::: "memory");
}
__device__ __forceinline__ void wait_dep(int k) {
    mbar_wait(base + BAR_DEP + k * 8, 0);
    fence_async_global();
}

#define WG_REGS                                                                                                     \
    "{%0,%1,%2,%3,%4,%5,%6,%7,%8,%9,%10,%11,%12,%13,%14,%15,%16,%17,%18,%19,%20,%21,%22,%23,%24,%25,%26,%27,"       \
    "%28,%29,%30,%31,%32,%33,%34,%35,%36,%37,%38,%39,%40,%41,%42,%43,%44,%45,%46,%47,%48,%49,%50,%51,%52,%53,%54,%55}"
#define WG_OPS(C)                                                                                                   \
    C(d[0]), C(d[1]), C(d[2]), C(d[3]), C(d[4]), C(d[5]), C(d[6]), C(d[7]), C(d[8]), C(d[9]), C(d[10]), C(d[11]),   \
    C(d[12]), C(d[13]), C(d[14]), C(d[15]), C(d[16]), C(d[17]), C(d[18]), C(d[19]), C(d[20]), C(d[21]), C(d[22]),   \
    C(d[23]), C(d[24]), C(d[25]), C(d[26]), C(d[27]), C(d[28]), C(d[29]), C(d[30]), C(d[31]), C(d[32]), C(d[33]),   \
    C(d[34]), C(d[35]), C(d[36]), C(d[37]), C(d[38]), C(d[39]), C(d[40]), C(d[41]), C(d[42]), C(d[43]), C(d[44]),   \
    C(d[45]), C(d[46]), C(d[47]), C(d[48]), C(d[49]), C(d[50]), C(d[51]), C(d[52]), C(d[53]), C(d[54]), C(d[55])

template <int TA, int TB, int SB, bool INIT>
__device__ __forceinline__ void wgmma112(float (&d)[56], uint64_t da, uint64_t db) {
    if (INIT) {
        asm volatile("{\n.reg .pred p;\nsetp.ne.b32 p, 0, 0;\n"
                     "wgmma.mma_async.sync.aligned.m64n112k16.f32.bf16.bf16 " WG_REGS ", %56, %57, p, 1, %59, %60, %58;\n}\n"
                     : WG_OPS("=f") : "l"(da), "l"(db), "n"(TB), "n"(SB), "n"(TA));
    } else {
        asm volatile("{\n.reg .pred p;\nsetp.ne.b32 p, 1, 0;\n"
                     "wgmma.mma_async.sync.aligned.m64n112k16.f32.bf16.bf16 " WG_REGS ", %56, %57, p, 1, %59, %60, %58;\n}\n"
                     : WG_OPS("+f") : "l"(da), "l"(db), "n"(TB), "n"(SB), "n"(TA));
    }
}
__device__ __forceinline__ void acc_fence(float (&d)[56]) {
#pragma unroll
    for (int i = 0; i < 56; i++) asm volatile("" : "+f"(d[i])::"memory");
}

__device__ __forceinline__ uint32_t pack2(float lo, float hi) {
    uint32_t r;
    asm volatile("cvt.rn.bf16x2.f32 %0, %1, %2;" : "=r"(r) : "f"(hi), "f"(lo));
    return r;
}
__device__ __forceinline__ uint32_t movm(uint32_t a) {
    uint32_t r;
    asm volatile("movmatrix.sync.aligned.m8n8.trans.b16 %0, %1;" : "=r"(r) : "r"(a));
    return r;
}
__device__ __forceinline__ void stsm4(uint32_t addr, uint32_t a, uint32_t b, uint32_t c, uint32_t d) {
    asm volatile("stmatrix.sync.aligned.m8n8.x4.shared.b16 [%0], {%1,%2,%3,%4};" ::"r"(addr), "r"(a), "r"(b), "r"(c), "r"(d) : "memory");
}
__device__ __forceinline__ void sts1(uint32_t addr, uint32_t a) { asm volatile("st.shared.b32 [%0], %1;" ::"r"(addr), "r"(a) : "memory"); }
__device__ __forceinline__ uint32_t lds1(uint32_t addr) {
    uint32_t a;
    asm volatile("ld.shared.b32 %0, [%1];" : "=r"(a) : "r"(addr) : "memory");
    return a;
}
__device__ __forceinline__ void stg1(uint8_t* p, uint32_t a) { asm volatile("st.global.b32 [%0], %1;" ::"l"(p), "r"(a) : "memory"); }
__device__ __forceinline__ void st_part(uint8_t* p, const uint32_t* v, uint32_t parity) {
    asm volatile("{\n.reg .b64 x, y;\nmov.b64 x, {%1, %2};\nmov.b64 y, {%3, %4};\nst.relaxed.gpu.global.v2.b64 [%0], {x, y};\n}\n"
                 ::"l"(p), "r"((v[0] & ~1u) | parity), "r"(v[1]), "r"((v[2] & ~1u) | parity), "r"(v[3]) : "memory");
}
__device__ __forceinline__ void mma16816(float (&d)[4], const uint32_t (&a)[4], uint32_t b0, uint32_t b1) {
    asm volatile("mma.sync.aligned.m16n8k16.row.col.f32.bf16.bf16.f32 {%0,%1,%2,%3}, {%4,%5,%6,%7}, {%8,%9}, {%0,%1,%2,%3};"
                 : "+f"(d[0]), "+f"(d[1]), "+f"(d[2]), "+f"(d[3]) : "r"(a[0]), "r"(a[1]), "r"(a[2]), "r"(a[3]), "r"(b0), "r"(b1));
}
__device__ __forceinline__ uint32_t max2(uint32_t a, uint32_t b) {
    uint32_t r;
    asm("max.bf16x2 %0, %1, %2;" : "=r"(r) : "r"(a), "r"(b));
    return r;
}
__device__ __forceinline__ void st_tagged(uint8_t* p, uint32_t a, uint32_t b, uint32_t tag) {
    asm volatile("{\n.reg .b64 x, y;\nmov.b64 x, {%1, %3};\nmov.b64 y, {%2, %3};\nst.relaxed.gpu.global.v2.b64 [%0], {x, y};\n}\n"
                 ::"l"(p), "r"(a), "r"(b), "r"(tag) : "memory");
}
__device__ __forceinline__ void ld_tagged(const uint8_t* p, uint32_t& a, uint32_t& ta, uint32_t& b, uint32_t& tb) {
    asm volatile("{\n.reg .b64 x, y;\nld.relaxed.gpu.global.v2.b64 {x, y}, [%4];\nmov.b64 {%0, %1}, x;\nmov.b64 {%2, %3}, y;\n}\n"
                 : "=r"(a), "=r"(ta), "=r"(b), "=r"(tb) : "l"(p) : "memory");
}
__device__ __forceinline__ float bf_lo(uint32_t v) { return __uint_as_float(v << 16); }
__device__ __forceinline__ float bf_hi(uint32_t v) { return __uint_as_float(v & 0xFFFF0000u); }
__device__ __forceinline__ float rcp(float x) { float r; asm("rcp.approx.ftz.f32 %0, %1;" : "=f"(r) : "f"(x)); return r; }
__device__ __forceinline__ float ex2(float x) { float r; asm volatile("ex2.approx.ftz.f32 %0, %1;" : "=f"(r) : "f"(x)); return r; }

__device__ __forceinline__ uint32_t full_bar(int stage) { return base + BAR_FULL + (stage & 7) * 8; }
__device__ __forceinline__ void wait_released(int j) { mbar_wait(base + BAR_EMPTY + (j & 7) * 8, (j >> 3) & 1); }

template <int V>
struct Int { static constexpr int value = V; };

__host__ __device__ constexpr int bslot_e(int i) { return (i < 2 || i >= 14) ? (i + 5) % 7 : (i + 1) % 5; }
__host__ __device__ constexpr int bslot_l(int i) { return i % 6; }

template <uint32_t OFF>
struct Feed {
    int stage;
    uint32_t dst;
    __device__ __forceinline__ void seek(int i, int slot) { stage = i; dst = base + OFF + slot * SLOT; }
    template <int N>
    __device__ __forceinline__ uint32_t acquire() { wait_released(stage - N); return full_bar(stage); }
    template <int N>
    __device__ __forceinline__ void next() {
        stage++;
        dst += SLOT;
        if (dst == base + OFF + N * SLOT) dst = base + OFF;
    }
};
__device__ __forceinline__ int skip_own(int n, int mt) { return n == mt ? 15 : n; }

__host__ __device__ constexpr uint64_t desc_const(uint32_t lbo, uint32_t sbo, uint32_t mode) {
    return ((uint64_t)((sbo >> 4) | (mode << 30)) << 32) | ((lbo >> 4) << 16);
}
constexpr uint64_t D_K128 = desc_const(16, 1024, 1);
constexpr uint64_t D_N128 = desc_const(8192, 1024, 1);
constexpr uint64_t D_BLOB = desc_const(128, 256, 0);
constexpr uint64_t D_OT = desc_const(2048, 128, 0);

enum Kind { XW, XWN, QK, BIG, OUT };

struct Ring {
    int stage;
    uint32_t a, b;
    uint32_t wg;
    uint32_t zero;
    __device__ __forceinline__ void seek(int i, int bslot) {
        stage = i;
        a = (base + (i % NA) * SLOT) >> 4;
        b = (base + BRING + bslot * SLOT) >> 4;
    }
    __device__ __forceinline__ void wait() {
        mbar_wait(full_bar(stage), (stage >> 3) & 1);
    }
    __device__ __forceinline__ void pin() {
        uint32_t n = 0;
#pragma unroll 1
        do {
            asm volatile("pmevent 7;" ::: "memory");
        } while (n++ < zero);
    }
    template <Kind K, int NBS, bool INIT, int SB = 1, bool WAIT = true>
    __device__ __forceinline__ void run(float (&d)[56], float (&e)[56]) {
        if (WAIT) wait();
        asm volatile("wgmma.fence.sync.aligned;" ::: "memory");
        if (K == QK) {
            const uint64_t da = D_K128 + ((base >> 4) + (stage >> 1) * (SLOT >> 4) + (stage & 1) * 4 + wg * 512), db = D_N128 + b;
            wgmma112<0, 1, 1, INIT>(d, da, db);
            wgmma112<0, 1, 1, INIT>(e, da, db + 256);
            wgmma112<0, 1, 1, false>(d, da + 2, db + 128);
            wgmma112<0, 1, 1, false>(e, da + 2, db + 384);
        } else {
            constexpr int TA = K == OUT, TB = K != XW;
            constexpr uint32_t sa = K == OUT ? 256 : 2, sb = K == XW ? 2 : K == BIG ? 224 : 128;
            const uint64_t da = (K == OUT ? D_OT : D_K128) + (a + wg * (K == OUT ? 64 : 512));
            const uint64_t db = (K == XW ? D_K128 : K == BIG ? D_BLOB : D_N128) + b;
            wgmma112<TA, TB, SB, INIT>(d, da, db);
            wgmma112<TA, TB, SB, false>(d, da + sa, db + sb);
            wgmma112<TA, TB, SB, false>(d, da + 2 * sa, db + 2 * sb);
            wgmma112<TA, TB, SB, false>(d, da + 3 * sa, db + 3 * sb);
        }
        asm volatile("wgmma.commit_group.sync.aligned;" ::: "memory");
        asm volatile("wgmma.wait_group.sync.aligned 1;" ::: "memory");
        if (stage > 0 && elect()) mbar_arrive(base + BAR_EMPTY + ((stage - 1) & 7) * 8);
        stage++;
        a += SLOT >> 4;
        if (a == (base + NA * SLOT) >> 4) a = base >> 4;
        b += SLOT >> 4;
        if (b == (base + BRING + NBS * SLOT) >> 4) b = (base + BRING) >> 4;
    }
    template <Kind K, int NBS, bool INIT, int SB = 1, bool WAIT = true>
    __device__ __forceinline__ void run(float (&d)[56]) { run<K, NBS, INIT, SB, WAIT>(d, d); }
};

__device__ __forceinline__ void pack_all(const float (&d)[56], uint32_t (&p)[28]) {
#pragma unroll
    for (int i = 0; i < 28; i++) p[i] = pack2(d[2 * i], d[2 * i + 1]);
}
template <int I0, int I1>
__device__ __forceinline__ void store_frags(uint8_t* dst, const uint32_t (&p)[28]) {
#pragma unroll
    for (int i = I0; i < I1; i++) stg1(dst + i * 128, p[i]);
}
template <int I0, int I1>
__device__ __forceinline__ void stage_frags(uint32_t lane_addr, const uint32_t (&p)[28]) {
#pragma unroll
    for (int i = I0; i < I1; i += 4) stsm4(lane_addr + i * 128, p[i], p[i + 1], p[i + 2], p[i + 3]);
}
__device__ __forceinline__ void store_out(const uint32_t (&p)[28], int lane, uint32_t slab, const CUtensorMap* m, int c0, int c1) {
    const bool swap = lane & 16;
    const uint32_t addr = slab + (lane & 15) * 224 + (((lane >> 4) ^ (lane >> 2)) & 1) * 16;
#pragma unroll
    for (int i = 0; i < 28; i += 4)
        stsm4(addr + i * 8, swap ? p[i + 2] : p[i], swap ? p[i + 3] : p[i + 1], swap ? p[i] : p[i + 2], swap ? p[i + 1] : p[i + 3]);
    fence_async_smem();
    __syncwarp();
    if (elect()) {
        tma_st2(m, c0, c1, slab);
        bulk_commit();
        bulk_wait_read();
    }
}
__host__ __device__ constexpr int tile_of(int t) { return 7 * (t >> 2) + 3 * ((t >> 1) & 1) + 2 * (t & 1); }

__global__ void __launch_bounds__(384, 1) fused_kernel(Scratch* sc, const __grid_constant__ Maps maps) {
    extern __shared__ uint8_t smem_raw[];
    if ((uint32_t)__cvta_generic_to_shared(smem_raw) != base) return;
    const int warp = __shfl_sync(0xffffffffu, threadIdx.x >> 5, 0);
    int lane = threadIdx.x & 31;
    asm volatile("" : "+r"(lane));
    const int bid = blockIdx.x < 2 * SPARE0 || blockIdx.x >= 130 ? blockIdx.x
                    : (blockIdx.x >> 1) == SPARE0                ? 128 + (blockIdx.x & 1)
                                                                 : blockIdx.x - 2;
    const bool roleH = bid >= 128;
    const int roleL = (bid >> 4) & 1;
    const int mt = ((bid >> 5) << 2) | ((bid >> 2) & 3);
    const int ns = bid & 3;
    const int par = mt >> 3, blk = mt & 7;

    const int col = ns * 112;
    auto fill = [&](auto i0, auto i1) {
        if (roleL) {
#pragma unroll
            for (int i = decltype(i0)::value; i < decltype(i1)::value; i++) {
                const uint32_t bar = full_bar(i), dst = base + BRING + i * SLOT;
                if (i < 6) mbar_expect(bar, SLOT);
                if (i & 1) {
                    mbar_arrive(bar);
                } else {
                    mbar_expect(bar, SLOT);
                    tma_ld2(base + (i >> 1) * SLOT, &maps.m[M_XA], par * 448 + i * 32, blk * 128, bar);
                }
                if (i < 6) {
                    tma_ld4(dst, &maps.m[M_WQK], 0, i * 32, 0, ns, bar);
                    tma_ld4(dst + 8192, &maps.m[M_WQK], 64, i * 32, 0, ns, bar);
                }
            }
        } else if (!roleH) {
#pragma unroll
            for (int i = decltype(i0)::value; i < decltype(i1)::value; i++) {
                const uint32_t bar = full_bar(i);
                mbar_expect(bar, SLOT);
                mbar_expect(bar, BLOB);
                tma_ld3(base + i * SLOT, &maps.m[M_XB], i * 64, mt * 64, 0, bar);
                tma_ld2(base + BRING + bslot_e(i) * SLOT, &maps.m[M_WR], i * 64, col, bar);
            }
        } else {
#pragma unroll 1
            for (int i = decltype(i0)::value; i < decltype(i1)::value; i++) {
                const uint32_t bar = full_bar(i), dst = base + BRING + i * SLOT;
                mbar_expect(bar, SLOT);
                mbar_expect(bar, SLOT);
                tma_ld4(base + i * SLOT, &maps.m[M_XH], i * 64, 120, 0, 0, bar);
                tma_ld3(dst, &maps.m[M_WV], 0, i * 64, 4 + ns, bar);
                tma_ld3(dst + 8192, &maps.m[M_WV], 64, i * 64, 4 + ns, bar);
            }
        }
    };
    if (warp == 8) {
        if (elect()) {
#pragma unroll
            for (int i = 0; i < 8; i++) mbar_init(base + BAR_FULL + i * 8, 2);
            asm volatile("fence.mbarrier_init.release.cluster;" ::: "memory");
            fill(Int<0>(), Int<LEAD>());
        }
    } else if (warp == 9) {
        if (elect()) {
#pragma unroll
            for (int i = 0; i < 8; i++) mbar_init(base + BAR_EMPTY + i * 8, 8);
            asm volatile("fence.mbarrier_init.release.cluster;" ::: "memory");
        }
    } else if (warp == 10) {
        if (elect()) {
#pragma unroll
            for (int i = 0; i < 4; i++) mbar_init(base + BAR_RDY + i * 8, 8);
#pragma unroll
            for (int i = 0; i < 2; i++) mbar_init(base + BAR_HALO + i * 8, 8);
            asm volatile("fence.mbarrier_init.release.cluster;" ::: "memory");
        }
    } else if (warp == 11) {
        if (elect()) {
#pragma unroll
            for (int i = 0; i < 3; i++) mbar_init(base + BAR_DEP + i * 8, 1);
            asm volatile("fence.mbarrier_init.release.cluster;" ::: "memory");
        }
    }
    __syncthreads();

    if (__builtin_expect(warp >= 8, 1)) {
        asm volatile("setmaxnreg.dec.sync.aligned.u32 56;");
#define PROF_FEED_A
#define PROF_FEED_B
        if (__builtin_expect(warp == 8, 1)) {
            if (elect()) {
                PROF(129);
                fill(Int<LEAD>(), Int<7>());
                PROF(134);
                Feed<0> f;
                const int row = mt * 128;
                auto c_run = [&](const CUtensorMap* m, int off, int n0, int n1) {
#pragma unroll 1
                    for (int n = n0; n < n1; n++) {
                        const uint32_t bar = f.acquire<NA>();
                        mbar_expect(bar, SLOT);
                        tma_ld2(f.dst, m, (off + skip_own(n, mt)) * 64, row, bar);
                        PROF_FEED_A;
                        f.next<NA>();
                    }
                };
                if (roleH) {
                } else if (!roleL) {
                    f.seek(14, 0);
                    mbar_wait(base + BAR_RDY, 0);
#pragma unroll 1
                    for (int i = 0; i < 4; i++) {
                        const uint32_t bar = f.acquire<NA>();
                        mbar_expect(bar, SLOT);
                        tma_ld2(f.dst, &maps.m[M_CR + (i >> 1)], ((i & 1) * 16 + mt) * 64, row, bar);
                        mbar_arrive(bar);
                        PROF_FEED_A;
                        f.next<NA>();
                    }
                    c_run(&maps.m[M_CR], 0, 0, 15);
                    c_run(&maps.m[M_CI], 0, 0, NBE);
                    wait_dep(2);
#pragma unroll 1
                    for (int i = 0; i < 7; i++) {
                        const uint32_t bar = f.acquire<NA>();
                        mbar_expect(bar, SLOT);
                        bulk_ld(f.dst, sc->o + (size_t)(mt * 7 + i) * SLOT, SLOT, bar);
                        PROF_FEED_A;
                        f.next<NA>();
                    }
                } else {
#pragma unroll 1
                    for (int i = 4; i < 7; i++) {
                        wait_released(2 * i - 8);
                        mbar_expect(full_bar(2 * i), SLOT);
                        tma_ld2(base + i * SLOT, &maps.m[M_XA], par * 448 + i * 64, blk * 128, full_bar(2 * i));
                    }
                    wait_released(7);
                    f.seek(21, 0);
                    c_run(&maps.m[M_CR], 16, 0, 15);
                    c_run(&maps.m[M_CI], 16, 0, 15);
                    c_run(&maps.m[M_CI], 0, NBE, 15);
                }
            }
        } else if (warp == 11) {
            if (elect()) {
                Feed<BRING> f;
                auto blob_run = [&](auto nbs, int quarter, int n0, int n1) {
                    constexpr int N = decltype(nbs)::value;
                    const uint8_t* src = sc->ab + (size_t)(quarter * 64 + ns) * BLOB;
#pragma unroll 1
                    for (int n = n0; n < n1; n++) {
                        const uint32_t bar = f.template acquire<N>();
                        mbar_expect(bar, BLOB);
                        bulk_ld(f.dst, src + skip_own(n, mt) * (4 * BLOB), BLOB, bar);
                        PROF_FEED_B;
                        f.template next<N>();
                    }
                };
                auto w_run = [&](auto nbs, const CUtensorMap* m, int slice, bool no_a) {
                    constexpr int N = decltype(nbs)::value;
#pragma unroll 1
                    for (int i = 0; i < 7; i++) {
                        const uint32_t bar = f.template acquire<N>();
                        mbar_expect(bar, SLOT);
                        tma_ld3(f.dst, m, 0, i * 64, slice, bar);
                        tma_ld3(f.dst + 8192, m, 64, i * 64, slice, bar);
                        if (no_a) mbar_arrive(bar);
                        PROF_FEED_B;
                        f.template next<N>();
                    }
                };
                if (roleH) {
                    f.seek(7, 0);
                    w_run(Int<7>(), &maps.m[M_WV], 8 + ns, true);
                } else if (!roleL) {
                    f.seek(7, bslot_e(7));
#pragma unroll 1
                    for (int i = 0; i < 7; i++) {
                        const uint32_t bar = f.acquire<5>();
                        mbar_expect(bar, BLOB);
                        tma_ld2(f.dst, &maps.m[M_WI], i * 64, col, bar);
                        mbar_arrive(bar);
                        PROF_FEED_B;
                        f.next<5>();
                    }
                    f.seek(18, bslot_e(18));
                    wait_dep(0);
                    blob_run(Int<7>(), 0, 0, 15);
                    wait_dep(1);
                    blob_run(Int<7>(), 2, 0, NBE);
                    w_run(Int<7>(), &maps.m[M_WO], ns, false);
                } else {
                    f.seek(6, 0);
#pragma unroll 1
                    for (int i = 6; i < 14; i++) {
                        const uint32_t bar = f.acquire<6>();
                        mbar_expect(bar, SLOT);
                        tma_ld4(f.dst, &maps.m[M_WQK], 0, i * 32, 0, ns, bar);
                        tma_ld4(f.dst + 8192, &maps.m[M_WQK], 64, i * 32, 0, ns, bar);
                        if (i & 1) mbar_arrive(bar);
                        PROF_FEED_B;
                        f.next<6>();
                    }
                    w_run(Int<6>(), &maps.m[M_WV], 8 + ns, true);
                    wait_dep(0);
                    blob_run(Int<6>(), 1, 0, 15);
                    wait_dep(1);
                    blob_run(Int<6>(), 3, 0, 15);
                    blob_run(Int<6>(), 2, NBE, 15);
                }
            }
        } else if (roleH) {
        } else if (warp == 10) {
            if (elect()) {
                unsigned* epoch_ptr = &sc->epoch[(bid * 4 + 2) * 8];
                const unsigned ep = *epoch_ptr + 1;
                sts1(base + TAG, ep);
                await(sc, CNT_A + ns, ep * 16);
                mbar_arrive(base + BAR_DEP);
                PROF(150);
                await(sc, CNT_B + ns, ep * 16);
                mbar_arrive(base + BAR_DEP + 8);
                PROF(151);
                if (!roleL) {
                    await(sc, CNT_O + mt, ep * 4);
                    mbar_arrive(base + BAR_DEP + 16);
                }
                PROF(152);
                *epoch_ptr = ep;
            }
        } else if (!roleL) {
            if (elect()) {
                mbar_wait(base + BAR_RDY, 0);
                PROF(130);
                signal(sc, CNT_A + ns);
                PROF(131);
                mbar_wait(base + BAR_RDY + 24, 0);
                PROF(132);
                signal(sc, CNT_B + ns);
                PROF(133);
            }
        } else {
            const unsigned t_start = clk32();
            unsigned* epoch_ptr = &sc->epoch[(bid * 4 + 1) * 8];
            const unsigned tag = *epoch_ptr + 1;
#pragma unroll 1
            for (int kv = 0; kv < 2; kv++) {
                uint32_t v[14], t[14];
#pragma unroll
                for (int i = 0; i < 14; i++) v[i] = 0;

                if (blk > 0) {
                    const uint8_t* src = sc->halo + (size_t)(((mt - 1) * 4 + ns) * 2 + kv) * (2 * HSLOT) + lane * 16;
                    pause_until(t_start, HALO_DELAY + kv * 3200);
#pragma unroll 1
                    for (int n = 0; n < SPIN_LIMIT; n++) {
                        bool ok = true;
#pragma unroll
                        for (int i = 0; i < 7; i++) ld_tagged(src + i * 512, v[2 * i], t[2 * i], v[2 * i + 1], t[2 * i + 1]);
#pragma unroll
                        for (int i = 0; i < 14; i++) ok = ok && t[i] == tag;
                        if (__all_sync(0xffffffffu, ok)) break;
                    }
                }
#pragma unroll
                for (int i = 0; i < 14; i++) sts1(base + HALO + kv * (8 * HSLOT) + i * 128 + lane * 4, v[i]);
                warp_arrive(base + BAR_HALO + kv * 8);
                if (lane == 0) PROF(142 + kv);
            }
            if (elect()) {
                mbar_wait(base + BAR_RDY, 0);
                PROF(130);
                signal(sc, CNT_O + mt);
                PROF(131);
                *epoch_ptr = tag;
            }
        }
    } else {
        asm volatile("setmaxnreg.inc.sync.aligned.u32 224;");
        Ring r;
        r.wg = warp >> 2;
        r.zero = blockIdx.y;
        const int wg = warp >> 2;
        uint8_t* part = sc->part + (size_t)(ns * 16 + mt) * (2 * BLOB) + warp * 512 + lane * 16;
        uint32_t p[28];

        if (roleH) {
            unsigned* epoch_ptr = &sc->epoch[bid * 4 * 8];
            const unsigned tag = *epoch_ptr + 1;
            uint8_t* hout = sc->halo + (size_t)((warp * 8 + ns) * 2) * (2 * HSLOT) + lane * 16;
            float x0[56], x1[56];
            r.seek(0, 0);
            r.run<XWN, 7, true>(x0);
#pragma unroll 1
            for (int i = 1; i < 7; i++) r.run<XWN, 7, false>(x0);
            r.run<XWN, 7, true>(x1);
            acc_fence(x0);
            pack_all(x0, p);
#pragma unroll
            for (int i = 0; i < 14; i++) st_tagged(hout + (i & 1) * (16 * HSLOT) + (i >> 1) * 512, p[(i >> 1) * 4 + (i & 1)], p[(i >> 1) * 4 + (i & 1) + 2], tag);
#pragma unroll 1
            for (int i = 1; i < 7; i++) r.run<XWN, 7, false>(x1);
            asm volatile("wgmma.wait_group.sync.aligned 0;" ::: "memory");
            acc_fence(x1);
            pack_all(x1, p);
#pragma unroll
            for (int i = 0; i < 28; i++) p[i] = movm(p[i]);
#pragma unroll
            for (int i = 0; i < 14; i++)
                st_tagged(hout + 2 * HSLOT + (i & 1) * (16 * HSLOT) + (i >> 1) * 512, p[(i >> 1) * 4 + (i & 1)], p[(i >> 1) * 4 + (i & 1) + 2], tag);
            if (threadIdx.x == 0) *epoch_ptr = tag;
        } else if (!roleL) {
            uint8_t* blob = sc->ab + (size_t)((wg * 16 + mt) * 4 + ns) * BLOB + (warp & 3) * WSLOT + lane * 4;
            const uint32_t own = base + BRING + wg * SLOT + (warp & 3) * WSLOT + lane * 16;
            float x0[56], x1[56];
            r.seek(0, bslot_e(0));
            r.run<XW, 7, true>(x0);
            r.run<XW, 7, false>(x0);
            r.seek(2, bslot_e(2));
#pragma unroll 1
            for (int i = 2; i < 7; i++) r.run<XW, 5, false>(x0);

            r.seek(7, bslot_e(7));
            r.run<XW, 5, true, -1>(x1);
            acc_fence(x0);
            pack_all(x0, p);
            store_frags<0, 9>(blob, p);
            r.run<XW, 5, false, -1>(x1);
            store_frags<9, 18>(blob, p);
            r.run<XW, 5, false, -1>(x1);
            store_frags<18, 28>(blob, p);
            warp_arrive(base + BAR_RDY);
            r.run<XW, 5, false, -1>(x1);
            stage_frags<0, 8>(own + 5 * SLOT, p);
            r.run<XW, 5, false, -1>(x1);
            stage_frags<8, 20>(own + 5 * SLOT, p);
            r.run<XW, 5, false, -1>(x1);
            stage_frags<20, 28>(own + 5 * SLOT, p);
            warp_arrive(base + BAR_RDY + 8);
            r.run<XW, 5, false, -1>(x1);

            mbar_wait(base + BAR_RDY + 8, 0);
            fence_async_smem();
            r.seek(14, bslot_e(14));
            r.run<BIG, 7, true>(x0);
            acc_fence(x1);
            pack_all(x1, p);
            wait_released(10);
            stage_frags<0, 28>(own, p);
            warp_arrive(base + BAR_RDY + 16);
            r.run<BIG, 7, false>(x0);
            mbar_wait(base + BAR_RDY + 16, 0);
            fence_async_smem();
            blob += (size_t)128 * BLOB;
#pragma unroll
            for (int i = 0; i < 28; i++) {
                if (i % B_SLICE == 0) r.run<BIG, 7, false>(x0);
                stg1(blob + i * 128, p[i]);
            }
            warp_arrive(base + BAR_RDY + 24);
#pragma unroll 1
            for (int i = 17 + 27 / B_SLICE; i < POUT; i++) r.run<BIG, 7, false>(x0);

            const uint32_t tag = lds1(base + TAG);
            r.seek(POUT, bslot_e(POUT));
            r.run<OUT, 7, true>(x1);
            acc_fence(x0);
            pack_all(x0, p);
            st_part(part, p, tag & 1);
#pragma unroll
            for (int i = 0; i < 3; i++) {
                r.run<OUT, 7, false>(x1);
                st_part(part + (2 * i + 1) * 4096, p + 8 * i + 4, tag & 1);
                st_part(part + (2 * i + 2) * 4096, p + 8 * i + 8, tag & 1);
            }
#pragma unroll 1
            for (int i = 4; i < 7; i++) r.run<OUT, 7, false>(x1);

            wait_released(ELAST - 6);
            asm volatile("wgmma.wait_group.sync.aligned 0;" ::: "memory");
            acc_fence(x1);
            pack_all(x1, p);
            const uint32_t slab = base + (wg ? BRING + bslot_e(ELAST - 6) * SLOT : ((ELAST - 6) % NA) * SLOT) + (warp & 3) * WSLOT;
            store_out(p, lane, slab, &maps.m[M_OUTA], par * 896 + col, blk * 128 + warp * 16);
        } else {
            const int g = lane >> 2, tig = lane & 3;
            const uint32_t hin = base + HALO + warp * HSLOT + lane * 4;
            auto publish = [&](const uint32_t (&h)[14], int kv) {
                if (warp < 7) {
#pragma unroll
                    for (int c = 0; c < 14; c++) sts1(hin + HSLOT + c * 128, h[c]);
                    warp_arrive(base + BAR_HALO + kv * 8);
                }
            };
            float y0[56], y1[56], y2[56];
            r.seek(0, 0);
            r.run<QK, 6, true>(y0, y1);
#pragma unroll 1
            for (int i = 1; i < 14; i++) r.run<QK, 6, false>(y0, y1);

            uint32_t m1[8][4], m0[8][4], lo[14], hi[14];
            r.seek(14, bslot_l(14));
            r.run<XWN, 6, true>(y2);
            acc_fence(y0);
            acc_fence(y1);
#pragma unroll
            for (int c = 0; c < 14; c++) hi[c] = pack2(y1[4 * c + 2], y1[4 * c + 3]);
            publish(hi, 0);
            r.run<XWN, 6, false>(y2);
            r.pin();
#pragma unroll
            for (int c = 0; c < 14; c++) lo[c] = pack2(y1[4 * c], y1[4 * c + 1]);
#pragma unroll
            for (int t = 0; t < 8; t++) {
                const int c = tile_of(t);
                const bool shared = (t & 3) == 2;
                m1[t][0] = shared ? dup(lo[c], r.zero) : lo[c];
                m1[t][1] = shared ? dup(hi[c], r.zero) : hi[c];
                m1[t][2] = lo[c + 1];
                m1[t][3] = hi[c + 1];
                m0[t][0] = dup(m1[t][0], r.zero);
                m0[t][2] = dup(lo[c + 1], 2 * r.zero);
            }
            r.run<XWN, 6, false>(y2);
            r.pin();
            uint32_t q[2][8][2];
#pragma unroll
            for (int b = 0; b < 2; b++) {
                uint32_t v[14];
#pragma unroll
                for (int c = 0; c < 14; c++) v[c] = pack2(y0[4 * c + 2 * b], y0[4 * c + 2 * b + 1]);
#pragma unroll
                for (int t = 0; t < 8; t++) {
                    const int c = tile_of(t);
                    q[b][t][0] = (t & 3) == 2 ? (tig >= 2 ? v[c] : 0u) : v[c];
                    q[b][t][1] = (t & 3) == 1 ? (tig < 2 ? v[c + 1] : 0u) : v[c + 1];
                }
            }
            r.run<XWN, 6, false>(y2);
            mbar_wait(base + BAR_HALO, 0);
#pragma unroll
            for (int t = 0; t < 8; t++) {
                m0[t][1] = lds1(hin + tile_of(t) * 128 + ((t & 3) == 2 ? r.zero : 0u));
                m0[t][3] = lds1(hin + tile_of(t) * 128 + 128);
            }
            r.wait();
            float s[8][4];
#pragma unroll
            for (int step = 0; step < 2; step++) {
#pragma unroll
                for (int i = 0; i < 8; i++) {
                    const int b = 1 - (i >> 2), h = i & 3, t = 2 * h + step;
                    float (&d)[4] = s[2 * h + b];
                    if (step == 0) d[0] = d[1] = d[2] = d[3] = 0.f;
                    mma16816(d, b ? m1[t] : m0[t], q[b][t][0], q[b][t][1]);
                }
            }
            r.pin();
            r.run<XWN, 6, false, 1, false>(y2);
            r.pin();

            uint32_t pr[8], mx[4], mx1[4];
            {
                const bool cur0 = g <= 2 * tig, cur1 = g <= 2 * tig + 1;
#pragma unroll
                for (int i = 0; i < 8; i++) {
                    const int c = (i & 1) ? 2 : 0;
                    pr[i] = movm(pack2(cur0 ? s[i][c] : s[i][2 - c], cur1 ? s[i][c + 1] : s[i][3 - c]));
                }
            }
            r.run<XWN, 6, false>(y2);
            r.pin();
            const uint32_t curmask = (2 * tig <= g ? 0x0000FFFFu : 0u) | (2 * tig + 1 <= g ? 0xFFFF0000u : 0u);
#pragma unroll
            for (int i = 0; i < 8; i++) pr[i] = pack2(bf_lo(pr[i]) * 0.18898223650461362f, bf_hi(pr[i]) * 0.18898223650461362f);
            r.run<XWN, 6, false>(y2);
            r.pin();
            {
                const uint32_t keep = (blk == 0 && warp == 0) ? curmask : 0xFFFFFFFFu;
#pragma unroll
                for (int i = 0; i < 4; i++) {
                    pr[2 * i] = (pr[2 * i] & keep) | (0xCE6ECE6Eu & ~keep);
                    mx[i] = max2(__byte_perm(pr[2 * i], pr[2 * i + 1], 0x5410), __byte_perm(pr[2 * i], pr[2 * i + 1], 0x7632));
                }
#pragma unroll
                for (int i = 0; i < 4; i++) mx[i] = max2(mx[i], __shfl_xor_sync(0xffffffffu, mx[i], 1));
#pragma unroll
                for (int i = 0; i < 4; i++) mx1[i] = __shfl_xor_sync(0xffffffffu, mx[i], 2);
            }

            r.seek(21, bslot_l(21));
            r.run<BIG, 6, true>(y0);
            acc_fence(y2);
#pragma unroll
            for (int c = 0; c < 14; c++) hi[c] = movm(pack2(y2[4 * c + 2], y2[4 * c + 3]));
            r.run<BIG, 6, false>(y0);
            wait_released(18);
            publish(hi, 1);
            float e0[8], e1[8], sm[8], sm1[8];
#pragma unroll
            for (int i = 0; i < 8; i++) {
                const uint32_t m2 = max2(mx[i >> 1], mx1[i >> 1]);
                sm[i] = fmul(((i & 1) ? bf_hi(m2) : bf_lo(m2)), -1.4426950408889634f);
            }
            r.run<BIG, 6, false>(y0);
            r.pin();
#pragma unroll
            for (int c = 0; c < 14; c++) lo[c] = movm(pack2(y2[4 * c], y2[4 * c + 1]));
            r.run<BIG, 6, false>(y0);
            r.pin();
#pragma unroll
            for (int i = 0; i < 8; i++) {
                e0[i] = ex2(fmaf(bf_lo(pr[i]), 1.4426950408889634f, sm[i]));
                e1[i] = ex2(fmaf(bf_hi(pr[i]), 1.4426950408889634f, sm[i]));
            }
            r.run<BIG, 6, false>(y0);
            r.pin();
#pragma unroll
            for (int i = 0; i < 8; i++) {
                sm[i] = e0[i] + e1[i];
                sm1[i] = __shfl_xor_sync(0xffffffffu, sm[i], 1);
            }
#pragma unroll
            for (int t = 0; t < 8; t++) {
                const int c = tile_of(t);
                const bool shared = (t & 3) == 2;
                m1[t][0] = shared ? dup(lo[c], r.zero) : lo[c];
                m1[t][1] = lo[c + 1];
                m1[t][2] = shared ? dup(hi[c], r.zero) : hi[c];
                m1[t][3] = hi[c + 1];
                m0[t][0] = dup(m1[t][0], r.zero);
                m0[t][1] = dup(lo[c + 1], 2 * r.zero);
            }
            r.run<BIG, 6, false>(y0);
            r.pin();
#pragma unroll
            for (int i = 0; i < 8; i++) sm[i] += sm1[i];
#pragma unroll
            for (int i = 0; i < 8; i++) {
                const float inv = rcp(sm[i] + __shfl_xor_sync(0xffffffffu, sm[i], 2));
                pr[i] = pack2(e0[i] * inv, e1[i] * inv);
            }
            r.run<BIG, 6, false>(y0);
            mbar_wait(base + BAR_HALO + 8, 0);
            const uint32_t vin = warp ? hin : hin + 8 * HSLOT;
#pragma unroll
            for (int t = 0; t < 8; t++) {
                m0[t][2] = lds1(vin + tile_of(t) * 128 + ((t & 3) == 2 ? r.zero : 0u));
                m0[t][3] = lds1(vin + tile_of(t) * 128 + 128);
            }
            uint32_t pb[8][2];
#pragma unroll
            for (int i = 0; i < 8; i++) {
                pb[i][i & 1] = band(pr[i], curmask);
                pb[i][1 - (i & 1)] = band(pr[i], ~curmask);
            }
            r.wait();
            float o[2][8][4];
#pragma unroll
            for (int i = 0; i < 16; i++) {
                const int b = 1 - (i >> 3), t = i & 7;
                float (&d)[4] = o[b][t];
                d[0] = d[1] = d[2] = d[3] = 0.f;
                mma16816(d, b ? m1[t] : m0[t], pb[(t & 6) + b][0], pb[(t & 6) + b][1]);
            }
            r.pin();
            r.run<BIG, 6, false, 1, false>(y0);
            r.pin();
            uint8_t* odst = sc->o + (size_t)mt * 7 * SLOT + ns * (14 * 2048) + warp * 256 + lane * 4;
#pragma unroll
            for (int hp = 0; hp < 2; hp++) {
#pragma unroll
                for (int b = 0; b < 2; b++) {
                    const float (&u)[8][4] = o[b];
                    const int t = 4 * hp;
                    uint32_t* w = p + 14 * hp + b;
                    w[0] = pack2(u[t][0], u[t][1]);
                    w[2] = pack2(u[t][2], u[t][3]);
                    w[4] = pack2(u[t + 1][0], u[t + 1][1]);
                    w[6] = pack2(g < 4 ? u[t + 1][2] : u[t + 2][0], g < 4 ? u[t + 1][3] : u[t + 2][1]);
                    w[8] = pack2(u[t + 2][2], u[t + 2][3]);
                    w[10] = pack2(u[t + 3][0], u[t + 3][1]);
                    w[12] = pack2(u[t + 3][2], u[t + 3][3]);
                }
            }
#pragma unroll
            for (int i = 0; i < 28; i++) {
                if (i && i % O_SLICE == 0) r.run<BIG, 6, false>(y0);
                stg1(odst + (i >> 1) * 2048 + (i & 1) * 128, p[i]);
            }
            warp_arrive(base + BAR_RDY);

#pragma unroll 1
            for (int i = 29 + 27 / O_SLICE; i < LLAST; i++) r.run<BIG, 6, false>(y0);
#pragma unroll
            for (int i = 0; i < 7; i++) ld_tagged(part + i * 4096, p[4 * i], p[4 * i + 1], p[4 * i + 2], p[4 * i + 3]);
            const uint32_t tag = lds1(base + TAG);
            r.seek(LLAST, bslot_l(LLAST));
            r.run<BIG, 6, false>(y0);
            wait_released(LLAST - 6);
#pragma unroll 1
            for (int n = 0; n < SPIN_LIMIT; n++) {
                uint32_t stale = 0;
#pragma unroll
                for (int i = 0; i < 28; i += 2) stale |= p[i] ^ tag;
                if (__all_sync(0xffffffffu, !(stale & 1))) break;
#pragma unroll
                for (int i = 0; i < 7; i++) ld_tagged(part + i * 4096, p[4 * i], p[4 * i + 1], p[4 * i + 2], p[4 * i + 3]);
            }
            asm volatile("wgmma.wait_group.sync.aligned 0;" ::: "memory");
            acc_fence(y0);
#pragma unroll
            for (int i = 0; i < 28; i++) p[i] = pack2(y0[2 * i] + bf_lo(p[i]), y0[2 * i + 1] + bf_hi(p[i]));
            const uint32_t slab = base + (wg ? HALO : ((LLAST - 6) % NA) * SLOT) + (warp & 3) * WSLOT;
            store_out(p, lane, slab, &maps.m[M_OUTB], 448 + col, mt * 128 + warp * 16);
        }
    }
}

typedef CUresult (*EncodeFn)(CUtensorMap*, CUtensorMapDataType, cuuint32_t, void*, const cuuint64_t*, const cuuint64_t*,
                             const cuuint32_t*, const cuuint32_t*, CUtensorMapInterleave, CUtensorMapSwizzle,
                             CUtensorMapL2promotion, CUtensorMapFloatOOBfill);

struct Dim { uint64_t size, stride; uint32_t box; };
void encode(EncodeFn fn, CUtensorMap* m, const void* ptr, CUtensorMapSwizzle sw, Dim d0, Dim d1, Dim d2 = {0, 0, 0}, Dim d3 = {0, 0, 0}) {
    const cuuint64_t dims[4] = {d0.size, d1.size, d2.size, d3.size};
    const cuuint64_t strides[3] = {d1.stride, d2.stride, d3.stride};
    const cuuint32_t box[4] = {d0.box, d1.box, d2.box, d3.box};
    const cuuint32_t es[4] = {1, 1, 1, 1};
    fn(m, CU_TENSOR_MAP_DATA_TYPE_BFLOAT16, d3.size ? 4 : d2.size ? 3 : 2, const_cast<void*>(ptr), dims, strides, box, es,
       CU_TENSOR_MAP_INTERLEAVE_NONE, sw, CU_TENSOR_MAP_L2_PROMOTION_L2_128B, CU_TENSOR_MAP_FLOAT_OOB_FILL_NONE);
}

}

extern "C" void kernel_launch(void* const* d_in, const int* in_sizes, int n_in, void* d_out, int out_size) {
    (void)in_sizes; (void)n_in; (void)out_size;
    void* fnp = nullptr;
    cudaDriverEntryPointQueryResult st;
    cudaGetDriverEntryPoint("cuTensorMapEncodeTiled", &fnp, cudaEnableDefault, &st);
    EncodeFn fn = (EncodeFn)fnp;
    void* scratch = nullptr;
    cudaGetSymbolAddress(&scratch, g_scratch);
    cudaFuncSetAttribute(fused_kernel, cudaFuncAttributeMaxDynamicSharedMemorySize, SMEM_BYTES);

    const CUtensorMapSwizzle S128 = CU_TENSOR_MAP_SWIZZLE_128B, S0 = CU_TENSOR_MAP_SWIZZLE_NONE;
    Maps maps;
    encode(fn, &maps.m[M_XA], d_in[0], S128, {896, 2, 64}, {1024, 1792, 128});
    encode(fn, &maps.m[M_WQK], d_in[1], S128, {112, 2, 64}, {448, 2688, 32}, {3, 896, 2}, {4, 224, 1});
    encode(fn, &maps.m[M_WV], d_in[1], S128, {112, 2, 64}, {448, 2688, 64}, {12, 224, 1});
    encode(fn, &maps.m[M_XH], d_in[0], S128, {448, 2, 64}, {128, 1792, 8}, {8, 128 * 1792, 8}, {2, 896, 2});
    encode(fn, &maps.m[M_WO], d_in[2], S128, {112, 2, 64}, {448, 896, 64}, {4, 224, 1});
    encode(fn, &maps.m[M_XB], d_in[3], S128, {448, 2, 64}, {1024, 896, 64}, {2, 896 * 1024, 2});
    encode(fn, &maps.m[M_CR], d_in[4], S128, {2048, 2, 64}, {2048, 4096, 128});
    encode(fn, &maps.m[M_CI], d_in[5], S128, {2048, 2, 64}, {2048, 4096, 128});
    encode(fn, &maps.m[M_WR], d_in[6], S128, {448, 2, 64}, {448, 896, 112});
    encode(fn, &maps.m[M_WI], d_in[7], S128, {448, 2, 64}, {448, 896, 112});
    encode(fn, &maps.m[M_OUTA], d_out, S0, {1792, 2, 112}, {1024, 3584, 16});
    encode(fn, &maps.m[M_OUTB], d_out, S0, {896, 2, 112}, {2048, 1792, 16});

    fused_kernel<<<132, 384, SMEM_BYTES>>>((Scratch*)scratch, maps);
}
```

```cpp
#include <cuda.h>
#include <cuda_bf16.h>
#include <cuda_runtime.h>
#include <stdint.h>

namespace {

constexpr uint32_t SLOT = 16384;
constexpr int NA = 7;
constexpr uint32_t BRING = NA * SLOT;
constexpr uint32_t HALO = BRING + 6 * SLOT;
constexpr uint32_t HSLOT = 1792;
constexpr uint32_t WSLOT = 3584;
constexpr uint32_t BLOB = 14336;
constexpr uint32_t BARS = 14 * SLOT;
constexpr uint32_t BAR_FULL = BARS;
constexpr uint32_t BAR_EMPTY = BARS + 64;
constexpr uint32_t BAR_RDY = BARS + 128;
constexpr uint32_t BAR_DEP = BARS + 160;
constexpr uint32_t BAR_HALO = BARS + 192;
constexpr uint32_t TAG = BARS + 208;
constexpr uint32_t SMEM_BYTES = BARS + 256 + 1024;
constexpr uint32_t base = 1024;
constexpr int SPIN_LIMIT = 1 << 16;

#define E_EXTRA 0
#define HALO_DELAY 7000
#define O_SLICE 5
#define B_SLICE 5
#define LEAD 3
#define PINGPONG 1
#define MAPPING 2
#define SPARE0 12
constexpr int NBE = 13 + E_EXTRA;
constexpr int POUT = 33 + NBE;
constexpr int ELAST = POUT + 6;
constexpr int LLAST = 52 - E_EXTRA;

enum { M_XA, M_XH, M_WQK, M_WV, M_WO, M_XB, M_WR, M_WI, M_CR, M_CI, M_OUTA, M_OUTB, M_COUNT };
struct __align__(64) Maps { CUtensorMap m[M_COUNT]; };

constexpr int CNT_A = 0;
constexpr int CNT_B = 4;
constexpr int CNT_O = 16;
constexpr int CNT_COUNT = 32;

struct Scratch {
    uint8_t ab[64 * 4 * BLOB];
    uint8_t o[16 * 7 * SLOT];
    uint8_t part[64 * 2 * BLOB];
    uint8_t halo[64 * 2 * 2 * HSLOT];
    unsigned cnt[CNT_COUNT * 32];
    unsigned epoch[132 * 4 * 8];
};
__device__ __align__(1024) Scratch g_scratch;

__device__ __forceinline__ unsigned clk32() { unsigned c; asm volatile("mov.u32 %0, %%clock;" : "=r"(c)); return c; }
__device__ __forceinline__ void pause_until(unsigned t0, unsigned cycles) {
    while (clk32() - t0 < cycles) {}
}

#define PROF(idx)

__device__ __forceinline__ void mbar_init(uint32_t bar, uint32_t cnt) {
    asm volatile("mbarrier.init.shared::cta.b64 [%0], %1;" ::"r"(bar), "r"(cnt) : "memory");
}
__device__ __forceinline__ void mbar_expect(uint32_t bar, uint32_t bytes) {
    asm volatile("mbarrier.arrive.expect_tx.shared::cta.b64 _, [%0], %1;" ::"r"(bar), "r"(bytes) : "memory");
}
__device__ __forceinline__ void mbar_arrive(uint32_t bar) {
    asm volatile("mbarrier.arrive.shared::cta.b64 _, [%0];" ::"r"(bar) : "memory");
}
__device__ __forceinline__ bool mbar_try(uint32_t bar, uint32_t parity) {
    uint32_t ok;
    asm volatile("{\n.reg .pred p;\nmbarrier.try_wait.parity.shared::cta.b64 p, [%1], %2;\nselp.u32 %0, 1, 0, p;\n}\n"
                 : "=r"(ok) : "r"(bar), "r"(parity) : "memory");
    return ok;
}
__device__ __forceinline__ void mbar_wait(uint32_t bar, uint32_t parity) {
#pragma unroll 1
    for (int n = 0; n < SPIN_LIMIT; n++)
        if (mbar_try(bar, parity)) break;
}
__device__ __forceinline__ bool elect() {
    uint32_t p;
    asm volatile("{\n.reg .pred p;\nelect.sync _|p, 0xffffffff;\nselp.u32 %0, 1, 0, p;\n}\n" : "=r"(p));
    return p;
}
__device__ __forceinline__ void nb_sync(int id, int n) { asm volatile("bar.sync %0, %1;" ::"r"(id), "r"(n) : "memory"); }
__device__ __forceinline__ void nb_arrive(int id, int n) { asm volatile("bar.arrive %0, %1;" ::"r"(id), "r"(n) : "memory"); }
__device__ __forceinline__ void warp_arrive(uint32_t bar) {
    __syncwarp();
    if (elect()) mbar_arrive(bar);
}
__device__ __forceinline__ uint32_t band(uint32_t x, uint32_t m) {
    uint32_t r;
    asm volatile("and.b32 %0, %1, %2;" : "=r"(r) : "r"(x), "r"(m));
    return r;
}
__device__ __forceinline__ float fmul(float x, float y) {
    float r;
    asm volatile("mul.f32 %0, %1, %2;" : "=f"(r) : "f"(x), "f"(y));
    return r;
}
__device__ __forceinline__ uint32_t dup(uint32_t x, uint32_t zero) {
    uint32_t r;
    asm volatile("xor.b32 %0, %1, %2;" : "=r"(r) : "r"(x), "r"(zero));
    return r;
}

__device__ __forceinline__ void tma_ld2(uint32_t dst, const CUtensorMap* m, int c0, int c1, uint32_t bar) {
    asm volatile("cp.async.bulk.tensor.2d.shared::cluster.global.mbarrier::complete_tx::bytes [%0], [%1, {%3, %4}], [%2];"
                 ::"r"(dst), "l"(m), "r"(bar), "r"(c0), "r"(c1) : "memory");
}
__device__ __forceinline__ void tma_ld3(uint32_t dst, const CUtensorMap* m, int c0, int c1, int c2, uint32_t bar) {
    asm volatile("cp.async.bulk.tensor.3d.shared::cluster.global.mbarrier::complete_tx::bytes [%0], [%1, {%3, %4, %5}], [%2];"
                 ::"r"(dst), "l"(m), "r"(bar), "r"(c0), "r"(c1), "r"(c2) : "memory");
}
__device__ __forceinline__ void tma_ld4(uint32_t dst, const CUtensorMap* m, int c0, int c1, int c2, int c3, uint32_t bar) {
    asm volatile("cp.async.bulk.tensor.4d.shared::cluster.global.mbarrier::complete_tx::bytes [%0], [%1, {%3, %4, %5, %6}], [%2];"
                 ::"r"(dst), "l"(m), "r"(bar), "r"(c0), "r"(c1), "r"(c2), "r"(c3) : "memory");
}
__device__ __forceinline__ void bulk_ld(uint32_t dst, const void* src, uint32_t bytes, uint32_t bar) {
    asm volatile("cp.async.bulk.shared::cluster.global.mbarrier::complete_tx::bytes [%0], [%1], %2, [%3];"
                 ::"r"(dst), "l"(src), "r"(bytes), "r"(bar) : "memory");
}
__device__ __forceinline__ void tma_st2(const CUtensorMap* m, int c0, int c1, uint32_t src) {
    asm volatile("cp.async.bulk.tensor.2d.global.shared::cta.bulk_group [%0, {%1, %2}], [%3];"
                 ::"l"(m), "r"(c0), "r"(c1), "r"(src) : "memory");
}
__device__ __forceinline__ void bulk_commit() { asm volatile("cp.async.bulk.commit_group;" ::: "memory"); }
__device__ __forceinline__ void bulk_wait_read() { asm volatile("cp.async.bulk.wait_group.read 0;" ::: "memory"); }
__device__ __forceinline__ void fence_async_smem() { asm volatile("fence.proxy.async.shared::cta;" ::: "memory"); }
__device__ __forceinline__ void fence_async_global() { asm volatile("fence.proxy.async.global;" ::: "memory"); }

__device__ __forceinline__ void signal(Scratch* sc, int idx) {
    asm volatile("fence.proxy.async;\nred.relaxed.gpu.global.add.u32 [%0], 1;" ::"l"(&sc->cnt[idx * 32]) : "memory");
}
__device__ __forceinline__ void await(Scratch* sc, int idx, unsigned target) {
#pragma unroll 1
    for (int n = 0; n < SPIN_LIMIT; n++) {
        unsigned v;
        asm volatile("ld.relaxed.gpu.global.u32 %0, [%1];" : "=r"(v) : "l"(&sc->cnt[idx * 32]) : "memory");
        if ((int)(v - target) >= 0) break;
    }
    asm volatile("fence.acquire.gpu;" ::: "memory");
}
__device__ __forceinline__ void wait_dep(int k) {
    mbar_wait(base + BAR_DEP + k * 8, 0);
    fence_async_global();
}

#define WG_REGS                                                                                                     \
    "{%0,%1,%2,%3,%4,%5,%6,%7,%8,%9,%10,%11,%12,%13,%14,%15,%16,%17,%18,%19,%20,%21,%22,%23,%24,%25,%26,%27,"       \
    "%28,%29,%30,%31,%32,%33,%34,%35,%36,%37,%38,%39,%40,%41,%42,%43,%44,%45,%46,%47,%48,%49,%50,%51,%52,%53,%54,%55}"
#define WG_OPS(C)                                                                                                   \
    C(d[0]), C(d[1]), C(d[2]), C(d[3]), C(d[4]), C(d[5]), C(d[6]), C(d[7]), C(d[8]), C(d[9]), C(d[10]), C(d[11]),   \
    C(d[12]), C(d[13]), C(d[14]), C(d[15]), C(d[16]), C(d[17]), C(d[18]), C(d[19]), C(d[20]), C(d[21]), C(d[22]),   \
    C(d[23]), C(d[24]), C(d[25]), C(d[26]), C(d[27]), C(d[28]), C(d[29]), C(d[30]), C(d[31]), C(d[32]), C(d[33]),   \
    C(d[34]), C(d[35]), C(d[36]), C(d[37]), C(d[38]), C(d[39]), C(d[40]), C(d[41]), C(d[42]), C(d[43]), C(d[44]),   \
    C(d[45]), C(d[46]), C(d[47]), C(d[48]), C(d[49]), C(d[50]), C(d[51]), C(d[52]), C(d[53]), C(d[54]), C(d[55])

template <int TA, int TB, int SB, bool INIT>
__device__ __forceinline__ void wgmma112(float (&d)[56], uint64_t da, uint64_t db) {
    if (INIT) {
        asm volatile("{\n.reg .pred p;\nsetp.ne.b32 p, 0, 0;\n"
                     "wgmma.mma_async.sync.aligned.m64n112k16.f32.bf16.bf16 " WG_REGS ", %56, %57, p, 1, %59, %60, %58;\n}\n"
                     : WG_OPS("=f") : "l"(da), "l"(db), "n"(TB), "n"(SB), "n"(TA));
    } else {
        asm volatile("{\n.reg .pred p;\nsetp.ne.b32 p, 1, 0;\n"
                     "wgmma.mma_async.sync.aligned.m64n112k16.f32.bf16.bf16 " WG_REGS ", %56, %57, p, 1, %59, %60, %58;\n}\n"
                     : WG_OPS("+f") : "l"(da), "l"(db), "n"(TB), "n"(SB), "n"(TA));
    }
}
__device__ __forceinline__ void acc_fence(float (&d)[56]) {
#pragma unroll
    for (int i = 0; i < 56; i++) asm volatile("" : "+f"(d[i])::"memory");
}

__device__ __forceinline__ uint32_t pack2(float lo, float hi) {
    uint32_t r;
    asm volatile("cvt.rn.bf16x2.f32 %0, %1, %2;" : "=r"(r) : "f"(hi), "f"(lo));
    return r;
}
__device__ __forceinline__ uint32_t movm(uint32_t a) {
    uint32_t r;
    asm volatile("movmatrix.sync.aligned.m8n8.trans.b16 %0, %1;" : "=r"(r) : "r"(a));
    return r;
}
__device__ __forceinline__ void stsm4(uint32_t addr, uint32_t a, uint32_t b, uint32_t c, uint32_t d) {
    asm volatile("stmatrix.sync.aligned.m8n8.x4.shared.b16 [%0], {%1,%2,%3,%4};" ::"r"(addr), "r"(a), "r"(b), "r"(c), "r"(d) : "memory");
}
__device__ __forceinline__ void sts1(uint32_t addr, uint32_t a) { asm volatile("st.shared.b32 [%0], %1;" ::"r"(addr), "r"(a) : "memory"); }
__device__ __forceinline__ uint32_t lds1(uint32_t addr) {
    uint32_t a;
    asm volatile("ld.shared.b32 %0, [%1];" : "=r"(a) : "r"(addr) : "memory");
    return a;
}
__device__ __forceinline__ void stg1(uint8_t* p, uint32_t a) { asm volatile("st.global.b32 [%0], %1;" ::"l"(p), "r"(a) : "memory"); }
__device__ __forceinline__ void st_part(uint8_t* p, const uint32_t* v, uint32_t parity) {
    asm volatile("{\n.reg .b64 x, y;\nmov.b64 x, {%1, %2};\nmov.b64 y, {%3, %4};\nst.relaxed.gpu.global.v2.b64 [%0], {x, y};\n}\n"
                 ::"l"(p), "r"((v[0] & ~1u) | parity), "r"(v[1]), "r"((v[2] & ~1u) | parity), "r"(v[3]) : "memory");
}
__device__ __forceinline__ void mma16816(float (&d)[4], const uint32_t (&a)[4], uint32_t b0, uint32_t b1) {
    asm volatile("mma.sync.aligned.m16n8k16.row.col.f32.bf16.bf16.f32 {%0,%1,%2,%3}, {%4,%5,%6,%7}, {%8,%9}, {%0,%1,%2,%3};"
                 : "+f"(d[0]), "+f"(d[1]), "+f"(d[2]), "+f"(d[3]) : "r"(a[0]), "r"(a[1]), "r"(a[2]), "r"(a[3]), "r"(b0), "r"(b1));
}
__device__ __forceinline__ uint32_t max2(uint32_t a, uint32_t b) {
    uint32_t r;
    asm("max.bf16x2 %0, %1, %2;" : "=r"(r) : "r"(a), "r"(b));
    return r;
}
__device__ __forceinline__ void st_tagged(uint8_t* p, uint32_t a, uint32_t b, uint32_t tag) {
    asm volatile("{\n.reg .b64 x, y;\nmov.b64 x, {%1, %3};\nmov.b64 y, {%2, %3};\nst.relaxed.gpu.global.v2.b64 [%0], {x, y};\n}\n"
                 ::"l"(p), "r"(a), "r"(b), "r"(tag) : "memory");
}
__device__ __forceinline__ void ld_tagged(const uint8_t* p, uint32_t& a, uint32_t& ta, uint32_t& b, uint32_t& tb) {
    asm volatile("{\n.reg .b64 x, y;\nld.relaxed.gpu.global.v2.b64 {x, y}, [%4];\nmov.b64 {%0, %1}, x;\nmov.b64 {%2, %3}, y;\n}\n"
                 : "=r"(a), "=r"(ta), "=r"(b), "=r"(tb) : "l"(p) : "memory");
}
__device__ __forceinline__ float bf_lo(uint32_t v) { return __uint_as_float(v << 16); }
__device__ __forceinline__ float bf_hi(uint32_t v) { return __uint_as_float(v & 0xFFFF0000u); }
__device__ __forceinline__ float rcp(float x) { float r; asm("rcp.approx.ftz.f32 %0, %1;" : "=f"(r) : "f"(x)); return r; }
__device__ __forceinline__ float ex2(float x) { float r; asm volatile("ex2.approx.ftz.f32 %0, %1;" : "=f"(r) : "f"(x)); return r; }

__device__ __forceinline__ uint32_t full_bar(int stage) { return base + BAR_FULL + (stage & 7) * 8; }
__device__ __forceinline__ void wait_released(int j) { mbar_wait(base + BAR_EMPTY + (j & 7) * 8, (j >> 3) & 1); }

template <int V>
struct Int { static constexpr int value = V; };

__host__ __device__ constexpr int bslot_e(int i) { return (i < 2 || i >= 14) ? (i + 5) % 7 : (i + 1) % 5; }
__host__ __device__ constexpr int bslot_l(int i) { return i % 6; }

template <uint32_t OFF>
struct Feed {
    int stage;
    uint32_t dst;
    __device__ __forceinline__ void seek(int i, int slot) { stage = i; dst = base + OFF + slot * SLOT; }
    template <int N>
    __device__ __forceinline__ uint32_t acquire() { wait_released(stage - N); return full_bar(stage); }
    template <int N>
    __device__ __forceinline__ void next() {
        stage++;
        dst += SLOT;
        if (dst == base + OFF + N * SLOT) dst = base + OFF;
    }
};
__device__ __forceinline__ int skip_own(int n, int mt) { return n == mt ? 15 : n; }

__host__ __device__ constexpr uint64_t desc_const(uint32_t lbo, uint32_t sbo, uint32_t mode) {
    return ((uint64_t)((sbo >> 4) | (mode << 30)) << 32) | ((lbo >> 4) << 16);
}
constexpr uint64_t D_K128 = desc_const(16, 1024, 1);
constexpr uint64_t D_N128 = desc_const(8192, 1024, 1);
constexpr uint64_t D_BLOB = desc_const(128, 256, 0);
constexpr uint64_t D_OT = desc_const(2048, 128, 0);

enum Kind { XW, XWN, QK, BIG, OUT };

struct Ring {
    int stage;
    uint32_t a, b;
    uint32_t wg;
    uint32_t zero;
    __device__ __forceinline__ void seek(int i, int bslot) {
        stage = i;
        a = (base + (i % NA) * SLOT) >> 4;
        b = (base + BRING + bslot * SLOT) >> 4;
    }
    __device__ __forceinline__ void wait() {
        mbar_wait(full_bar(stage), (stage >> 3) & 1);
        if (PINGPONG) nb_sync(1 + wg, 256);
    }
    __device__ __forceinline__ void pin() {
        uint32_t n = 0;
#pragma unroll 1
        do {
            asm volatile("pmevent 7;" ::: "memory");
        } while (n++ < zero);
    }
    template <Kind K, int NBS, bool INIT, int SB = 1, bool WAIT = true>
    __device__ __forceinline__ void run(float (&d)[56], float (&e)[56]) {
        if (WAIT) wait();
        asm volatile("wgmma.fence.sync.aligned;" ::: "memory");
        if (K == QK) {
            const uint64_t da = D_K128 + ((base >> 4) + (stage >> 1) * (SLOT >> 4) + (stage & 1) * 4 + wg * 512), db = D_N128 + b;
            wgmma112<0, 1, 1, INIT>(d, da, db);
            wgmma112<0, 1, 1, INIT>(e, da, db + 256);
            wgmma112<0, 1, 1, false>(d, da + 2, db + 128);
            wgmma112<0, 1, 1, false>(e, da + 2, db + 384);
        } else {
            constexpr int TA = K == OUT, TB = K != XW;
            constexpr uint32_t sa = K == OUT ? 256 : 2, sb = K == XW ? 2 : K == BIG ? 224 : 128;
            const uint64_t da = (K == OUT ? D_OT : D_K128) + (a + wg * (K == OUT ? 64 : 512));
            const uint64_t db = (K == XW ? D_K128 : K == BIG ? D_BLOB : D_N128) + b;
            wgmma112<TA, TB, SB, INIT>(d, da, db);
            wgmma112<TA, TB, SB, false>(d, da + sa, db + sb);
            wgmma112<TA, TB, SB, false>(d, da + 2 * sa, db + 2 * sb);
            wgmma112<TA, TB, SB, false>(d, da + 3 * sa, db + 3 * sb);
        }
        asm volatile("wgmma.commit_group.sync.aligned;" ::: "memory");
        if (PINGPONG) nb_arrive(2 - wg, 256);
        asm volatile("wgmma.wait_group.sync.aligned 1;" ::: "memory");
        if (stage > 0 && elect()) mbar_arrive(base + BAR_EMPTY + ((stage - 1) & 7) * 8);
        stage++;
        a += SLOT >> 4;
        if (a == (base + NA * SLOT) >> 4) a = base >> 4;
        b += SLOT >> 4;
        if (b == (base + BRING + NBS * SLOT) >> 4) b = (base + BRING) >> 4;
    }
    template <Kind K, int NBS, bool INIT, int SB = 1, bool WAIT = true>
    __device__ __forceinline__ void run(float (&d)[56]) { run<K, NBS, INIT, SB, WAIT>(d, d); }
};

__device__ __forceinline__ void pack_all(const float (&d)[56], uint32_t (&p)[28]) {
#pragma unroll
    for (int i = 0; i < 28; i++) p[i] = pack2(d[2 * i], d[2 * i + 1]);
}
template <int I0, int I1>
__device__ __forceinline__ void store_frags(uint8_t* dst, const uint32_t (&p)[28]) {
#pragma unroll
    for (int i = I0; i < I1; i++) stg1(dst + i * 128, p[i]);
}
template <int I0, int I1>
__device__ __forceinline__ void stage_frags(uint32_t lane_addr, const uint32_t (&p)[28]) {
#pragma unroll
    for (int i = I0; i < I1; i += 4) stsm4(lane_addr + i * 128, p[i], p[i + 1], p[i + 2], p[i + 3]);
}
__device__ __forceinline__ void store_out(const uint32_t (&p)[28], int lane, uint32_t slab, const CUtensorMap* m, int c0, int c1) {
    const bool swap = lane & 16;
    const uint32_t addr = slab + (lane & 15) * 224 + (((lane >> 4) ^ (lane >> 2)) & 1) * 16;
#pragma unroll
    for (int i = 0; i < 28; i += 4)
        stsm4(addr + i * 8, swap ? p[i + 2] : p[i], swap ? p[i + 3] : p[i + 1], swap ? p[i] : p[i + 2], swap ? p[i + 1] : p[i + 3]);
    fence_async_smem();
    __syncwarp();
    if (elect()) {
        tma_st2(m, c0, c1, slab);
        bulk_commit();
        bulk_wait_read();
    }
}
__host__ __device__ constexpr int tile_of(int t) { return 7 * (t >> 2) + 3 * ((t >> 1) & 1) + 2 * (t & 1); }

__global__ void __launch_bounds__(384, 1) fused_kernel(Scratch* sc, const __grid_constant__ Maps maps) {
    extern __shared__ uint8_t smem_raw[];
    if ((uint32_t)__cvta_generic_to_shared(smem_raw) != base) return;
    const int warp = __shfl_sync(0xffffffffu, threadIdx.x >> 5, 0);
    int lane = threadIdx.x & 31;
    asm volatile("" : "+r"(lane));
    const int bid = blockIdx.x < 2 * SPARE0 || blockIdx.x >= 130 ? blockIdx.x
                    : (blockIdx.x >> 1) == SPARE0                ? 128 + (blockIdx.x & 1)
                                                                 : blockIdx.x - 2;
    const bool roleH = bid >= 128;
    const int roleL = (bid >> 4) & 1;
    const int mt = ((bid >> 5) << 2) | ((bid >> 2) & 3);
    const int ns = bid & 3;
    const int par = mt >> 3, blk = mt & 7;

    const int col = ns * 112;
    auto fill = [&](auto i0, auto i1) {
        if (roleL) {
#pragma unroll
            for (int i = decltype(i0)::value; i < decltype(i1)::value; i++) {
                const uint32_t bar = full_bar(i), dst = base + BRING + i * SLOT;
                if (i < 6) mbar_expect(bar, SLOT);
                if (i & 1) {
                    mbar_arrive(bar);
                } else {
                    mbar_expect(bar, SLOT);
                    tma_ld2(base + (i >> 1) * SLOT, &maps.m[M_XA], par * 448 + i * 32, blk * 128, bar);
                }
                if (i < 6) {
                    tma_ld4(dst, &maps.m[M_WQK], 0, i * 32, 0, ns, bar);
                    tma_ld4(dst + 8192, &maps.m[M_WQK], 64, i * 32, 0, ns, bar);
                }
            }
        } else if (!roleH) {
#pragma unroll
            for (int i = decltype(i0)::value; i < decltype(i1)::value; i++) {
                const uint32_t bar = full_bar(i);
                mbar_expect(bar, SLOT);
                mbar_expect(bar, BLOB);
                tma_ld3(base + i * SLOT, &maps.m[M_XB], i * 64, mt * 64, 0, bar);
                tma_ld2(base + BRING + bslot_e(i) * SLOT, &maps.m[M_WR], i * 64, col, bar);
            }
        } else {
#pragma unroll 1
            for (int i = decltype(i0)::value; i < decltype(i1)::value; i++) {
                const uint32_t bar = full_bar(i), dst = base + BRING + i * SLOT;
                mbar_expect(bar, SLOT);
                mbar_expect(bar, SLOT);
                tma_ld4(base + i * SLOT, &maps.m[M_XH], i * 64, 120, 0, 0, bar);
                tma_ld3(dst, &maps.m[M_WV], 0, i * 64, 4 + ns, bar);
                tma_ld3(dst + 8192, &maps.m[M_WV], 64, i * 64, 4 + ns, bar);
            }
        }
    };
    if (warp == 8) {
        if (elect()) {
#pragma unroll
            for (int i = 0; i < 8; i++) mbar_init(base + BAR_FULL + i * 8, 2);
            asm volatile("fence.mbarrier_init.release.cluster;" ::: "memory");
            fill(Int<0>(), Int<LEAD>());
        }
    } else if (warp == 9) {
        if (elect()) {
#pragma unroll
            for (int i = 0; i < 8; i++) mbar_init(base + BAR_EMPTY + i * 8, 8);
            asm volatile("fence.mbarrier_init.release.cluster;" ::: "memory");
        }
    } else if (warp == 10) {
        if (elect()) {
#pragma unroll
            for (int i = 0; i < 4; i++) mbar_init(base + BAR_RDY + i * 8, 8);
#pragma unroll
            for (int i = 0; i < 2; i++) mbar_init(base + BAR_HALO + i * 8, 8);
            asm volatile("fence.mbarrier_init.release.cluster;" ::: "memory");
        }
    } else if (warp == 11) {
        if (elect()) {
#pragma unroll
            for (int i = 0; i < 3; i++) mbar_init(base + BAR_DEP + i * 8, 1);
            asm volatile("fence.mbarrier_init.release.cluster;" ::: "memory");
        }
    }
    __syncthreads();

    if (__builtin_expect(warp >= 8, 1)) {
        asm volatile("setmaxnreg.dec.sync.aligned.u32 56;");
#define PROF_FEED_A
#define PROF_FEED_B
        if (__builtin_expect(warp == 8, 1)) {
            if (elect()) {
                PROF(129);
                fill(Int<LEAD>(), Int<7>());
                PROF(134);
                Feed<0> f;
                const int row = mt * 128;
                auto c_run = [&](const CUtensorMap* m, int off, int n0, int n1) {
#pragma unroll 1
                    for (int n = n0; n < n1; n++) {
                        const uint32_t bar = f.acquire<NA>();
                        mbar_expect(bar, SLOT);
                        tma_ld2(f.dst, m, (off + skip_own(n, mt)) * 64, row, bar);
                        PROF_FEED_A;
                        f.next<NA>();
                    }
                };
                if (roleH) {
                } else if (!roleL) {
                    f.seek(14, 0);
                    mbar_wait(base + BAR_RDY, 0);
#pragma unroll 1
                    for (int i = 0; i < 4; i++) {
                        const uint32_t bar = f.acquire<NA>();
                        mbar_expect(bar, SLOT);
                        tma_ld2(f.dst, &maps.m[M_CR + (i >> 1)], ((i & 1) * 16 + mt) * 64, row, bar);
                        mbar_arrive(bar);
                        PROF_FEED_A;
                        f.next<NA>();
                    }
                    c_run(&maps.m[M_CR], 0, 0, 15);
                    c_run(&maps.m[M_CI], 0, 0, NBE);
                    wait_dep(2);
#pragma unroll 1
                    for (int i = 0; i < 7; i++) {
                        const uint32_t bar = f.acquire<NA>();
                        mbar_expect(bar, SLOT);
                        bulk_ld(f.dst, sc->o + (size_t)(mt * 7 + i) * SLOT, SLOT, bar);
                        PROF_FEED_A;
                        f.next<NA>();
                    }
                } else {
#pragma unroll 1
                    for (int i = 4; i < 7; i++) {
                        wait_released(2 * i - 8);
                        mbar_expect(full_bar(2 * i), SLOT);
                        tma_ld2(base + i * SLOT, &maps.m[M_XA], par * 448 + i * 64, blk * 128, full_bar(2 * i));
                    }
                    wait_released(7);
                    f.seek(21, 0);
                    c_run(&maps.m[M_CR], 16, 0, 15);
                    c_run(&maps.m[M_CI], 16, 0, 15);
                    c_run(&maps.m[M_CI], 0, NBE, 15);
                }
            }
        } else if (warp == 11) {
            if (elect()) {
                Feed<BRING> f;
                auto blob_run = [&](auto nbs, int quarter, int n0, int n1) {
                    constexpr int N = decltype(nbs)::value;
                    const uint8_t* src = sc->ab + (size_t)(quarter * 64 + ns) * BLOB;
#pragma unroll 1
                    for (int n = n0; n < n1; n++) {
                        const uint32_t bar = f.template acquire<N>();
                        mbar_expect(bar, BLOB);
                        bulk_ld(f.dst, src + skip_own(n, mt) * (4 * BLOB), BLOB, bar);
                        PROF_FEED_B;
                        f.template next<N>();
                    }
                };
                auto w_run = [&](auto nbs, const CUtensorMap* m, int slice, bool no_a) {
                    constexpr int N = decltype(nbs)::value;
#pragma unroll 1
                    for (int i = 0; i < 7; i++) {
                        const uint32_t bar = f.template acquire<N>();
                        mbar_expect(bar, SLOT);
                        tma_ld3(f.dst, m, 0, i * 64, slice, bar);
                        tma_ld3(f.dst + 8192, m, 64, i * 64, slice, bar);
                        if (no_a) mbar_arrive(bar);
                        PROF_FEED_B;
                        f.template next<N>();
                    }
                };
                if (roleH) {
                    f.seek(7, 0);
                    w_run(Int<7>(), &maps.m[M_WV], 8 + ns, true);
                } else if (!roleL) {
                    f.seek(7, bslot_e(7));
#pragma unroll 1
                    for (int i = 0; i < 7; i++) {
                        const uint32_t bar = f.acquire<5>();
                        mbar_expect(bar, BLOB);
                        tma_ld2(f.dst, &maps.m[M_WI], i * 64, col, bar);
                        mbar_arrive(bar);
                        PROF_FEED_B;
                        f.next<5>();
                    }
                    f.seek(18, bslot_e(18));
                    wait_dep(0);
                    blob_run(Int<7>(), 0, 0, 15);
                    wait_dep(1);
                    blob_run(Int<7>(), 2, 0, NBE);
                    w_run(Int<7>(), &maps.m[M_WO], ns, false);
                } else {
                    f.seek(6, 0);
#pragma unroll 1
                    for (int i = 6; i < 14; i++) {
                        const uint32_t bar = f.acquire<6>();
                        mbar_expect(bar, SLOT);
                        tma_ld4(f.dst, &maps.m[M_WQK], 0, i * 32, 0, ns, bar);
                        tma_ld4(f.dst + 8192, &maps.m[M_WQK], 64, i * 32, 0, ns, bar);
                        if (i & 1) mbar_arrive(bar);
                        PROF_FEED_B;
                        f.next<6>();
                    }
                    w_run(Int<6>(), &maps.m[M_WV], 8 + ns, true);
                    wait_dep(0);
                    blob_run(Int<6>(), 1, 0, 15);
                    wait_dep(1);
                    blob_run(Int<6>(), 3, 0, 15);
                    blob_run(Int<6>(), 2, NBE, 15);
                }
            }
        } else if (roleH) {
        } else if (warp == 10) {
            if (elect()) {
                unsigned* epoch_ptr = &sc->epoch[(bid * 4 + 2) * 8];
                const unsigned ep = *epoch_ptr + 1;
                sts1(base + TAG, ep);
                await(sc, CNT_A + ns, ep * 16);
                mbar_arrive(base + BAR_DEP);
                PROF(150);
                await(sc, CNT_B + ns, ep * 16);
                mbar_arrive(base + BAR_DEP + 8);
                PROF(151);
                if (!roleL) {
                    await(sc, CNT_O + mt, ep * 4);
                    mbar_arrive(base + BAR_DEP + 16);
                }
                PROF(152);
                *epoch_ptr = ep;
            }
        } else if (!roleL) {
            if (elect()) {
                mbar_wait(base + BAR_RDY, 0);
                PROF(130);
                signal(sc, CNT_A + ns);
                PROF(131);
                mbar_wait(base + BAR_RDY + 24, 0);
                PROF(132);
                signal(sc, CNT_B + ns);
                PROF(133);
            }
        } else {
            const unsigned t_start = clk32();
            unsigned* epoch_ptr = &sc->epoch[(bid * 4 + 1) * 8];
            const unsigned tag = *epoch_ptr + 1;
#pragma unroll 1
            for (int kv = 0; kv < 2; kv++) {
                uint32_t v[14], t[14];
#pragma unroll
                for (int i = 0; i < 14; i++) v[i] = 0;

                if (blk > 0) {
                    const uint8_t* src = sc->halo + (size_t)(((mt - 1) * 4 + ns) * 2 + kv) * (2 * HSLOT) + lane * 16;
                    pause_until(t_start, HALO_DELAY + kv * 3200);
#pragma unroll 1
                    for (int n = 0; n < SPIN_LIMIT; n++) {
                        bool ok = true;
#pragma unroll
                        for (int i = 0; i < 7; i++) ld_tagged(src + i * 512, v[2 * i], t[2 * i], v[2 * i + 1], t[2 * i + 1]);
#pragma unroll
                        for (int i = 0; i < 14; i++) ok = ok && t[i] == tag;
                        if (__all_sync(0xffffffffu, ok)) break;
                    }
                }
#pragma unroll
                for (int i = 0; i < 14; i++) sts1(base + HALO + kv * (8 * HSLOT) + i * 128 + lane * 4, v[i]);
                warp_arrive(base + BAR_HALO + kv * 8);
                if (lane == 0) PROF(142 + kv);
            }
            if (elect()) {
                mbar_wait(base + BAR_RDY, 0);
                PROF(130);
                signal(sc, CNT_O + mt);
                PROF(131);
                *epoch_ptr = tag;
            }
        }
    } else {
        asm volatile("setmaxnreg.inc.sync.aligned.u32 224;");
        Ring r;
        r.wg = warp >> 2;
        r.zero = blockIdx.y;
        const int wg = warp >> 2;
        if (PINGPONG && wg) nb_arrive(1, 256);
        uint8_t* part = sc->part + (size_t)(ns * 16 + mt) * (2 * BLOB) + warp * 512 + lane * 16;
        uint32_t p[28];

        if (roleH) {
            unsigned* epoch_ptr = &sc->epoch[bid * 4 * 8];
            const unsigned tag = *epoch_ptr + 1;
            uint8_t* hout = sc->halo + (size_t)((warp * 8 + ns) * 2) * (2 * HSLOT) + lane * 16;
            float x0[56], x1[56];
            r.seek(0, 0);
            r.run<XWN, 7, true>(x0);
#pragma unroll 1
            for (int i = 1; i < 7; i++) r.run<XWN, 7, false>(x0);
            r.run<XWN, 7, true>(x1);
            acc_fence(x0);
            pack_all(x0, p);
#pragma unroll
            for (int i = 0; i < 14; i++) st_tagged(hout + (i & 1) * (16 * HSLOT) + (i >> 1) * 512, p[(i >> 1) * 4 + (i & 1)], p[(i >> 1) * 4 + (i & 1) + 2], tag);
#pragma unroll 1
            for (int i = 1; i < 7; i++) r.run<XWN, 7, false>(x1);
            asm volatile("wgmma.wait_group.sync.aligned 0;" ::: "memory");
            acc_fence(x1);
            pack_all(x1, p);
#pragma unroll
            for (int i = 0; i < 28; i++) p[i] = movm(p[i]);
#pragma unroll
            for (int i = 0; i < 14; i++)
                st_tagged(hout + 2 * HSLOT + (i & 1) * (16 * HSLOT) + (i >> 1) * 512, p[(i >> 1) * 4 + (i & 1)], p[(i >> 1) * 4 + (i & 1) + 2], tag);
            if (threadIdx.x == 0) *epoch_ptr = tag;
        } else if (!roleL) {
            uint8_t* blob = sc->ab + (size_t)((wg * 16 + mt) * 4 + ns) * BLOB + (warp & 3) * WSLOT + lane * 4;
            const uint32_t own = base + BRING + wg * SLOT + (warp & 3) * WSLOT + lane * 16;
            float x0[56], x1[56];
            r.seek(0, bslot_e(0));
            r.run<XW, 7, true>(x0);
            r.run<XW, 7, false>(x0);
            r.seek(2, bslot_e(2));
#pragma unroll 1
            for (int i = 2; i < 7; i++) r.run<XW, 5, false>(x0);

            r.seek(7, bslot_e(7));
            r.run<XW, 5, true, -1>(x1);
            acc_fence(x0);
            pack_all(x0, p);
            store_frags<0, 9>(blob, p);
            r.run<XW, 5, false, -1>(x1);
            store_frags<9, 18>(blob, p);
            r.run<XW, 5, false, -1>(x1);
            store_frags<18, 28>(blob, p);
            warp_arrive(base + BAR_RDY);
            r.run<XW, 5, false, -1>(x1);
            stage_frags<0, 8>(own + 5 * SLOT, p);
            r.run<XW, 5, false, -1>(x1);
            stage_frags<8, 20>(own + 5 * SLOT, p);
            r.run<XW, 5, false, -1>(x1);
            stage_frags<20, 28>(own + 5 * SLOT, p);
            warp_arrive(base + BAR_RDY + 8);
            r.run<XW, 5, false, -1>(x1);

            mbar_wait(base + BAR_RDY + 8, 0);
            fence_async_smem();
            r.seek(14, bslot_e(14));
            r.run<BIG, 7, true>(x0);
            acc_fence(x1);
            pack_all(x1, p);
            wait_released(10);
            stage_frags<0, 28>(own, p);
            warp_arrive(base + BAR_RDY + 16);
            r.run<BIG, 7, false>(x0);
            mbar_wait(base + BAR_RDY + 16, 0);
            fence_async_smem();
            blob += (size_t)128 * BLOB;
#pragma unroll
            for (int i = 0; i < 28; i++) {
                if (i % B_SLICE == 0) r.run<BIG, 7, false>(x0);
                stg1(blob + i * 128, p[i]);
            }
            warp_arrive(base + BAR_RDY + 24);
#pragma unroll 1
            for (int i = 17 + 27 / B_SLICE; i < POUT; i++) r.run<BIG, 7, false>(x0);

            const uint32_t tag = lds1(base + TAG);
            r.seek(POUT, bslot_e(POUT));
            r.run<OUT, 7, true>(x1);
            acc_fence(x0);
            pack_all(x0, p);
#pragma unroll
            for (int i = 0; i < 7; i++) {
                if (i == 2 || i == 5) r.run<OUT, 7, false>(x1);
                st_part(part + i * 4096, p + 4 * i, tag & 1);
            }
#pragma unroll 1
            for (int i = 3; i < 7; i++) r.run<OUT, 7, false>(x1);

            wait_released(ELAST - 6);
            asm volatile("wgmma.wait_group.sync.aligned 0;" ::: "memory");
            acc_fence(x1);
            pack_all(x1, p);
            const uint32_t slab = base + (wg ? BRING + bslot_e(ELAST - 6) * SLOT : ((ELAST - 6) % NA) * SLOT) + (warp & 3) * WSLOT;
            store_out(p, lane, slab, &maps.m[M_OUTA], par * 896 + col, blk * 128 + warp * 16);
        } else {
            const int g = lane >> 2, tig = lane & 3;
            const uint32_t hin = base + HALO + warp * HSLOT + lane * 4;
            auto publish = [&](const uint32_t (&h)[14], int kv) {
                if (warp < 7) {
#pragma unroll
                    for (int c = 0; c < 14; c++) sts1(hin + HSLOT + c * 128, h[c]);
                    warp_arrive(base + BAR_HALO + kv * 8);
                }
            };
            float y0[56], y1[56], y2[56];
            r.seek(0, 0);
            r.run<QK, 6, true>(y0, y1);
#pragma unroll 1
            for (int i = 1; i < 14; i++) r.run<QK, 6, false>(y0, y1);

            uint32_t m1[8][4], m0[8][4], lo[14], hi[14];
            r.seek(14, bslot_l(14));
            r.run<XWN, 6, true>(y2);
            acc_fence(y0);
            acc_fence(y1);
#pragma unroll
            for (int c = 0; c < 14; c++) hi[c] = pack2(y1[4 * c + 2], y1[4 * c + 3]);
            publish(hi, 0);
            r.run<XWN, 6, false>(y2);
            r.pin();
#pragma unroll
            for (int c = 0; c < 14; c++) lo[c] = pack2(y1[4 * c], y1[4 * c + 1]);
#pragma unroll
            for (int t = 0; t < 8; t++) {
                const int c = tile_of(t);
                const bool shared = (t & 3) == 2;
                m1[t][0] = shared ? dup(lo[c], r.zero) : lo[c];
                m1[t][1] = shared ? dup(hi[c], r.zero) : hi[c];
                m1[t][2] = lo[c + 1];
                m1[t][3] = hi[c + 1];
                m0[t][0] = dup(m1[t][0], r.zero);
                m0[t][2] = dup(lo[c + 1], 2 * r.zero);
            }
            r.run<XWN, 6, false>(y2);
            r.pin();
            uint32_t q[2][8][2];
#pragma unroll
            for (int b = 0; b < 2; b++) {
                uint32_t v[14];
#pragma unroll
                for (int c = 0; c < 14; c++) v[c] = pack2(y0[4 * c + 2 * b], y0[4 * c + 2 * b + 1]);
#pragma unroll
                for (int t = 0; t < 8; t++) {
                    const int c = tile_of(t);
                    q[b][t][0] = (t & 3) == 2 ? (tig >= 2 ? v[c] : 0u) : v[c];
                    q[b][t][1] = (t & 3) == 1 ? (tig < 2 ? v[c + 1] : 0u) : v[c + 1];
                }
            }
            r.run<XWN, 6, false>(y2);
            mbar_wait(base + BAR_HALO, 0);
#pragma unroll
            for (int t = 0; t < 8; t++) {
                m0[t][1] = lds1(hin + tile_of(t) * 128 + ((t & 3) == 2 ? r.zero : 0u));
                m0[t][3] = lds1(hin + tile_of(t) * 128 + 128);
            }
            r.wait();
            float s[8][4];
#pragma unroll
            for (int step = 0; step < 2; step++) {
#pragma unroll
                for (int i = 0; i < 8; i++) {
                    const int b = 1 - (i >> 2), h = i & 3, t = 2 * h + step;
                    float (&d)[4] = s[2 * h + b];
                    if (step == 0) d[0] = d[1] = d[2] = d[3] = 0.f;
                    mma16816(d, b ? m1[t] : m0[t], q[b][t][0], q[b][t][1]);
                }
            }
            r.pin();
            r.run<XWN, 6, false, 1, false>(y2);
            r.pin();

            uint32_t pr[8], mx[4], mx1[4];
            {
                const bool cur0 = g <= 2 * tig, cur1 = g <= 2 * tig + 1;
#pragma unroll
                for (int i = 0; i < 8; i++) {
                    const int c = (i & 1) ? 2 : 0;
                    pr[i] = movm(pack2(cur0 ? s[i][c] : s[i][2 - c], cur1 ? s[i][c + 1] : s[i][3 - c]));
                }
            }
            r.run<XWN, 6, false>(y2);
            r.pin();
            const uint32_t curmask = (2 * tig <= g ? 0x0000FFFFu : 0u) | (2 * tig + 1 <= g ? 0xFFFF0000u : 0u);
#pragma unroll
            for (int i = 0; i < 8; i++) pr[i] = pack2(bf_lo(pr[i]) * 0.18898223650461362f, bf_hi(pr[i]) * 0.18898223650461362f);
            r.run<XWN, 6, false>(y2);
            r.pin();
            {
                const uint32_t keep = (blk == 0 && warp == 0) ? curmask : 0xFFFFFFFFu;
#pragma unroll
                for (int i = 0; i < 4; i++) {
                    pr[2 * i] = (pr[2 * i] & keep) | (0xCE6ECE6Eu & ~keep);
                    mx[i] = max2(__byte_perm(pr[2 * i], pr[2 * i + 1], 0x5410), __byte_perm(pr[2 * i], pr[2 * i + 1], 0x7632));
                }
#pragma unroll
                for (int i = 0; i < 4; i++) mx[i] = max2(mx[i], __shfl_xor_sync(0xffffffffu, mx[i], 1));
#pragma unroll
                for (int i = 0; i < 4; i++) mx1[i] = __shfl_xor_sync(0xffffffffu, mx[i], 2);
            }

            r.seek(21, bslot_l(21));
            r.run<BIG, 6, true>(y0);
            acc_fence(y2);
#pragma unroll
            for (int c = 0; c < 14; c++) hi[c] = movm(pack2(y2[4 * c + 2], y2[4 * c + 3]));
            r.run<BIG, 6, false>(y0);
            wait_released(18);
            publish(hi, 1);
            float e0[8], e1[8], sm[8], sm1[8];
#pragma unroll
            for (int i = 0; i < 8; i++) {
                const uint32_t m2 = max2(mx[i >> 1], mx1[i >> 1]);
                sm[i] = fmul(((i & 1) ? bf_hi(m2) : bf_lo(m2)), -1.4426950408889634f);
            }
            r.run<BIG, 6, false>(y0);
            r.pin();
#pragma unroll
            for (int c = 0; c < 14; c++) lo[c] = movm(pack2(y2[4 * c], y2[4 * c + 1]));
            r.run<BIG, 6, false>(y0);
            r.pin();
#pragma unroll
            for (int i = 0; i < 8; i++) {
                e0[i] = ex2(fmaf(bf_lo(pr[i]), 1.4426950408889634f, sm[i]));
                e1[i] = ex2(fmaf(bf_hi(pr[i]), 1.4426950408889634f, sm[i]));
            }
            r.run<BIG, 6, false>(y0);
            r.pin();
#pragma unroll
            for (int i = 0; i < 8; i++) {
                sm[i] = e0[i] + e1[i];
                sm1[i] = __shfl_xor_sync(0xffffffffu, sm[i], 1);
            }
#pragma unroll
            for (int t = 0; t < 8; t++) {
                const int c = tile_of(t);
                const bool shared = (t & 3) == 2;
                m1[t][0] = shared ? dup(lo[c], r.zero) : lo[c];
                m1[t][1] = lo[c + 1];
                m1[t][2] = shared ? dup(hi[c], r.zero) : hi[c];
                m1[t][3] = hi[c + 1];
                m0[t][0] = dup(m1[t][0], r.zero);
                m0[t][1] = dup(lo[c + 1], 2 * r.zero);
            }
            r.run<BIG, 6, false>(y0);
            r.pin();
#pragma unroll
            for (int i = 0; i < 8; i++) sm[i] += sm1[i];
#pragma unroll
            for (int i = 0; i < 8; i++) {
                const float inv = rcp(sm[i] + __shfl_xor_sync(0xffffffffu, sm[i], 2));
                pr[i] = pack2(e0[i] * inv, e1[i] * inv);
            }
            r.run<BIG, 6, false>(y0);
            mbar_wait(base + BAR_HALO + 8, 0);
            const uint32_t vin = warp ? hin : hin + 8 * HSLOT;
#pragma unroll
            for (int t = 0; t < 8; t++) {
                m0[t][2] = lds1(vin + tile_of(t) * 128 + ((t & 3) == 2 ? r.zero : 0u));
                m0[t][3] = lds1(vin + tile_of(t) * 128 + 128);
            }
            uint32_t pb[8][2];
#pragma unroll
            for (int i = 0; i < 8; i++) {
                pb[i][i & 1] = band(pr[i], curmask);
                pb[i][1 - (i & 1)] = band(pr[i], ~curmask);
            }
            r.wait();
            float o[2][8][4];
#pragma unroll
            for (int i = 0; i < 16; i++) {
                const int b = 1 - (i >> 3), t = i & 7;
                float (&d)[4] = o[b][t];
                d[0] = d[1] = d[2] = d[3] = 0.f;
                mma16816(d, b ? m1[t] : m0[t], pb[(t & 6) + b][0], pb[(t & 6) + b][1]);
            }
            r.pin();
            r.run<BIG, 6, false, 1, false>(y0);
            r.pin();
            uint8_t* odst = sc->o + (size_t)mt * 7 * SLOT + ns * (14 * 2048) + warp * 256 + lane * 4;
#pragma unroll
            for (int hp = 0; hp < 2; hp++) {
#pragma unroll
                for (int b = 0; b < 2; b++) {
                    const float (&u)[8][4] = o[b];
                    const int t = 4 * hp;
                    uint32_t* w = p + 14 * hp + b;
                    w[0] = pack2(u[t][0], u[t][1]);
                    w[2] = pack2(u[t][2], u[t][3]);
                    w[4] = pack2(u[t + 1][0], u[t + 1][1]);
                    w[6] = pack2(g < 4 ? u[t + 1][2] : u[t + 2][0], g < 4 ? u[t + 1][3] : u[t + 2][1]);
                    w[8] = pack2(u[t + 2][2], u[t + 2][3]);
                    w[10] = pack2(u[t + 3][0], u[t + 3][1]);
                    w[12] = pack2(u[t + 3][2], u[t + 3][3]);
                }
            }
#pragma unroll
            for (int i = 0; i < 28; i++) {
                if (i && i % O_SLICE == 0) r.run<BIG, 6, false>(y0);
                stg1(odst + (i >> 1) * 2048 + (i & 1) * 128, p[i]);
            }
            warp_arrive(base + BAR_RDY);

#pragma unroll 1
            for (int i = 29 + 27 / O_SLICE; i <= LLAST; i++) r.run<BIG, 6, false>(y0);
            const uint32_t tag = lds1(base + TAG);
#pragma unroll 1
            for (int n = 0; n < SPIN_LIMIT; n++) {
#pragma unroll
                for (int i = 0; i < 7; i++) ld_tagged(part + i * 4096, p[4 * i], p[4 * i + 1], p[4 * i + 2], p[4 * i + 3]);
                uint32_t stale = 0;
#pragma unroll
                for (int i = 0; i < 28; i += 2) stale |= p[i] ^ tag;
                if (__all_sync(0xffffffffu, !(stale & 1))) break;
            }
            wait_released(LLAST - 6);
            asm volatile("wgmma.wait_group.sync.aligned 0;" ::: "memory");
            acc_fence(y0);
#pragma unroll
            for (int i = 0; i < 28; i++) p[i] = pack2(y0[2 * i] + bf_lo(p[i]), y0[2 * i + 1] + bf_hi(p[i]));
            const uint32_t slab = base + (wg ? HALO : ((LLAST - 6) % NA) * SLOT) + (warp & 3) * WSLOT;
            store_out(p, lane, slab, &maps.m[M_OUTB], 448 + col, mt * 128 + warp * 16);
        }
    }
}

typedef CUresult (*EncodeFn)(CUtensorMap*, CUtensorMapDataType, cuuint32_t, void*, const cuuint64_t*, const cuuint64_t*,
                             const cuuint32_t*, const cuuint32_t*, CUtensorMapInterleave, CUtensorMapSwizzle,
                             CUtensorMapL2promotion, CUtensorMapFloatOOBfill);

struct Dim { uint64_t size, stride; uint32_t box; };
void encode(EncodeFn fn, CUtensorMap* m, const void* ptr, CUtensorMapSwizzle sw, Dim d0, Dim d1, Dim d2 = {0, 0, 0}, Dim d3 = {0, 0, 0}) {
    const cuuint64_t dims[4] = {d0.size, d1.size, d2.size, d3.size};
    const cuuint64_t strides[3] = {d1.stride, d2.stride, d3.stride};
    const cuuint32_t box[4] = {d0.box, d1.box, d2.box, d3.box};
    const cuuint32_t es[4] = {1, 1, 1, 1};
    fn(m, CU_TENSOR_MAP_DATA_TYPE_BFLOAT16, d3.size ? 4 : d2.size ? 3 : 2, const_cast<void*>(ptr), dims, strides, box, es,
       CU_TENSOR_MAP_INTERLEAVE_NONE, sw, CU_TENSOR_MAP_L2_PROMOTION_L2_128B, CU_TENSOR_MAP_FLOAT_OOB_FILL_NONE);
}

}

extern "C" void kernel_launch(void* const* d_in, const int* in_sizes, int n_in, void* d_out, int out_size) {
    (void)in_sizes; (void)n_in; (void)out_size;
    void* fnp = nullptr;
    cudaDriverEntryPointQueryResult st;
    cudaGetDriverEntryPoint("cuTensorMapEncodeTiled", &fnp, cudaEnableDefault, &st);
    EncodeFn fn = (EncodeFn)fnp;
    void* scratch = nullptr;
    cudaGetSymbolAddress(&scratch, g_scratch);
    cudaFuncSetAttribute(fused_kernel, cudaFuncAttributeMaxDynamicSharedMemorySize, SMEM_BYTES);

    const CUtensorMapSwizzle S128 = CU_TENSOR_MAP_SWIZZLE_128B, S0 = CU_TENSOR_MAP_SWIZZLE_NONE;
    Maps maps;
    encode(fn, &maps.m[M_XA], d_in[0], S128, {896, 2, 64}, {1024, 1792, 128});
    encode(fn, &maps.m[M_WQK], d_in[1], S128, {112, 2, 64}, {448, 2688, 32}, {3, 896, 2}, {4, 224, 1});
    encode(fn, &maps.m[M_WV], d_in[1], S128, {112, 2, 64}, {448, 2688, 64}, {12, 224, 1});
    encode(fn, &maps.m[M_XH], d_in[0], S128, {448, 2, 64}, {128, 1792, 8}, {8, 128 * 1792, 8}, {2, 896, 2});
    encode(fn, &maps.m[M_WO], d_in[2], S128, {112, 2, 64}, {448, 896, 64}, {4, 224, 1});
    encode(fn, &maps.m[M_XB], d_in[3], S128, {448, 2, 64}, {1024, 896, 64}, {2, 896 * 1024, 2});
    encode(fn, &maps.m[M_CR], d_in[4], S128, {2048, 2, 64}, {2048, 4096, 128});
    encode(fn, &maps.m[M_CI], d_in[5], S128, {2048, 2, 64}, {2048, 4096, 128});
    encode(fn, &maps.m[M_WR], d_in[6], S128, {448, 2, 64}, {448, 896, 112});
    encode(fn, &maps.m[M_WI], d_in[7], S128, {448, 2, 64}, {448, 896, 112});
    encode(fn, &maps.m[M_OUTA], d_out, S0, {1792, 2, 112}, {1024, 3584, 16});
    encode(fn, &maps.m[M_OUTB], d_out, S0, {896, 2, 112}, {2048, 1792, 16});

    fused_kernel<<<132, 384, SMEM_BYTES>>>((Scratch*)scratch, maps);
}
```

```cpp
#include <cuda.h>
#include <cuda_bf16.h>
#include <cuda_runtime.h>
#include <stdint.h>

namespace {

constexpr uint32_t SLOT = 16384;
constexpr int NA = 7;
constexpr uint32_t BRING = NA * SLOT;
constexpr uint32_t HALO = BRING + 6 * SLOT;
constexpr uint32_t HSLOT = 1792;
constexpr uint32_t WSLOT = 3584;
constexpr uint32_t BLOB = 14336;
constexpr uint32_t BARS = 14 * SLOT;
constexpr uint32_t BAR_FULL = BARS;
constexpr uint32_t BAR_EMPTY = BARS + 64;
constexpr uint32_t BAR_RDY = BARS + 128;
constexpr uint32_t BAR_DEP = BARS + 168;
constexpr uint32_t BAR_HALO = BARS + 192;
constexpr uint32_t TAG = BARS + 208;
constexpr uint32_t SMEM_BYTES = BARS + 256 + 1024;
constexpr uint32_t base = 1024;
constexpr int SPIN_LIMIT = 1 << 16;

#define E_EXTRA 0
#define HALO_DELAY 7000
#define O_SLICE 5
#define B_SLICE 5
#define LEAD 3
#define PINGPONG 1
#define PART_LEAD 1
#define A_FIRST 14
#define MAPPING 2
#define SPARE0 12
constexpr int NBE = 13 + E_EXTRA;
constexpr int POUT = 33 + NBE;
constexpr int ELAST = POUT + 6;
constexpr int LLAST = 52 - E_EXTRA;

enum { M_XA, M_XH, M_WQK, M_WV, M_WO, M_XB, M_WR, M_WI, M_CR, M_CI, M_OUTA, M_OUTB, M_COUNT };
struct __align__(64) Maps { CUtensorMap m[M_COUNT]; };

constexpr int CNT_A = 0;
constexpr int CNT_B = 8;
constexpr int CNT_O = 16;
constexpr int CNT_COUNT = 32;

struct Scratch {
    uint8_t ab[64 * 4 * BLOB];
    uint8_t o[16 * 7 * SLOT];
    uint8_t part[64 * 2 * BLOB];
    uint8_t halo[64 * 2 * 2 * HSLOT];
    unsigned cnt[CNT_COUNT * 32];
    unsigned epoch[132 * 4 * 8];
};
__device__ __align__(1024) Scratch g_scratch;

__device__ __forceinline__ unsigned clk32() { unsigned c; asm volatile("mov.u32 %0, %%clock;" : "=r"(c)); return c; }
__device__ __forceinline__ void pause_until(unsigned t0, unsigned cycles) {
    while (clk32() - t0 < cycles) {}
}

#define PROF(idx)

__device__ __forceinline__ void mbar_init(uint32_t bar, uint32_t cnt) {
    asm volatile("mbarrier.init.shared::cta.b64 [%0], %1;" ::"r"(bar), "r"(cnt) : "memory");
}
__device__ __forceinline__ void mbar_expect(uint32_t bar, uint32_t bytes) {
    asm volatile("mbarrier.arrive.expect_tx.shared::cta.b64 _, [%0], %1;" ::"r"(bar), "r"(bytes) : "memory");
}
__device__ __forceinline__ void mbar_arrive(uint32_t bar) {
    asm volatile("mbarrier.arrive.shared::cta.b64 _, [%0];" ::"r"(bar) : "memory");
}
__device__ __forceinline__ bool mbar_try(uint32_t bar, uint32_t parity) {
    uint32_t ok;
    asm volatile("{\n.reg .pred p;\nmbarrier.try_wait.parity.shared::cta.b64 p, [%1], %2;\nselp.u32 %0, 1, 0, p;\n}\n"
                 : "=r"(ok) : "r"(bar), "r"(parity) : "memory");
    return ok;
}
__device__ __forceinline__ void mbar_wait(uint32_t bar, uint32_t parity) {
#pragma unroll 1
    for (int n = 0; n < SPIN_LIMIT; n++)
        if (mbar_try(bar, parity)) break;
}
__device__ __forceinline__ bool elect() {
    uint32_t p;
    asm volatile("{\n.reg .pred p;\nelect.sync _|p, 0xffffffff;\nselp.u32 %0, 1, 0, p;\n}\n" : "=r"(p));
    return p;
}
__device__ __forceinline__ void nb_sync(int id, int n) { asm volatile("bar.sync %0, %1;" ::"r"(id), "r"(n) : "memory"); }
__device__ __forceinline__ void nb_arrive(int id, int n) { asm volatile("bar.arrive %0, %1;" ::"r"(id), "r"(n) : "memory"); }
__device__ __forceinline__ void warp_arrive(uint32_t bar) {
    __syncwarp();
    if (elect()) mbar_arrive(bar);
}
__device__ __forceinline__ uint32_t band(uint32_t x, uint32_t m) {
    uint32_t r;
    asm volatile("and.b32 %0, %1, %2;" : "=r"(r) : "r"(x), "r"(m));
    return r;
}
__device__ __forceinline__ uint32_t dup(uint32_t x, uint32_t zero) {
    uint32_t r;
    asm volatile("xor.b32 %0, %1, %2;" : "=r"(r) : "r"(x), "r"(zero));
    return r;
}

__device__ __forceinline__ void tma_ld2(uint32_t dst, const CUtensorMap* m, int c0, int c1, uint32_t bar) {
    asm volatile("cp.async.bulk.tensor.2d.shared::cluster.global.mbarrier::complete_tx::bytes [%0], [%1, {%3, %4}], [%2];"
                 ::"r"(dst), "l"(m), "r"(bar), "r"(c0), "r"(c1) : "memory");
}
__device__ __forceinline__ void tma_ld3(uint32_t dst, const CUtensorMap* m, int c0, int c1, int c2, uint32_t bar) {
    asm volatile("cp.async.bulk.tensor.3d.shared::cluster.global.mbarrier::complete_tx::bytes [%0], [%1, {%3, %4, %5}], [%2];"
                 ::"r"(dst), "l"(m), "r"(bar), "r"(c0), "r"(c1), "r"(c2) : "memory");
}
__device__ __forceinline__ void tma_ld4(uint32_t dst, const CUtensorMap* m, int c0, int c1, int c2, int c3, uint32_t bar) {
    asm volatile("cp.async.bulk.tensor.4d.shared::cluster.global.mbarrier::complete_tx::bytes [%0], [%1, {%3, %4, %5, %6}], [%2];"
                 ::"r"(dst), "l"(m), "r"(bar), "r"(c0), "r"(c1), "r"(c2), "r"(c3) : "memory");
}
__device__ __forceinline__ void bulk_ld(uint32_t dst, const void* src, uint32_t bytes, uint32_t bar) {
    asm volatile("cp.async.bulk.shared::cluster.global.mbarrier::complete_tx::bytes [%0], [%1], %2, [%3];"
                 ::"r"(dst), "l"(src), "r"(bytes), "r"(bar) : "memory");
}
__device__ __forceinline__ void tma_st2(const CUtensorMap* m, int c0, int c1, uint32_t src) {
    asm volatile("cp.async.bulk.tensor.2d.global.shared::cta.bulk_group [%0, {%1, %2}], [%3];"
                 ::"l"(m), "r"(c0), "r"(c1), "r"(src) : "memory");
}
__device__ __forceinline__ void bulk_commit() { asm volatile("cp.async.bulk.commit_group;" ::: "memory"); }
__device__ __forceinline__ void bulk_wait_read() { asm volatile("cp.async.bulk.wait_group.read 0;" ::: "memory"); }
__device__ __forceinline__ void fence_async_smem() { asm volatile("fence.proxy.async.shared::cta;" ::: "memory"); }
__device__ __forceinline__ void fence_async_global() { asm volatile("fence.proxy.async.global;" ::: "memory"); }

__device__ __forceinline__ void signal(Scratch* sc, int idx) {
    asm volatile("fence.proxy.async;\nred.relaxed.gpu.global.add.u32 [%0], 1;" ::"l"(&sc->cnt[idx * 32]) : "memory");
}
__device__ __forceinline__ void await(Scratch* sc, int idx, unsigned target) {
#pragma unroll 1
    for (int n = 0; n < SPIN_LIMIT; n++) {
        unsigned v;
        asm volatile("ld.relaxed.gpu.global.u32 %0, [%1];" : "=r"(v) : "l"(&sc->cnt[idx * 32]) : "memory");
        if ((int)(v - target) >= 0) break;
    }
    asm volatile("fence.acquire.gpu;" ::: "memory");
}
__device__ __forceinline__ void wait_dep(int k) {
    mbar_wait(base + BAR_DEP + k * 8, 0);
    fence_async_global();
}

#define WG_REGS                                                                                                     \
    "{%0,%1,%2,%3,%4,%5,%6,%7,%8,%9,%10,%11,%12,%13,%14,%15,%16,%17,%18,%19,%20,%21,%22,%23,%24,%25,%26,%27,"       \
    "%28,%29,%30,%31,%32,%33,%34,%35,%36,%37,%38,%39,%40,%41,%42,%43,%44,%45,%46,%47,%48,%49,%50,%51,%52,%53,%54,%55}"
#define WG_OPS(C)                                                                                                   \
    C(d[0]), C(d[1]), C(d[2]), C(d[3]), C(d[4]), C(d[5]), C(d[6]), C(d[7]), C(d[8]), C(d[9]), C(d[10]), C(d[11]),   \
    C(d[12]), C(d[13]), C(d[14]), C(d[15]), C(d[16]), C(d[17]), C(d[18]), C(d[19]), C(d[20]), C(d[21]), C(d[22]),   \
    C(d[23]), C(d[24]), C(d[25]), C(d[26]), C(d[27]), C(d[28]), C(d[29]), C(d[30]), C(d[31]), C(d[32]), C(d[33]),   \
    C(d[34]), C(d[35]), C(d[36]), C(d[37]), C(d[38]), C(d[39]), C(d[40]), C(d[41]), C(d[42]), C(d[43]), C(d[44]),   \
    C(d[45]), C(d[46]), C(d[47]), C(d[48]), C(d[49]), C(d[50]), C(d[51]), C(d[52]), C(d[53]), C(d[54]), C(d[55])

template <int TA, int TB, int SB, bool INIT>
__device__ __forceinline__ void wgmma112(float (&d)[56], uint64_t da, uint64_t db) {
    if (INIT) {
        asm volatile("{\n.reg .pred p;\nsetp.ne.b32 p, 0, 0;\n"
                     "wgmma.mma_async.sync.aligned.m64n112k16.f32.bf16.bf16 " WG_REGS ", %56, %57, p, 1, %59, %60, %58;\n}\n"
                     : WG_OPS("=f") : "l"(da), "l"(db), "n"(TB), "n"(SB), "n"(TA));
    } else {
        asm volatile("{\n.reg .pred p;\nsetp.ne.b32 p, 1, 0;\n"
                     "wgmma.mma_async.sync.aligned.m64n112k16.f32.bf16.bf16 " WG_REGS ", %56, %57, p, 1, %59, %60, %58;\n}\n"
                     : WG_OPS("+f") : "l"(da), "l"(db), "n"(TB), "n"(SB), "n"(TA));
    }
}
__device__ __forceinline__ void acc_fence(float (&d)[56]) {
#pragma unroll
    for (int i = 0; i < 56; i++) asm volatile("" : "+f"(d[i])::"memory");
}

__device__ __forceinline__ uint32_t pack2(float lo, float hi) {
    uint32_t r;
    asm volatile("cvt.rn.bf16x2.f32 %0, %1, %2;" : "=r"(r) : "f"(hi), "f"(lo));
    return r;
}
__device__ __forceinline__ uint32_t movm(uint32_t a) {
    uint32_t r;
    asm volatile("movmatrix.sync.aligned.m8n8.trans.b16 %0, %1;" : "=r"(r) : "r"(a));
    return r;
}
__device__ __forceinline__ void stsm4(uint32_t addr, uint32_t a, uint32_t b, uint32_t c, uint32_t d) {
    asm volatile("stmatrix.sync.aligned.m8n8.x4.shared.b16 [%0], {%1,%2,%3,%4};" ::"r"(addr), "r"(a), "r"(b), "r"(c), "r"(d) : "memory");
}
__device__ __forceinline__ void sts1(uint32_t addr, uint32_t a) { asm volatile("st.shared.b32 [%0], %1;" ::"r"(addr), "r"(a) : "memory"); }
__device__ __forceinline__ uint32_t lds1(uint32_t addr) {
    uint32_t a;
    asm volatile("ld.shared.b32 %0, [%1];" : "=r"(a) : "r"(addr) : "memory");
    return a;
}
__device__ __forceinline__ void stg1(uint8_t* p, uint32_t a) { asm volatile("st.global.b32 [%0], %1;" ::"l"(p), "r"(a) : "memory"); }
__device__ __forceinline__ void st_part(uint8_t* p, const uint32_t* v, uint32_t parity) {
    asm volatile("{\n.reg .b64 x, y;\nmov.b64 x, {%1, %2};\nmov.b64 y, {%3, %4};\nst.relaxed.gpu.global.v2.b64 [%0], {x, y};\n}\n"
                 ::"l"(p), "r"((v[0] & ~1u) | parity), "r"(v[1]), "r"((v[2] & ~1u) | parity), "r"(v[3]) : "memory");
}
__device__ __forceinline__ void mma16816(float (&d)[4], const uint32_t (&a)[4], uint32_t b0, uint32_t b1) {
    asm volatile("mma.sync.aligned.m16n8k16.row.col.f32.bf16.bf16.f32 {%0,%1,%2,%3}, {%4,%5,%6,%7}, {%8,%9}, {%0,%1,%2,%3};"
                 : "+f"(d[0]), "+f"(d[1]), "+f"(d[2]), "+f"(d[3]) : "r"(a[0]), "r"(a[1]), "r"(a[2]), "r"(a[3]), "r"(b0), "r"(b1));
}
__device__ __forceinline__ uint32_t add2(uint32_t a, uint32_t b) {
    uint32_t r;
    asm("add.rn.bf16x2 %0, %1, %2;" : "=r"(r) : "r"(a), "r"(b));
    return r;
}
__device__ __forceinline__ uint32_t max2(uint32_t a, uint32_t b) {
    uint32_t r;
    asm("max.bf16x2 %0, %1, %2;" : "=r"(r) : "r"(a), "r"(b));
    return r;
}
__device__ __forceinline__ void st_tagged(uint8_t* p, uint32_t a, uint32_t b, uint32_t tag) {
    asm volatile("{\n.reg .b64 x, y;\nmov.b64 x, {%1, %3};\nmov.b64 y, {%2, %3};\nst.relaxed.gpu.global.v2.b64 [%0], {x, y};\n}\n"
                 ::"l"(p), "r"(a), "r"(b), "r"(tag) : "memory");
}
__device__ __forceinline__ void ld_tagged(const uint8_t* p, uint32_t& a, uint32_t& ta, uint32_t& b, uint32_t& tb) {
    asm volatile("{\n.reg .b64 x, y;\nld.relaxed.gpu.global.v2.b64 {x, y}, [%4];\nmov.b64 {%0, %1}, x;\nmov.b64 {%2, %3}, y;\n}\n"
                 : "=r"(a), "=r"(ta), "=r"(b), "=r"(tb) : "l"(p) : "memory");
}
__device__ __forceinline__ float bf_lo(uint32_t v) { return __uint_as_float(v << 16); }
__device__ __forceinline__ float bf_hi(uint32_t v) { return __uint_as_float(v & 0xFFFF0000u); }
__device__ __forceinline__ float rcp(float x) { float r; asm("rcp.approx.ftz.f32 %0, %1;" : "=f"(r) : "f"(x)); return r; }
__device__ __forceinline__ float ex2(float x) { float r; asm volatile("ex2.approx.ftz.f32 %0, %1;" : "=f"(r) : "f"(x)); return r; }

__device__ __forceinline__ uint32_t full_bar(int stage) { return base + BAR_FULL + (stage & 7) * 8; }
__device__ __forceinline__ void wait_released(int j) { mbar_wait(base + BAR_EMPTY + (j & 7) * 8, (j >> 3) & 1); }

template <int V>
struct Int { static constexpr int value = V; };

__host__ __device__ constexpr int bslot_e(int i) { return (i < 2 || i >= 14) ? (i + 5) % 7 : (i + 1) % 5; }
__host__ __device__ constexpr int bslot_l(int i) { return i % 6; }

template <uint32_t OFF>
struct Feed {
    int stage;
    uint32_t dst;
    __device__ __forceinline__ void seek(int i, int slot) { stage = i; dst = base + OFF + slot * SLOT; }
    template <int N>
    __device__ __forceinline__ uint32_t acquire() { wait_released(stage - N); return full_bar(stage); }
    template <int N>
    __device__ __forceinline__ void next() {
        stage++;
        dst += SLOT;
        if (dst == base + OFF + N * SLOT) dst = base + OFF;
    }
};
__device__ __forceinline__ int skip_own(int n, int mt) { return n == mt ? 15 : n; }

__host__ __device__ constexpr uint64_t desc_const(uint32_t lbo, uint32_t sbo, uint32_t mode) {
    return ((uint64_t)((sbo >> 4) | (mode << 30)) << 32) | ((lbo >> 4) << 16);
}
constexpr uint64_t D_K128 = desc_const(16, 1024, 1);
constexpr uint64_t D_N128 = desc_const(8192, 1024, 1);
constexpr uint64_t D_BLOB = desc_const(128, 256, 0);
constexpr uint64_t D_OT = desc_const(2048, 128, 0);

enum Kind { XW, XWN, QK, BIG, OUT };

struct Ring {
    int stage;
    uint32_t a, b;
    uint32_t wg;
    uint32_t zero;
    __device__ __forceinline__ void seek(int i, int bslot) {
        stage = i;
        a = (base + (i % NA) * SLOT) >> 4;
        b = (base + BRING + bslot * SLOT) >> 4;
    }
    __device__ __forceinline__ void wait() {
        mbar_wait(full_bar(stage), (stage >> 3) & 1);
        if (PINGPONG) nb_sync(1 + wg, 256);
    }
    __device__ __forceinline__ void pin() {
        uint32_t n = 0;
#pragma unroll 1
        do {
            asm volatile("pmevent 7;" ::: "memory");
        } while (n++ < zero);
    }
    template <Kind K, int NBS, bool INIT, int SB = 1, bool WAIT = true>
    __device__ __forceinline__ void run(float (&d)[56], float (&e)[56]) {
        if (WAIT) wait();
        asm volatile("wgmma.fence.sync.aligned;" ::: "memory");
        if (K == QK) {
            const uint64_t da = D_K128 + ((base >> 4) + (stage >> 1) * (SLOT >> 4) + (stage & 1) * 4 + wg * 512), db = D_N128 + b;
            wgmma112<0, 1, 1, INIT>(d, da, db);
            wgmma112<0, 1, 1, INIT>(e, da, db + 256);
            wgmma112<0, 1, 1, false>(d, da + 2, db + 128);
            wgmma112<0, 1, 1, false>(e, da + 2, db + 384);
        } else {
            constexpr int TA = K == OUT, TB = K != XW;
            constexpr uint32_t sa = K == OUT ? 256 : 2, sb = K == XW ? 2 : K == BIG ? 224 : 128;
            const uint64_t da = (K == OUT ? D_OT : D_K128) + (a + wg * (K == OUT ? 64 : 512));
            const uint64_t db = (K == XW ? D_K128 : K == BIG ? D_BLOB : D_N128) + b;
            wgmma112<TA, TB, SB, INIT>(d, da, db);
            wgmma112<TA, TB, SB, false>(d, da + sa, db + sb);
            wgmma112<TA, TB, SB, false>(d, da + 2 * sa, db + 2 * sb);
            wgmma112<TA, TB, SB, false>(d, da + 3 * sa, db + 3 * sb);
        }
        asm volatile("wgmma.commit_group.sync.aligned;" ::: "memory");
        if (PINGPONG) nb_arrive(2 - wg, 256);
        asm volatile("wgmma.wait_group.sync.aligned 1;" ::: "memory");
        if (stage > 0 && elect()) mbar_arrive(base + BAR_EMPTY + ((stage - 1) & 7) * 8);
        stage++;
        a += SLOT >> 4;
        if (a == (base + NA * SLOT) >> 4) a = base >> 4;
        b += SLOT >> 4;
        if (b == (base + BRING + NBS * SLOT) >> 4) b = (base + BRING) >> 4;
    }
    template <Kind K, int NBS, bool INIT, int SB = 1, bool WAIT = true>
    __device__ __forceinline__ void run(float (&d)[56]) { run<K, NBS, INIT, SB, WAIT>(d, d); }
};

__device__ __forceinline__ void pack_all(const float (&d)[56], uint32_t (&p)[28]) {
#pragma unroll
    for (int i = 0; i < 28; i++) p[i] = pack2(d[2 * i], d[2 * i + 1]);
}
template <int I0, int I1>
__device__ __forceinline__ void store_frags(uint8_t* dst, const uint32_t (&p)[28]) {
#pragma unroll
    for (int i = I0; i < I1; i++) stg1(dst + i * 128, p[i]);
}
template <int I0, int I1>
__device__ __forceinline__ void stage_frags(uint32_t lane_addr, const uint32_t (&p)[28]) {
#pragma unroll
    for (int i = I0; i < I1; i += 4) stsm4(lane_addr + i * 128, p[i], p[i + 1], p[i + 2], p[i + 3]);
}
__device__ __forceinline__ void store_out(const uint32_t (&p)[28], int lane, uint32_t slab, const CUtensorMap* m, int c0, int c1) {
    const bool swap = lane & 16;
    const uint32_t addr = slab + (lane & 15) * 224 + (((lane >> 4) ^ (lane >> 2)) & 1) * 16;
#pragma unroll
    for (int i = 0; i < 28; i += 4)
        stsm4(addr + i * 8, swap ? p[i + 2] : p[i], swap ? p[i + 3] : p[i + 1], swap ? p[i] : p[i + 2], swap ? p[i + 1] : p[i + 3]);
    fence_async_smem();
    __syncwarp();
    if (elect()) {
        tma_st2(m, c0, c1, slab);
        bulk_commit();
        bulk_wait_read();
    }
}
__host__ __device__ constexpr int tile_of(int t) { return 7 * (t >> 2) + 3 * ((t >> 1) & 1) + 2 * (t & 1); }

__global__ void __launch_bounds__(384, 1) fused_kernel(Scratch* sc, const __grid_constant__ Maps maps) {
    extern __shared__ uint8_t smem_raw[];
    if ((uint32_t)__cvta_generic_to_shared(smem_raw) != base) return;
    const int warp = __shfl_sync(0xffffffffu, threadIdx.x >> 5, 0);
    int lane = threadIdx.x & 31;
    asm volatile("" : "+r"(lane));
    const int bid = blockIdx.x < 2 * SPARE0 || blockIdx.x >= 130 ? blockIdx.x
                    : (blockIdx.x >> 1) == SPARE0                ? 128 + (blockIdx.x & 1)
                                                                 : blockIdx.x - 2;
    const bool roleH = bid >= 128;
    const int roleL = (bid >> 4) & 1;
    const int mt = ((bid >> 5) << 2) | ((bid >> 2) & 3);
    const int ns = bid & 3;
    const int par = mt >> 3, blk = mt & 7;

    const int col = ns * 112;
    auto fill = [&](auto i0, auto i1) {
        if (roleL) {
#pragma unroll
            for (int i = decltype(i0)::value; i < decltype(i1)::value; i++) {
                const uint32_t bar = full_bar(i), dst = base + BRING + i * SLOT;
                if (i < 6) mbar_expect(bar, SLOT);
                if (i & 1) {
                    mbar_arrive(bar);
                } else {
                    mbar_expect(bar, SLOT);
                    tma_ld2(base + (i >> 1) * SLOT, &maps.m[M_XA], par * 448 + i * 32, blk * 128, bar);
                }
                if (i < 6) {
                    tma_ld4(dst, &maps.m[M_WQK], 0, i * 32, 0, ns, bar);
                    tma_ld4(dst + 8192, &maps.m[M_WQK], 64, i * 32, 0, ns, bar);
                }
            }
        } else if (!roleH) {
#pragma unroll
            for (int i = decltype(i0)::value; i < decltype(i1)::value; i++) {
                const uint32_t bar = full_bar(i);
                mbar_expect(bar, SLOT);
                mbar_expect(bar, BLOB);
                tma_ld3(base + i * SLOT, &maps.m[M_XB], i * 64, mt * 64, 0, bar);
                tma_ld2(base + BRING + bslot_e(i) * SLOT, &maps.m[M_WR], i * 64, col, bar);
            }
        } else {
#pragma unroll 1
            for (int i = decltype(i0)::value; i < decltype(i1)::value; i++) {
                const uint32_t bar = full_bar(i), dst = base + BRING + i * SLOT;
                mbar_expect(bar, SLOT);
                mbar_expect(bar, SLOT);
                tma_ld4(base + i * SLOT, &maps.m[M_XH], i * 64, 120, 0, 0, bar);
                tma_ld3(dst, &maps.m[M_WV], 0, i * 64, 4 + ns, bar);
                tma_ld3(dst + 8192, &maps.m[M_WV], 64, i * 64, 4 + ns, bar);
            }
        }
    };
    if (warp == 8) {
        if (elect()) {
#pragma unroll
            for (int i = 0; i < 8; i++) mbar_init(base + BAR_FULL + i * 8, 2);
            asm volatile("fence.mbarrier_init.release.cluster;" ::: "memory");
            fill(Int<0>(), Int<LEAD>());
        }
    } else if (warp == 9) {
        if (elect()) {
#pragma unroll
            for (int i = 0; i < 8; i++) mbar_init(base + BAR_EMPTY + i * 8, 8);
            asm volatile("fence.mbarrier_init.release.cluster;" ::: "memory");
        }
    } else if (warp == 10) {
        if (elect()) {
#pragma unroll
            for (int i = 0; i < 5; i++) mbar_init(base + BAR_RDY + i * 8, i < 2 ? 4 : 8);
#pragma unroll
            for (int i = 0; i < 2; i++) mbar_init(base + BAR_HALO + i * 8, 8);
            asm volatile("fence.mbarrier_init.release.cluster;" ::: "memory");
        }
    } else if (warp == 11) {
        if (elect()) {
#pragma unroll
            for (int i = 0; i < 3; i++) mbar_init(base + BAR_DEP + i * 8, 1);
            asm volatile("fence.mbarrier_init.release.cluster;" ::: "memory");
        }
    }
    __syncthreads();

    if (__builtin_expect(warp >= 8, 1)) {
        asm volatile("setmaxnreg.dec.sync.aligned.u32 56;");
#define PROF_FEED_A
#define PROF_FEED_B
        if (__builtin_expect(warp == 8, 1)) {
            if (elect()) {
                PROF(129);
                fill(Int<LEAD>(), Int<7>());
                PROF(134);
                Feed<0> f;
                const int row = mt * 128;
                auto c_run = [&](const CUtensorMap* m, int off, int n0, int n1) {
#pragma unroll 1
                    for (int n = n0; n < n1; n++) {
                        const uint32_t bar = f.acquire<NA>();
                        mbar_expect(bar, SLOT);
                        tma_ld2(f.dst, m, (off + skip_own(n, mt)) * 64, row, bar);
                        PROF_FEED_A;
                        f.next<NA>();
                    }
                };
                if (roleH) {
                } else if (!roleL) {
                    f.seek(14, 0);
                    mbar_wait(base + BAR_RDY, 0);
#pragma unroll 1
                    for (int i = 0; i < 4; i++) {
                        const uint32_t bar = f.acquire<NA>();
                        mbar_expect(bar, SLOT);
                        tma_ld2(f.dst, &maps.m[M_CR + (i >> 1)], ((i & 1) * 16 + mt) * 64, row, bar);
                        mbar_arrive(bar);
                        PROF_FEED_A;
                        f.next<NA>();
                    }
                    c_run(&maps.m[M_CR], 0, 0, 15);
                    c_run(&maps.m[M_CI], 0, 0, NBE);
                    wait_dep(2);
#pragma unroll 1
                    for (int i = 0; i < 7; i++) {
                        const uint32_t bar = f.acquire<NA>();
                        mbar_expect(bar, SLOT);
                        bulk_ld(f.dst, sc->o + (size_t)(mt * 7 + i) * SLOT, SLOT, bar);
                        PROF_FEED_A;
                        f.next<NA>();
                    }
                } else {
#pragma unroll 1
                    for (int i = 4; i < 7; i++) {
                        wait_released(2 * i - 8);
                        mbar_expect(full_bar(2 * i), SLOT);
                        tma_ld2(base + i * SLOT, &maps.m[M_XA], par * 448 + i * 64, blk * 128, full_bar(2 * i));
                    }
                    wait_released(7);
                    f.seek(21, 0);
                    c_run(&maps.m[M_CR], 16, 0, 15);
                    c_run(&maps.m[M_CI], 16, 0, 15);
                    c_run(&maps.m[M_CI], 0, NBE, 15);
                }
            }
        } else if (warp == 11) {
            if (elect()) {
                Feed<BRING> f;
                auto blob_run = [&](auto nbs, int quarter, int n0, int n1) {
                    constexpr int N = decltype(nbs)::value;
                    const uint8_t* src = sc->ab + (size_t)(quarter * 64 + ns) * BLOB;
#pragma unroll 1
                    for (int n = n0; n < n1; n++) {
                        const uint32_t bar = f.template acquire<N>();
                        mbar_expect(bar, BLOB);
                        bulk_ld(f.dst, src + skip_own(n, mt) * (4 * BLOB), BLOB, bar);
                        PROF_FEED_B;
                        f.template next<N>();
                    }
                };
                auto w_run = [&](auto nbs, const CUtensorMap* m, int slice, bool no_a) {
                    constexpr int N = decltype(nbs)::value;
#pragma unroll 1
                    for (int i = 0; i < 7; i++) {
                        const uint32_t bar = f.template acquire<N>();
                        mbar_expect(bar, SLOT);
                        tma_ld3(f.dst, m, 0, i * 64, slice, bar);
                        tma_ld3(f.dst + 8192, m, 64, i * 64, slice, bar);
                        if (no_a) mbar_arrive(bar);
                        PROF_FEED_B;
                        f.template next<N>();
                    }
                };
                if (roleH) {
                    f.seek(7, 0);
                    w_run(Int<7>(), &maps.m[M_WV], 8 + ns, true);
                } else if (!roleL) {
                    f.seek(7, bslot_e(7));
#pragma unroll 1
                    for (int i = 0; i < 7; i++) {
                        const uint32_t bar = f.acquire<5>();
                        mbar_expect(bar, BLOB);
                        tma_ld2(f.dst, &maps.m[M_WI], i * 64, col, bar);
                        mbar_arrive(bar);
                        PROF_FEED_B;
                        f.next<5>();
                    }
                    f.seek(18, bslot_e(18));
                    wait_dep(0);
                    blob_run(Int<7>(), 0, 0, 15);
                    wait_dep(1);
                    blob_run(Int<7>(), 2, 0, NBE);
                    w_run(Int<7>(), &maps.m[M_WO], ns, false);
                } else {
                    f.seek(6, 0);
#pragma unroll 1
                    for (int i = 6; i < 14; i++) {
                        const uint32_t bar = f.acquire<6>();
                        mbar_expect(bar, SLOT);
                        tma_ld4(f.dst, &maps.m[M_WQK], 0, i * 32, 0, ns, bar);
                        tma_ld4(f.dst + 8192, &maps.m[M_WQK], 64, i * 32, 0, ns, bar);
                        if (i & 1) mbar_arrive(bar);
                        PROF_FEED_B;
                        f.next<6>();
                    }
                    w_run(Int<6>(), &maps.m[M_WV], 8 + ns, true);
                    wait_dep(0);
                    blob_run(Int<6>(), 1, 0, 15);
                    wait_dep(1);
                    blob_run(Int<6>(), 3, 0, 15);
                    blob_run(Int<6>(), 2, NBE, 15);
                }
            }
        } else if (roleH) {
        } else if (warp == 10) {
            if (elect()) {
                unsigned* epoch_ptr = &sc->epoch[(bid * 4 + 2) * 8];
                const unsigned ep = *epoch_ptr + 1;
                sts1(base + TAG, ep);
                await(sc, CNT_A + roleL * 4 + ns, ep * 16);
                mbar_arrive(base + BAR_DEP);
                PROF(150);
                await(sc, CNT_B + ns, ep * 16);
                mbar_arrive(base + BAR_DEP + 8);
                PROF(151);
                if (!roleL) {
                    await(sc, CNT_O + mt, ep * 4);
                    mbar_arrive(base + BAR_DEP + 16);
                }
                PROF(152);
                *epoch_ptr = ep;
            }
        } else if (!roleL) {
            if (elect()) {
                mbar_wait(base + BAR_RDY, 0);
                PROF(130);
                signal(sc, CNT_A + ns);
                PROF(131);
                mbar_wait(base + BAR_RDY + 8, 0);
                signal(sc, CNT_A + 4 + ns);
                PROF(135);
                mbar_wait(base + BAR_RDY + 32, 0);
                PROF(132);
                signal(sc, CNT_B + ns);
                PROF(133);
            }
        } else {
            const unsigned t_start = clk32();
            unsigned* epoch_ptr = &sc->epoch[(bid * 4 + 1) * 8];
            const unsigned tag = *epoch_ptr + 1;
#pragma unroll 1
            for (int kv = 0; kv < 2; kv++) {
                uint32_t v[14], t[14];
#pragma unroll
                for (int i = 0; i < 14; i++) v[i] = 0;

                if (blk > 0) {
                    const uint8_t* src = sc->halo + (size_t)(((mt - 1) * 4 + ns) * 2 + kv) * (2 * HSLOT) + lane * 16;
                    pause_until(t_start, HALO_DELAY + kv * 3200);
#pragma unroll 1
                    for (int n = 0; n < SPIN_LIMIT; n++) {
                        bool ok = true;
#pragma unroll
                        for (int i = 0; i < 7; i++) ld_tagged(src + i * 512, v[2 * i], t[2 * i], v[2 * i + 1], t[2 * i + 1]);
#pragma unroll
                        for (int i = 0; i < 14; i++) ok = ok && t[i] == tag;
                        if (__all_sync(0xffffffffu, ok)) break;
                    }
                }
#pragma unroll
                for (int i = 0; i < 14; i++) sts1(base + HALO + kv * (8 * HSLOT) + i * 128 + lane * 4, v[i]);
                warp_arrive(base + BAR_HALO + kv * 8);
                if (lane == 0) PROF(142 + kv);
            }
            if (elect()) {
                mbar_wait(base + BAR_RDY + 16, 0);
                PROF(130);
                signal(sc, CNT_O + mt);
                PROF(131);
                *epoch_ptr = tag;
            }
        }
    } else {
        asm volatile("setmaxnreg.inc.sync.aligned.u32 224;");
        Ring r;
        r.wg = warp >> 2;
        r.zero = blockIdx.y;
        const int wg = warp >> 2;
        if (PINGPONG && wg) nb_arrive(1, 256);
        uint8_t* part = sc->part + (size_t)(ns * 16 + mt) * (2 * BLOB) + warp * 512 + lane * 16;
        uint32_t p[28];

        if (roleH) {
            unsigned* epoch_ptr = &sc->epoch[bid * 4 * 8];
            const unsigned tag = *epoch_ptr + 1;
            uint8_t* hout = sc->halo + (size_t)((warp * 8 + ns) * 2) * (2 * HSLOT) + lane * 16;
            float x0[56], x1[56];
            r.seek(0, 0);
            r.run<XWN, 7, true>(x0);
#pragma unroll 1
            for (int i = 1; i < 7; i++) r.run<XWN, 7, false>(x0);
            r.run<XWN, 7, true>(x1);
            acc_fence(x0);
            pack_all(x0, p);
#pragma unroll
            for (int i = 0; i < 14; i++) st_tagged(hout + (i & 1) * (16 * HSLOT) + (i >> 1) * 512, p[(i >> 1) * 4 + (i & 1)], p[(i >> 1) * 4 + (i & 1) + 2], tag);
#pragma unroll 1
            for (int i = 1; i < 7; i++) r.run<XWN, 7, false>(x1);
            asm volatile("wgmma.wait_group.sync.aligned 0;" ::: "memory");
            acc_fence(x1);
            pack_all(x1, p);
#pragma unroll
            for (int i = 0; i < 28; i++) p[i] = movm(p[i]);
#pragma unroll
            for (int i = 0; i < 14; i++)
                st_tagged(hout + 2 * HSLOT + (i & 1) * (16 * HSLOT) + (i >> 1) * 512, p[(i >> 1) * 4 + (i & 1)], p[(i >> 1) * 4 + (i & 1) + 2], tag);
            if (threadIdx.x == 0) *epoch_ptr = tag;
        } else if (!roleL) {
            uint8_t* blob = sc->ab + (size_t)((wg * 16 + mt) * 4 + ns) * BLOB + (warp & 3) * WSLOT + lane * 4;
            const uint32_t own = base + BRING + wg * SLOT + (warp & 3) * WSLOT + lane * 16;
            float x0[56], x1[56];
            r.seek(0, bslot_e(0));
            r.run<XW, 7, true>(x0);
            r.run<XW, 7, false>(x0);
            r.seek(2, bslot_e(2));
#pragma unroll 1
            for (int i = 2; i < 7; i++) r.run<XW, 5, false>(x0);

            r.seek(7, bslot_e(7));
            r.run<XW, 5, true, -1>(x1);
            acc_fence(x0);
            pack_all(x0, p);
#pragma unroll
            for (int i = 0; i < 2; i++) {
                if (wg == i) store_frags<0, A_FIRST>(blob, p);
                else stage_frags<0, 16>(own + 5 * SLOT, p);
                r.run<XW, 5, false, -1>(x1);
                if (wg == i) {
                    store_frags<A_FIRST, 28>(blob, p);
                    warp_arrive(base + BAR_RDY + i * 8);
                } else {
                    stage_frags<16, 28>(own + 5 * SLOT, p);
                    warp_arrive(base + BAR_RDY + 16);
                }
                r.run<XW, 5, false, -1>(x1);
            }
            r.run<XW, 5, false, -1>(x1);
            r.run<XW, 5, false, -1>(x1);

            mbar_wait(base + BAR_RDY + 16, 0);
            fence_async_smem();
            r.seek(14, bslot_e(14));
            r.run<BIG, 7, true>(x0);
            acc_fence(x1);
            pack_all(x1, p);
            wait_released(10);
            stage_frags<0, 28>(own, p);
            warp_arrive(base + BAR_RDY + 24);
            r.run<BIG, 7, false>(x0);
            mbar_wait(base + BAR_RDY + 24, 0);
            fence_async_smem();
            blob += (size_t)128 * BLOB;
#pragma unroll
            for (int i = 0; i < 28; i++) {
                if (i % B_SLICE == 0) r.run<BIG, 7, false>(x0);
                stg1(blob + i * 128, p[i]);
            }
            warp_arrive(base + BAR_RDY + 32);
#pragma unroll 1
            for (int i = 17 + 27 / B_SLICE; i < POUT; i++) r.run<BIG, 7, false>(x0);

            const uint32_t tag = lds1(base + TAG);
            r.seek(POUT, bslot_e(POUT));
            r.run<OUT, 7, true>(x1);
            acc_fence(x0);
            pack_all(x0, p);
#pragma unroll
            for (int i = 0; i < 7; i++) {
                if (i == 2 || i == 5) r.run<OUT, 7, false>(x1);
                st_part(part + i * 4096, p + 4 * i, tag & 1);
            }
#pragma unroll 1
            for (int i = 3; i < 7; i++) r.run<OUT, 7, false>(x1);

            wait_released(ELAST - 6);
            asm volatile("wgmma.wait_group.sync.aligned 0;" ::: "memory");
            acc_fence(x1);
            pack_all(x1, p);
            const uint32_t slab = base + (wg ? BRING + bslot_e(ELAST - 6) * SLOT : ((ELAST - 6) % NA) * SLOT) + (warp & 3) * WSLOT;
            store_out(p, lane, slab, &maps.m[M_OUTA], par * 896 + col, blk * 128 + warp * 16);
        } else {
            const int g = lane >> 2, tig = lane & 3;
            const uint32_t hin = base + HALO + warp * HSLOT + lane * 4;
            auto publish = [&](const uint32_t (&h)[14], int kv) {
                if (warp < 7) {
#pragma unroll
                    for (int c = 0; c < 14; c++) sts1(hin + HSLOT + c * 128, h[c]);
                    warp_arrive(base + BAR_HALO + kv * 8);
                }
            };
            float y0[56], y1[56], y2[56];
            r.seek(0, 0);
            r.run<QK, 6, true>(y0, y1);
#pragma unroll 1
            for (int i = 1; i < 14; i++) r.run<QK, 6, false>(y0, y1);

            uint32_t m1[8][4], m0[8][4], lo[14], hi[14];
            r.seek(14, bslot_l(14));
            r.run<XWN, 6, true>(y2);
            acc_fence(y0);
            acc_fence(y1);
#pragma unroll
            for (int c = 0; c < 14; c++) hi[c] = pack2(y1[4 * c + 2], y1[4 * c + 3]);
            publish(hi, 0);
            r.run<XWN, 6, false>(y2);
            r.pin();
#pragma unroll
            for (int c = 0; c < 14; c++) lo[c] = pack2(y1[4 * c], y1[4 * c + 1]);
#pragma unroll
            for (int t = 0; t < 8; t++) {
                const int c = tile_of(t);
                const bool shared = (t & 3) == 2;
                m1[t][0] = shared ? dup(lo[c], r.zero) : lo[c];
                m1[t][1] = shared ? dup(hi[c], r.zero) : hi[c];
                m1[t][2] = lo[c + 1];
                m1[t][3] = hi[c + 1];
                m0[t][0] = dup(m1[t][0], r.zero);
                m0[t][2] = dup(lo[c + 1], 2 * r.zero);
            }
            r.run<XWN, 6, false>(y2);
            r.pin();
            uint32_t q[2][8][2];
#pragma unroll
            for (int b = 0; b < 2; b++) {
                uint32_t v[14];
#pragma unroll
                for (int c = 0; c < 14; c++) v[c] = pack2(y0[4 * c + 2 * b], y0[4 * c + 2 * b + 1]);
#pragma unroll
                for (int t = 0; t < 8; t++) {
                    const int c = tile_of(t);
                    q[b][t][0] = (t & 3) == 2 ? (tig >= 2 ? v[c] : 0u) : v[c];
                    q[b][t][1] = (t & 3) == 1 ? (tig < 2 ? v[c + 1] : 0u) : v[c + 1];
                }
            }
            r.run<XWN, 6, false>(y2);
            mbar_wait(base + BAR_HALO, 0);
#pragma unroll
            for (int t = 0; t < 8; t++) {
                m0[t][1] = lds1(hin + tile_of(t) * 128 + ((t & 3) == 2 ? r.zero : 0u));
                m0[t][3] = lds1(hin + tile_of(t) * 128 + 128);
            }
            r.wait();
            float s[8][4];
#pragma unroll
            for (int step = 0; step < 2; step++) {
#pragma unroll
                for (int i = 0; i < 8; i++) {
                    const int b = 1 - (i >> 2), h = i & 3, t = 2 * h + step;
                    float (&d)[4] = s[2 * h + b];
                    if (step == 0) d[0] = d[1] = d[2] = d[3] = 0.f;
                    mma16816(d, b ? m1[t] : m0[t], q[b][t][0], q[b][t][1]);
                }
            }
            r.pin();
            r.run<XWN, 6, false, 1, false>(y2);
            r.pin();

            uint32_t pr[8], mx[4], mx1[4];
            {
                const bool cur0 = g <= 2 * tig, cur1 = g <= 2 * tig + 1;
#pragma unroll
                for (int i = 0; i < 8; i++) {
                    const int c = (i & 1) ? 2 : 0;
                    pr[i] = movm(pack2(cur0 ? s[i][c] : s[i][2 - c], cur1 ? s[i][c + 1] : s[i][3 - c]));
                }
            }
            r.run<XWN, 6, false>(y2);
            r.pin();
            const uint32_t curmask = (2 * tig <= g ? 0x0000FFFFu : 0u) | (2 * tig + 1 <= g ? 0xFFFF0000u : 0u);
            {
                const uint32_t keep = (blk == 0 && warp == 0) ? curmask : 0xFFFFFFFFu;
#pragma unroll
                for (int i = 0; i < 4; i++) {
                    pr[2 * i] = (pr[2 * i] & keep) | (0xCF9ECF9Eu & ~keep);
                    mx[i] = max2(__byte_perm(pr[2 * i], pr[2 * i + 1], 0x5410), __byte_perm(pr[2 * i], pr[2 * i + 1], 0x7632));
                }
#pragma unroll
                for (int i = 0; i < 4; i++) mx[i] = max2(mx[i], __shfl_xor_sync(0xffffffffu, mx[i], 1));
#pragma unroll
                for (int i = 0; i < 4; i++) mx1[i] = __shfl_xor_sync(0xffffffffu, mx[i], 2);
            }
            r.run<XWN, 6, false>(y2);
            r.pin();
            constexpr float SCL = 0.18898223650461362f * 1.4426950408889634f;
            float e0[8], e1[8], sm[8], sm1[8];
#pragma unroll
            for (int i = 0; i < 8; i++) {
                const uint32_t m2 = max2(mx[i >> 1], mx1[i >> 1]);
                sm[i] = ((i & 1) ? bf_hi(m2) : bf_lo(m2)) * -SCL;
                e0[i] = ex2(fmaf(bf_lo(pr[i]), SCL, sm[i]));
            }

            r.seek(21, bslot_l(21));
            r.run<BIG, 6, true>(y0);
            acc_fence(y2);
#pragma unroll
            for (int c = 0; c < 14; c++) hi[c] = movm(pack2(y2[4 * c + 2], y2[4 * c + 3]));
            r.run<BIG, 6, false>(y0);
            wait_released(18);
            publish(hi, 1);
            r.run<BIG, 6, false>(y0);
            r.pin();
#pragma unroll
            for (int i = 0; i < 8; i++) {
                e1[i] = ex2(fmaf(bf_hi(pr[i]), SCL, sm[i]));
                sm[i] = e0[i] + e1[i];
                sm1[i] = __shfl_xor_sync(0xffffffffu, sm[i], 1);
            }
            r.run<BIG, 6, false>(y0);
            r.pin();
#pragma unroll
            for (int c = 0; c < 14; c++) lo[c] = movm(pack2(y2[4 * c], y2[4 * c + 1]));
            r.run<BIG, 6, false>(y0);
            r.pin();
#pragma unroll
            for (int i = 0; i < 8; i++) {
                sm[i] += sm1[i];
                sm1[i] = __shfl_xor_sync(0xffffffffu, sm[i], 2);
            }
#pragma unroll
            for (int t = 0; t < 8; t++) {
                const int c = tile_of(t);
                const bool shared = (t & 3) == 2;
                m1[t][0] = shared ? dup(lo[c], r.zero) : lo[c];
                m1[t][1] = lo[c + 1];
                m1[t][2] = shared ? dup(hi[c], r.zero) : hi[c];
                m1[t][3] = hi[c + 1];
                m0[t][0] = dup(m1[t][0], r.zero);
                m0[t][1] = dup(lo[c + 1], 2 * r.zero);
            }
            r.run<BIG, 6, false>(y0);
            r.pin();
            uint32_t pb[8][2];
#pragma unroll
            for (int i = 0; i < 8; i++) {
                const float inv = rcp(sm[i] + sm1[i]);
                const uint32_t w = pack2(e0[i] * inv, e1[i] * inv);
                pb[i][i & 1] = band(w, curmask);
                pb[i][1 - (i & 1)] = band(w, ~curmask);
            }
            r.run<BIG, 6, false>(y0);
            mbar_wait(base + BAR_HALO + 8, 0);
            const uint32_t vin = warp ? hin : hin + 8 * HSLOT;
#pragma unroll
            for (int t = 0; t < 8; t++) {
                m0[t][2] = lds1(vin + tile_of(t) * 128 + ((t & 3) == 2 ? r.zero : 0u));
                m0[t][3] = lds1(vin + tile_of(t) * 128 + 128);
            }
            r.wait();
            float o[2][8][4];
#pragma unroll
            for (int i = 0; i < 16; i++) {
                const int b = 1 - (i >> 3), t = i & 7;
                float (&d)[4] = o[b][t];
                d[0] = d[1] = d[2] = d[3] = 0.f;
                mma16816(d, b ? m1[t] : m0[t], pb[(t & 6) + b][0], pb[(t & 6) + b][1]);
            }
            r.pin();
            r.run<BIG, 6, false, 1, false>(y0);
            r.pin();
            uint8_t* odst = sc->o + (size_t)mt * 7 * SLOT + ns * (14 * 2048) + warp * 256 + lane * 4;
#pragma unroll
            for (int hp = 0; hp < 2; hp++) {
#pragma unroll
                for (int b = 0; b < 2; b++) {
                    const float (&u)[8][4] = o[b];
                    const int t = 4 * hp;
                    uint32_t* w = p + 14 * hp + b;
                    w[0] = pack2(u[t][0], u[t][1]);
                    w[2] = pack2(u[t][2], u[t][3]);
                    w[4] = pack2(u[t + 1][0], u[t + 1][1]);
                    w[6] = pack2(g < 4 ? u[t + 1][2] : u[t + 2][0], g < 4 ? u[t + 1][3] : u[t + 2][1]);
                    w[8] = pack2(u[t + 2][2], u[t + 2][3]);
                    w[10] = pack2(u[t + 3][0], u[t + 3][1]);
                    w[12] = pack2(u[t + 3][2], u[t + 3][3]);
                }
            }
#pragma unroll
            for (int i = 0; i < 28; i++) {
                if (i && i % O_SLICE == 0) r.run<BIG, 6, false>(y0);
                stg1(odst + (i >> 1) * 2048 + (i & 1) * 128, p[i]);
            }
            warp_arrive(base + BAR_RDY + 16);

#pragma unroll 1
            for (int i = 29 + 27 / O_SLICE; i <= LLAST - PART_LEAD; i++) r.run<BIG, 6, false>(y0);
            const uint32_t tag = lds1(base + TAG);
#pragma unroll
            for (int i = 0; i < 7; i++) ld_tagged(part + i * 4096, p[4 * i], p[4 * i + 1], p[4 * i + 2], p[4 * i + 3]);
#pragma unroll 1
            for (int i = 0; i < PART_LEAD; i++) r.run<BIG, 6, false>(y0);
#pragma unroll 1
            for (int n = 0; n < SPIN_LIMIT; n++) {
                uint32_t stale = 0;
#pragma unroll
                for (int i = 0; i < 28; i += 2) stale |= p[i] ^ tag;
                if (__all_sync(0xffffffffu, !(stale & 1))) break;
#pragma unroll
                for (int i = 0; i < 7; i++) ld_tagged(part + i * 4096, p[4 * i], p[4 * i + 1], p[4 * i + 2], p[4 * i + 3]);
            }
            wait_released(LLAST - 6);
            asm volatile("wgmma.wait_group.sync.aligned 0;" ::: "memory");
            acc_fence(y0);
#pragma unroll
            for (int i = 0; i < 28; i++) p[i] = add2(pack2(y0[2 * i], y0[2 * i + 1]), p[i]);
            const uint32_t slab = base + (wg ? HALO : ((LLAST - 6) % NA) * SLOT) + (warp & 3) * WSLOT;
            store_out(p, lane, slab, &maps.m[M_OUTB], 448 + col, mt * 128 + warp * 16);
        }
    }
}

typedef CUresult (*EncodeFn)(CUtensorMap*, CUtensorMapDataType, cuuint32_t, void*, const cuuint64_t*, const cuuint64_t*,
                             const cuuint32_t*, const cuuint32_t*, CUtensorMapInterleave, CUtensorMapSwizzle,
                             CUtensorMapL2promotion, CUtensorMapFloatOOBfill);

struct Dim { uint64_t size, stride; uint32_t box; };
void encode(EncodeFn fn, CUtensorMap* m, const void* ptr, CUtensorMapSwizzle sw, Dim d0, Dim d1, Dim d2 = {0, 0, 0}, Dim d3 = {0, 0, 0}) {
    const cuuint64_t dims[4] = {d0.size, d1.size, d2.size, d3.size};
    const cuuint64_t strides[3] = {d1.stride, d2.stride, d3.stride};
    const cuuint32_t box[4] = {d0.box, d1.box, d2.box, d3.box};
    const cuuint32_t es[4] = {1, 1, 1, 1};
    fn(m, CU_TENSOR_MAP_DATA_TYPE_BFLOAT16, d3.size ? 4 : d2.size ? 3 : 2, const_cast<void*>(ptr), dims, strides, box, es,
       CU_TENSOR_MAP_INTERLEAVE_NONE, sw, CU_TENSOR_MAP_L2_PROMOTION_L2_128B, CU_TENSOR_MAP_FLOAT_OOB_FILL_NONE);
}

}

extern "C" void kernel_launch(void* const* d_in, const int* in_sizes, int n_in, void* d_out, int out_size) {
    (void)in_sizes; (void)n_in; (void)out_size;
    void* fnp = nullptr;
    cudaDriverEntryPointQueryResult st;
    cudaGetDriverEntryPoint("cuTensorMapEncodeTiled", &fnp, cudaEnableDefault, &st);
    EncodeFn fn = (EncodeFn)fnp;
    void* scratch = nullptr;
    cudaGetSymbolAddress(&scratch, g_scratch);
    cudaFuncSetAttribute(fused_kernel, cudaFuncAttributeMaxDynamicSharedMemorySize, SMEM_BYTES);

    const CUtensorMapSwizzle S128 = CU_TENSOR_MAP_SWIZZLE_128B, S0 = CU_TENSOR_MAP_SWIZZLE_NONE;
    Maps maps;
    encode(fn, &maps.m[M_XA], d_in[0], S128, {896, 2, 64}, {1024, 1792, 128});
    encode(fn, &maps.m[M_WQK], d_in[1], S128, {112, 2, 64}, {448, 2688, 32}, {3, 896, 2}, {4, 224, 1});
    encode(fn, &maps.m[M_WV], d_in[1], S128, {112, 2, 64}, {448, 2688, 64}, {12, 224, 1});
    encode(fn, &maps.m[M_XH], d_in[0], S128, {448, 2, 64}, {128, 1792, 8}, {8, 128 * 1792, 8}, {2, 896, 2});
    encode(fn, &maps.m[M_WO], d_in[2], S128, {112, 2, 64}, {448, 896, 64}, {4, 224, 1});
    encode(fn, &maps.m[M_XB], d_in[3], S128, {448, 2, 64}, {1024, 896, 64}, {2, 896 * 1024, 2});
    encode(fn, &maps.m[M_CR], d_in[4], S128, {2048, 2, 64}, {2048, 4096, 128});
    encode(fn, &maps.m[M_CI], d_in[5], S128, {2048, 2, 64}, {2048, 4096, 128});
    encode(fn, &maps.m[M_WR], d_in[6], S128, {448, 2, 64}, {448, 896, 112});
    encode(fn, &maps.m[M_WI], d_in[7], S128, {448, 2, 64}, {448, 896, 112});
    encode(fn, &maps.m[M_OUTA], d_out, S0, {1792, 2, 112}, {1024, 3584, 16});
    encode(fn, &maps.m[M_OUTB], d_out, S0, {896, 2, 112}, {2048, 1792, 16});

    fused_kernel<<<132, 384, SMEM_BYTES>>>((Scratch*)scratch, maps);
}
```

```cpp
#include <cuda.h>
#include <cuda_bf16.h>
#include <cuda_runtime.h>
#include <stdint.h>

namespace {

constexpr uint32_t SLOT = 16384;
constexpr int NA = 7;
constexpr uint32_t BRING = NA * SLOT;
constexpr uint32_t HALO = BRING + 6 * SLOT;
constexpr uint32_t HSLOT = 1792;
constexpr uint32_t WSLOT = 3584;
constexpr uint32_t BLOB = 14336;
constexpr uint32_t BARS = 14 * SLOT;
constexpr uint32_t BAR_FULL = BARS;
constexpr uint32_t BAR_EMPTY = BARS + 64;
constexpr uint32_t BAR_RDY = BARS + 128;
constexpr uint32_t BAR_DEP = BARS + 168;
constexpr uint32_t BAR_HALO = BARS + 192;
constexpr uint32_t TAG = BARS + 208;
constexpr uint32_t SMEM_BYTES = BARS + 256 + 1024;
constexpr uint32_t base = 1024;
constexpr int SPIN_LIMIT = 1 << 16;

#define E_EXTRA 0
#define HALO_DELAY 7000
#define O_SLICE 4
#define B_SLICE 4
#define LEAD 3
#define TURN 3
#define MAPPING 2
#define SPARE0 12
constexpr int NBE = 13 + E_EXTRA;
constexpr int POUT = 33 + NBE;
constexpr int ELAST = POUT + 6;
constexpr int LLAST = 52 - E_EXTRA;

enum { M_XA, M_XH, M_WQK, M_WV, M_WO, M_XB, M_WR, M_WI, M_CR, M_CI, M_OUTA, M_OUTB, M_COUNT };
struct __align__(64) Maps { CUtensorMap m[M_COUNT]; };

constexpr int CNT_A = 0;
constexpr int CNT_B = 8;
constexpr int CNT_O = 16;
constexpr int CNT_COUNT = 32;

struct Scratch {
    uint8_t ab[64 * 4 * BLOB];
    uint8_t o[16 * 7 * SLOT];
    uint8_t part[64 * 2 * BLOB];
    uint8_t halo[64 * 2 * 2 * HSLOT];
    unsigned cnt[CNT_COUNT * 32];
    unsigned epoch[132 * 4 * 8];
};
__device__ __align__(1024) Scratch g_scratch;

__device__ __forceinline__ unsigned clk32() { unsigned c; asm volatile("mov.u32 %0, %%clock;" : "=r"(c)); return c; }
__device__ __forceinline__ void pause_until(unsigned t0, unsigned cycles) {
    while (clk32() - t0 < cycles) {}
}

#define PROF(idx)

__device__ __forceinline__ void mbar_init(uint32_t bar, uint32_t cnt) {
    asm volatile("mbarrier.init.shared::cta.b64 [%0], %1;" ::"r"(bar), "r"(cnt) : "memory");
}
__device__ __forceinline__ void mbar_expect(uint32_t bar, uint32_t bytes) {
    asm volatile("mbarrier.arrive.expect_tx.shared::cta.b64 _, [%0], %1;" ::"r"(bar), "r"(bytes) : "memory");
}
__device__ __forceinline__ void mbar_arrive(uint32_t bar) {
    asm volatile("mbarrier.arrive.shared::cta.b64 _, [%0];" ::"r"(bar) : "memory");
}
__device__ __forceinline__ bool mbar_try(uint32_t bar, uint32_t parity) {
    uint32_t ok;
    asm volatile("{\n.reg .pred p;\nmbarrier.try_wait.parity.shared::cta.b64 p, [%1], %2;\nselp.u32 %0, 1, 0, p;\n}\n"
                 : "=r"(ok) : "r"(bar), "r"(parity) : "memory");
    return ok;
}
__device__ __forceinline__ void mbar_wait(uint32_t bar, uint32_t parity) {
#pragma unroll 1
    for (int n = 0; n < SPIN_LIMIT; n++)
        if (mbar_try(bar, parity)) break;
}
__device__ __forceinline__ bool elect() {
    uint32_t p;
    asm volatile("{\n.reg .pred p;\nelect.sync _|p, 0xffffffff;\nselp.u32 %0, 1, 0, p;\n}\n" : "=r"(p));
    return p;
}
__device__ __forceinline__ void nb_sync(int id, int n) { asm volatile("bar.sync %0, %1;" ::"r"(id), "r"(n) : "memory"); }
__device__ __forceinline__ void nb_arrive(int id, int n) { asm volatile("bar.arrive %0, %1;" ::"r"(id), "r"(n) : "memory"); }
__device__ __forceinline__ void warp_arrive(uint32_t bar) {
    __syncwarp();
    if (elect()) mbar_arrive(bar);
}
__device__ __forceinline__ uint32_t band(uint32_t x, uint32_t m) {
    uint32_t r;
    asm volatile("and.b32 %0, %1, %2;" : "=r"(r) : "r"(x), "r"(m));
    return r;
}
__device__ __forceinline__ uint32_t dup(uint32_t x, uint32_t zero) {
    uint32_t r;
    asm volatile("xor.b32 %0, %1, %2;" : "=r"(r) : "r"(x), "r"(zero));
    return r;
}

__device__ __forceinline__ void tma_ld2(uint32_t dst, const CUtensorMap* m, int c0, int c1, uint32_t bar) {
    asm volatile("cp.async.bulk.tensor.2d.shared::cluster.global.mbarrier::complete_tx::bytes [%0], [%1, {%3, %4}], [%2];"
                 ::"r"(dst), "l"(m), "r"(bar), "r"(c0), "r"(c1) : "memory");
}
__device__ __forceinline__ void tma_ld3(uint32_t dst, const CUtensorMap* m, int c0, int c1, int c2, uint32_t bar) {
    asm volatile("cp.async.bulk.tensor.3d.shared::cluster.global.mbarrier::complete_tx::bytes [%0], [%1, {%3, %4, %5}], [%2];"
                 ::"r"(dst), "l"(m), "r"(bar), "r"(c0), "r"(c1), "r"(c2) : "memory");
}
__device__ __forceinline__ void tma_ld4(uint32_t dst, const CUtensorMap* m, int c0, int c1, int c2, int c3, uint32_t bar) {
    asm volatile("cp.async.bulk.tensor.4d.shared::cluster.global.mbarrier::complete_tx::bytes [%0], [%1, {%3, %4, %5, %6}], [%2];"
                 ::"r"(dst), "l"(m), "r"(bar), "r"(c0), "r"(c1), "r"(c2), "r"(c3) : "memory");
}
__device__ __forceinline__ void bulk_ld(uint32_t dst, const void* src, uint32_t bytes, uint32_t bar) {
    asm volatile("cp.async.bulk.shared::cluster.global.mbarrier::complete_tx::bytes [%0], [%1], %2, [%3];"
                 ::"r"(dst), "l"(src), "r"(bytes), "r"(bar) : "memory");
}
__device__ __forceinline__ void tma_st2(const CUtensorMap* m, int c0, int c1, uint32_t src) {
    asm volatile("cp.async.bulk.tensor.2d.global.shared::cta.bulk_group [%0, {%1, %2}], [%3];"
                 ::"l"(m), "r"(c0), "r"(c1), "r"(src) : "memory");
}
__device__ __forceinline__ void bulk_commit() { asm volatile("cp.async.bulk.commit_group;" ::: "memory"); }
__device__ __forceinline__ void bulk_wait_read() { asm volatile("cp.async.bulk.wait_group.read 0;" ::: "memory"); }
__device__ __forceinline__ void fence_async_smem() { asm volatile("fence.proxy.async.shared::cta;" ::: "memory"); }
__device__ __forceinline__ void fence_async_global() { asm volatile("fence.proxy.async.global;" ::: "memory"); }

__device__ __forceinline__ void signal(Scratch* sc, int idx) {
    asm volatile("fence.proxy.async;\nred.relaxed.gpu.global.add.u32 [%0], 1;" ::"l"(&sc->cnt[idx * 32]) : "memory");
}
__device__ __forceinline__ void await(Scratch* sc, int idx, unsigned target) {
#pragma unroll 1
    for (int n = 0; n < SPIN_LIMIT; n++) {
        unsigned v;
        asm volatile("ld.relaxed.gpu.global.u32 %0, [%1];" : "=r"(v) : "l"(&sc->cnt[idx * 32]) : "memory");
        if ((int)(v - target) >= 0) break;
    }
    asm volatile("fence.acquire.gpu;" ::: "memory");
}
__device__ __forceinline__ void wait_dep(int k) {
    mbar_wait(base + BAR_DEP + k * 8, 0);
    fence_async_global();
}

#define WG_REGS                                                                                                     \
    "{%0,%1,%2,%3,%4,%5,%6,%7,%8,%9,%10,%11,%12,%13,%14,%15,%16,%17,%18,%19,%20,%21,%22,%23,%24,%25,%26,%27,"       \
    "%28,%29,%30,%31,%32,%33,%34,%35,%36,%37,%38,%39,%40,%41,%42,%43,%44,%45,%46,%47,%48,%49,%50,%51,%52,%53,%54,%55}"
#define WG_OPS(C)                                                                                                   \
    C(d[0]), C(d[1]), C(d[2]), C(d[3]), C(d[4]), C(d[5]), C(d[6]), C(d[7]), C(d[8]), C(d[9]), C(d[10]), C(d[11]),   \
    C(d[12]), C(d[13]), C(d[14]), C(d[15]), C(d[16]), C(d[17]), C(d[18]), C(d[19]), C(d[20]), C(d[21]), C(d[22]),   \
    C(d[23]), C(d[24]), C(d[25]), C(d[26]), C(d[27]), C(d[28]), C(d[29]), C(d[30]), C(d[31]), C(d[32]), C(d[33]),   \
    C(d[34]), C(d[35]), C(d[36]), C(d[37]), C(d[38]), C(d[39]), C(d[40]), C(d[41]), C(d[42]), C(d[43]), C(d[44]),   \
    C(d[45]), C(d[46]), C(d[47]), C(d[48]), C(d[49]), C(d[50]), C(d[51]), C(d[52]), C(d[53]), C(d[54]), C(d[55])

template <int TA, int TB, int SB, bool INIT>
__device__ __forceinline__ void wgmma112(float (&d)[56], uint64_t da, uint64_t db) {
    if (INIT) {
        asm volatile("{\n.reg .pred p;\nsetp.ne.b32 p, 0, 0;\n"
                     "wgmma.mma_async.sync.aligned.m64n112k16.f32.bf16.bf16 " WG_REGS ", %56, %57, p, 1, %59, %60, %58;\n}\n"
                     : WG_OPS("=f") : "l"(da), "l"(db), "n"(TB), "n"(SB), "n"(TA));
    } else {
        asm volatile("{\n.reg .pred p;\nsetp.ne.b32 p, 1, 0;\n"
                     "wgmma.mma_async.sync.aligned.m64n112k16.f32.bf16.bf16 " WG_REGS ", %56, %57, p, 1, %59, %60, %58;\n}\n"
                     : WG_OPS("+f") : "l"(da), "l"(db), "n"(TB), "n"(SB), "n"(TA));
    }
}
__device__ __forceinline__ void acc_fence(float (&d)[56]) {
#pragma unroll
    for (int i = 0; i < 56; i++) asm volatile("" : "+f"(d[i])::"memory");
}

__device__ __forceinline__ uint32_t pack2(float lo, float hi) {
    uint32_t r;
    asm volatile("cvt.rn.bf16x2.f32 %0, %1, %2;" : "=r"(r) : "f"(hi), "f"(lo));
    return r;
}
__device__ __forceinline__ uint32_t movm(uint32_t a) {
    uint32_t r;
    asm volatile("movmatrix.sync.aligned.m8n8.trans.b16 %0, %1;" : "=r"(r) : "r"(a));
    return r;
}
__device__ __forceinline__ void stsm4(uint32_t addr, uint32_t a, uint32_t b, uint32_t c, uint32_t d) {
    asm volatile("stmatrix.sync.aligned.m8n8.x4.shared.b16 [%0], {%1,%2,%3,%4};" ::"r"(addr), "r"(a), "r"(b), "r"(c), "r"(d) : "memory");
}
__device__ __forceinline__ void sts1(uint32_t addr, uint32_t a) { asm volatile("st.shared.b32 [%0], %1;" ::"r"(addr), "r"(a) : "memory"); }
__device__ __forceinline__ uint32_t lds1(uint32_t addr) {
    uint32_t a;
    asm volatile("ld.shared.b32 %0, [%1];" : "=r"(a) : "r"(addr) : "memory");
    return a;
}
__device__ __forceinline__ void stg1(uint8_t* p, uint32_t a) { asm volatile("st.global.b32 [%0], %1;" ::"l"(p), "r"(a) : "memory"); }
__device__ __forceinline__ void st_part(uint8_t* p, const uint32_t* v, uint32_t parity) {
    asm volatile("{\n.reg .b64 x, y;\nmov.b64 x, {%1, %2};\nmov.b64 y, {%3, %4};\nst.relaxed.gpu.global.v2.b64 [%0], {x, y};\n}\n"
                 ::"l"(p), "r"((v[0] & ~1u) | parity), "r"(v[1]), "r"((v[2] & ~1u) | parity), "r"(v[3]) : "memory");
}
__device__ __forceinline__ void mma16816(float (&d)[4], const uint32_t (&a)[4], uint32_t b0, uint32_t b1) {
    asm volatile("mma.sync.aligned.m16n8k16.row.col.f32.bf16.bf16.f32 {%0,%1,%2,%3}, {%4,%5,%6,%7}, {%8,%9}, {%0,%1,%2,%3};"
                 : "+f"(d[0]), "+f"(d[1]), "+f"(d[2]), "+f"(d[3]) : "r"(a[0]), "r"(a[1]), "r"(a[2]), "r"(a[3]), "r"(b0), "r"(b1));
}
__device__ __forceinline__ uint32_t add2(uint32_t a, uint32_t b) {
    uint32_t r;
    asm("add.rn.bf16x2 %0, %1, %2;" : "=r"(r) : "r"(a), "r"(b));
    return r;
}
__device__ __forceinline__ uint32_t max2(uint32_t a, uint32_t b) {
    uint32_t r;
    asm("max.bf16x2 %0, %1, %2;" : "=r"(r) : "r"(a), "r"(b));
    return r;
}
__device__ __forceinline__ void st_tagged(uint8_t* p, uint32_t a, uint32_t b, uint32_t tag) {
    asm volatile("{\n.reg .b64 x, y;\nmov.b64 x, {%1, %3};\nmov.b64 y, {%2, %3};\nst.relaxed.gpu.global.v2.b64 [%0], {x, y};\n}\n"
                 ::"l"(p), "r"(a), "r"(b), "r"(tag) : "memory");
}
__device__ __forceinline__ void ld_tagged(const uint8_t* p, uint32_t& a, uint32_t& ta, uint32_t& b, uint32_t& tb) {
    asm volatile("{\n.reg .b64 x, y;\nld.relaxed.gpu.global.v2.b64 {x, y}, [%4];\nmov.b64 {%0, %1}, x;\nmov.b64 {%2, %3}, y;\n}\n"
                 : "=r"(a), "=r"(ta), "=r"(b), "=r"(tb) : "l"(p) : "memory");
}
__device__ __forceinline__ float bf_lo(uint32_t v) { return __uint_as_float(v << 16); }
__device__ __forceinline__ float bf_hi(uint32_t v) { return __uint_as_float(v & 0xFFFF0000u); }
__device__ __forceinline__ float rcp(float x) { float r; asm("rcp.approx.ftz.f32 %0, %1;" : "=f"(r) : "f"(x)); return r; }
__device__ __forceinline__ float ex2(float x) { float r; asm volatile("ex2.approx.ftz.f32 %0, %1;" : "=f"(r) : "f"(x)); return r; }

__device__ __forceinline__ uint32_t full_bar(int stage) { return base + BAR_FULL + (stage & 7) * 8; }
__device__ __forceinline__ void wait_released(int j) { mbar_wait(base + BAR_EMPTY + (j & 7) * 8, (j >> 3) & 1); }

template <int V>
struct Int { static constexpr int value = V; };

__host__ __device__ constexpr int bslot_e(int i) { return (i < 2 || i >= 14) ? (i + 5) % 7 : (i + 1) % 5; }
__host__ __device__ constexpr int bslot_l(int i) { return i % 6; }

template <uint32_t OFF>
struct Feed {
    int stage;
    uint32_t dst;
    __device__ __forceinline__ void seek(int i, int slot) { stage = i; dst = base + OFF + slot * SLOT; }
    template <int N>
    __device__ __forceinline__ uint32_t acquire() { wait_released(stage - N); return full_bar(stage); }
    template <int N>
    __device__ __forceinline__ void next() {
        stage++;
        dst += SLOT;
        if (dst == base + OFF + N * SLOT) dst = base + OFF;
    }
};
__device__ __forceinline__ int skip_own(int n, int mt) { return n == mt ? 15 : n; }

__host__ __device__ constexpr uint64_t desc_const(uint32_t lbo, uint32_t sbo, uint32_t mode) {
    return ((uint64_t)((sbo >> 4) | (mode << 30)) << 32) | ((lbo >> 4) << 16);
}
constexpr uint64_t D_K128 = desc_const(16, 1024, 1);
constexpr uint64_t D_N128 = desc_const(8192, 1024, 1);
constexpr uint64_t D_BLOB = desc_const(128, 256, 0);
constexpr uint64_t D_OT = desc_const(2048, 128, 0);

enum Kind { XW, XWN, QK, BIG, OUT };

struct Ring {
    int stage;
    uint32_t a, b;
    uint32_t wg;
    uint32_t zero;
    __device__ __forceinline__ void seek(int i, int bslot) {
        stage = i;
        a = (base + (i % NA) * SLOT) >> 4;
        b = (base + BRING + bslot * SLOT) >> 4;
    }
    __device__ __forceinline__ void wait(bool take_turn = true) {
        mbar_wait(full_bar(stage), (stage >> 3) & 1);
        if (take_turn) nb_sync(1 + wg, 256);
    }
    __device__ __forceinline__ void pin() {
        uint32_t n = 0;
#pragma unroll 1
        do {
            asm volatile("pmevent 7;" ::: "memory");
        } while (n++ < zero);
    }
    template <Kind K, int NBS, bool INIT, int SB = 1, bool WAIT = true>
    __device__ __forceinline__ void run(float (&d)[56], float (&e)[56], bool first = true, bool last = true, bool release = true) {
        if (WAIT) wait(first);
        asm volatile("wgmma.fence.sync.aligned;" ::: "memory");
        if (K == QK) {
            const uint64_t da = D_K128 + ((base >> 4) + (stage >> 1) * (SLOT >> 4) + (stage & 1) * 4 + wg * 512), db = D_N128 + b;
            wgmma112<0, 1, 1, INIT>(d, da, db);
            wgmma112<0, 1, 1, INIT>(e, da, db + 256);
            wgmma112<0, 1, 1, false>(d, da + 2, db + 128);
            wgmma112<0, 1, 1, false>(e, da + 2, db + 384);
        } else {
            constexpr int TA = K == OUT, TB = K != XW;
            constexpr uint32_t sa = K == OUT ? 256 : 2, sb = K == XW ? 2 : K == BIG ? 224 : 128;
            const uint64_t da = (K == OUT ? D_OT : D_K128) + (a + wg * (K == OUT ? 64 : 512));
            const uint64_t db = (K == XW ? D_K128 : K == BIG ? D_BLOB : D_N128) + b;
            wgmma112<TA, TB, SB, INIT>(d, da, db);
            wgmma112<TA, TB, SB, false>(d, da + sa, db + sb);
            wgmma112<TA, TB, SB, false>(d, da + 2 * sa, db + 2 * sb);
            wgmma112<TA, TB, SB, false>(d, da + 3 * sa, db + 3 * sb);
        }
        asm volatile("wgmma.commit_group.sync.aligned;" ::: "memory");
        if (last) nb_arrive(2 - wg, 256);
        asm volatile("wgmma.wait_group.sync.aligned 1;" ::: "memory");
        if (release && stage > 0 && elect()) mbar_arrive(base + BAR_EMPTY + ((stage - 1) & 7) * 8);
        stage++;
        a += SLOT >> 4;
        if (a == (base + NA * SLOT) >> 4) a = base >> 4;
        b += SLOT >> 4;
        if (b == (base + BRING + NBS * SLOT) >> 4) b = (base + BRING) >> 4;
    }
    template <Kind K, int NBS, bool INIT, int SB = 1, bool WAIT = true>
    __device__ __forceinline__ void run(float (&d)[56], bool first = true, bool last = true, bool release = true) {
        run<K, NBS, INIT, SB, WAIT>(d, d, first, last, release);
    }
    __device__ __forceinline__ void drain() {
        asm volatile("wgmma.wait_group.sync.aligned 0;" ::: "memory");
        if (elect()) mbar_arrive(base + BAR_EMPTY + ((stage - 1) & 7) * 8);
    }
};

__device__ __forceinline__ void pack_all(const float (&d)[56], uint32_t (&p)[28]) {
#pragma unroll
    for (int i = 0; i < 28; i++) p[i] = pack2(d[2 * i], d[2 * i + 1]);
}
template <int I0, int I1>
__device__ __forceinline__ void store_frags(uint8_t* dst, const uint32_t (&p)[28]) {
#pragma unroll
    for (int i = I0; i < I1; i++) stg1(dst + i * 128, p[i]);
}
template <int I0, int I1>
__device__ __forceinline__ void stage_frags(uint32_t lane_addr, const uint32_t (&p)[28]) {
#pragma unroll
    for (int i = I0; i < I1; i += 4) stsm4(lane_addr + i * 128, p[i], p[i + 1], p[i + 2], p[i + 3]);
}
__device__ __forceinline__ void store_out(const uint32_t (&p)[28], int lane, uint32_t slab, const CUtensorMap* m, int c0, int c1) {
    const bool swap = lane & 16;
    const uint32_t addr = slab + (lane & 15) * 224 + (((lane >> 4) ^ (lane >> 2)) & 1) * 16;
#pragma unroll
    for (int i = 0; i < 28; i += 4)
        stsm4(addr + i * 8, swap ? p[i + 2] : p[i], swap ? p[i + 3] : p[i + 1], swap ? p[i] : p[i + 2], swap ? p[i + 1] : p[i + 3]);
    fence_async_smem();
    __syncwarp();
    if (elect()) {
        tma_st2(m, c0, c1, slab);
        bulk_commit();
        bulk_wait_read();
    }
}
__host__ __device__ constexpr int tile_of(int t) { return 7 * (t >> 2) + 3 * ((t >> 1) & 1) + 2 * (t & 1); }

__global__ void __launch_bounds__(384, 1) fused_kernel(Scratch* sc, const __grid_constant__ Maps maps) {
    extern __shared__ uint8_t smem_raw[];
    if ((uint32_t)__cvta_generic_to_shared(smem_raw) != base) return;
    const int warp = __shfl_sync(0xffffffffu, threadIdx.x >> 5, 0);
    int lane = threadIdx.x & 31;
    asm volatile("" : "+r"(lane));
    const int bid = blockIdx.x < 2 * SPARE0 || blockIdx.x >= 130 ? blockIdx.x
                    : (blockIdx.x >> 1) == SPARE0                ? 128 + (blockIdx.x & 1)
                                                                 : blockIdx.x - 2;
    const bool roleH = bid >= 128;
    const int roleL = (bid >> 4) & 1;
    const int mt = ((bid >> 5) << 2) | ((bid >> 2) & 3);
    const int ns = bid & 3;
    const int par = mt >> 3, blk = mt & 7;

    const int col = ns * 112;
    auto fill = [&](auto i0, auto i1) {
        if (roleL) {
#pragma unroll
            for (int i = decltype(i0)::value; i < decltype(i1)::value; i++) {
                const uint32_t bar = full_bar(i), dst = base + BRING + i * SLOT;
                if (i < 6) mbar_expect(bar, SLOT);
                if (i & 1) {
                    mbar_arrive(bar);
                } else {
                    mbar_expect(bar, SLOT);
                    tma_ld2(base + (i >> 1) * SLOT, &maps.m[M_XA], par * 448 + i * 32, blk * 128, bar);
                }
                if (i < 6) {
                    tma_ld4(dst, &maps.m[M_WQK], 0, i * 32, 0, ns, bar);
                    tma_ld4(dst + 8192, &maps.m[M_WQK], 64, i * 32, 0, ns, bar);
                }
            }
        } else if (!roleH) {
#pragma unroll
            for (int i = decltype(i0)::value; i < decltype(i1)::value; i++) {
                const uint32_t bar = full_bar(i);
                mbar_expect(bar, SLOT);
                mbar_expect(bar, BLOB);
                tma_ld3(base + i * SLOT, &maps.m[M_XB], i * 64, mt * 64, 0, bar);
                tma_ld2(base + BRING + bslot_e(i) * SLOT, &maps.m[M_WR], i * 64, col, bar);
            }
        } else {
#pragma unroll 1
            for (int i = decltype(i0)::value; i < decltype(i1)::value; i++) {
                const uint32_t bar = full_bar(i), dst = base + BRING + i * SLOT;
                mbar_expect(bar, SLOT);
                mbar_expect(bar, SLOT);
                tma_ld4(base + i * SLOT, &maps.m[M_XH], i * 64, 120, 0, 0, bar);
                tma_ld3(dst, &maps.m[M_WV], 0, i * 64, 4 + ns, bar);
                tma_ld3(dst + 8192, &maps.m[M_WV], 64, i * 64, 4 + ns, bar);
            }
        }
    };
    if (warp == 8) {
        if (elect()) {
#pragma unroll
            for (int i = 0; i < 8; i++) mbar_init(base + BAR_FULL + i * 8, 2);
            asm volatile("fence.mbarrier_init.release.cluster;" ::: "memory");
            fill(Int<0>(), Int<LEAD>());
        }
    } else if (warp == 9) {
        if (elect()) {
#pragma unroll
            for (int i = 0; i < 8; i++) mbar_init(base + BAR_EMPTY + i * 8, 8);
            asm volatile("fence.mbarrier_init.release.cluster;" ::: "memory");
        }
    } else if (warp == 10) {
        if (elect()) {
#pragma unroll
            for (int i = 0; i < 5; i++) mbar_init(base + BAR_RDY + i * 8, i < 2 ? 4 : 8);
#pragma unroll
            for (int i = 0; i < 2; i++) mbar_init(base + BAR_HALO + i * 8, 8);
            asm volatile("fence.mbarrier_init.release.cluster;" ::: "memory");
        }
    } else if (warp == 11) {
        if (elect()) {
#pragma unroll
            for (int i = 0; i < 3; i++) mbar_init(base + BAR_DEP + i * 8, 1);
            asm volatile("fence.mbarrier_init.release.cluster;" ::: "memory");
        }
    }
    __syncthreads();

    if (__builtin_expect(warp >= 8, 1)) {
        asm volatile("setmaxnreg.dec.sync.aligned.u32 56;");
#define PROF_FEED_A
#define PROF_FEED_B
        if (__builtin_expect(warp == 8, 1)) {
            if (elect()) {
                PROF(129);
                fill(Int<LEAD>(), Int<7>());
                PROF(134);
                Feed<0> f;
                const int row = mt * 128;
                auto c_run = [&](const CUtensorMap* m, int off, int n0, int n1) {
#pragma unroll 1
                    for (int n = n0; n < n1; n++) {
                        const uint32_t bar = f.acquire<NA>();
                        mbar_expect(bar, SLOT);
                        tma_ld2(f.dst, m, (off + skip_own(n, mt)) * 64, row, bar);
                        PROF_FEED_A;
                        f.next<NA>();
                    }
                };
                if (roleH) {
                } else if (!roleL) {
                    f.seek(14, 0);
                    mbar_wait(base + BAR_RDY, 0);
#pragma unroll 1
                    for (int i = 0; i < 4; i++) {
                        const uint32_t bar = f.acquire<NA>();
                        mbar_expect(bar, SLOT);
                        tma_ld2(f.dst, &maps.m[M_CR + (i >> 1)], ((i & 1) * 16 + mt) * 64, row, bar);
                        mbar_arrive(bar);
                        PROF_FEED_A;
                        f.next<NA>();
                    }
                    c_run(&maps.m[M_CR], 0, 0, 15);
                    c_run(&maps.m[M_CI], 0, 0, NBE);
                    wait_dep(2);
#pragma unroll 1
                    for (int i = 0; i < 7; i++) {
                        const uint32_t bar = f.acquire<NA>();
                        mbar_expect(bar, SLOT);
                        bulk_ld(f.dst, sc->o + (size_t)(mt * 7 + i) * SLOT, SLOT, bar);
                        PROF_FEED_A;
                        f.next<NA>();
                    }
                } else {
#pragma unroll 1
                    for (int i = 4; i < 7; i++) {
                        wait_released(2 * i - 8);
                        mbar_expect(full_bar(2 * i), SLOT);
                        tma_ld2(base + i * SLOT, &maps.m[M_XA], par * 448 + i * 64, blk * 128, full_bar(2 * i));
                    }
                    wait_released(7);
                    f.seek(21, 0);
                    c_run(&maps.m[M_CR], 16, 0, 15);
                    c_run(&maps.m[M_CI], 16, 0, 15);
                    c_run(&maps.m[M_CI], 0, NBE, 15);
                }
            }
        } else if (warp == 11) {
            if (elect()) {
                Feed<BRING> f;
                auto blob_run = [&](auto nbs, int quarter, int n0, int n1) {
                    constexpr int N = decltype(nbs)::value;
                    const uint8_t* src = sc->ab + (size_t)(quarter * 64 + ns) * BLOB;
#pragma unroll 1
                    for (int n = n0; n < n1; n++) {
                        const uint32_t bar = f.template acquire<N>();
                        mbar_expect(bar, BLOB);
                        bulk_ld(f.dst, src + skip_own(n, mt) * (4 * BLOB), BLOB, bar);
                        PROF_FEED_B;
                        f.template next<N>();
                    }
                };
                auto w_run = [&](auto nbs, const CUtensorMap* m, int slice, bool no_a) {
                    constexpr int N = decltype(nbs)::value;
#pragma unroll 1
                    for (int i = 0; i < 7; i++) {
                        const uint32_t bar = f.template acquire<N>();
                        mbar_expect(bar, SLOT);
                        tma_ld3(f.dst, m, 0, i * 64, slice, bar);
                        tma_ld3(f.dst + 8192, m, 64, i * 64, slice, bar);
                        if (no_a) mbar_arrive(bar);
                        PROF_FEED_B;
                        f.template next<N>();
                    }
                };
                if (roleH) {
                    f.seek(7, 0);
                    w_run(Int<7>(), &maps.m[M_WV], 8 + ns, true);
                } else if (!roleL) {
                    f.seek(7, bslot_e(7));
#pragma unroll 1
                    for (int i = 0; i < 7; i++) {
                        const uint32_t bar = f.acquire<5>();
                        mbar_expect(bar, BLOB);
                        tma_ld2(f.dst, &maps.m[M_WI], i * 64, col, bar);
                        mbar_arrive(bar);
                        PROF_FEED_B;
                        f.next<5>();
                    }
                    f.seek(18, bslot_e(18));
                    wait_dep(0);
                    blob_run(Int<7>(), 0, 0, 15);
                    wait_dep(1);
                    blob_run(Int<7>(), 2, 0, NBE);
                    w_run(Int<7>(), &maps.m[M_WO], ns, false);
                } else {
                    f.seek(6, 0);
#pragma unroll 1
                    for (int i = 6; i < 14; i++) {
                        const uint32_t bar = f.acquire<6>();
                        mbar_expect(bar, SLOT);
                        tma_ld4(f.dst, &maps.m[M_WQK], 0, i * 32, 0, ns, bar);
                        tma_ld4(f.dst + 8192, &maps.m[M_WQK], 64, i * 32, 0, ns, bar);
                        if (i & 1) mbar_arrive(bar);
                        PROF_FEED_B;
                        f.next<6>();
                    }
                    w_run(Int<6>(), &maps.m[M_WV], 8 + ns, true);
                    wait_dep(0);
                    blob_run(Int<6>(), 1, 0, 15);
                    wait_dep(1);
                    blob_run(Int<6>(), 3, 0, 15);
                    blob_run(Int<6>(), 2, NBE, 15);
                }
            }
        } else if (roleH) {
        } else if (warp == 10) {
            if (elect()) {
                unsigned* epoch_ptr = &sc->epoch[(bid * 4 + 2) * 8];
                const unsigned ep = *epoch_ptr + 1;
                sts1(base + TAG, ep);
                await(sc, CNT_A + roleL * 4 + ns, ep * 16);
                mbar_arrive(base + BAR_DEP);
                PROF(150);
                await(sc, CNT_B + ns, ep * 16);
                mbar_arrive(base + BAR_DEP + 8);
                PROF(151);
                if (!roleL) {
                    await(sc, CNT_O + mt, ep * 4);
                    mbar_arrive(base + BAR_DEP + 16);
                }
                PROF(152);
                *epoch_ptr = ep;
            }
        } else if (!roleL) {
            if (elect()) {
                mbar_wait(base + BAR_RDY, 0);
                PROF(130);
                signal(sc, CNT_A + ns);
                PROF(131);
                mbar_wait(base + BAR_RDY + 8, 0);
                signal(sc, CNT_A + 4 + ns);
                PROF(135);
                mbar_wait(base + BAR_RDY + 32, 0);
                PROF(132);
                signal(sc, CNT_B + ns);
                PROF(133);
            }
        } else {
            const unsigned t_start = clk32();
            unsigned* epoch_ptr = &sc->epoch[(bid * 4 + 1) * 8];
            const unsigned tag = *epoch_ptr + 1;
#pragma unroll 1
            for (int kv = 0; kv < 2; kv++) {
                uint32_t v[14], t[14];
#pragma unroll
                for (int i = 0; i < 14; i++) v[i] = 0;

                if (blk > 0) {
                    const uint8_t* src = sc->halo + (size_t)(((mt - 1) * 4 + ns) * 2 + kv) * (2 * HSLOT) + lane * 16;
                    pause_until(t_start, HALO_DELAY + kv * 3200);
#pragma unroll 1
                    for (int n = 0; n < SPIN_LIMIT; n++) {
                        bool ok = true;
#pragma unroll
                        for (int i = 0; i < 7; i++) ld_tagged(src + i * 512, v[2 * i], t[2 * i], v[2 * i + 1], t[2 * i + 1]);
#pragma unroll
                        for (int i = 0; i < 14; i++) ok = ok && t[i] == tag;
                        if (__all_sync(0xffffffffu, ok)) break;
                    }
                }
#pragma unroll
                for (int i = 0; i < 14; i++) sts1(base + HALO + kv * (8 * HSLOT) + i * 128 + lane * 4, v[i]);
                warp_arrive(base + BAR_HALO + kv * 8);
                if (lane == 0) PROF(142 + kv);
            }
            if (elect()) {
                mbar_wait(base + BAR_RDY + 16, 0);
                PROF(130);
                signal(sc, CNT_O + mt);
                PROF(131);
                *epoch_ptr = tag;
            }
        }
    } else {
        asm volatile("setmaxnreg.inc.sync.aligned.u32 224;");
        Ring r;
        r.wg = warp >> 2;
        r.zero = blockIdx.y;
        const int wg = warp >> 2;
        if (wg) nb_arrive(1, 256);
        uint8_t* part = sc->part + (size_t)(ns * 16 + mt) * (2 * BLOB) + warp * 512 + lane * 16;
        uint32_t p[28];

        if (roleH) {
            unsigned* epoch_ptr = &sc->epoch[bid * 4 * 8];
            const unsigned tag = *epoch_ptr + 1;
            uint8_t* hout = sc->halo + (size_t)((warp * 8 + ns) * 2) * (2 * HSLOT) + lane * 16;
            float x0[56], x1[56];
            r.seek(0, 0);
            r.run<XWN, 7, true>(x0);
#pragma unroll 1
            for (int i = 1; i < 7; i++) r.run<XWN, 7, false>(x0);
            r.run<XWN, 7, true>(x1);
            acc_fence(x0);
            pack_all(x0, p);
#pragma unroll
            for (int i = 0; i < 14; i++) st_tagged(hout + (i & 1) * (16 * HSLOT) + (i >> 1) * 512, p[(i >> 1) * 4 + (i & 1)], p[(i >> 1) * 4 + (i & 1) + 2], tag);
#pragma unroll 1
            for (int i = 1; i < 7; i++) r.run<XWN, 7, false>(x1);
            asm volatile("wgmma.wait_group.sync.aligned 0;" ::: "memory");
            acc_fence(x1);
            pack_all(x1, p);
#pragma unroll
            for (int i = 0; i < 28; i++) p[i] = movm(p[i]);
#pragma unroll
            for (int i = 0; i < 14; i++)
                st_tagged(hout + 2 * HSLOT + (i & 1) * (16 * HSLOT) + (i >> 1) * 512, p[(i >> 1) * 4 + (i & 1)], p[(i >> 1) * 4 + (i & 1) + 2], tag);
            if (threadIdx.x == 0) *epoch_ptr = tag;
        } else if (!roleL) {
            uint8_t* blob = sc->ab + (size_t)((wg * 16 + mt) * 4 + ns) * BLOB + (warp & 3) * WSLOT + lane * 4;
            const uint32_t own = base + BRING + wg * SLOT + (warp & 3) * WSLOT + lane * 16;
            float x0[56], x1[56];
            r.seek(0, bslot_e(0));
            r.run<XW, 7, true>(x0);
            r.run<XW, 7, false>(x0);
            r.seek(2, bslot_e(2));
#pragma unroll 1
            for (int i = 2; i < 7; i++) r.run<XW, 5, false>(x0);

            r.seek(7, bslot_e(7));
            r.run<XW, 5, true, -1>(x1);
            acc_fence(x0);
            pack_all(x0, p);
#pragma unroll
            for (int i = 0; i < 2; i++) {
                if (wg == i) store_frags<0, 14>(blob, p);
                else stage_frags<0, 4>(own + 5 * SLOT, p);
                r.run<XW, 5, false, -1>(x1);
                if (wg == i) {
                    store_frags<14, 28>(blob, p);
                    warp_arrive(base + BAR_RDY + i * 8);
                } else {
                    stage_frags<4, 8>(own + 5 * SLOT, p);
                }
                r.run<XW, 5, false, -1>(x1);
            }
            stage_frags<8, 20>(own + 5 * SLOT, p);
            r.run<XW, 5, false, -1>(x1);
            stage_frags<20, 28>(own + 5 * SLOT, p);
            warp_arrive(base + BAR_RDY + 16);
            r.run<XW, 5, false, -1>(x1);

            mbar_wait(base + BAR_RDY + 16, 0);
            fence_async_smem();
            r.seek(14, bslot_e(14));
            r.run<BIG, 7, true>(x0);
            acc_fence(x1);
            pack_all(x1, p);
            wait_released(10);
            stage_frags<0, 28>(own, p);
            warp_arrive(base + BAR_RDY + 24);
            r.run<BIG, 7, false>(x0);
            mbar_wait(base + BAR_RDY + 24, 0);
            fence_async_smem();
            blob += (size_t)128 * BLOB;
#pragma unroll
            for (int i = 0; i < 28; i++) {
                if (i % B_SLICE == 0) r.run<BIG, 7, false>(x0);
                stg1(blob + i * 128, p[i]);
            }
            warp_arrive(base + BAR_RDY + 32);
#pragma unroll 1
            for (int i = 17 + 27 / B_SLICE; i < POUT; i++) r.run<BIG, 7, false>(x0, i <= POUT - TURN, i < POUT - TURN || i == POUT - 1);

            const uint32_t tag = lds1(base + TAG);
            r.drain();
            acc_fence(x0);
            pack_all(x0, p);
#pragma unroll
            for (int i = 0; i < 7; i++) st_part(part + i * 4096, p + 4 * i, tag & 1);
            r.seek(POUT, bslot_e(POUT));
            r.run<OUT, 7, true>(x1, true, false, false);
#pragma unroll 1
            for (int i = 1; i < 7; i++) r.run<OUT, 7, false>(x1, i == 7 - TURN, i == 6 - TURN || i == 6);

            wait_released(ELAST - 6);
            asm volatile("wgmma.wait_group.sync.aligned 0;" ::: "memory");
            acc_fence(x1);
            pack_all(x1, p);
            const uint32_t slab = base + (wg ? BRING + bslot_e(ELAST - 6) * SLOT : ((ELAST - 6) % NA) * SLOT) + (warp & 3) * WSLOT;
            store_out(p, lane, slab, &maps.m[M_OUTA], par * 896 + col, blk * 128 + warp * 16);
        } else {
            const int g = lane >> 2, tig = lane & 3;
            const uint32_t hin = base + HALO + warp * HSLOT + lane * 4;
            auto publish = [&](const uint32_t (&h)[14], int kv) {
                if (warp < 7) {
#pragma unroll
                    for (int c = 0; c < 14; c++) sts1(hin + HSLOT + c * 128, h[c]);
                    warp_arrive(base + BAR_HALO + kv * 8);
                }
            };
            float y0[56], y1[56], y2[56];
            r.seek(0, 0);
            r.run<QK, 6, true>(y0, y1);
#pragma unroll 1
            for (int i = 1; i < 14; i++) r.run<QK, 6, false>(y0, y1);

            uint32_t m1[8][4], m0[8][4], lo[14], hi[14];
            r.seek(14, bslot_l(14));
            r.run<XWN, 6, true>(y2);
            acc_fence(y0);
            acc_fence(y1);
#pragma unroll
            for (int c = 0; c < 14; c++) hi[c] = pack2(y1[4 * c + 2], y1[4 * c + 3]);
            publish(hi, 0);
            r.run<XWN, 6, false>(y2);
            r.pin();
#pragma unroll
            for (int c = 0; c < 14; c++) lo[c] = pack2(y1[4 * c], y1[4 * c + 1]);
#pragma unroll
            for (int t = 0; t < 8; t++) {
                const int c = tile_of(t);
                const bool shared = (t & 3) == 2;
                m1[t][0] = shared ? dup(lo[c], r.zero) : lo[c];
                m1[t][1] = shared ? dup(hi[c], r.zero) : hi[c];
                m1[t][2] = lo[c + 1];
                m1[t][3] = hi[c + 1];
                m0[t][0] = dup(m1[t][0], r.zero);
                m0[t][2] = dup(lo[c + 1], 2 * r.zero);
            }
            r.run<XWN, 6, false>(y2);
            r.pin();
            uint32_t q[2][8][2];
#pragma unroll
            for (int b = 0; b < 2; b++) {
                uint32_t v[14];
#pragma unroll
                for (int c = 0; c < 14; c++) v[c] = pack2(y0[4 * c + 2 * b], y0[4 * c + 2 * b + 1]);
#pragma unroll
                for (int t = 0; t < 8; t++) {
                    const int c = tile_of(t);
                    q[b][t][0] = (t & 3) == 2 ? (tig >= 2 ? v[c] : 0u) : v[c];
                    q[b][t][1] = (t & 3) == 1 ? (tig < 2 ? v[c + 1] : 0u) : v[c + 1];
                }
            }
            r.run<XWN, 6, false>(y2);
            mbar_wait(base + BAR_HALO, 0);
#pragma unroll
            for (int t = 0; t < 8; t++) {
                m0[t][1] = lds1(hin + tile_of(t) * 128 + ((t & 3) == 2 ? r.zero : 0u));
                m0[t][3] = lds1(hin + tile_of(t) * 128 + 128);
            }
            r.wait();
            float s[8][4];
#pragma unroll
            for (int step = 0; step < 2; step++) {
#pragma unroll
                for (int i = 0; i < 8; i++) {
                    const int b = 1 - (i >> 2), h = i & 3, t = 2 * h + step;
                    float (&d)[4] = s[2 * h + b];
                    if (step == 0) d[0] = d[1] = d[2] = d[3] = 0.f;
                    mma16816(d, b ? m1[t] : m0[t], q[b][t][0], q[b][t][1]);
                }
            }
            r.pin();
            r.run<XWN, 6, false, 1, false>(y2);
            r.pin();

            uint32_t pr[8], mx[4], mx1[4];
            {
                const bool cur0 = g <= 2 * tig, cur1 = g <= 2 * tig + 1;
#pragma unroll
                for (int i = 0; i < 8; i++) {
                    const int c = (i & 1) ? 2 : 0;
                    pr[i] = movm(pack2(cur0 ? s[i][c] : s[i][2 - c], cur1 ? s[i][c + 1] : s[i][3 - c]));
                }
            }
            r.run<XWN, 6, false>(y2);
            r.pin();
            const uint32_t curmask = (2 * tig <= g ? 0x0000FFFFu : 0u) | (2 * tig + 1 <= g ? 0xFFFF0000u : 0u);
            {
                const uint32_t keep = (blk == 0 && warp == 0) ? curmask : 0xFFFFFFFFu;
#pragma unroll
                for (int i = 0; i < 4; i++) {
                    pr[2 * i] = (pr[2 * i] & keep) | (0xCF9ECF9Eu & ~keep);
                    mx[i] = max2(__byte_perm(pr[2 * i], pr[2 * i + 1], 0x5410), __byte_perm(pr[2 * i], pr[2 * i + 1], 0x7632));
                }
#pragma unroll
                for (int i = 0; i < 4; i++) mx[i] = max2(mx[i], __shfl_xor_sync(0xffffffffu, mx[i], 1));
#pragma unroll
                for (int i = 0; i < 4; i++) mx1[i] = __shfl_xor_sync(0xffffffffu, mx[i], 2);
            }
            r.run<XWN, 6, false>(y2);
            r.pin();
            constexpr float SCL = 0.18898223650461362f * 1.4426950408889634f;
            float e0[8], e1[8], sm[8], sm1[8];
#pragma unroll
            for (int i = 0; i < 8; i++) {
                const uint32_t m2 = max2(mx[i >> 1], mx1[i >> 1]);
                sm[i] = ((i & 1) ? bf_hi(m2) : bf_lo(m2)) * -SCL;
                e0[i] = ex2(fmaf(bf_lo(pr[i]), SCL, sm[i]));
            }

            r.seek(21, bslot_l(21));
            r.run<BIG, 6, true>(y0);
            acc_fence(y2);
#pragma unroll
            for (int c = 0; c < 14; c++) hi[c] = movm(pack2(y2[4 * c + 2], y2[4 * c + 3]));
            r.run<BIG, 6, false>(y0);
            wait_released(18);
            publish(hi, 1);
            r.run<BIG, 6, false>(y0);
            r.pin();
#pragma unroll
            for (int i = 0; i < 8; i++) {
                e1[i] = ex2(fmaf(bf_hi(pr[i]), SCL, sm[i]));
                sm[i] = e0[i] + e1[i];
                sm1[i] = __shfl_xor_sync(0xffffffffu, sm[i], 1);
            }
            r.run<BIG, 6, false>(y0);
            r.pin();
#pragma unroll
            for (int c = 0; c < 14; c++) lo[c] = movm(pack2(y2[4 * c], y2[4 * c + 1]));
            r.run<BIG, 6, false>(y0);
            r.pin();
#pragma unroll
            for (int i = 0; i < 8; i++) {
                sm[i] += sm1[i];
                sm1[i] = __shfl_xor_sync(0xffffffffu, sm[i], 2);
            }
#pragma unroll
            for (int t = 0; t < 8; t++) {
                const int c = tile_of(t);
                const bool shared = (t & 3) == 2;
                m1[t][0] = shared ? dup(lo[c], r.zero) : lo[c];
                m1[t][1] = lo[c + 1];
                m1[t][2] = shared ? dup(hi[c], r.zero) : hi[c];
                m1[t][3] = hi[c + 1];
                m0[t][0] = dup(m1[t][0], r.zero);
                m0[t][1] = dup(lo[c + 1], 2 * r.zero);
            }
            r.run<BIG, 6, false>(y0);
            r.pin();
            uint32_t pb[8][2];
#pragma unroll
            for (int i = 0; i < 8; i++) {
                const float inv = rcp(sm[i] + sm1[i]);
                const uint32_t w = pack2(e0[i] * inv, e1[i] * inv);
                pb[i][i & 1] = band(w, curmask);
                pb[i][1 - (i & 1)] = band(w, ~curmask);
            }
            r.run<BIG, 6, false>(y0);
            mbar_wait(base + BAR_HALO + 8, 0);
            const uint32_t vin = warp ? hin : hin + 8 * HSLOT;
#pragma unroll
            for (int t = 0; t < 8; t++) {
                m0[t][2] = lds1(vin + tile_of(t) * 128 + ((t & 3) == 2 ? r.zero : 0u));
                m0[t][3] = lds1(vin + tile_of(t) * 128 + 128);
            }
            r.wait();
            float o[2][8][4];
#pragma unroll
            for (int i = 0; i < 16; i++) {
                const int b = 1 - (i >> 3), t = i & 7;
                float (&d)[4] = o[b][t];
                d[0] = d[1] = d[2] = d[3] = 0.f;
                mma16816(d, b ? m1[t] : m0[t], pb[(t & 6) + b][0], pb[(t & 6) + b][1]);
            }
            r.pin();
            r.run<BIG, 6, false, 1, false>(y0);
            r.pin();
            uint8_t* odst = sc->o + (size_t)mt * 7 * SLOT + ns * (14 * 2048) + warp * 256 + lane * 4;
#pragma unroll
            for (int hp = 0; hp < 2; hp++) {
#pragma unroll
                for (int b = 0; b < 2; b++) {
                    const float (&u)[8][4] = o[b];
                    const int t = 4 * hp;
                    uint32_t* w = p + 14 * hp + b;
                    w[0] = pack2(u[t][0], u[t][1]);
                    w[2] = pack2(u[t][2], u[t][3]);
                    w[4] = pack2(u[t + 1][0], u[t + 1][1]);
                    w[6] = pack2(g < 4 ? u[t + 1][2] : u[t + 2][0], g < 4 ? u[t + 1][3] : u[t + 2][1]);
                    w[8] = pack2(u[t + 2][2], u[t + 2][3]);
                    w[10] = pack2(u[t + 3][0], u[t + 3][1]);
                    w[12] = pack2(u[t + 3][2], u[t + 3][3]);
                }
            }
#pragma unroll
            for (int i = 0; i < 28; i++) {
                if (i && i % O_SLICE == 0) r.run<BIG, 6, false>(y0);
                stg1(odst + (i >> 1) * 2048 + (i & 1) * 128, p[i]);
            }
            warp_arrive(base + BAR_RDY + 16);

#pragma unroll 1
            for (int i = 29 + 27 / O_SLICE; i <= LLAST + 1 - TURN; i++) r.run<BIG, 6, false>(y0, true, i <= LLAST - TURN);
            const uint32_t tag = lds1(base + TAG);
#pragma unroll
            for (int i = 0; i < 7; i++) ld_tagged(part + i * 4096, p[4 * i], p[4 * i + 1], p[4 * i + 2], p[4 * i + 3]);
#pragma unroll 1
            for (int i = 1; i < TURN; i++) r.run<BIG, 6, false>(y0, false, i == TURN - 1);
#pragma unroll 1
            for (int n = 0; n < SPIN_LIMIT; n++) {
                uint32_t stale = 0;
#pragma unroll
                for (int i = 0; i < 28; i += 2) stale |= p[i] ^ tag;
                if (__all_sync(0xffffffffu, !(stale & 1))) break;
#pragma unroll
                for (int i = 0; i < 7; i++) ld_tagged(part + i * 4096, p[4 * i], p[4 * i + 1], p[4 * i + 2], p[4 * i + 3]);
            }
            wait_released(LLAST - 6);
            asm volatile("wgmma.wait_group.sync.aligned 0;" ::: "memory");
            acc_fence(y0);
#pragma unroll
            for (int i = 0; i < 28; i++) p[i] = add2(pack2(y0[2 * i], y0[2 * i + 1]), p[i]);
            const uint32_t slab = base + (wg ? HALO : ((LLAST - 6) % NA) * SLOT) + (warp & 3) * WSLOT;
            store_out(p, lane, slab, &maps.m[M_OUTB], 448 + col, mt * 128 + warp * 16);
        }
    }
}

typedef CUresult (*EncodeFn)(CUtensorMap*, CUtensorMapDataType, cuuint32_t, void*, const cuuint64_t*, const cuuint64_t*,
                             const cuuint32_t*, const cuuint32_t*, CUtensorMapInterleave, CUtensorMapSwizzle,
                             CUtensorMapL2promotion, CUtensorMapFloatOOBfill);

struct Dim { uint64_t size, stride; uint32_t box; };
void encode(EncodeFn fn, CUtensorMap* m, const void* ptr, CUtensorMapSwizzle sw, Dim d0, Dim d1, Dim d2 = {0, 0, 0}, Dim d3 = {0, 0, 0}) {
    const cuuint64_t dims[4] = {d0.size, d1.size, d2.size, d3.size};
    const cuuint64_t strides[3] = {d1.stride, d2.stride, d3.stride};
    const cuuint32_t box[4] = {d0.box, d1.box, d2.box, d3.box};
    const cuuint32_t es[4] = {1, 1, 1, 1};
    fn(m, CU_TENSOR_MAP_DATA_TYPE_BFLOAT16, d3.size ? 4 : d2.size ? 3 : 2, const_cast<void*>(ptr), dims, strides, box, es,
       CU_TENSOR_MAP_INTERLEAVE_NONE, sw, CU_TENSOR_MAP_L2_PROMOTION_L2_128B, CU_TENSOR_MAP_FLOAT_OOB_FILL_NONE);
}

}

extern "C" void kernel_launch(void* const* d_in, const int* in_sizes, int n_in, void* d_out, int out_size) {
    (void)in_sizes; (void)n_in; (void)out_size;
    void* fnp = nullptr;
    cudaDriverEntryPointQueryResult st;
    cudaGetDriverEntryPoint("cuTensorMapEncodeTiled", &fnp, cudaEnableDefault, &st);
    EncodeFn fn = (EncodeFn)fnp;
    void* scratch = nullptr;
    cudaGetSymbolAddress(&scratch, g_scratch);
    cudaFuncSetAttribute(fused_kernel, cudaFuncAttributeMaxDynamicSharedMemorySize, SMEM_BYTES);

    const CUtensorMapSwizzle S128 = CU_TENSOR_MAP_SWIZZLE_128B, S0 = CU_TENSOR_MAP_SWIZZLE_NONE;
    Maps maps;
    encode(fn, &maps.m[M_XA], d_in[0], S128, {896, 2, 64}, {1024, 1792, 128});
    encode(fn, &maps.m[M_WQK], d_in[1], S128, {112, 2, 64}, {448, 2688, 32}, {3, 896, 2}, {4, 224, 1});
    encode(fn, &maps.m[M_WV], d_in[1], S128, {112, 2, 64}, {448, 2688, 64}, {12, 224, 1});
    encode(fn, &maps.m[M_XH], d_in[0], S128, {448, 2, 64}, {128, 1792, 8}, {8, 128 * 1792, 8}, {2, 896, 2});
    encode(fn, &maps.m[M_WO], d_in[2], S128, {112, 2, 64}, {448, 896, 64}, {4, 224, 1});
    encode(fn, &maps.m[M_XB], d_in[3], S128, {448, 2, 64}, {1024, 896, 64}, {2, 896 * 1024, 2});
    encode(fn, &maps.m[M_CR], d_in[4], S128, {2048, 2, 64}, {2048, 4096, 128});
    encode(fn, &maps.m[M_CI], d_in[5], S128, {2048, 2, 64}, {2048, 4096, 128});
    encode(fn, &maps.m[M_WR], d_in[6], S128, {448, 2, 64}, {448, 896, 112});
    encode(fn, &maps.m[M_WI], d_in[7], S128, {448, 2, 64}, {448, 896, 112});
    encode(fn, &maps.m[M_OUTA], d_out, S0, {1792, 2, 112}, {1024, 3584, 16});
    encode(fn, &maps.m[M_OUTB], d_out, S0, {896, 2, 112}, {2048, 1792, 16});

    fused_kernel<<<132, 384, SMEM_BYTES>>>((Scratch*)scratch, maps);
}
```

```cpp
#include <cuda.h>
#include <cuda_bf16.h>
#include <cuda_runtime.h>
#include <stdint.h>

namespace {

constexpr uint32_t SLOT = 16384;
constexpr int NA = 7;
constexpr uint32_t BRING = NA * SLOT;
constexpr uint32_t HALO = BRING + 6 * SLOT;
constexpr uint32_t HSLOT = 1792;
constexpr uint32_t WSLOT = 3584;
constexpr uint32_t BLOB = 14336;
constexpr uint32_t BARS = 14 * SLOT;
constexpr uint32_t BAR_FULL = BARS;
constexpr uint32_t BAR_EMPTY = BARS + 64;
constexpr uint32_t BAR_RDY = BARS + 128;
constexpr uint32_t BAR_DEP = BARS + 168;
constexpr uint32_t BAR_HALO = BARS + 192;
constexpr uint32_t TAG = BARS + 208;
constexpr uint32_t SMEM_BYTES = BARS + 256 + 1024;
constexpr uint32_t base = 1024;
constexpr int SPIN_LIMIT = 1 << 16;

#define E_EXTRA 0
#define HALO_DELAY 7000
#define O_SLICE 4
#define B_SLICE 4
#define LEAD 3
#define TURN 3
#define MAPPING 2
constexpr int NBE = 13 + E_EXTRA;
constexpr int POUT = 33 + NBE;
constexpr int ELAST = POUT + 6;
constexpr int LLAST = 52 - E_EXTRA;

enum { M_XA, M_XH, M_WQK, M_WV, M_WO, M_XB, M_WR, M_WI, M_CR, M_CI, M_OUTA, M_OUTB, M_COUNT };
struct __align__(64) Maps { CUtensorMap m[M_COUNT]; };

constexpr int CNT_A = 0;
constexpr int CNT_B = 8;
constexpr int CNT_O = 16;
constexpr int CNT_COUNT = 32;

struct Scratch {
    uint8_t ab[64 * 4 * BLOB];
    uint8_t o[16 * 7 * SLOT];
    uint8_t part[64 * 2 * BLOB];
    uint8_t halo[64 * 2 * 2 * HSLOT];
    unsigned cnt[CNT_COUNT * 32];
    unsigned epoch[132 * 4 * 8];
};
__device__ __align__(1024) Scratch g_scratch;

__device__ __forceinline__ unsigned clk32() { unsigned c; asm volatile("mov.u32 %0, %%clock;" : "=r"(c)); return c; }
__device__ __forceinline__ void pause_until(unsigned t0, unsigned cycles) {
    while (clk32() - t0 < cycles) {}
}

#define PROF(idx)

__device__ __forceinline__ void mbar_init(uint32_t bar, uint32_t cnt) {
    asm volatile("mbarrier.init.shared::cta.b64 [%0], %1;" ::"r"(bar), "r"(cnt) : "memory");
}
__device__ __forceinline__ void mbar_expect(uint32_t bar, uint32_t bytes) {
    asm volatile("mbarrier.arrive.expect_tx.shared::cta.b64 _, [%0], %1;" ::"r"(bar), "r"(bytes) : "memory");
}
__device__ __forceinline__ void mbar_arrive(uint32_t bar) {
    asm volatile("mbarrier.arrive.shared::cta.b64 _, [%0];" ::"r"(bar) : "memory");
}
__device__ __forceinline__ bool mbar_try(uint32_t bar, uint32_t parity) {
    uint32_t ok;
    asm volatile("{\n.reg .pred p;\nmbarrier.try_wait.parity.shared::cta.b64 p, [%1], %2;\nselp.u32 %0, 1, 0, p;\n}\n"
                 : "=r"(ok) : "r"(bar), "r"(parity) : "memory");
    return ok;
}
__device__ __forceinline__ void mbar_wait(uint32_t bar, uint32_t parity) {
#pragma unroll 1
    for (int n = 0; n < SPIN_LIMIT; n++)
        if (mbar_try(bar, parity)) break;
}
__device__ __forceinline__ bool elect() {
    uint32_t p;
    asm volatile("{\n.reg .pred p;\nelect.sync _|p, 0xffffffff;\nselp.u32 %0, 1, 0, p;\n}\n" : "=r"(p));
    return p;
}
__device__ __forceinline__ void nb_sync(int id, int n) { asm volatile("bar.sync %0, %1;" ::"r"(id), "r"(n) : "memory"); }
__device__ __forceinline__ void nb_arrive(int id, int n) { asm volatile("bar.arrive %0, %1;" ::"r"(id), "r"(n) : "memory"); }
__device__ __forceinline__ void warp_arrive(uint32_t bar) {
    __syncwarp();
    if (elect()) mbar_arrive(bar);
}
__device__ __forceinline__ uint32_t band(uint32_t x, uint32_t m) {
    uint32_t r;
    asm volatile("and.b32 %0, %1, %2;" : "=r"(r) : "r"(x), "r"(m));
    return r;
}
__device__ __forceinline__ uint32_t dup(uint32_t x, uint32_t zero) {
    uint32_t r;
    asm volatile("xor.b32 %0, %1, %2;" : "=r"(r) : "r"(x), "r"(zero));
    return r;
}

__device__ __forceinline__ void tma_ld2(uint32_t dst, const CUtensorMap* m, int c0, int c1, uint32_t bar) {
    asm volatile("cp.async.bulk.tensor.2d.shared::cluster.global.mbarrier::complete_tx::bytes [%0], [%1, {%3, %4}], [%2];"
                 ::"r"(dst), "l"(m), "r"(bar), "r"(c0), "r"(c1) : "memory");
}
__device__ __forceinline__ void tma_ld3(uint32_t dst, const CUtensorMap* m, int c0, int c1, int c2, uint32_t bar) {
    asm volatile("cp.async.bulk.tensor.3d.shared::cluster.global.mbarrier::complete_tx::bytes [%0], [%1, {%3, %4, %5}], [%2];"
                 ::"r"(dst), "l"(m), "r"(bar), "r"(c0), "r"(c1), "r"(c2) : "memory");
}
__device__ __forceinline__ void tma_ld4(uint32_t dst, const CUtensorMap* m, int c0, int c1, int c2, int c3, uint32_t bar) {
    asm volatile("cp.async.bulk.tensor.4d.shared::cluster.global.mbarrier::complete_tx::bytes [%0], [%1, {%3, %4, %5, %6}], [%2];"
                 ::"r"(dst), "l"(m), "r"(bar), "r"(c0), "r"(c1), "r"(c2), "r"(c3) : "memory");
}
__device__ __forceinline__ void bulk_ld(uint32_t dst, const void* src, uint32_t bytes, uint32_t bar) {
    asm volatile("cp.async.bulk.shared::cluster.global.mbarrier::complete_tx::bytes [%0], [%1], %2, [%3];"
                 ::"r"(dst), "l"(src), "r"(bytes), "r"(bar) : "memory");
}
__device__ __forceinline__ void tma_st2(const CUtensorMap* m, int c0, int c1, uint32_t src) {
    asm volatile("cp.async.bulk.tensor.2d.global.shared::cta.bulk_group [%0, {%1, %2}], [%3];"
                 ::"l"(m), "r"(c0), "r"(c1), "r"(src) : "memory");
}
__device__ __forceinline__ void bulk_commit() { asm volatile("cp.async.bulk.commit_group;" ::: "memory"); }
__device__ __forceinline__ void bulk_wait_read() { asm volatile("cp.async.bulk.wait_group.read 0;" ::: "memory"); }
__device__ __forceinline__ void fence_async_smem() { asm volatile("fence.proxy.async.shared::cta;" ::: "memory"); }
__device__ __forceinline__ void fence_async_global() { asm volatile("fence.proxy.async.global;" ::: "memory"); }

__device__ __forceinline__ void signal(Scratch* sc, int idx) {
    asm volatile("fence.proxy.async;\nred.relaxed.gpu.global.add.u32 [%0], 1;" ::"l"(&sc->cnt[idx * 32]) : "memory");
}
__device__ __forceinline__ void await(Scratch* sc, int idx, unsigned target) {
#pragma unroll 1
    for (int n = 0; n < SPIN_LIMIT; n++) {
        unsigned v;
        asm volatile("ld.relaxed.gpu.global.u32 %0, [%1];" : "=r"(v) : "l"(&sc->cnt[idx * 32]) : "memory");
        if ((int)(v - target) >= 0) break;
    }
    asm volatile("fence.acquire.gpu;" ::: "memory");
}
__device__ __forceinline__ void wait_dep(int k) {
    mbar_wait(base + BAR_DEP + k * 8, 0);
    fence_async_global();
}

#define WG_REGS                                                                                                     \
    "{%0,%1,%2,%3,%4,%5,%6,%7,%8,%9,%10,%11,%12,%13,%14,%15,%16,%17,%18,%19,%20,%21,%22,%23,%24,%25,%26,%27,"       \
    "%28,%29,%30,%31,%32,%33,%34,%35,%36,%37,%38,%39,%40,%41,%42,%43,%44,%45,%46,%47,%48,%49,%50,%51,%52,%53,%54,%55}"
#define WG_OPS(C)                                                                                                   \
    C(d[0]), C(d[1]), C(d[2]), C(d[3]), C(d[4]), C(d[5]), C(d[6]), C(d[7]), C(d[8]), C(d[9]), C(d[10]), C(d[11]),   \
    C(d[12]), C(d[13]), C(d[14]), C(d[15]), C(d[16]), C(d[17]), C(d[18]), C(d[19]), C(d[20]), C(d[21]), C(d[22]),   \
    C(d[23]), C(d[24]), C(d[25]), C(d[26]), C(d[27]), C(d[28]), C(d[29]), C(d[30]), C(d[31]), C(d[32]), C(d[33]),   \
    C(d[34]), C(d[35]), C(d[36]), C(d[37]), C(d[38]), C(d[39]), C(d[40]), C(d[41]), C(d[42]), C(d[43]), C(d[44]),   \
    C(d[45]), C(d[46]), C(d[47]), C(d[48]), C(d[49]), C(d[50]), C(d[51]), C(d[52]), C(d[53]), C(d[54]), C(d[55])

template <int TA, int TB, int SB, bool INIT, uint32_t AH, uint32_t BH>
__device__ __forceinline__ void wgmma112(float (&d)[56], uint32_t alo, uint32_t blo) {
    if (INIT) {
        asm volatile("{\n.reg .pred p;\n.reg .b64 da, db;\nsetp.ne.b32 p, 0, 0;\nmov.b64 da, {%56, %61};\nmov.b64 db, {%57, %62};\n"
                     "wgmma.mma_async.sync.aligned.m64n112k16.f32.bf16.bf16 " WG_REGS ", da, db, p, 1, %59, %60, %58;\n}\n"
                     : WG_OPS("=f") : "r"(alo), "r"(blo), "n"(TB), "n"(SB), "n"(TA), "n"(AH), "n"(BH));
    } else {
        asm volatile("{\n.reg .pred p;\n.reg .b64 da, db;\nsetp.ne.b32 p, 1, 0;\nmov.b64 da, {%56, %61};\nmov.b64 db, {%57, %62};\n"
                     "wgmma.mma_async.sync.aligned.m64n112k16.f32.bf16.bf16 " WG_REGS ", da, db, p, 1, %59, %60, %58;\n}\n"
                     : WG_OPS("+f") : "r"(alo), "r"(blo), "n"(TB), "n"(SB), "n"(TA), "n"(AH), "n"(BH));
    }
}
__device__ __forceinline__ void acc_fence(float (&d)[56]) {
#pragma unroll
    for (int i = 0; i < 56; i++) asm volatile("" : "+f"(d[i])::"memory");
}

__device__ __forceinline__ uint32_t pack2(float lo, float hi) {
    uint32_t r;
    asm volatile("cvt.rn.bf16x2.f32 %0, %1, %2;" : "=r"(r) : "f"(hi), "f"(lo));
    return r;
}
__device__ __forceinline__ uint32_t movm(uint32_t a) {
    uint32_t r;
    asm volatile("movmatrix.sync.aligned.m8n8.trans.b16 %0, %1;" : "=r"(r) : "r"(a));
    return r;
}
__device__ __forceinline__ void stsm4(uint32_t addr, uint32_t a, uint32_t b, uint32_t c, uint32_t d) {
    asm volatile("stmatrix.sync.aligned.m8n8.x4.shared.b16 [%0], {%1,%2,%3,%4};" ::"r"(addr), "r"(a), "r"(b), "r"(c), "r"(d) : "memory");
}
__device__ __forceinline__ void sts1(uint32_t addr, uint32_t a) { asm volatile("st.shared.b32 [%0], %1;" ::"r"(addr), "r"(a) : "memory"); }
__device__ __forceinline__ uint32_t lds1(uint32_t addr) {
    uint32_t a;
    asm volatile("ld.shared.b32 %0, [%1];" : "=r"(a) : "r"(addr) : "memory");
    return a;
}
__device__ __forceinline__ void stg1(uint8_t* p, uint32_t a) { asm volatile("st.global.b32 [%0], %1;" ::"l"(p), "r"(a) : "memory"); }
__device__ __forceinline__ void st_part(uint8_t* p, const uint32_t* v, uint32_t parity) {
    asm volatile("{\n.reg .b64 x, y;\nmov.b64 x, {%1, %2};\nmov.b64 y, {%3, %4};\nst.relaxed.gpu.global.v2.b64 [%0], {x, y};\n}\n"
                 ::"l"(p), "r"((v[0] & ~1u) | parity), "r"(v[1]), "r"((v[2] & ~1u) | parity), "r"(v[3]) : "memory");
}
__device__ __forceinline__ void mma16816(float (&d)[4], const uint32_t (&a)[4], uint32_t b0, uint32_t b1) {
    asm volatile("mma.sync.aligned.m16n8k16.row.col.f32.bf16.bf16.f32 {%0,%1,%2,%3}, {%4,%5,%6,%7}, {%8,%9}, {%0,%1,%2,%3};"
                 : "+f"(d[0]), "+f"(d[1]), "+f"(d[2]), "+f"(d[3]) : "r"(a[0]), "r"(a[1]), "r"(a[2]), "r"(a[3]), "r"(b0), "r"(b1));
}
__device__ __forceinline__ uint32_t add2(uint32_t a, uint32_t b) {
    uint32_t r;
    asm("add.rn.bf16x2 %0, %1, %2;" : "=r"(r) : "r"(a), "r"(b));
    return r;
}
__device__ __forceinline__ uint32_t max2(uint32_t a, uint32_t b) {
    uint32_t r;
    asm("max.bf16x2 %0, %1, %2;" : "=r"(r) : "r"(a), "r"(b));
    return r;
}
__device__ __forceinline__ void st_tagged(uint8_t* p, uint32_t a, uint32_t b, uint32_t tag) {
    asm volatile("{\n.reg .b64 x, y;\nmov.b64 x, {%1, %3};\nmov.b64 y, {%2, %3};\nst.relaxed.gpu.global.v2.b64 [%0], {x, y};\n}\n"
                 ::"l"(p), "r"(a), "r"(b), "r"(tag) : "memory");
}
__device__ __forceinline__ void ld_tagged(const uint8_t* p, uint32_t& a, uint32_t& ta, uint32_t& b, uint32_t& tb) {
    asm volatile("{\n.reg .b64 x, y;\nld.relaxed.gpu.global.v2.b64 {x, y}, [%4];\nmov.b64 {%0, %1}, x;\nmov.b64 {%2, %3}, y;\n}\n"
                 : "=r"(a), "=r"(ta), "=r"(b), "=r"(tb) : "l"(p) : "memory");
}
__device__ __forceinline__ float bf_lo(uint32_t v) { return __uint_as_float(v << 16); }
__device__ __forceinline__ float bf_hi(uint32_t v) { return __uint_as_float(v & 0xFFFF0000u); }
__device__ __forceinline__ float rcp(float x) { float r; asm("rcp.approx.ftz.f32 %0, %1;" : "=f"(r) : "f"(x)); return r; }
__device__ __forceinline__ float ex2(float x) { float r; asm volatile("ex2.approx.ftz.f32 %0, %1;" : "=f"(r) : "f"(x)); return r; }

__device__ __forceinline__ uint32_t full_bar(int stage) { return base + BAR_FULL + (stage & 7) * 8; }
__device__ __forceinline__ void wait_released(int j) { mbar_wait(base + BAR_EMPTY + (j & 7) * 8, (j >> 3) & 1); }

template <int V>
struct Int { static constexpr int value = V; };

__host__ __device__ constexpr int bslot_e(int i) { return (i < 2 || i >= 14) ? (i + 5) % 7 : (i + 1) % 5; }
__host__ __device__ constexpr int bslot_l(int i) { return i % 6; }

template <uint32_t OFF>
struct Feed {
    int stage;
    uint32_t dst;
    __device__ __forceinline__ void seek(int i, int slot) { stage = i; dst = base + OFF + slot * SLOT; }
    template <int N>
    __device__ __forceinline__ uint32_t acquire() { wait_released(stage - N); return full_bar(stage); }
    template <int N>
    __device__ __forceinline__ void next() {
        stage++;
        dst += SLOT;
        if (dst == base + OFF + N * SLOT) dst = base + OFF;
    }
};
__device__ __forceinline__ int skip_own(int n, int mt) { return n == mt ? 15 : n; }

struct Desc { uint32_t lo, hi; };
__host__ __device__ constexpr Desc desc_const(uint32_t lbo, uint32_t sbo, uint32_t mode) { return {(lbo >> 4) << 16, (sbo >> 4) | (mode << 30)}; }
constexpr Desc D_K128 = desc_const(16, 1024, 1);
constexpr Desc D_N128 = desc_const(8192, 1024, 1);
constexpr Desc D_BLOB = desc_const(128, 256, 0);
constexpr Desc D_OT = desc_const(2048, 128, 0);

enum Kind { XW, XWN, QK, BIG, OUT };

struct Ring {
    int stage;
    uint32_t a, b;
    uint32_t wg;
    uint32_t zero;
    __device__ __forceinline__ void seek(int i, int bslot) {
        stage = i;
        a = (base + (i % NA) * SLOT) >> 4;
        b = (base + BRING + bslot * SLOT) >> 4;
    }
    __device__ __forceinline__ void wait() { mbar_wait(full_bar(stage), (stage >> 3) & 1); }
    __device__ __forceinline__ void take_turn() { nb_sync(1 + wg, 256); }
    __device__ __forceinline__ void pin() {
        uint32_t n = 0;
#pragma unroll 1
        do {
            asm volatile("pmevent 7;" ::: "memory");
        } while (n++ < zero);
    }
    template <Kind K, int NBS, bool INIT, int SB = 1>
    __device__ __forceinline__ void run(float (&d)[56], float (&e)[56], bool first = true, bool last = true, bool more = true) {
        if (first) take_turn();
        asm volatile("wgmma.fence.sync.aligned;" ::: "memory");
        if (K == QK) {
            const uint32_t da = D_K128.lo + (base >> 4) + (stage >> 1) * (SLOT >> 4) + (stage & 1) * 4 + wg * 512, db = D_N128.lo + b;
            wgmma112<0, 1, 1, INIT, D_K128.hi, D_N128.hi>(d, da, db);
            wgmma112<0, 1, 1, INIT, D_K128.hi, D_N128.hi>(e, da, db + 256);
            wgmma112<0, 1, 1, false, D_K128.hi, D_N128.hi>(d, da + 2, db + 128);
            wgmma112<0, 1, 1, false, D_K128.hi, D_N128.hi>(e, da + 2, db + 384);
        } else {
            constexpr int TA = K == OUT, TB = K != XW;
            constexpr uint32_t sa = K == OUT ? 256 : 2, sb = K == XW ? 2 : K == BIG ? 224 : 128;
            constexpr Desc A = K == OUT ? D_OT : D_K128, B = K == XW ? D_K128 : K == BIG ? D_BLOB : D_N128;
            const uint32_t da = A.lo + a + wg * (K == OUT ? 64 : 512), db = B.lo + b;
            wgmma112<TA, TB, SB, INIT, A.hi, B.hi>(d, da, db);
            wgmma112<TA, TB, SB, false, A.hi, B.hi>(d, da + sa, db + sb);
            wgmma112<TA, TB, SB, false, A.hi, B.hi>(d, da + 2 * sa, db + 2 * sb);
            wgmma112<TA, TB, SB, false, A.hi, B.hi>(d, da + 3 * sa, db + 3 * sb);
        }
        asm volatile("wgmma.commit_group.sync.aligned;" ::: "memory");
        if (last) nb_arrive(2 - wg, 256);
        asm volatile("wgmma.wait_group.sync.aligned 1;" ::: "memory");
        if (stage > 0 && elect()) mbar_arrive(base + BAR_EMPTY + ((stage - 1) & 7) * 8);
        stage++;
        a += SLOT >> 4;
        if (a == (base + NA * SLOT) >> 4) a = base >> 4;
        b += SLOT >> 4;
        if (b == (base + BRING + NBS * SLOT) >> 4) b = (base + BRING) >> 4;
        if (more) wait();
    }
    template <Kind K, int NBS, bool INIT, int SB = 1>
    __device__ __forceinline__ void run(float (&d)[56], bool first = true, bool last = true, bool more = true) {
        run<K, NBS, INIT, SB>(d, d, first, last, more);
    }
};

__device__ __forceinline__ void pack_all(const float (&d)[56], uint32_t (&p)[28]) {
#pragma unroll
    for (int i = 0; i < 28; i++) p[i] = pack2(d[2 * i], d[2 * i + 1]);
}
template <int I0, int I1>
__device__ __forceinline__ void store_frags(uint8_t* dst, const uint32_t (&p)[28]) {
#pragma unroll
    for (int i = I0; i < I1; i++) stg1(dst + i * 128, p[i]);
}
template <int I0, int I1>
__device__ __forceinline__ void stage_frags(uint32_t lane_addr, const uint32_t (&p)[28]) {
#pragma unroll
    for (int i = I0; i < I1; i += 4) stsm4(lane_addr + i * 128, p[i], p[i + 1], p[i + 2], p[i + 3]);
}
__device__ __forceinline__ void store_out(const uint32_t (&p)[28], int lane, uint32_t slab, const CUtensorMap* m, int c0, int c1) {
    const bool swap = lane & 16;
    const uint32_t addr = slab + (lane & 15) * 224 + (((lane >> 4) ^ (lane >> 2)) & 1) * 16;
#pragma unroll
    for (int i = 0; i < 28; i += 4)
        stsm4(addr + i * 8, swap ? p[i + 2] : p[i], swap ? p[i + 3] : p[i + 1], swap ? p[i] : p[i + 2], swap ? p[i + 1] : p[i + 3]);
    fence_async_smem();
    __syncwarp();
    if (elect()) {
        tma_st2(m, c0, c1, slab);
        bulk_commit();
        bulk_wait_read();
    }
}
__host__ __device__ constexpr int tile_of(int t) { return 7 * (t >> 2) + 3 * ((t >> 1) & 1) + 2 * (t & 1); }

__global__ void __launch_bounds__(384, 1) fused_kernel(Scratch* sc, const __grid_constant__ Maps maps) {
    extern __shared__ uint8_t smem_raw[];
    if ((uint32_t)__cvta_generic_to_shared(smem_raw) != base) return;
    const int warp = __shfl_sync(0xffffffffu, threadIdx.x >> 5, 0);
    int lane = threadIdx.x & 31;
    asm volatile("" : "+r"(lane));
    uint32_t sm, nsm;
    asm("mov.u32 %0, %%smid;" : "=r"(sm));
    asm("mov.u32 %0, %%nsmid;" : "=r"(nsm));
    if (nsm != 132) sm = blockIdx.x;
    const int tpc = sm >> 1;
    const int t2 = tpc - 32, q2 = (t2 * 37) >> 8;
    const int oct = tpc < 32 ? 2 * (tpc & 7) : tpc < 60 ? 2 * (t2 - 7 * q2) + 3 : 1;
    const int pos = tpc < 32 ? tpc >> 3 : tpc < 60 ? q2 : tpc - 60;
    const int bid = sm >= 128 ? sm : oct * 8 + pos * 2 + (sm & 1);
    const bool roleH = bid >= 128;
    const int roleL = (bid >> 4) & 1;
    const int mt = ((bid >> 5) << 2) | ((bid >> 2) & 3);
    const int ns = bid & 3;
    const int par = mt >> 3, blk = mt & 7;

    const int col = ns * 112;
    auto fill = [&](auto i0, auto i1) {
        if (roleL) {
#pragma unroll
            for (int i = decltype(i0)::value; i < decltype(i1)::value; i++) {
                const uint32_t bar = full_bar(i), dst = base + BRING + i * SLOT;
                if (i < 6) mbar_expect(bar, SLOT);
                if (i & 1) {
                    mbar_arrive(bar);
                } else {
                    mbar_expect(bar, SLOT);
                    tma_ld2(base + (i >> 1) * SLOT, &maps.m[M_XA], par * 448 + i * 32, blk * 128, bar);
                }
                if (i < 6) {
                    tma_ld4(dst, &maps.m[M_WQK], 0, i * 32, 0, ns, bar);
                    tma_ld4(dst + 8192, &maps.m[M_WQK], 64, i * 32, 0, ns, bar);
                }
            }
        } else if (!roleH) {
#pragma unroll
            for (int i = decltype(i0)::value; i < decltype(i1)::value; i++) {
                const uint32_t bar = full_bar(i);
                mbar_expect(bar, SLOT);
                mbar_expect(bar, BLOB);
                tma_ld3(base + i * SLOT, &maps.m[M_XB], i * 64, mt * 64, 0, bar);
                tma_ld2(base + BRING + bslot_e(i) * SLOT, &maps.m[M_WR], i * 64, col, bar);
            }
        } else {
#pragma unroll 1
            for (int i = decltype(i0)::value; i < decltype(i1)::value; i++) {
                const uint32_t bar = full_bar(i), dst = base + BRING + i * SLOT;
                mbar_expect(bar, SLOT);
                mbar_expect(bar, SLOT);
                tma_ld4(base + i * SLOT, &maps.m[M_XH], i * 64, 120, 0, 0, bar);
                tma_ld3(dst, &maps.m[M_WV], 0, i * 64, 4 + ns, bar);
                tma_ld3(dst + 8192, &maps.m[M_WV], 64, i * 64, 4 + ns, bar);
            }
        }
    };
    if (warp == 8) {
        if (elect()) {
#pragma unroll
            for (int i = 0; i < 8; i++) mbar_init(base + BAR_FULL + i * 8, 2);
            asm volatile("fence.mbarrier_init.release.cluster;" ::: "memory");
            fill(Int<0>(), Int<LEAD>());
        }
    } else if (warp == 9) {
        if (elect()) {
#pragma unroll
            for (int i = 0; i < 8; i++) mbar_init(base + BAR_EMPTY + i * 8, 8);
            asm volatile("fence.mbarrier_init.release.cluster;" ::: "memory");
        }
    } else if (warp == 10) {
        if (elect()) {
#pragma unroll
            for (int i = 0; i < 5; i++) mbar_init(base + BAR_RDY + i * 8, i < 2 ? 4 : 8);
#pragma unroll
            for (int i = 0; i < 2; i++) mbar_init(base + BAR_HALO + i * 8, 8);
            asm volatile("fence.mbarrier_init.release.cluster;" ::: "memory");
        }
    } else if (warp == 11) {
        if (elect()) {
#pragma unroll
            for (int i = 0; i < 3; i++) mbar_init(base + BAR_DEP + i * 8, 1);
            asm volatile("fence.mbarrier_init.release.cluster;" ::: "memory");
        }
    }
    __syncthreads();

    if (__builtin_expect(warp >= 8, 1)) {
        asm volatile("setmaxnreg.dec.sync.aligned.u32 56;");
#define PROF_FEED_A
#define PROF_FEED_B
        if (__builtin_expect(warp == 8, 1)) {
            if (elect()) {
                PROF(129);
                fill(Int<LEAD>(), Int<7>());
                PROF(134);
                Feed<0> f;
                const int row = mt * 128;
                auto c_run = [&](const CUtensorMap* m, int off, int n0, int n1) {
#pragma unroll 1
                    for (int n = n0; n < n1; n++) {
                        const uint32_t bar = f.acquire<NA>();
                        mbar_expect(bar, SLOT);
                        tma_ld2(f.dst, m, (off + skip_own(n, mt)) * 64, row, bar);
                        PROF_FEED_A;
                        f.next<NA>();
                    }
                };
                if (roleH) {
                } else if (!roleL) {
                    f.seek(14, 0);
                    mbar_wait(base + BAR_RDY, 0);
#pragma unroll 1
                    for (int i = 0; i < 4; i++) {
                        const uint32_t bar = f.acquire<NA>();
                        mbar_expect(bar, SLOT);
                        tma_ld2(f.dst, &maps.m[M_CR + (i >> 1)], ((i & 1) * 16 + mt) * 64, row, bar);
                        mbar_arrive(bar);
                        PROF_FEED_A;
                        f.next<NA>();
                    }
                    c_run(&maps.m[M_CR], 0, 0, 15);
                    c_run(&maps.m[M_CI], 0, 0, NBE);
                    wait_dep(2);
#pragma unroll 1
                    for (int i = 0; i < 7; i++) {
                        const uint32_t bar = f.acquire<NA>();
                        mbar_expect(bar, SLOT);
                        bulk_ld(f.dst, sc->o + (size_t)(mt * 7 + i) * SLOT, SLOT, bar);
                        PROF_FEED_A;
                        f.next<NA>();
                    }
                } else {
#pragma unroll 1
                    for (int i = 4; i < 7; i++) {
                        wait_released(2 * i - 8);
                        mbar_expect(full_bar(2 * i), SLOT);
                        tma_ld2(base + i * SLOT, &maps.m[M_XA], par * 448 + i * 64, blk * 128, full_bar(2 * i));
                    }
                    wait_released(7);
                    f.seek(21, 0);
                    c_run(&maps.m[M_CR], 16, 0, 15);
                    c_run(&maps.m[M_CI], 16, 0, 15);
                    c_run(&maps.m[M_CI], 0, NBE, 15);
                }
            }
        } else if (warp == 11) {
            if (elect()) {
                Feed<BRING> f;
                auto blob_run = [&](auto nbs, int quarter, int n0, int n1) {
                    constexpr int N = decltype(nbs)::value;
                    const uint8_t* src = sc->ab + (size_t)(quarter * 64 + ns) * BLOB;
#pragma unroll 1
                    for (int n = n0; n < n1; n++) {
                        const uint32_t bar = f.template acquire<N>();
                        mbar_expect(bar, BLOB);
                        bulk_ld(f.dst, src + skip_own(n, mt) * (4 * BLOB), BLOB, bar);
                        PROF_FEED_B;
                        f.template next<N>();
                    }
                };
                auto w_run = [&](auto nbs, const CUtensorMap* m, int slice, bool no_a) {
                    constexpr int N = decltype(nbs)::value;
#pragma unroll 1
                    for (int i = 0; i < 7; i++) {
                        const uint32_t bar = f.template acquire<N>();
                        mbar_expect(bar, SLOT);
                        tma_ld3(f.dst, m, 0, i * 64, slice, bar);
                        tma_ld3(f.dst + 8192, m, 64, i * 64, slice, bar);
                        if (no_a) mbar_arrive(bar);
                        PROF_FEED_B;
                        f.template next<N>();
                    }
                };
                if (roleH) {
                    f.seek(7, 0);
                    w_run(Int<7>(), &maps.m[M_WV], 8 + ns, true);
                } else if (!roleL) {
                    f.seek(7, bslot_e(7));
#pragma unroll 1
                    for (int i = 0; i < 7; i++) {
                        const uint32_t bar = f.acquire<5>();
                        mbar_expect(bar, BLOB);
                        tma_ld2(f.dst, &maps.m[M_WI], i * 64, col, bar);
                        mbar_arrive(bar);
                        PROF_FEED_B;
                        f.next<5>();
                    }
                    f.seek(18, bslot_e(18));
                    wait_dep(0);
                    blob_run(Int<7>(), 0, 0, 15);
                    wait_dep(1);
                    blob_run(Int<7>(), 2, 0, NBE);
                    w_run(Int<7>(), &maps.m[M_WO], ns, false);
                } else {
                    f.seek(6, 0);
#pragma unroll 1
                    for (int i = 6; i < 14; i++) {
                        const uint32_t bar = f.acquire<6>();
                        mbar_expect(bar, SLOT);
                        tma_ld4(f.dst, &maps.m[M_WQK], 0, i * 32, 0, ns, bar);
                        tma_ld4(f.dst + 8192, &maps.m[M_WQK], 64, i * 32, 0, ns, bar);
                        if (i & 1) mbar_arrive(bar);
                        PROF_FEED_B;
                        f.next<6>();
                    }
                    w_run(Int<6>(), &maps.m[M_WV], 8 + ns, true);
                    wait_dep(0);
                    blob_run(Int<6>(), 1, 0, 15);
                    wait_dep(1);
                    blob_run(Int<6>(), 3, 0, 15);
                    blob_run(Int<6>(), 2, NBE, 15);
                }
            }
        } else if (roleH) {
        } else if (warp == 10) {
            if (elect()) {
                unsigned* epoch_ptr = &sc->epoch[(bid * 4 + 2) * 8];
                const unsigned ep = *epoch_ptr + 1;
                sts1(base + TAG, ep);
                await(sc, CNT_A + roleL * 4 + ns, ep * 16);
                mbar_arrive(base + BAR_DEP);
                PROF(150);
                await(sc, CNT_B + ns, ep * 16);
                mbar_arrive(base + BAR_DEP + 8);
                PROF(151);
                if (!roleL) {
                    await(sc, CNT_O + mt, ep * 4);
                    mbar_arrive(base + BAR_DEP + 16);
                }
                PROF(152);
                *epoch_ptr = ep;
            }
        } else if (!roleL) {
            if (elect()) {
                mbar_wait(base + BAR_RDY, 0);
                PROF(130);
                signal(sc, CNT_A + ns);
                PROF(131);
                mbar_wait(base + BAR_RDY + 8, 0);
                signal(sc, CNT_A + 4 + ns);
                PROF(135);
                mbar_wait(base + BAR_RDY + 32, 0);
                PROF(132);
                signal(sc, CNT_B + ns);
                PROF(133);
            }
        } else {
            const unsigned t_start = clk32();
            unsigned* epoch_ptr = &sc->epoch[(bid * 4 + 1) * 8];
            const unsigned tag = *epoch_ptr + 1;
#pragma unroll 1
            for (int kv = 0; kv < 2; kv++) {
                uint32_t v[14], t[14];
#pragma unroll
                for (int i = 0; i < 14; i++) v[i] = 0;

                if (blk > 0) {
                    const uint8_t* src = sc->halo + (size_t)(((mt - 1) * 4 + ns) * 2 + kv) * (2 * HSLOT) + lane * 16;
                    pause_until(t_start, HALO_DELAY + kv * 3200);
#pragma unroll 1
                    for (int n = 0; n < SPIN_LIMIT; n++) {
                        bool ok = true;
#pragma unroll
                        for (int i = 0; i < 7; i++) ld_tagged(src + i * 512, v[2 * i], t[2 * i], v[2 * i + 1], t[2 * i + 1]);
#pragma unroll
                        for (int i = 0; i < 14; i++) ok = ok && t[i] == tag;
                        if (__all_sync(0xffffffffu, ok)) break;
                    }
                }
#pragma unroll
                for (int i = 0; i < 14; i++) sts1(base + HALO + kv * (8 * HSLOT) + i * 128 + lane * 4, v[i]);
                warp_arrive(base + BAR_HALO + kv * 8);
                if (lane == 0) PROF(142 + kv);
            }
            if (elect()) {
                mbar_wait(base + BAR_RDY + 16, 0);
                PROF(130);
                signal(sc, CNT_O + mt);
                PROF(131);
                *epoch_ptr = tag;
            }
        }
    } else {
        asm volatile("setmaxnreg.inc.sync.aligned.u32 224;");
        Ring r;
        r.wg = warp >> 2;
        r.zero = blockIdx.y;
        const int wg = warp >> 2;
        if (wg) nb_arrive(1, 256);
        r.stage = 0;
        r.wait();
        uint8_t* part = sc->part + (size_t)(ns * 16 + mt) * (2 * BLOB) + warp * 512 + lane * 16;
        uint32_t p[28];

        if (roleH) {
            unsigned* epoch_ptr = &sc->epoch[bid * 4 * 8];
            const unsigned tag = *epoch_ptr + 1;
            uint8_t* hout = sc->halo + (size_t)((warp * 8 + ns) * 2) * (2 * HSLOT) + lane * 16;
            float x0[56], x1[56];
            r.seek(0, 0);
            r.run<XWN, 7, true>(x0);
#pragma unroll 1
            for (int i = 1; i < 7; i++) r.run<XWN, 7, false>(x0);
            r.run<XWN, 7, true>(x1);
            acc_fence(x0);
            pack_all(x0, p);
#pragma unroll
            for (int i = 0; i < 14; i++) st_tagged(hout + (i & 1) * (16 * HSLOT) + (i >> 1) * 512, p[(i >> 1) * 4 + (i & 1)], p[(i >> 1) * 4 + (i & 1) + 2], tag);
#pragma unroll 1
            for (int i = 1; i < 7; i++) r.run<XWN, 7, false>(x1, true, true, i < 6);
            asm volatile("wgmma.wait_group.sync.aligned 0;" ::: "memory");
            acc_fence(x1);
            pack_all(x1, p);
#pragma unroll
            for (int i = 0; i < 28; i++) p[i] = movm(p[i]);
#pragma unroll
            for (int i = 0; i < 14; i++)
                st_tagged(hout + 2 * HSLOT + (i & 1) * (16 * HSLOT) + (i >> 1) * 512, p[(i >> 1) * 4 + (i & 1)], p[(i >> 1) * 4 + (i & 1) + 2], tag);
            if (threadIdx.x == 0) *epoch_ptr = tag;
        } else if (!roleL) {
            uint8_t* blob = sc->ab + (size_t)((wg * 16 + mt) * 4 + ns) * BLOB + (warp & 3) * WSLOT + lane * 4;
            const uint32_t own = base + BRING + wg * SLOT + (warp & 3) * WSLOT + lane * 16;
            float x0[56], x1[56];
            r.seek(0, bslot_e(0));
            r.run<XW, 7, true>(x0);
            r.run<XW, 7, false>(x0);
            r.seek(2, bslot_e(2));
#pragma unroll 1
            for (int i = 2; i < 7; i++) r.run<XW, 5, false>(x0);

            r.seek(7, bslot_e(7));
            r.run<XW, 5, true, -1>(x1);
            acc_fence(x0);
            pack_all(x0, p);
#pragma unroll
            for (int i = 0; i < 2; i++) {
                if (wg == i) store_frags<0, 14>(blob, p);
                else stage_frags<0, 4>(own + 5 * SLOT, p);
                r.run<XW, 5, false, -1>(x1);
                if (wg == i) {
                    store_frags<14, 28>(blob, p);
                    warp_arrive(base + BAR_RDY + i * 8);
                } else {
                    stage_frags<4, 8>(own + 5 * SLOT, p);
                }
                r.run<XW, 5, false, -1>(x1);
            }
            stage_frags<8, 20>(own + 5 * SLOT, p);
            r.run<XW, 5, false, -1>(x1);
            stage_frags<20, 28>(own + 5 * SLOT, p);
            warp_arrive(base + BAR_RDY + 16);
            r.run<XW, 5, false, -1>(x1);

            mbar_wait(base + BAR_RDY + 16, 0);
            fence_async_smem();
            r.seek(14, bslot_e(14));
            r.run<BIG, 7, true>(x0);
            acc_fence(x1);
            pack_all(x1, p);
            wait_released(10);
            stage_frags<0, 28>(own, p);
            warp_arrive(base + BAR_RDY + 24);
            r.run<BIG, 7, false>(x0);
            mbar_wait(base + BAR_RDY + 24, 0);
            fence_async_smem();
            blob += (size_t)128 * BLOB;
#pragma unroll
            for (int i = 0; i < 28; i++) {
                if (i % B_SLICE == 0) r.run<BIG, 7, false>(x0);
                stg1(blob + i * 128, p[i]);
            }
            warp_arrive(base + BAR_RDY + 32);
#pragma unroll 1
            for (int i = 17 + 27 / B_SLICE; i < POUT; i++) r.run<BIG, 7, false>(x0);

            const uint32_t tag = lds1(base + TAG);
            r.seek(POUT, bslot_e(POUT));
            r.run<OUT, 7, true>(x1);
            acc_fence(x0);
            pack_all(x0, p);
#pragma unroll
            for (int k = 0; k < 3; k++) {
                if (k < 2 && wg == k) {
#pragma unroll
                    for (int i = 0; i < 4; i++) st_part(part + i * 4096, p + 4 * i, tag & 1);
                }
                if (k > 0 && wg == k - 1) {
#pragma unroll
                    for (int i = 4; i < 7; i++) st_part(part + i * 4096, p + 4 * i, tag & 1);
                }
                if (k < 2) r.run<OUT, 7, false>(x1);
            }
#pragma unroll 1
            for (int i = 3; i < 7; i++) r.run<OUT, 7, false>(x1, i <= 7 - TURN, i < 7 - TURN || i == 6, i < 6);

            wait_released(ELAST - 6);
            asm volatile("wgmma.wait_group.sync.aligned 0;" ::: "memory");
            acc_fence(x1);
            pack_all(x1, p);
            const uint32_t slab = base + (wg ? BRING + bslot_e(ELAST - 6) * SLOT : ((ELAST - 6) % NA) * SLOT) + (warp & 3) * WSLOT;
            store_out(p, lane, slab, &maps.m[M_OUTA], par * 896 + col, blk * 128 + warp * 16);
        } else {
            const int g = lane >> 2, tig = lane & 3;
            const uint32_t hin = base + HALO + warp * HSLOT + lane * 4;
            auto publish = [&](const uint32_t (&h)[14], int kv) {
                if (warp < 7) {
#pragma unroll
                    for (int c = 0; c < 14; c++) sts1(hin + HSLOT + c * 128, h[c]);
                    warp_arrive(base + BAR_HALO + kv * 8);
                }
            };
            float y0[56], y1[56], y2[56];
            r.seek(0, 0);
            r.run<QK, 6, true>(y0, y1);
#pragma unroll 1
            for (int i = 1; i < 14; i++) r.run<QK, 6, false>(y0, y1);

            uint32_t m1[8][4], m0[8][4], lo[14], hi[14];
            r.seek(14, bslot_l(14));
            r.run<XWN, 6, true>(y2);
            acc_fence(y0);
            acc_fence(y1);
#pragma unroll
            for (int c = 0; c < 14; c++) hi[c] = pack2(y1[4 * c + 2], y1[4 * c + 3]);
            publish(hi, 0);
            r.run<XWN, 6, false>(y2);
#pragma unroll
            for (int c = 0; c < 14; c++) lo[c] = pack2(y1[4 * c], y1[4 * c + 1]);
#pragma unroll
            for (int t = 0; t < 8; t++) {
                const int c = tile_of(t);
                const bool shared = (t & 3) == 2;
                m1[t][0] = shared ? dup(lo[c], r.zero) : lo[c];
                m1[t][1] = shared ? dup(hi[c], r.zero) : hi[c];
                m1[t][2] = lo[c + 1];
                m1[t][3] = hi[c + 1];
                m0[t][0] = dup(m1[t][0], r.zero);
                m0[t][2] = dup(lo[c + 1], 2 * r.zero);
            }
            r.run<XWN, 6, false>(y2);
            uint32_t q[2][8][2];
#pragma unroll
            for (int b = 0; b < 2; b++) {
                uint32_t v[14];
#pragma unroll
                for (int c = 0; c < 14; c++) v[c] = pack2(y0[4 * c + 2 * b], y0[4 * c + 2 * b + 1]);
#pragma unroll
                for (int t = 0; t < 8; t++) {
                    const int c = tile_of(t);
                    q[b][t][0] = (t & 3) == 2 ? (tig >= 2 ? v[c] : 0u) : v[c];
                    q[b][t][1] = (t & 3) == 1 ? (tig < 2 ? v[c + 1] : 0u) : v[c + 1];
                }
            }
            r.run<XWN, 6, false>(y2);
            mbar_wait(base + BAR_HALO, 0);
#pragma unroll
            for (int t = 0; t < 8; t++) {
                m0[t][1] = lds1(hin + tile_of(t) * 128 + ((t & 3) == 2 ? r.zero : 0u));
                m0[t][3] = lds1(hin + tile_of(t) * 128 + 128);
            }
            r.pin();
            r.take_turn();
            float s[8][4];
#pragma unroll
            for (int step = 0; step < 2; step++) {
#pragma unroll
                for (int i = 0; i < 8; i++) {
                    const int b = 1 - (i >> 2), h = i & 3, t = 2 * h + step;
                    float (&d)[4] = s[2 * h + b];
                    if (step == 0) d[0] = d[1] = d[2] = d[3] = 0.f;
                    mma16816(d, b ? m1[t] : m0[t], q[b][t][0], q[b][t][1]);
                }
            }
            r.pin();
            r.run<XWN, 6, false>(y2, false);

            uint32_t pr[8], mx[4], mx1[4];
            {
                const bool cur0 = g <= 2 * tig, cur1 = g <= 2 * tig + 1;
#pragma unroll
                for (int i = 0; i < 8; i++) {
                    const int c = (i & 1) ? 2 : 0;
                    pr[i] = movm(pack2(cur0 ? s[i][c] : s[i][2 - c], cur1 ? s[i][c + 1] : s[i][3 - c]));
                }
            }
            r.run<XWN, 6, false>(y2);
            const uint32_t curmask = (2 * tig <= g ? 0x0000FFFFu : 0u) | (2 * tig + 1 <= g ? 0xFFFF0000u : 0u);
            {
                const uint32_t keep = (blk == 0 && warp == 0) ? curmask : 0xFFFFFFFFu;
#pragma unroll
                for (int i = 0; i < 4; i++) {
                    pr[2 * i] = (pr[2 * i] & keep) | (0xCF9ECF9Eu & ~keep);
                    mx[i] = max2(__byte_perm(pr[2 * i], pr[2 * i + 1], 0x5410), __byte_perm(pr[2 * i], pr[2 * i + 1], 0x7632));
                }
#pragma unroll
                for (int i = 0; i < 4; i++) mx[i] = max2(mx[i], __shfl_xor_sync(0xffffffffu, mx[i], 1));
#pragma unroll
                for (int i = 0; i < 4; i++) mx1[i] = __shfl_xor_sync(0xffffffffu, mx[i], 2);
            }
            r.run<XWN, 6, false>(y2);
            constexpr float SCL = 0.18898223650461362f * 1.4426950408889634f;
            float e0[8], e1[8], sm[8], sm1[8];
#pragma unroll
            for (int i = 0; i < 8; i++) {
                const uint32_t m2 = max2(mx[i >> 1], mx1[i >> 1]);
                sm[i] = ((i & 1) ? bf_hi(m2) : bf_lo(m2)) * -SCL;
                e0[i] = ex2(fmaf(bf_lo(pr[i]), SCL, sm[i]));
            }

            r.seek(21, bslot_l(21));
            r.run<BIG, 6, true>(y0);
            acc_fence(y2);
#pragma unroll
            for (int c = 0; c < 14; c++) hi[c] = movm(pack2(y2[4 * c + 2], y2[4 * c + 3]));
            r.run<BIG, 6, false>(y0);
            wait_released(18);
            publish(hi, 1);
            r.run<BIG, 6, false>(y0);
#pragma unroll
            for (int i = 0; i < 8; i++) {
                e1[i] = ex2(fmaf(bf_hi(pr[i]), SCL, sm[i]));
                sm[i] = e0[i] + e1[i];
                sm1[i] = __shfl_xor_sync(0xffffffffu, sm[i], 1);
            }
            r.run<BIG, 6, false>(y0);
#pragma unroll
            for (int c = 0; c < 14; c++) lo[c] = movm(pack2(y2[4 * c], y2[4 * c + 1]));
            r.run<BIG, 6, false>(y0);
#pragma unroll
            for (int i = 0; i < 8; i++) {
                sm[i] += sm1[i];
                sm1[i] = __shfl_xor_sync(0xffffffffu, sm[i], 2);
            }
#pragma unroll
            for (int t = 0; t < 8; t++) {
                const int c = tile_of(t);
                const bool shared = (t & 3) == 2;
                m1[t][0] = shared ? dup(lo[c], r.zero) : lo[c];
                m1[t][1] = lo[c + 1];
                m1[t][2] = shared ? dup(hi[c], r.zero) : hi[c];
                m1[t][3] = hi[c + 1];
                m0[t][0] = dup(m1[t][0], r.zero);
                m0[t][1] = dup(lo[c + 1], 2 * r.zero);
            }
            r.run<BIG, 6, false>(y0);
            uint32_t pb[8][2];
#pragma unroll
            for (int i = 0; i < 8; i++) {
                const float inv = rcp(sm[i] + sm1[i]);
                const uint32_t w = pack2(e0[i] * inv, e1[i] * inv);
                pb[i][i & 1] = band(w, curmask);
                pb[i][1 - (i & 1)] = band(w, ~curmask);
            }
            r.run<BIG, 6, false>(y0);
            mbar_wait(base + BAR_HALO + 8, 0);
            const uint32_t vin = warp ? hin : hin + 8 * HSLOT;
#pragma unroll
            for (int t = 0; t < 8; t++) {
                m0[t][2] = lds1(vin + tile_of(t) * 128 + ((t & 3) == 2 ? r.zero : 0u));
                m0[t][3] = lds1(vin + tile_of(t) * 128 + 128);
            }
            r.pin();
            r.take_turn();
            float o[2][8][4];
#pragma unroll
            for (int i = 0; i < 16; i++) {
                const int b = 1 - (i >> 3), t = i & 7;
                float (&d)[4] = o[b][t];
                d[0] = d[1] = d[2] = d[3] = 0.f;
                mma16816(d, b ? m1[t] : m0[t], pb[(t & 6) + b][0], pb[(t & 6) + b][1]);
            }
            r.pin();
            r.run<BIG, 6, false>(y0, false);
            uint8_t* odst = sc->o + (size_t)mt * 7 * SLOT + ns * (14 * 2048) + warp * 256 + lane * 4;
#pragma unroll
            for (int hp = 0; hp < 2; hp++) {
#pragma unroll
                for (int b = 0; b < 2; b++) {
                    const float (&u)[8][4] = o[b];
                    const int t = 4 * hp;
                    uint32_t* w = p + 14 * hp + b;
                    w[0] = pack2(u[t][0], u[t][1]);
                    w[2] = pack2(u[t][2], u[t][3]);
                    w[4] = pack2(u[t + 1][0], u[t + 1][1]);
                    w[6] = pack2(g < 4 ? u[t + 1][2] : u[t + 2][0], g < 4 ? u[t + 1][3] : u[t + 2][1]);
                    w[8] = pack2(u[t + 2][2], u[t + 2][3]);
                    w[10] = pack2(u[t + 3][0], u[t + 3][1]);
                    w[12] = pack2(u[t + 3][2], u[t + 3][3]);
                }
            }
#pragma unroll
            for (int i = 0; i < 28; i++) {
                if (i && i % O_SLICE == 0) r.run<BIG, 6, false>(y0);
                stg1(odst + (i >> 1) * 2048 + (i & 1) * 128, p[i]);
            }
            warp_arrive(base + BAR_RDY + 16);

#pragma unroll 1
            for (int i = 29 + 27 / O_SLICE; i <= LLAST + 1 - TURN; i++) r.run<BIG, 6, false>(y0, true, i <= LLAST - TURN);
            const uint32_t tag = lds1(base + TAG);
#pragma unroll
            for (int i = 0; i < 7; i++) ld_tagged(part + i * 4096, p[4 * i], p[4 * i + 1], p[4 * i + 2], p[4 * i + 3]);
#pragma unroll 1
            for (int i = 1; i < TURN; i++) r.run<BIG, 6, false>(y0, false, i == TURN - 1, i < TURN - 1);
#pragma unroll 1
            for (int n = 0; n < SPIN_LIMIT; n++) {
                uint32_t stale = 0;
#pragma unroll
                for (int i = 0; i < 28; i += 2) stale |= p[i] ^ tag;
                if (__all_sync(0xffffffffu, !(stale & 1))) break;
#pragma unroll
                for (int i = 0; i < 7; i++) ld_tagged(part + i * 4096, p[4 * i], p[4 * i + 1], p[4 * i + 2], p[4 * i + 3]);
            }
            wait_released(LLAST - 6);
            asm volatile("wgmma.wait_group.sync.aligned 0;" ::: "memory");
            acc_fence(y0);
#pragma unroll
            for (int i = 0; i < 28; i++) p[i] = add2(pack2(y0[2 * i], y0[2 * i + 1]), p[i]);
            const uint32_t slab = base + (wg ? HALO : ((LLAST - 6) % NA) * SLOT) + (warp & 3) * WSLOT;
            store_out(p, lane, slab, &maps.m[M_OUTB], 448 + col, mt * 128 + warp * 16);
        }
    }
}

typedef CUresult (*EncodeFn)(CUtensorMap*, CUtensorMapDataType, cuuint32_t, void*, const cuuint64_t*, const cuuint64_t*,
                             const cuuint32_t*, const cuuint32_t*, CUtensorMapInterleave, CUtensorMapSwizzle,
                             CUtensorMapL2promotion, CUtensorMapFloatOOBfill);

struct Dim { uint64_t size, stride; uint32_t box; };
void encode(EncodeFn fn, CUtensorMap* m, const void* ptr, CUtensorMapSwizzle sw, Dim d0, Dim d1, Dim d2 = {0, 0, 0}, Dim d3 = {0, 0, 0}) {
    const cuuint64_t dims[4] = {d0.size, d1.size, d2.size, d3.size};
    const cuuint64_t strides[3] = {d1.stride, d2.stride, d3.stride};
    const cuuint32_t box[4] = {d0.box, d1.box, d2.box, d3.box};
    const cuuint32_t es[4] = {1, 1, 1, 1};
    fn(m, CU_TENSOR_MAP_DATA_TYPE_BFLOAT16, d3.size ? 4 : d2.size ? 3 : 2, const_cast<void*>(ptr), dims, strides, box, es,
       CU_TENSOR_MAP_INTERLEAVE_NONE, sw, CU_TENSOR_MAP_L2_PROMOTION_L2_128B, CU_TENSOR_MAP_FLOAT_OOB_FILL_NONE);
}

}

extern "C" void kernel_launch(void* const* d_in, const int* in_sizes, int n_in, void* d_out, int out_size) {
    (void)in_sizes; (void)n_in; (void)out_size;
    void* fnp = nullptr;
    cudaDriverEntryPointQueryResult st;
    cudaGetDriverEntryPoint("cuTensorMapEncodeTiled", &fnp, cudaEnableDefault, &st);
    EncodeFn fn = (EncodeFn)fnp;
    void* scratch = nullptr;
    cudaGetSymbolAddress(&scratch, g_scratch);
    cudaFuncSetAttribute(fused_kernel, cudaFuncAttributeMaxDynamicSharedMemorySize, SMEM_BYTES);

    const CUtensorMapSwizzle S128 = CU_TENSOR_MAP_SWIZZLE_128B, S0 = CU_TENSOR_MAP_SWIZZLE_NONE;
    Maps maps;
    encode(fn, &maps.m[M_XA], d_in[0], S128, {896, 2, 64}, {1024, 1792, 128});
    encode(fn, &maps.m[M_WQK], d_in[1], S128, {112, 2, 64}, {448, 2688, 32}, {3, 896, 2}, {4, 224, 1});
    encode(fn, &maps.m[M_WV], d_in[1], S128, {112, 2, 64}, {448, 2688, 64}, {12, 224, 1});
    encode(fn, &maps.m[M_XH], d_in[0], S128, {448, 2, 64}, {128, 1792, 8}, {8, 128 * 1792, 8}, {2, 896, 2});
    encode(fn, &maps.m[M_WO], d_in[2], S128, {112, 2, 64}, {448, 896, 64}, {4, 224, 1});
    encode(fn, &maps.m[M_XB], d_in[3], S128, {448, 2, 64}, {1024, 896, 64}, {2, 896 * 1024, 2});
    encode(fn, &maps.m[M_CR], d_in[4], S128, {2048, 2, 64}, {2048, 4096, 128});
    encode(fn, &maps.m[M_CI], d_in[5], S128, {2048, 2, 64}, {2048, 4096, 128});
    encode(fn, &maps.m[M_WR], d_in[6], S128, {448, 2, 64}, {448, 896, 112});
    encode(fn, &maps.m[M_WI], d_in[7], S128, {448, 2, 64}, {448, 896, 112});
    encode(fn, &maps.m[M_OUTA], d_out, S0, {1792, 2, 112}, {1024, 3584, 16});
    encode(fn, &maps.m[M_OUTB], d_out, S0, {896, 2, 112}, {2048, 1792, 16});

    fused_kernel<<<132, 384, SMEM_BYTES>>>((Scratch*)scratch, maps);
}
```

```cpp
#include <cuda.h>
#include <cuda_bf16.h>
#include <cuda_runtime.h>
#include <stdint.h>

namespace {

constexpr uint32_t SLOT = 16384;
constexpr int NA = 7;
constexpr uint32_t BRING = NA * SLOT;
constexpr uint32_t HALO = BRING + 6 * SLOT;
constexpr uint32_t HSLOT = 1792;
constexpr uint32_t WSLOT = 3584;
constexpr uint32_t BLOB = 14336;
constexpr uint32_t BARS = 14 * SLOT;
constexpr uint32_t BAR_FULL = BARS;
constexpr uint32_t BAR_EMPTY = BARS + 64;
constexpr uint32_t BAR_RDY = BARS + 128;
constexpr uint32_t BAR_DEP = BARS + 168;
constexpr uint32_t BAR_HALO = BARS + 192;
constexpr uint32_t TAG = BARS + 208;
constexpr uint32_t SMEM_BYTES = BARS + 256 + 1024;
constexpr uint32_t base = 1024;
constexpr int SPIN_LIMIT = 1 << 16;

#define E_EXTRA 0
#define HALO_DELAY 7000
#define O_SLICE 4
#define B_SLICE 4
#define LEAD 3
#define TURN 3
#define PIN r.pin()
#define OPENER 0
#define MAPPING 2
constexpr int NBE = 13 + E_EXTRA;
constexpr int POUT = 33 + NBE;
constexpr int ELAST = POUT + 6;
constexpr int LLAST = 52 - E_EXTRA;

enum { M_XA, M_XH, M_WQK, M_WV, M_WO, M_XB, M_WR, M_WI, M_CR, M_CI, M_OUTA, M_OUTB, M_COUNT };
struct __align__(64) Maps { CUtensorMap m[M_COUNT]; };

constexpr int CNT_A = 0;
constexpr int CNT_B = 8;
constexpr int CNT_O = 16;
constexpr int CNT_COUNT = 32;

struct Scratch {
    uint8_t ab[64 * 4 * BLOB];
    uint8_t o[16 * 7 * SLOT];
    uint8_t part[64 * 2 * BLOB];
    uint8_t halo[64 * 2 * 2 * HSLOT];
    unsigned cnt[CNT_COUNT * 32];
    unsigned epoch[132 * 4 * 8];
};
__device__ __align__(1024) Scratch g_scratch;

__device__ __forceinline__ unsigned clk32() { unsigned c; asm volatile("mov.u32 %0, %%clock;" : "=r"(c)); return c; }
__device__ __forceinline__ void pause_until(unsigned t0, unsigned cycles) {
    while (clk32() - t0 < cycles) {}
}

#define PROF(idx)

__device__ __forceinline__ void mbar_init(uint32_t bar, uint32_t cnt) {
    asm volatile("mbarrier.init.shared::cta.b64 [%0], %1;" ::"r"(bar), "r"(cnt) : "memory");
}
__device__ __forceinline__ void mbar_expect(uint32_t bar, uint32_t bytes) {
    asm volatile("mbarrier.arrive.expect_tx.shared::cta.b64 _, [%0], %1;" ::"r"(bar), "r"(bytes) : "memory");
}
__device__ __forceinline__ void mbar_arrive(uint32_t bar) {
    asm volatile("mbarrier.arrive.shared::cta.b64 _, [%0];" ::"r"(bar) : "memory");
}
__device__ __forceinline__ bool mbar_try(uint32_t bar, uint32_t parity) {
    uint32_t ok;
    asm volatile("{\n.reg .pred p;\nmbarrier.try_wait.parity.shared::cta.b64 p, [%1], %2;\nselp.u32 %0, 1, 0, p;\n}\n"
                 : "=r"(ok) : "r"(bar), "r"(parity) : "memory");
    return ok;
}
__device__ __forceinline__ void mbar_wait(uint32_t bar, uint32_t parity) {
#pragma unroll 1
    for (int n = 0; n < SPIN_LIMIT; n++)
        if (mbar_try(bar, parity)) break;
}
__device__ __forceinline__ bool elect() {
    uint32_t p;
    asm volatile("{\n.reg .pred p;\nelect.sync _|p, 0xffffffff;\nselp.u32 %0, 1, 0, p;\n}\n" : "=r"(p));
    return p;
}
__device__ __forceinline__ void nb_sync(int id, int n) { asm volatile("bar.sync %0, %1;" ::"r"(id), "r"(n) : "memory"); }
__device__ __forceinline__ void nb_arrive(int id, int n) { asm volatile("bar.arrive %0, %1;" ::"r"(id), "r"(n) : "memory"); }
__device__ __forceinline__ void warp_arrive(uint32_t bar) {
    __syncwarp();
    if (elect()) mbar_arrive(bar);
}
__device__ __forceinline__ uint32_t band(uint32_t x, uint32_t m) {
    uint32_t r;
    asm volatile("and.b32 %0, %1, %2;" : "=r"(r) : "r"(x), "r"(m));
    return r;
}
__device__ __forceinline__ uint32_t dup(uint32_t x, uint32_t zero) {
    uint32_t r;
    asm volatile("xor.b32 %0, %1, %2;" : "=r"(r) : "r"(x), "r"(zero));
    return r;
}

__device__ __forceinline__ void tma_ld2(uint32_t dst, const CUtensorMap* m, int c0, int c1, uint32_t bar) {
    asm volatile("cp.async.bulk.tensor.2d.shared::cluster.global.mbarrier::complete_tx::bytes [%0], [%1, {%3, %4}], [%2];"
                 ::"r"(dst), "l"(m), "r"(bar), "r"(c0), "r"(c1) : "memory");
}
__device__ __forceinline__ void tma_ld3(uint32_t dst, const CUtensorMap* m, int c0, int c1, int c2, uint32_t bar) {
    asm volatile("cp.async.bulk.tensor.3d.shared::cluster.global.mbarrier::complete_tx::bytes [%0], [%1, {%3, %4, %5}], [%2];"
                 ::"r"(dst), "l"(m), "r"(bar), "r"(c0), "r"(c1), "r"(c2) : "memory");
}
__device__ __forceinline__ void tma_ld4(uint32_t dst, const CUtensorMap* m, int c0, int c1, int c2, int c3, uint32_t bar) {
    asm volatile("cp.async.bulk.tensor.4d.shared::cluster.global.mbarrier::complete_tx::bytes [%0], [%1, {%3, %4, %5, %6}], [%2];"
                 ::"r"(dst), "l"(m), "r"(bar), "r"(c0), "r"(c1), "r"(c2), "r"(c3) : "memory");
}
__device__ __forceinline__ void bulk_ld(uint32_t dst, const void* src, uint32_t bytes, uint32_t bar) {
    asm volatile("cp.async.bulk.shared::cluster.global.mbarrier::complete_tx::bytes [%0], [%1], %2, [%3];"
                 ::"r"(dst), "l"(src), "r"(bytes), "r"(bar) : "memory");
}
__device__ __forceinline__ void tma_st2(const CUtensorMap* m, int c0, int c1, uint32_t src) {
    asm volatile("cp.async.bulk.tensor.2d.global.shared::cta.bulk_group [%0, {%1, %2}], [%3];"
                 ::"l"(m), "r"(c0), "r"(c1), "r"(src) : "memory");
}
__device__ __forceinline__ void bulk_commit() { asm volatile("cp.async.bulk.commit_group;" ::: "memory"); }
__device__ __forceinline__ void bulk_wait_read() { asm volatile("cp.async.bulk.wait_group.read 0;" ::: "memory"); }
__device__ __forceinline__ void fence_async_smem() { asm volatile("fence.proxy.async.shared::cta;" ::: "memory"); }
__device__ __forceinline__ void fence_async_global() { asm volatile("fence.proxy.async.global;" ::: "memory"); }

__device__ __forceinline__ void signal(Scratch* sc, int idx) {
    asm volatile("fence.proxy.async;\nred.relaxed.gpu.global.add.u32 [%0], 1;" ::"l"(&sc->cnt[idx * 32]) : "memory");
}
__device__ __forceinline__ void await(Scratch* sc, int idx, unsigned target) {
#pragma unroll 1
    for (int n = 0; n < SPIN_LIMIT; n++) {
        unsigned v;
        asm volatile("ld.relaxed.gpu.global.u32 %0, [%1];" : "=r"(v) : "l"(&sc->cnt[idx * 32]) : "memory");
        if ((int)(v - target) >= 0) break;
    }
    asm volatile("fence.acquire.gpu;" ::: "memory");
}
__device__ __forceinline__ void wait_dep(int k) {
    mbar_wait(base + BAR_DEP + k * 8, 0);
    fence_async_global();
}

#define WG_REGS                                                                                                     \
    "{%0,%1,%2,%3,%4,%5,%6,%7,%8,%9,%10,%11,%12,%13,%14,%15,%16,%17,%18,%19,%20,%21,%22,%23,%24,%25,%26,%27,"       \
    "%28,%29,%30,%31,%32,%33,%34,%35,%36,%37,%38,%39,%40,%41,%42,%43,%44,%45,%46,%47,%48,%49,%50,%51,%52,%53,%54,%55}"
#define WG_OPS(C)                                                                                                   \
    C(d[0]), C(d[1]), C(d[2]), C(d[3]), C(d[4]), C(d[5]), C(d[6]), C(d[7]), C(d[8]), C(d[9]), C(d[10]), C(d[11]),   \
    C(d[12]), C(d[13]), C(d[14]), C(d[15]), C(d[16]), C(d[17]), C(d[18]), C(d[19]), C(d[20]), C(d[21]), C(d[22]),   \
    C(d[23]), C(d[24]), C(d[25]), C(d[26]), C(d[27]), C(d[28]), C(d[29]), C(d[30]), C(d[31]), C(d[32]), C(d[33]),   \
    C(d[34]), C(d[35]), C(d[36]), C(d[37]), C(d[38]), C(d[39]), C(d[40]), C(d[41]), C(d[42]), C(d[43]), C(d[44]),   \
    C(d[45]), C(d[46]), C(d[47]), C(d[48]), C(d[49]), C(d[50]), C(d[51]), C(d[52]), C(d[53]), C(d[54]), C(d[55])

template <int TA, int TB, int SB, bool INIT, uint32_t AH, uint32_t BH>
__device__ __forceinline__ void wgmma112(float (&d)[56], uint32_t alo, uint32_t blo) {
    if (INIT) {
        asm volatile("{\n.reg .pred p;\n.reg .b64 da, db;\nsetp.ne.b32 p, 0, 0;\nmov.b64 da, {%56, %61};\nmov.b64 db, {%57, %62};\n"
                     "wgmma.mma_async.sync.aligned.m64n112k16.f32.bf16.bf16 " WG_REGS ", da, db, p, 1, %59, %60, %58;\n}\n"
                     : WG_OPS("=f") : "r"(alo), "r"(blo), "n"(TB), "n"(SB), "n"(TA), "n"(AH), "n"(BH));
    } else {
        asm volatile("{\n.reg .pred p;\n.reg .b64 da, db;\nsetp.ne.b32 p, 1, 0;\nmov.b64 da, {%56, %61};\nmov.b64 db, {%57, %62};\n"
                     "wgmma.mma_async.sync.aligned.m64n112k16.f32.bf16.bf16 " WG_REGS ", da, db, p, 1, %59, %60, %58;\n}\n"
                     : WG_OPS("+f") : "r"(alo), "r"(blo), "n"(TB), "n"(SB), "n"(TA), "n"(AH), "n"(BH));
    }
}
__device__ __forceinline__ void acc_fence(float (&d)[56]) {
#pragma unroll
    for (int i = 0; i < 56; i++) asm volatile("" : "+f"(d[i])::"memory");
}

__device__ __forceinline__ uint32_t pack2(float lo, float hi) {
    uint32_t r;
    asm volatile("cvt.rn.bf16x2.f32 %0, %1, %2;" : "=r"(r) : "f"(hi), "f"(lo));
    return r;
}
__device__ __forceinline__ uint32_t movm(uint32_t a) {
    uint32_t r;
    asm volatile("movmatrix.sync.aligned.m8n8.trans.b16 %0, %1;" : "=r"(r) : "r"(a));
    return r;
}
__device__ __forceinline__ void stsm4(uint32_t addr, uint32_t a, uint32_t b, uint32_t c, uint32_t d) {
    asm volatile("stmatrix.sync.aligned.m8n8.x4.shared.b16 [%0], {%1,%2,%3,%4};" ::"r"(addr), "r"(a), "r"(b), "r"(c), "r"(d) : "memory");
}
__device__ __forceinline__ void sts1(uint32_t addr, uint32_t a) { asm volatile("st.shared.b32 [%0], %1;" ::"r"(addr), "r"(a) : "memory"); }
__device__ __forceinline__ uint32_t lds1(uint32_t addr) {
    uint32_t a;
    asm volatile("ld.shared.b32 %0, [%1];" : "=r"(a) : "r"(addr) : "memory");
    return a;
}
__device__ __forceinline__ void stg1(uint8_t* p, uint32_t a) { asm volatile("st.global.b32 [%0], %1;" ::"l"(p), "r"(a) : "memory"); }
__device__ __forceinline__ void st_part(uint8_t* p, const uint32_t* v, uint32_t parity) {
    asm volatile("{\n.reg .b64 x, y;\nmov.b64 x, {%1, %2};\nmov.b64 y, {%3, %4};\nst.relaxed.gpu.global.v2.b64 [%0], {x, y};\n}\n"
                 ::"l"(p), "r"((v[0] & ~1u) | parity), "r"(v[1]), "r"((v[2] & ~1u) | parity), "r"(v[3]) : "memory");
}
__device__ __forceinline__ void mma16816(float (&d)[4], const uint32_t (&a)[4], uint32_t b0, uint32_t b1) {
    asm volatile("mma.sync.aligned.m16n8k16.row.col.f32.bf16.bf16.f32 {%0,%1,%2,%3}, {%4,%5,%6,%7}, {%8,%9}, {%0,%1,%2,%3};"
                 : "+f"(d[0]), "+f"(d[1]), "+f"(d[2]), "+f"(d[3]) : "r"(a[0]), "r"(a[1]), "r"(a[2]), "r"(a[3]), "r"(b0), "r"(b1));
}
__device__ __forceinline__ uint32_t add2(uint32_t a, uint32_t b) {
    uint32_t r;
    asm("add.rn.bf16x2 %0, %1, %2;" : "=r"(r) : "r"(a), "r"(b));
    return r;
}
__device__ __forceinline__ uint32_t max2(uint32_t a, uint32_t b) {
    uint32_t r;
    asm("max.bf16x2 %0, %1, %2;" : "=r"(r) : "r"(a), "r"(b));
    return r;
}
__device__ __forceinline__ void st_tagged(uint8_t* p, uint32_t a, uint32_t b, uint32_t tag) {
    asm volatile("{\n.reg .b64 x, y;\nmov.b64 x, {%1, %3};\nmov.b64 y, {%2, %3};\nst.relaxed.gpu.global.v2.b64 [%0], {x, y};\n}\n"
                 ::"l"(p), "r"(a), "r"(b), "r"(tag) : "memory");
}
__device__ __forceinline__ void ld_tagged(const uint8_t* p, uint32_t& a, uint32_t& ta, uint32_t& b, uint32_t& tb) {
    asm volatile("{\n.reg .b64 x, y;\nld.relaxed.gpu.global.v2.b64 {x, y}, [%4];\nmov.b64 {%0, %1}, x;\nmov.b64 {%2, %3}, y;\n}\n"
                 : "=r"(a), "=r"(ta), "=r"(b), "=r"(tb) : "l"(p) : "memory");
}
__device__ __forceinline__ float bf_lo(uint32_t v) { return __uint_as_float(v << 16); }
__device__ __forceinline__ float bf_hi(uint32_t v) { return __uint_as_float(v & 0xFFFF0000u); }
__device__ __forceinline__ float rcp(float x) { float r; asm("rcp.approx.ftz.f32 %0, %1;" : "=f"(r) : "f"(x)); return r; }
__device__ __forceinline__ float ex2(float x) { float r; asm volatile("ex2.approx.ftz.f32 %0, %1;" : "=f"(r) : "f"(x)); return r; }

__device__ __forceinline__ uint32_t full_bar(int stage) { return base + BAR_FULL + (stage & 7) * 8; }
__device__ __forceinline__ void wait_released(int j) { mbar_wait(base + BAR_EMPTY + (j & 7) * 8, (j >> 3) & 1); }

template <int V>
struct Int { static constexpr int value = V; };

__host__ __device__ constexpr int bslot_e(int i) { return (i < 2 || i >= 14) ? (i + 5) % 7 : (i + 1) % 5; }
__host__ __device__ constexpr int bslot_l(int i) { return i % 6; }

template <uint32_t OFF>
struct Feed {
    int stage;
    uint32_t dst;
    __device__ __forceinline__ void seek(int i, int slot) { stage = i; dst = base + OFF + slot * SLOT; }
    template <int N>
    __device__ __forceinline__ uint32_t acquire() { wait_released(stage - N); return full_bar(stage); }
    template <int N>
    __device__ __forceinline__ void next() {
        stage++;
        dst += SLOT;
        if (dst == base + OFF + N * SLOT) dst = base + OFF;
    }
};
__device__ __forceinline__ int skip_own(int n, int mt) { return n == mt ? 15 : n; }

struct Desc { uint32_t lo, hi; };
__host__ __device__ constexpr Desc desc_const(uint32_t lbo, uint32_t sbo, uint32_t mode) { return {(lbo >> 4) << 16, (sbo >> 4) | (mode << 30)}; }
constexpr Desc D_K128 = desc_const(16, 1024, 1);
constexpr Desc D_N128 = desc_const(8192, 1024, 1);
constexpr Desc D_BLOB = desc_const(128, 256, 0);
constexpr Desc D_OT = desc_const(2048, 128, 0);

enum Kind { XW, XWN, QK, BIG, OUT };

struct Ring {
    int stage;
    uint32_t a, b;
    uint32_t wg;
    uint32_t zero;
    __device__ __forceinline__ void seek(int i, int bslot) {
        stage = i;
        a = (base + (i % NA) * SLOT) >> 4;
        b = (base + BRING + bslot * SLOT) >> 4;
    }
    __device__ __forceinline__ void wait() { mbar_wait(full_bar(stage), (stage >> 3) & 1); }
    __device__ __forceinline__ void take_turn() { nb_sync(1 + wg, 256); }
    __device__ __forceinline__ void pin() {
        uint32_t n = 0;
#pragma unroll 1
        do {
            asm volatile("pmevent 7;" ::: "memory");
        } while (n++ < zero);
    }
    template <Kind K, int NBS, bool INIT, int SB = 1>
    __device__ __forceinline__ void run(float (&d)[56], float (&e)[56], bool first = true, bool last = true, bool more = true) {
        if (first) take_turn();
        asm volatile("wgmma.fence.sync.aligned;" ::: "memory");
        if (K == QK) {
            const uint32_t da = D_K128.lo + (base >> 4) + (stage >> 1) * (SLOT >> 4) + (stage & 1) * 4 + wg * 512, db = D_N128.lo + b;
            wgmma112<0, 1, 1, INIT, D_K128.hi, D_N128.hi>(d, da, db);
            wgmma112<0, 1, 1, INIT, D_K128.hi, D_N128.hi>(e, da, db + 256);
            wgmma112<0, 1, 1, false, D_K128.hi, D_N128.hi>(d, da + 2, db + 128);
            wgmma112<0, 1, 1, false, D_K128.hi, D_N128.hi>(e, da + 2, db + 384);
        } else {
            constexpr int TA = K == OUT, TB = K != XW;
            constexpr uint32_t sa = K == OUT ? 256 : 2, sb = K == XW ? 2 : K == BIG ? 224 : 128;
            constexpr Desc A = K == OUT ? D_OT : D_K128, B = K == XW ? D_K128 : K == BIG ? D_BLOB : D_N128;
            const uint32_t da = A.lo + a + wg * (K == OUT ? 64 : 512), db = B.lo + b;
            wgmma112<TA, TB, SB, INIT, A.hi, B.hi>(d, da, db);
            wgmma112<TA, TB, SB, false, A.hi, B.hi>(d, da + sa, db + sb);
            wgmma112<TA, TB, SB, false, A.hi, B.hi>(d, da + 2 * sa, db + 2 * sb);
            wgmma112<TA, TB, SB, false, A.hi, B.hi>(d, da + 3 * sa, db + 3 * sb);
        }
        asm volatile("wgmma.commit_group.sync.aligned;" ::: "memory");
        if (last) nb_arrive(2 - wg, 256);
        asm volatile("wgmma.wait_group.sync.aligned 1;" ::: "memory");
        if (stage > 0 && elect()) mbar_arrive(base + BAR_EMPTY + ((stage - 1) & 7) * 8);
        stage++;
        a += SLOT >> 4;
        if (a == (base + NA * SLOT) >> 4) a = base >> 4;
        b += SLOT >> 4;
        if (b == (base + BRING + NBS * SLOT) >> 4) b = (base + BRING) >> 4;
        if (more) wait();
    }
    template <Kind K, int NBS, bool INIT, int SB = 1>
    __device__ __forceinline__ void run(float (&d)[56], bool first = true, bool last = true, bool more = true) {
        run<K, NBS, INIT, SB>(d, d, first, last, more);
    }
};

__device__ __forceinline__ void pack_all(const float (&d)[56], uint32_t (&p)[28]) {
#pragma unroll
    for (int i = 0; i < 28; i++) p[i] = pack2(d[2 * i], d[2 * i + 1]);
}
template <int I0, int I1>
__device__ __forceinline__ void store_frags(uint8_t* dst, const uint32_t (&p)[28]) {
#pragma unroll
    for (int i = I0; i < I1; i++) stg1(dst + i * 128, p[i]);
}
template <int I0, int I1>
__device__ __forceinline__ void stage_frags(uint32_t lane_addr, const uint32_t (&p)[28]) {
#pragma unroll
    for (int i = I0; i < I1; i += 4) stsm4(lane_addr + i * 128, p[i], p[i + 1], p[i + 2], p[i + 3]);
}
__device__ __forceinline__ void store_out(const uint32_t (&p)[28], int lane, uint32_t slab, const CUtensorMap* m, int c0, int c1) {
    const bool swap = lane & 16;
    const uint32_t addr = slab + (lane & 15) * 224 + (((lane >> 4) ^ (lane >> 2)) & 1) * 16;
#pragma unroll
    for (int i = 0; i < 28; i += 4)
        stsm4(addr + i * 8, swap ? p[i + 2] : p[i], swap ? p[i + 3] : p[i + 1], swap ? p[i] : p[i + 2], swap ? p[i + 1] : p[i + 3]);
    fence_async_smem();
    __syncwarp();
    if (elect()) {
        tma_st2(m, c0, c1, slab);
        bulk_commit();
        bulk_wait_read();
    }
}
__host__ __device__ constexpr int tile_of(int t) { return 7 * (t >> 2) + 3 * ((t >> 1) & 1) + 2 * (t & 1); }

struct Role {
    bool H;
    int L, mt, ns, id;
};
template <bool BY_SM>
__device__ __forceinline__ Role decode_role() {
    uint32_t sm;
    if (BY_SM) asm volatile("mov.u32 %0, %%smid;" : "=r"(sm));
    else asm volatile("mov.u32 %0, %%ctaid.x;" : "=r"(sm));
    const int tpc = sm >> 1, q2 = ((tpc - 32) * 37) >> 8;
    const int gpc = tpc < 32 ? tpc & 7 : tpc < 60 ? tpc - 31 - 7 * q2 : 0;
    const int pos = tpc < 32 ? tpc >> 3 : tpc < 60 ? q2 + 4 : tpc - 56;
    Role r;
    r.H = sm >= 128;
    r.L = gpc & 1;
    r.mt = (gpc >> 1) * 4 + (pos >> 1);
    r.ns = (pos & 1) * 2 + (sm & 1);
    r.id = r.H ? sm : gpc * 16 + pos * 2 + (sm & 1);
    return r;
}

template <int I0, int I1>
__device__ __forceinline__ void first_fill(const Maps& maps, const Role& r) {
    if (r.L) {
#pragma unroll
        for (int i = I0; i < I1; i++) {
            const uint32_t bar = full_bar(i), dst = base + BRING + i * SLOT;
            if (i < 6) mbar_expect(bar, SLOT);
            if (i & 1) {
                mbar_arrive(bar);
            } else {
                mbar_expect(bar, SLOT);
                tma_ld2(base + (i >> 1) * SLOT, &maps.m[M_XA], (r.mt >> 3) * 448 + i * 32, (r.mt & 7) * 128, bar);
            }
            if (i < 6) {
                tma_ld4(dst, &maps.m[M_WQK], 0, i * 32, 0, r.ns, bar);
                tma_ld4(dst + 8192, &maps.m[M_WQK], 64, i * 32, 0, r.ns, bar);
            }
        }
    } else if (!r.H) {
#pragma unroll
        for (int i = I0; i < I1; i++) {
            const uint32_t bar = full_bar(i);
            mbar_expect(bar, SLOT);
            tma_ld3(base + i * SLOT, &maps.m[M_XB], i * 64, r.mt * 64, 0, bar);
            mbar_expect(bar, BLOB);
            tma_ld2(base + BRING + bslot_e(i) * SLOT, &maps.m[M_WR], i * 64, r.ns * 112, bar);
        }
    } else {
#pragma unroll 1
        for (int i = I0; i < I1; i++) {
            const uint32_t bar = full_bar(i), dst = base + BRING + i * SLOT;
            mbar_expect(bar, SLOT);
            mbar_expect(bar, SLOT);
            tma_ld4(base + i * SLOT, &maps.m[M_XH], i * 64, 120, 0, 0, bar);
            tma_ld3(dst, &maps.m[M_WV], 0, i * 64, 4 + r.ns, bar);
            tma_ld3(dst + 8192, &maps.m[M_WV], 64, i * 64, 4 + r.ns, bar);
        }
    }
}

template <bool BY_SM>
__global__ void __launch_bounds__(384, 1) fused_kernel(Scratch* sc, const __grid_constant__ Maps maps) {
    const int warp = __shfl_sync(0xffffffffu, threadIdx.x >> 5, 0);
    const Role role = decode_role<BY_SM>();
    if (warp == OPENER) {
        if (elect()) {
            asm volatile("prefetch.tensormap [%0];" ::"l"(&maps.m[M_XB]) : "memory");
            asm volatile("prefetch.tensormap [%0];" ::"l"(&maps.m[M_XA]) : "memory");
            asm volatile("prefetch.tensormap [%0];" ::"l"(&maps.m[M_WR]) : "memory");
            asm volatile("prefetch.tensormap [%0];" ::"l"(&maps.m[M_WQK]) : "memory");
#pragma unroll
            for (int i = 0; i < 8; i++) mbar_init(base + BAR_FULL + i * 8, 2);
            asm volatile("fence.mbarrier_init.release.cluster;" ::: "memory");
            first_fill<0, LEAD>(maps, role);
        }
    }
    int lane = threadIdx.x & 31;
    asm volatile("" : "+r"(lane));
    const bool roleH = role.H;
    const int roleL = role.L, mt = role.mt, ns = role.ns, bid = role.id;
    const int par = mt >> 3, blk = mt & 7, col = ns * 112;
    if (warp == 9) {
        if (elect()) {
#pragma unroll
            for (int i = 0; i < 8; i++) mbar_init(base + BAR_EMPTY + i * 8, 8);
            asm volatile("fence.mbarrier_init.release.cluster;" ::: "memory");
        }
    } else if (warp == 10) {
        if (elect()) {
#pragma unroll
            for (int i = 0; i < 5; i++) mbar_init(base + BAR_RDY + i * 8, i < 2 ? 4 : 8);
#pragma unroll
            for (int i = 0; i < 2; i++) mbar_init(base + BAR_HALO + i * 8, 8);
            asm volatile("fence.mbarrier_init.release.cluster;" ::: "memory");
        }
    } else if (warp == 11) {
        if (elect()) {
#pragma unroll
            for (int i = 0; i < 3; i++) mbar_init(base + BAR_DEP + i * 8, 1);
            asm volatile("fence.mbarrier_init.release.cluster;" ::: "memory");
        }
    }
    __syncthreads();

    if (__builtin_expect(warp >= 8, 1)) {
        asm volatile("setmaxnreg.dec.sync.aligned.u32 56;");
#define PROF_FEED_A
#define PROF_FEED_B
        if (__builtin_expect(warp == 8, 1)) {
            if (elect()) {
                PROF(129);
                first_fill<LEAD, 7>(maps, role);
                PROF(134);
                Feed<0> f;
                const int row = mt * 128;
                auto c_run = [&](const CUtensorMap* m, int off, int n0, int n1) {
#pragma unroll 1
                    for (int n = n0; n < n1; n++) {
                        const uint32_t bar = f.acquire<NA>();
                        mbar_expect(bar, SLOT);
                        tma_ld2(f.dst, m, (off + skip_own(n, mt)) * 64, row, bar);
                        PROF_FEED_A;
                        f.next<NA>();
                    }
                };
                if (roleH) {
                } else if (!roleL) {
                    f.seek(14, 0);
                    mbar_wait(base + BAR_RDY, 0);
#pragma unroll 1
                    for (int i = 0; i < 4; i++) {
                        const uint32_t bar = f.acquire<NA>();
                        mbar_expect(bar, SLOT);
                        tma_ld2(f.dst, &maps.m[M_CR + (i >> 1)], ((i & 1) * 16 + mt) * 64, row, bar);
                        mbar_arrive(bar);
                        PROF_FEED_A;
                        f.next<NA>();
                    }
                    c_run(&maps.m[M_CR], 0, 0, 15);
                    c_run(&maps.m[M_CI], 0, 0, NBE);
                    wait_dep(2);
#pragma unroll 1
                    for (int i = 0; i < 7; i++) {
                        const uint32_t bar = f.acquire<NA>();
                        mbar_expect(bar, SLOT);
                        bulk_ld(f.dst, sc->o + (size_t)(mt * 7 + i) * SLOT, SLOT, bar);
                        PROF_FEED_A;
                        f.next<NA>();
                    }
                } else {
#pragma unroll 1
                    for (int i = 4; i < 7; i++) {
                        wait_released(2 * i - 8);
                        mbar_expect(full_bar(2 * i), SLOT);
                        tma_ld2(base + i * SLOT, &maps.m[M_XA], par * 448 + i * 64, blk * 128, full_bar(2 * i));
                    }
                    wait_released(7);
                    f.seek(21, 0);
                    c_run(&maps.m[M_CR], 16, 0, 15);
                    c_run(&maps.m[M_CI], 16, 0, 15);
                    c_run(&maps.m[M_CI], 0, NBE, 15);
                }
            }
        } else if (warp == 11) {
            if (elect()) {
                Feed<BRING> f;
                auto blob_run = [&](auto nbs, int quarter, int n0, int n1) {
                    constexpr int N = decltype(nbs)::value;
                    const uint8_t* src = sc->ab + (size_t)(quarter * 64 + ns) * BLOB;
#pragma unroll 1
                    for (int n = n0; n < n1; n++) {
                        const uint32_t bar = f.template acquire<N>();
                        mbar_expect(bar, BLOB);
                        bulk_ld(f.dst, src + skip_own(n, mt) * (4 * BLOB), BLOB, bar);
                        PROF_FEED_B;
                        f.template next<N>();
                    }
                };
                auto w_run = [&](auto nbs, const CUtensorMap* m, int slice, bool no_a) {
                    constexpr int N = decltype(nbs)::value;
#pragma unroll 1
                    for (int i = 0; i < 7; i++) {
                        const uint32_t bar = f.template acquire<N>();
                        mbar_expect(bar, SLOT);
                        tma_ld3(f.dst, m, 0, i * 64, slice, bar);
                        tma_ld3(f.dst + 8192, m, 64, i * 64, slice, bar);
                        if (no_a) mbar_arrive(bar);
                        PROF_FEED_B;
                        f.template next<N>();
                    }
                };
                if (roleH) {
                    f.seek(7, 0);
                    w_run(Int<7>(), &maps.m[M_WV], 8 + ns, true);
                } else if (!roleL) {
                    f.seek(7, bslot_e(7));
#pragma unroll 1
                    for (int i = 0; i < 7; i++) {
                        const uint32_t bar = f.acquire<5>();
                        mbar_expect(bar, BLOB);
                        tma_ld2(f.dst, &maps.m[M_WI], i * 64, col, bar);
                        mbar_arrive(bar);
                        PROF_FEED_B;
                        f.next<5>();
                    }
                    f.seek(18, bslot_e(18));
                    wait_dep(0);
                    blob_run(Int<7>(), 0, 0, 15);
                    wait_dep(1);
                    blob_run(Int<7>(), 2, 0, NBE);
                    w_run(Int<7>(), &maps.m[M_WO], ns, false);
                } else {
                    f.seek(6, 0);
#pragma unroll 1
                    for (int i = 6; i < 14; i++) {
                        const uint32_t bar = f.acquire<6>();
                        mbar_expect(bar, SLOT);
                        tma_ld4(f.dst, &maps.m[M_WQK], 0, i * 32, 0, ns, bar);
                        tma_ld4(f.dst + 8192, &maps.m[M_WQK], 64, i * 32, 0, ns, bar);
                        if (i & 1) mbar_arrive(bar);
                        PROF_FEED_B;
                        f.next<6>();
                    }
                    w_run(Int<6>(), &maps.m[M_WV], 8 + ns, true);
                    wait_dep(0);
                    blob_run(Int<6>(), 1, 0, 15);
                    wait_dep(1);
                    blob_run(Int<6>(), 3, 0, 15);
                    blob_run(Int<6>(), 2, NBE, 15);
                }
            }
        } else if (roleH) {
        } else if (warp == 10) {
            if (elect()) {
                unsigned* epoch_ptr = &sc->epoch[(bid * 4 + 2) * 8];
                const unsigned ep = *epoch_ptr + 1;
                sts1(base + TAG, ep);
                await(sc, CNT_A + roleL * 4 + ns, ep * 16);
                mbar_arrive(base + BAR_DEP);
                PROF(150);
                await(sc, CNT_B + ns, ep * 16);
                mbar_arrive(base + BAR_DEP + 8);
                PROF(151);
                if (!roleL) {
                    await(sc, CNT_O + mt, ep * 4);
                    mbar_arrive(base + BAR_DEP + 16);
                }
                PROF(152);
                *epoch_ptr = ep;
            }
        } else if (!roleL) {
            if (elect()) {
                mbar_wait(base + BAR_RDY, 0);
                PROF(130);
                signal(sc, CNT_A + ns);
                PROF(131);
                mbar_wait(base + BAR_RDY + 8, 0);
                signal(sc, CNT_A + 4 + ns);
                PROF(135);
                mbar_wait(base + BAR_RDY + 32, 0);
                PROF(132);
                signal(sc, CNT_B + ns);
                PROF(133);
            }
        } else {
            const unsigned t_start = clk32();
            unsigned* epoch_ptr = &sc->epoch[(bid * 4 + 1) * 8];
            const unsigned tag = *epoch_ptr + 1;
#pragma unroll 1
            for (int kv = 0; kv < 2; kv++) {
                uint32_t v[14], t[14];
#pragma unroll
                for (int i = 0; i < 14; i++) v[i] = 0;

                if (blk > 0) {
                    const uint8_t* src = sc->halo + (size_t)(((mt - 1) * 4 + ns) * 2 + kv) * (2 * HSLOT) + lane * 16;
                    pause_until(t_start, HALO_DELAY + kv * 3200);
#pragma unroll 1
                    for (int n = 0; n < SPIN_LIMIT; n++) {
                        bool ok = true;
#pragma unroll
                        for (int i = 0; i < 7; i++) ld_tagged(src + i * 512, v[2 * i], t[2 * i], v[2 * i + 1], t[2 * i + 1]);
#pragma unroll
                        for (int i = 0; i < 14; i++) ok = ok && t[i] == tag;
                        if (__all_sync(0xffffffffu, ok)) break;
                    }
                }
#pragma unroll
                for (int i = 0; i < 14; i++) sts1(base + HALO + kv * (8 * HSLOT) + i * 128 + lane * 4, v[i]);
                warp_arrive(base + BAR_HALO + kv * 8);
                if (lane == 0) PROF(142 + kv);
            }
            if (elect()) {
                mbar_wait(base + BAR_RDY + 16, 0);
                PROF(130);
                signal(sc, CNT_O + mt);
                PROF(131);
                *epoch_ptr = tag;
            }
        }
    } else {
        asm volatile("setmaxnreg.inc.sync.aligned.u32 224;");
        Ring r;
        r.wg = warp >> 2;
        r.zero = blockIdx.y;
        const int wg = warp >> 2;
        if (wg) nb_arrive(1, 256);
        r.stage = 0;
        r.wait();
        uint8_t* part = sc->part + (size_t)(ns * 16 + mt) * (2 * BLOB) + warp * 512 + lane * 16;
        uint32_t p[28];

        if (roleH) {
            unsigned* epoch_ptr = &sc->epoch[bid * 4 * 8];
            const unsigned tag = *epoch_ptr + 1;
            uint8_t* hout = sc->halo + (size_t)((warp * 8 + ns) * 2) * (2 * HSLOT) + lane * 16;
            float x0[56], x1[56];
            r.seek(0, 0);
            r.run<XWN, 7, true>(x0);
#pragma unroll 1
            for (int i = 1; i < 7; i++) r.run<XWN, 7, false>(x0);
            r.run<XWN, 7, true>(x1);
            acc_fence(x0);
            pack_all(x0, p);
#pragma unroll
            for (int i = 0; i < 14; i++) st_tagged(hout + (i & 1) * (16 * HSLOT) + (i >> 1) * 512, p[(i >> 1) * 4 + (i & 1)], p[(i >> 1) * 4 + (i & 1) + 2], tag);
#pragma unroll 1
            for (int i = 1; i < 7; i++) r.run<XWN, 7, false>(x1, true, true, i < 6);
            asm volatile("wgmma.wait_group.sync.aligned 0;" ::: "memory");
            acc_fence(x1);
            pack_all(x1, p);
#pragma unroll
            for (int i = 0; i < 28; i++) p[i] = movm(p[i]);
#pragma unroll
            for (int i = 0; i < 14; i++)
                st_tagged(hout + 2 * HSLOT + (i & 1) * (16 * HSLOT) + (i >> 1) * 512, p[(i >> 1) * 4 + (i & 1)], p[(i >> 1) * 4 + (i & 1) + 2], tag);
            if (threadIdx.x == 0) *epoch_ptr = tag;
        } else if (!roleL) {
            uint8_t* blob = sc->ab + (size_t)((wg * 16 + mt) * 4 + ns) * BLOB + (warp & 3) * WSLOT + lane * 4;
            const uint32_t own = base + BRING + wg * SLOT + (warp & 3) * WSLOT + lane * 16;
            float x0[56], x1[56];
            r.seek(0, bslot_e(0));
            r.run<XW, 7, true>(x0);
            r.run<XW, 7, false>(x0);
            r.seek(2, bslot_e(2));
#pragma unroll 1
            for (int i = 2; i < 7; i++) r.run<XW, 5, false>(x0);

            r.seek(7, bslot_e(7));
            r.run<XW, 5, true, -1>(x1);
            acc_fence(x0);
            pack_all(x0, p);
#pragma unroll
            for (int i = 0; i < 2; i++) {
                if (wg == i) store_frags<0, 14>(blob, p);
                else stage_frags<0, 4>(own + 5 * SLOT, p);
                r.run<XW, 5, false, -1>(x1);
                if (wg == i) {
                    store_frags<14, 28>(blob, p);
                    warp_arrive(base + BAR_RDY + i * 8);
                } else {
                    stage_frags<4, 8>(own + 5 * SLOT, p);
                }
                r.run<XW, 5, false, -1>(x1);
            }
            stage_frags<8, 20>(own + 5 * SLOT, p);
            r.run<XW, 5, false, -1>(x1);
            stage_frags<20, 28>(own + 5 * SLOT, p);
            warp_arrive(base + BAR_RDY + 16);
            r.run<XW, 5, false, -1>(x1);

            mbar_wait(base + BAR_RDY + 16, 0);
            fence_async_smem();
            r.seek(14, bslot_e(14));
            r.run<BIG, 7, true>(x0);
            acc_fence(x1);
            pack_all(x1, p);
            wait_released(10);
            stage_frags<0, 28>(own, p);
            warp_arrive(base + BAR_RDY + 24);
            r.run<BIG, 7, false>(x0);
            mbar_wait(base + BAR_RDY + 24, 0);
            fence_async_smem();
            blob += (size_t)128 * BLOB;
#pragma unroll
            for (int i = 0; i < 28; i++) {
                if (i % B_SLICE == 0) r.run<BIG, 7, false>(x0);
                stg1(blob + i * 128, p[i]);
            }
            warp_arrive(base + BAR_RDY + 32);
#pragma unroll 1
            for (int i = 17 + 27 / B_SLICE; i < POUT; i++) r.run<BIG, 7, false>(x0);

            const uint32_t tag = lds1(base + TAG);
            r.seek(POUT, bslot_e(POUT));
            r.run<OUT, 7, true>(x1);
            acc_fence(x0);
            pack_all(x0, p);
#pragma unroll
            for (int k = 0; k < 3; k++) {
                if (k < 2 && wg == k) {
#pragma unroll
                    for (int i = 0; i < 4; i++) st_part(part + i * 4096, p + 4 * i, tag & 1);
                }
                if (k > 0 && wg == k - 1) {
#pragma unroll
                    for (int i = 4; i < 7; i++) st_part(part + i * 4096, p + 4 * i, tag & 1);
                }
                if (k < 2) r.run<OUT, 7, false>(x1);
            }
#pragma unroll 1
            for (int i = 3; i < 7; i++) r.run<OUT, 7, false>(x1, i <= 7 - TURN, i < 7 - TURN || i == 6, i < 6);

            wait_released(ELAST - 6);
            asm volatile("wgmma.wait_group.sync.aligned 0;" ::: "memory");
            acc_fence(x1);
            pack_all(x1, p);
            const uint32_t slab = base + (wg ? BRING + bslot_e(ELAST - 6) * SLOT : ((ELAST - 6) % NA) * SLOT) + (warp & 3) * WSLOT;
            store_out(p, lane, slab, &maps.m[M_OUTA], par * 896 + col, blk * 128 + warp * 16);
        } else {
            const int g = lane >> 2, tig = lane & 3;
            const uint32_t hin = base + HALO + warp * HSLOT + lane * 4;
            auto publish = [&](const uint32_t (&h)[14], int kv) {
                if (warp < 7) {
#pragma unroll
                    for (int c = 0; c < 14; c++) sts1(hin + HSLOT + c * 128, h[c]);
                    warp_arrive(base + BAR_HALO + kv * 8);
                }
            };
            float y0[56], y1[56], y2[56];
            r.seek(0, 0);
            r.run<QK, 6, true>(y0, y1);
#pragma unroll 1
            for (int i = 1; i < 14; i++) r.run<QK, 6, false>(y0, y1);

            uint32_t m1[8][4], m0[8][4], lo[14], hi[14];
            r.seek(14, bslot_l(14));
            r.run<XWN, 6, true>(y2);
            acc_fence(y0);
            acc_fence(y1);
#pragma unroll
            for (int c = 0; c < 14; c++) hi[c] = pack2(y1[4 * c + 2], y1[4 * c + 3]);
            publish(hi, 0);
            r.run<XWN, 6, false>(y2);
#pragma unroll
            for (int c = 0; c < 14; c++) lo[c] = pack2(y1[4 * c], y1[4 * c + 1]);
#pragma unroll
            for (int t = 0; t < 8; t++) {
                const int c = tile_of(t);
                const bool shared = (t & 3) == 2;
                m1[t][0] = shared ? dup(lo[c], r.zero) : lo[c];
                m1[t][1] = shared ? dup(hi[c], r.zero) : hi[c];
                m1[t][2] = lo[c + 1];
                m1[t][3] = hi[c + 1];
                m0[t][0] = dup(m1[t][0], r.zero);
                m0[t][2] = dup(lo[c + 1], 2 * r.zero);
            }
            PIN;
            r.run<XWN, 6, false>(y2);
            uint32_t q[2][8][2];
#pragma unroll
            for (int b = 0; b < 2; b++) {
                uint32_t v[14];
#pragma unroll
                for (int c = 0; c < 14; c++) v[c] = pack2(y0[4 * c + 2 * b], y0[4 * c + 2 * b + 1]);
#pragma unroll
                for (int t = 0; t < 8; t++) {
                    const int c = tile_of(t);
                    q[b][t][0] = (t & 3) == 2 ? (tig >= 2 ? v[c] : 0u) : v[c];
                    q[b][t][1] = (t & 3) == 1 ? (tig < 2 ? v[c + 1] : 0u) : v[c + 1];
                }
            }
            PIN;
            r.run<XWN, 6, false>(y2);
            mbar_wait(base + BAR_HALO, 0);
#pragma unroll
            for (int t = 0; t < 8; t++) {
                m0[t][1] = lds1(hin + tile_of(t) * 128 + ((t & 3) == 2 ? r.zero : 0u));
                m0[t][3] = lds1(hin + tile_of(t) * 128 + 128);
            }
            r.pin();
            r.take_turn();
            float s[8][4];
#pragma unroll
            for (int step = 0; step < 2; step++) {
#pragma unroll
                for (int i = 0; i < 8; i++) {
                    const int b = 1 - (i >> 2), h = i & 3, t = 2 * h + step;
                    float (&d)[4] = s[2 * h + b];
                    if (step == 0) d[0] = d[1] = d[2] = d[3] = 0.f;
                    mma16816(d, b ? m1[t] : m0[t], q[b][t][0], q[b][t][1]);
                }
            }
            r.pin();
            r.run<XWN, 6, false>(y2, false);

            uint32_t pr[8], mx[4], mx1[4];
            {
                const bool cur0 = g <= 2 * tig, cur1 = g <= 2 * tig + 1;
#pragma unroll
                for (int i = 0; i < 8; i++) {
                    const int c = (i & 1) ? 2 : 0;
                    pr[i] = movm(pack2(cur0 ? s[i][c] : s[i][2 - c], cur1 ? s[i][c + 1] : s[i][3 - c]));
                }
            }
            PIN;
            r.run<XWN, 6, false>(y2);
            const uint32_t curmask = (2 * tig <= g ? 0x0000FFFFu : 0u) | (2 * tig + 1 <= g ? 0xFFFF0000u : 0u);
            {
                const uint32_t keep = (blk == 0 && warp == 0) ? curmask : 0xFFFFFFFFu;
#pragma unroll
                for (int i = 0; i < 4; i++) {
                    pr[2 * i] = (pr[2 * i] & keep) | (0xCF9ECF9Eu & ~keep);
                    mx[i] = max2(__byte_perm(pr[2 * i], pr[2 * i + 1], 0x5410), __byte_perm(pr[2 * i], pr[2 * i + 1], 0x7632));
                }
#pragma unroll
                for (int i = 0; i < 4; i++) mx[i] = max2(mx[i], __shfl_xor_sync(0xffffffffu, mx[i], 1));
#pragma unroll
                for (int i = 0; i < 4; i++) mx1[i] = __shfl_xor_sync(0xffffffffu, mx[i], 2);
            }
            PIN;
            r.run<XWN, 6, false>(y2);
            constexpr float SCL = 0.18898223650461362f * 1.4426950408889634f;
            float e0[8], e1[8], sm[8], sm1[8];
#pragma unroll
            for (int i = 0; i < 8; i++) {
                const uint32_t m2 = max2(mx[i >> 1], mx1[i >> 1]);
                sm[i] = ((i & 1) ? bf_hi(m2) : bf_lo(m2)) * -SCL;
                e0[i] = ex2(fmaf(bf_lo(pr[i]), SCL, sm[i]));
            }

            r.seek(21, bslot_l(21));
            PIN;
            r.run<BIG, 6, true>(y0);
            acc_fence(y2);
#pragma unroll
            for (int c = 0; c < 14; c++) hi[c] = movm(pack2(y2[4 * c + 2], y2[4 * c + 3]));
            PIN;
            r.run<BIG, 6, false>(y0);
            wait_released(18);
            publish(hi, 1);
            r.run<BIG, 6, false>(y0);
#pragma unroll
            for (int i = 0; i < 8; i++) {
                e1[i] = ex2(fmaf(bf_hi(pr[i]), SCL, sm[i]));
                sm[i] = e0[i] + e1[i];
                sm1[i] = __shfl_xor_sync(0xffffffffu, sm[i], 1);
            }
            PIN;
            r.run<BIG, 6, false>(y0);
#pragma unroll
            for (int c = 0; c < 14; c++) lo[c] = movm(pack2(y2[4 * c], y2[4 * c + 1]));
            PIN;
            r.run<BIG, 6, false>(y0);
#pragma unroll
            for (int i = 0; i < 8; i++) {
                sm[i] += sm1[i];
                sm1[i] = __shfl_xor_sync(0xffffffffu, sm[i], 2);
            }
#pragma unroll
            for (int t = 0; t < 8; t++) {
                const int c = tile_of(t);
                const bool shared = (t & 3) == 2;
                m1[t][0] = shared ? dup(lo[c], r.zero) : lo[c];
                m1[t][1] = lo[c + 1];
                m1[t][2] = shared ? dup(hi[c], r.zero) : hi[c];
                m1[t][3] = hi[c + 1];
                m0[t][0] = dup(m1[t][0], r.zero);
                m0[t][1] = dup(lo[c + 1], 2 * r.zero);
            }
            PIN;
            r.run<BIG, 6, false>(y0);
            uint32_t pb[8][2];
#pragma unroll
            for (int i = 0; i < 8; i++) {
                const float inv = rcp(sm[i] + sm1[i]);
                const uint32_t w = pack2(e0[i] * inv, e1[i] * inv);
                pb[i][i & 1] = band(w, curmask);
                pb[i][1 - (i & 1)] = band(w, ~curmask);
            }
            PIN;
            r.run<BIG, 6, false>(y0);
            mbar_wait(base + BAR_HALO + 8, 0);
            const uint32_t vin = warp ? hin : hin + 8 * HSLOT;
#pragma unroll
            for (int t = 0; t < 8; t++) {
                m0[t][2] = lds1(vin + tile_of(t) * 128 + ((t & 3) == 2 ? r.zero : 0u));
                m0[t][3] = lds1(vin + tile_of(t) * 128 + 128);
            }
            r.pin();
            r.take_turn();
            float o[2][8][4];
#pragma unroll
            for (int i = 0; i < 16; i++) {
                const int b = 1 - (i >> 3), t = i & 7;
                float (&d)[4] = o[b][t];
                d[0] = d[1] = d[2] = d[3] = 0.f;
                mma16816(d, b ? m1[t] : m0[t], pb[(t & 6) + b][0], pb[(t & 6) + b][1]);
            }
            r.pin();
            r.run<BIG, 6, false>(y0, false);
            uint8_t* odst = sc->o + (size_t)mt * 7 * SLOT + ns * (14 * 2048) + warp * 256 + lane * 4;
#pragma unroll
            for (int hp = 0; hp < 2; hp++) {
#pragma unroll
                for (int b = 0; b < 2; b++) {
                    const float (&u)[8][4] = o[b];
                    const int t = 4 * hp;
                    uint32_t* w = p + 14 * hp + b;
                    w[0] = pack2(u[t][0], u[t][1]);
                    w[2] = pack2(u[t][2], u[t][3]);
                    w[4] = pack2(u[t + 1][0], u[t + 1][1]);
                    w[6] = pack2(g < 4 ? u[t + 1][2] : u[t + 2][0], g < 4 ? u[t + 1][3] : u[t + 2][1]);
                    w[8] = pack2(u[t + 2][2], u[t + 2][3]);
                    w[10] = pack2(u[t + 3][0], u[t + 3][1]);
                    w[12] = pack2(u[t + 3][2], u[t + 3][3]);
                }
            }
#pragma unroll
            for (int i = 0; i < 28; i++) {
                if (i && i % O_SLICE == 0) r.run<BIG, 6, false>(y0);
                stg1(odst + (i >> 1) * 2048 + (i & 1) * 128, p[i]);
            }
            warp_arrive(base + BAR_RDY + 16);

#pragma unroll 1
            for (int i = 29 + 27 / O_SLICE; i <= LLAST + 1 - TURN; i++) r.run<BIG, 6, false>(y0, true, i <= LLAST - TURN);
            const uint32_t tag = lds1(base + TAG);
#pragma unroll
            for (int i = 0; i < 7; i++) ld_tagged(part + i * 4096, p[4 * i], p[4 * i + 1], p[4 * i + 2], p[4 * i + 3]);
#pragma unroll 1
            for (int i = 1; i < TURN; i++) r.run<BIG, 6, false>(y0, false, i == TURN - 1, i < TURN - 1);
#pragma unroll 1
            for (int n = 0; n < SPIN_LIMIT; n++) {
                uint32_t stale = 0;
#pragma unroll
                for (int i = 0; i < 28; i += 2) stale |= p[i] ^ tag;
                if (__all_sync(0xffffffffu, !(stale & 1))) break;
#pragma unroll
                for (int i = 0; i < 7; i++) ld_tagged(part + i * 4096, p[4 * i], p[4 * i + 1], p[4 * i + 2], p[4 * i + 3]);
            }
            wait_released(LLAST - 6);
            asm volatile("wgmma.wait_group.sync.aligned 0;" ::: "memory");
            acc_fence(y0);
#pragma unroll
            for (int i = 0; i < 28; i++) p[i] = add2(pack2(y0[2 * i], y0[2 * i + 1]), p[i]);
            const uint32_t slab = base + (wg ? HALO : ((LLAST - 6) % NA) * SLOT) + (warp & 3) * WSLOT;
            store_out(p, lane, slab, &maps.m[M_OUTB], 448 + col, mt * 128 + warp * 16);
        }
    }
}

typedef CUresult (*EncodeFn)(CUtensorMap*, CUtensorMapDataType, cuuint32_t, void*, const cuuint64_t*, const cuuint64_t*,
                             const cuuint32_t*, const cuuint32_t*, CUtensorMapInterleave, CUtensorMapSwizzle,
                             CUtensorMapL2promotion, CUtensorMapFloatOOBfill);

struct Dim { uint64_t size, stride; uint32_t box; };
void encode(EncodeFn fn, CUtensorMap* m, const void* ptr, CUtensorMapSwizzle sw, Dim d0, Dim d1, Dim d2 = {0, 0, 0}, Dim d3 = {0, 0, 0}) {
    const cuuint64_t dims[4] = {d0.size, d1.size, d2.size, d3.size};
    const cuuint64_t strides[3] = {d1.stride, d2.stride, d3.stride};
    const cuuint32_t box[4] = {d0.box, d1.box, d2.box, d3.box};
    const cuuint32_t es[4] = {1, 1, 1, 1};
    fn(m, CU_TENSOR_MAP_DATA_TYPE_BFLOAT16, d3.size ? 4 : d2.size ? 3 : 2, const_cast<void*>(ptr), dims, strides, box, es,
       CU_TENSOR_MAP_INTERLEAVE_NONE, sw, CU_TENSOR_MAP_L2_PROMOTION_L2_128B, CU_TENSOR_MAP_FLOAT_OOB_FILL_NONE);
}

}

extern "C" void kernel_launch(void* const* d_in, const int* in_sizes, int n_in, void* d_out, int out_size) {
    (void)in_sizes; (void)n_in; (void)out_size;
    void* fnp = nullptr;
    cudaDriverEntryPointQueryResult st;
    cudaGetDriverEntryPoint("cuTensorMapEncodeTiled", &fnp, cudaEnableDefault, &st);
    EncodeFn fn = (EncodeFn)fnp;
    void* scratch = nullptr;
    cudaGetSymbolAddress(&scratch, g_scratch);
    int dev = 0, sms = 0;
    cudaGetDevice(&dev);
    cudaDeviceGetAttribute(&sms, cudaDevAttrMultiProcessorCount, dev);
    auto kernel = sms == 132 ? fused_kernel<true> : fused_kernel<false>;
    cudaFuncSetAttribute(kernel, cudaFuncAttributeMaxDynamicSharedMemorySize, SMEM_BYTES);

    const CUtensorMapSwizzle S128 = CU_TENSOR_MAP_SWIZZLE_128B, S0 = CU_TENSOR_MAP_SWIZZLE_NONE;
    Maps maps;
    encode(fn, &maps.m[M_XA], d_in[0], S128, {896, 2, 64}, {1024, 1792, 128});
    encode(fn, &maps.m[M_WQK], d_in[1], S128, {112, 2, 64}, {448, 2688, 32}, {3, 896, 2}, {4, 224, 1});
    encode(fn, &maps.m[M_WV], d_in[1], S128, {112, 2, 64}, {448, 2688, 64}, {12, 224, 1});
    encode(fn, &maps.m[M_XH], d_in[0], S128, {448, 2, 64}, {128, 1792, 8}, {8, 128 * 1792, 8}, {2, 896, 2});
    encode(fn, &maps.m[M_WO], d_in[2], S128, {112, 2, 64}, {448, 896, 64}, {4, 224, 1});
    encode(fn, &maps.m[M_XB], d_in[3], S128, {448, 2, 64}, {1024, 896, 64}, {2, 896 * 1024, 2});
    encode(fn, &maps.m[M_CR], d_in[4], S128, {2048, 2, 64}, {2048, 4096, 128});
    encode(fn, &maps.m[M_CI], d_in[5], S128, {2048, 2, 64}, {2048, 4096, 128});
    encode(fn, &maps.m[M_WR], d_in[6], S128, {448, 2, 64}, {448, 896, 112});
    encode(fn, &maps.m[M_WI], d_in[7], S128, {448, 2, 64}, {448, 896, 112});
    encode(fn, &maps.m[M_OUTA], d_out, S0, {1792, 2, 112}, {1024, 3584, 16});
    encode(fn, &maps.m[M_OUTB], d_out, S0, {896, 2, 112}, {2048, 1792, 16});

    kernel<<<132, 384, SMEM_BYTES>>>((Scratch*)scratch, maps);
}
```

```cpp
#include <cuda.h>
#include <cuda_bf16.h>
#include <cuda_runtime.h>
#include <stdint.h>

namespace {

constexpr uint32_t SLOT = 16384;
constexpr int NA = 7;
constexpr uint32_t BRING = NA * SLOT;
constexpr uint32_t HALO = BRING + 6 * SLOT;
constexpr uint32_t HSLOT = 1792;
constexpr uint32_t WSLOT = 3584;
constexpr uint32_t BLOB = 14336;
constexpr uint32_t BARS = 14 * SLOT;
constexpr uint32_t BAR_FULL = BARS;
constexpr uint32_t BAR_EMPTY = BARS + 64;
constexpr uint32_t BAR_RDY = BARS + 128;
constexpr uint32_t BAR_DEP = BARS + 168;
constexpr uint32_t BAR_HALO = BARS + 192;
constexpr uint32_t TAG = BARS + 208;
constexpr uint32_t SMEM_BYTES = BARS + 256 + 1024;
constexpr uint32_t base = 1024;
constexpr int SPIN_LIMIT = 1 << 16;

#define E_EXTRA 0
#define HALO_DELAY 7000
#define O_SLICE 4
#define B_SLICE 4
#define LEAD 3
#define TURN 3
#define PIN r.pin()
#define OPENER 8
#define X_SPLIT
#define MAPPING 2
constexpr int NBE = 13 + E_EXTRA;
constexpr int POUT = 33 + NBE;
constexpr int ELAST = POUT + 6;
constexpr int LLAST = 52 - E_EXTRA;

enum { M_XA, M_XH, M_WQK, M_WV, M_WO, M_XB, M_WR, M_WI, M_CR, M_CI, M_OUTA, M_OUTB, M_COUNT };
struct __align__(64) Maps { CUtensorMap m[M_COUNT]; };
struct Ptrs { const uint8_t* p[4]; };

constexpr int CNT_A = 0;
constexpr int CNT_B = 8;
constexpr int CNT_O = 16;
constexpr int CNT_COUNT = 32;

struct Scratch {
    uint8_t ab[64 * 4 * BLOB];
    uint8_t o[16 * 7 * SLOT];
    uint8_t part[64 * 2 * BLOB];
    uint8_t halo[64 * 2 * 2 * HSLOT];
    unsigned cnt[CNT_COUNT * 32];
    unsigned epoch[132 * 4 * 8];
};
__device__ __align__(1024) Scratch g_scratch;

__device__ __forceinline__ unsigned clk32() { unsigned c; asm volatile("mov.u32 %0, %%clock;" : "=r"(c)); return c; }
__device__ __forceinline__ void pause_until(unsigned t0, unsigned cycles) {
    while (clk32() - t0 < cycles) {}
}

#define PROF(idx)

__device__ __forceinline__ void mbar_init(uint32_t bar, uint32_t cnt) {
    asm volatile("mbarrier.init.shared::cta.b64 [%0], %1;" ::"r"(bar), "r"(cnt) : "memory");
}
__device__ __forceinline__ void mbar_expect(uint32_t bar, uint32_t bytes) {
    asm volatile("mbarrier.arrive.expect_tx.shared::cta.b64 _, [%0], %1;" ::"r"(bar), "r"(bytes) : "memory");
}
__device__ __forceinline__ void mbar_arrive(uint32_t bar) {
    asm volatile("mbarrier.arrive.shared::cta.b64 _, [%0];" ::"r"(bar) : "memory");
}
__device__ __forceinline__ bool mbar_try(uint32_t bar, uint32_t parity) {
    uint32_t ok;
    asm volatile("{\n.reg .pred p;\nmbarrier.try_wait.parity.shared::cta.b64 p, [%1], %2;\nselp.u32 %0, 1, 0, p;\n}\n"
                 : "=r"(ok) : "r"(bar), "r"(parity) : "memory");
    return ok;
}
__device__ __forceinline__ void mbar_wait(uint32_t bar, uint32_t parity) {
#pragma unroll 1
    for (int n = 0; n < SPIN_LIMIT; n++)
        if (mbar_try(bar, parity)) break;
}
__device__ __forceinline__ bool elect() {
    uint32_t p;
    asm volatile("{\n.reg .pred p;\nelect.sync _|p, 0xffffffff;\nselp.u32 %0, 1, 0, p;\n}\n" : "=r"(p));
    return p;
}
__device__ __forceinline__ void nb_sync(int id, int n) { asm volatile("bar.sync %0, %1;" ::"r"(id), "r"(n) : "memory"); }
__device__ __forceinline__ void nb_arrive(int id, int n) { asm volatile("bar.arrive %0, %1;" ::"r"(id), "r"(n) : "memory"); }
__device__ __forceinline__ void warp_arrive(uint32_t bar) {
    __syncwarp();
    if (elect()) mbar_arrive(bar);
}
__device__ __forceinline__ uint32_t band(uint32_t x, uint32_t m) {
    uint32_t r;
    asm volatile("and.b32 %0, %1, %2;" : "=r"(r) : "r"(x), "r"(m));
    return r;
}
__device__ __forceinline__ uint32_t dup(uint32_t x, uint32_t zero) {
    uint32_t r;
    asm volatile("xor.b32 %0, %1, %2;" : "=r"(r) : "r"(x), "r"(zero));
    return r;
}

__device__ __forceinline__ void tma_ld2(uint32_t dst, const CUtensorMap* m, int c0, int c1, uint32_t bar) {
    asm volatile("cp.async.bulk.tensor.2d.shared::cluster.global.mbarrier::complete_tx::bytes [%0], [%1, {%3, %4}], [%2];"
                 ::"r"(dst), "l"(m), "r"(bar), "r"(c0), "r"(c1) : "memory");
}
__device__ __forceinline__ void tma_ld3(uint32_t dst, const CUtensorMap* m, int c0, int c1, int c2, uint32_t bar) {
    asm volatile("cp.async.bulk.tensor.3d.shared::cluster.global.mbarrier::complete_tx::bytes [%0], [%1, {%3, %4, %5}], [%2];"
                 ::"r"(dst), "l"(m), "r"(bar), "r"(c0), "r"(c1), "r"(c2) : "memory");
}
__device__ __forceinline__ void tma_ld4(uint32_t dst, const CUtensorMap* m, int c0, int c1, int c2, int c3, uint32_t bar) {
    asm volatile("cp.async.bulk.tensor.4d.shared::cluster.global.mbarrier::complete_tx::bytes [%0], [%1, {%3, %4, %5, %6}], [%2];"
                 ::"r"(dst), "l"(m), "r"(bar), "r"(c0), "r"(c1), "r"(c2), "r"(c3) : "memory");
}
__device__ __forceinline__ void bulk_ld(uint32_t dst, const void* src, uint32_t bytes, uint32_t bar) {
    asm volatile("cp.async.bulk.shared::cluster.global.mbarrier::complete_tx::bytes [%0], [%1], %2, [%3];"
                 ::"r"(dst), "l"(src), "r"(bytes), "r"(bar) : "memory");
}
__device__ __forceinline__ void tma_st2(const CUtensorMap* m, int c0, int c1, uint32_t src) {
    asm volatile("cp.async.bulk.tensor.2d.global.shared::cta.bulk_group [%0, {%1, %2}], [%3];"
                 ::"l"(m), "r"(c0), "r"(c1), "r"(src) : "memory");
}
__device__ __forceinline__ void bulk_commit() { asm volatile("cp.async.bulk.commit_group;" ::: "memory"); }
__device__ __forceinline__ void bulk_wait_read() { asm volatile("cp.async.bulk.wait_group.read 0;" ::: "memory"); }
__device__ __forceinline__ void fence_async_smem() { asm volatile("fence.proxy.async.shared::cta;" ::: "memory"); }
__device__ __forceinline__ void fence_async_global() { asm volatile("fence.proxy.async.global;" ::: "memory"); }

__device__ __forceinline__ void signal(Scratch* sc, int idx) {
    asm volatile("fence.proxy.async;\nred.relaxed.gpu.global.add.u32 [%0], 1;" ::"l"(&sc->cnt[idx * 32]) : "memory");
}
__device__ __forceinline__ void await(Scratch* sc, int idx, unsigned target) {
#pragma unroll 1
    for (int n = 0; n < SPIN_LIMIT; n++) {
        unsigned v;
        asm volatile("ld.relaxed.gpu.global.u32 %0, [%1];" : "=r"(v) : "l"(&sc->cnt[idx * 32]) : "memory");
        if ((int)(v - target) >= 0) break;
    }
    asm volatile("fence.acquire.gpu;" ::: "memory");
}
__device__ __forceinline__ void wait_dep(int k) {
    mbar_wait(base + BAR_DEP + k * 8, 0);
    fence_async_global();
}

#define WG_REGS                                                                                                     \
    "{%0,%1,%2,%3,%4,%5,%6,%7,%8,%9,%10,%11,%12,%13,%14,%15,%16,%17,%18,%19,%20,%21,%22,%23,%24,%25,%26,%27,"       \
    "%28,%29,%30,%31,%32,%33,%34,%35,%36,%37,%38,%39,%40,%41,%42,%43,%44,%45,%46,%47,%48,%49,%50,%51,%52,%53,%54,%55}"
#define WG_OPS(C)                                                                                                   \
    C(d[0]), C(d[1]), C(d[2]), C(d[3]), C(d[4]), C(d[5]), C(d[6]), C(d[7]), C(d[8]), C(d[9]), C(d[10]), C(d[11]),   \
    C(d[12]), C(d[13]), C(d[14]), C(d[15]), C(d[16]), C(d[17]), C(d[18]), C(d[19]), C(d[20]), C(d[21]), C(d[22]),   \
    C(d[23]), C(d[24]), C(d[25]), C(d[26]), C(d[27]), C(d[28]), C(d[29]), C(d[30]), C(d[31]), C(d[32]), C(d[33]),   \
    C(d[34]), C(d[35]), C(d[36]), C(d[37]), C(d[38]), C(d[39]), C(d[40]), C(d[41]), C(d[42]), C(d[43]), C(d[44]),   \
    C(d[45]), C(d[46]), C(d[47]), C(d[48]), C(d[49]), C(d[50]), C(d[51]), C(d[52]), C(d[53]), C(d[54]), C(d[55])

template <int TA, int TB, int SB, bool INIT, uint32_t AH, uint32_t BH>
__device__ __forceinline__ void wgmma112(float (&d)[56], uint32_t alo, uint32_t blo) {
    if (INIT) {
        asm volatile("{\n.reg .pred p;\n.reg .b64 da, db;\nsetp.ne.b32 p, 0, 0;\nmov.b64 da, {%56, %61};\nmov.b64 db, {%57, %62};\n"
                     "wgmma.mma_async.sync.aligned.m64n112k16.f32.bf16.bf16 " WG_REGS ", da, db, p, 1, %59, %60, %58;\n}\n"
                     : WG_OPS("=f") : "r"(alo), "r"(blo), "n"(TB), "n"(SB), "n"(TA), "n"(AH), "n"(BH));
    } else {
        asm volatile("{\n.reg .pred p;\n.reg .b64 da, db;\nsetp.ne.b32 p, 1, 0;\nmov.b64 da, {%56, %61};\nmov.b64 db, {%57, %62};\n"
                     "wgmma.mma_async.sync.aligned.m64n112k16.f32.bf16.bf16 " WG_REGS ", da, db, p, 1, %59, %60, %58;\n}\n"
                     : WG_OPS("+f") : "r"(alo), "r"(blo), "n"(TB), "n"(SB), "n"(TA), "n"(AH), "n"(BH));
    }
}
__device__ __forceinline__ void acc_fence(float (&d)[56]) {
#pragma unroll
    for (int i = 0; i < 56; i++) asm volatile("" : "+f"(d[i])::"memory");
}

__device__ __forceinline__ uint32_t pack2(float lo, float hi) {
    uint32_t r;
    asm volatile("cvt.rn.bf16x2.f32 %0, %1, %2;" : "=r"(r) : "f"(hi), "f"(lo));
    return r;
}
__device__ __forceinline__ uint32_t movm(uint32_t a) {
    uint32_t r;
    asm volatile("movmatrix.sync.aligned.m8n8.trans.b16 %0, %1;" : "=r"(r) : "r"(a));
    return r;
}
__device__ __forceinline__ void stsm4(uint32_t addr, uint32_t a, uint32_t b, uint32_t c, uint32_t d) {
    asm volatile("stmatrix.sync.aligned.m8n8.x4.shared.b16 [%0], {%1,%2,%3,%4};" ::"r"(addr), "r"(a), "r"(b), "r"(c), "r"(d) : "memory");
}
__device__ __forceinline__ void sts1(uint32_t addr, uint32_t a) { asm volatile("st.shared.b32 [%0], %1;" ::"r"(addr), "r"(a) : "memory"); }
__device__ __forceinline__ uint32_t lds1(uint32_t addr) {
    uint32_t a;
    asm volatile("ld.shared.b32 %0, [%1];" : "=r"(a) : "r"(addr) : "memory");
    return a;
}
__device__ __forceinline__ void stg1(uint8_t* p, uint32_t a) { asm volatile("st.global.b32 [%0], %1;" ::"l"(p), "r"(a) : "memory"); }
__device__ __forceinline__ void st_part(uint8_t* p, const uint32_t* v, uint32_t parity) {
    asm volatile("{\n.reg .b64 x, y;\nmov.b64 x, {%1, %2};\nmov.b64 y, {%3, %4};\nst.relaxed.gpu.global.v2.b64 [%0], {x, y};\n}\n"
                 ::"l"(p), "r"((v[0] & ~1u) | parity), "r"(v[1]), "r"((v[2] & ~1u) | parity), "r"(v[3]) : "memory");
}
__device__ __forceinline__ void mma16816(float (&d)[4], const uint32_t (&a)[4], uint32_t b0, uint32_t b1) {
    asm volatile("mma.sync.aligned.m16n8k16.row.col.f32.bf16.bf16.f32 {%0,%1,%2,%3}, {%4,%5,%6,%7}, {%8,%9}, {%0,%1,%2,%3};"
                 : "+f"(d[0]), "+f"(d[1]), "+f"(d[2]), "+f"(d[3]) : "r"(a[0]), "r"(a[1]), "r"(a[2]), "r"(a[3]), "r"(b0), "r"(b1));
}
__device__ __forceinline__ uint32_t add2(uint32_t a, uint32_t b) {
    uint32_t r;
    asm("add.rn.bf16x2 %0, %1, %2;" : "=r"(r) : "r"(a), "r"(b));
    return r;
}
__device__ __forceinline__ uint32_t max2(uint32_t a, uint32_t b) {
    uint32_t r;
    asm("max.bf16x2 %0, %1, %2;" : "=r"(r) : "r"(a), "r"(b));
    return r;
}
__device__ __forceinline__ void st_tagged(uint8_t* p, uint32_t a, uint32_t b, uint32_t tag) {
    asm volatile("{\n.reg .b64 x, y;\nmov.b64 x, {%1, %3};\nmov.b64 y, {%2, %3};\nst.relaxed.gpu.global.v2.b64 [%0], {x, y};\n}\n"
                 ::"l"(p), "r"(a), "r"(b), "r"(tag) : "memory");
}
__device__ __forceinline__ void ld_tagged(const uint8_t* p, uint32_t& a, uint32_t& ta, uint32_t& b, uint32_t& tb) {
    asm volatile("{\n.reg .b64 x, y;\nld.relaxed.gpu.global.v2.b64 {x, y}, [%4];\nmov.b64 {%0, %1}, x;\nmov.b64 {%2, %3}, y;\n}\n"
                 : "=r"(a), "=r"(ta), "=r"(b), "=r"(tb) : "l"(p) : "memory");
}
__device__ __forceinline__ float bf_lo(uint32_t v) { return __uint_as_float(v << 16); }
__device__ __forceinline__ float bf_hi(uint32_t v) { return __uint_as_float(v & 0xFFFF0000u); }
__device__ __forceinline__ float rcp(float x) { float r; asm("rcp.approx.ftz.f32 %0, %1;" : "=f"(r) : "f"(x)); return r; }
__device__ __forceinline__ float ex2(float x) { float r; asm volatile("ex2.approx.ftz.f32 %0, %1;" : "=f"(r) : "f"(x)); return r; }

__device__ __forceinline__ uint32_t full_bar(int stage) { return base + BAR_FULL + (stage & 7) * 8; }
__device__ __forceinline__ void wait_released(int j) { mbar_wait(base + BAR_EMPTY + (j & 7) * 8, (j >> 3) & 1); }

template <int V>
struct Int { static constexpr int value = V; };

__host__ __device__ constexpr int bslot_e(int i) { return (i < 2 || i >= 14) ? (i + 5) % 7 : (i + 1) % 5; }
__host__ __device__ constexpr int bslot_l(int i) { return i % 6; }

template <uint32_t OFF>
struct Feed {
    int stage;
    uint32_t dst;
    __device__ __forceinline__ void seek(int i, int slot) { stage = i; dst = base + OFF + slot * SLOT; }
    template <int N>
    __device__ __forceinline__ uint32_t acquire() { wait_released(stage - N); return full_bar(stage); }
    template <int N>
    __device__ __forceinline__ void next() {
        stage++;
        dst += SLOT;
        if (dst == base + OFF + N * SLOT) dst = base + OFF;
    }
};
__device__ __forceinline__ int skip_own(int n, int mt) { return n == mt ? 15 : n; }

struct Desc { uint32_t lo, hi; };
__host__ __device__ constexpr Desc desc_const(uint32_t lbo, uint32_t sbo, uint32_t mode) { return {(lbo >> 4) << 16, (sbo >> 4) | (mode << 30)}; }
constexpr Desc D_K128 = desc_const(16, 1024, 1);
constexpr Desc D_N128 = desc_const(8192, 1024, 1);
constexpr Desc D_BLOB = desc_const(128, 256, 0);
constexpr Desc D_OT = desc_const(2048, 128, 0);

enum Kind { XW, XWN, QK, BIG, OUT };

struct Ring {
    int stage;
    uint32_t a, b;
    uint32_t wg;
    uint32_t zero;
    __device__ __forceinline__ void seek(int i, int bslot) {
        stage = i;
        a = (base + (i % NA) * SLOT) >> 4;
        b = (base + BRING + bslot * SLOT) >> 4;
    }
    __device__ __forceinline__ void wait() { mbar_wait(full_bar(stage), (stage >> 3) & 1); }
    __device__ __forceinline__ void take_turn() { nb_sync(1 + wg, 256); }
    __device__ __forceinline__ void pin() {
        uint32_t n = 0;
#pragma unroll 1
        do {
            asm volatile("pmevent 7;" ::: "memory");
        } while (n++ < zero);
    }
    template <Kind K, int NBS, bool INIT, int SB = 1, bool TAIL = false>
    __device__ __forceinline__ void run(float (&d)[56], float (&e)[56], bool first = true, bool last = true, bool more = true) {
        if (first) take_turn();
        asm volatile("wgmma.fence.sync.aligned;" ::: "memory");
        if (K == QK) {
            const uint32_t da = D_K128.lo + (base >> 4) + (stage >> 1) * (SLOT >> 4) + (stage & 1) * 4 + wg * 512, db = D_N128.lo + b;
            wgmma112<0, 1, 1, INIT, D_K128.hi, D_N128.hi>(d, da, db);
            wgmma112<0, 1, 1, INIT, D_K128.hi, D_N128.hi>(e, da, db + 256);
            wgmma112<0, 1, 1, false, D_K128.hi, D_N128.hi>(d, da + 2, db + 128);
            wgmma112<0, 1, 1, false, D_K128.hi, D_N128.hi>(e, da + 2, db + 384);
        } else {
            constexpr int TA = K == OUT, TB = K != XW;
            constexpr uint32_t sa = K == OUT ? 256 : 2, sb = K == XW ? 2 : K == BIG ? 224 : 128;
            constexpr Desc A = K == OUT ? D_OT : D_K128, B = K == XW ? D_K128 : K == BIG ? D_BLOB : D_N128;
            const uint32_t da = A.lo + a + wg * (K == OUT ? 64 : 512), db = B.lo + b;
            wgmma112<TA, TB, SB, INIT, A.hi, B.hi>(d, da, db);
            wgmma112<TA, TB, SB, false, A.hi, B.hi>(d, da + sa, db + sb);
            wgmma112<TA, TB, SB, false, A.hi, B.hi>(d, da + 2 * sa, db + 2 * sb);
            wgmma112<TA, TB, SB, false, A.hi, B.hi>(d, da + 3 * sa, db + 3 * sb);
        }
        asm volatile("wgmma.commit_group.sync.aligned;" ::: "memory");
        if (last) nb_arrive(2 - wg, 256);
        if (!TAIL) asm volatile("wgmma.wait_group.sync.aligned 1;" ::: "memory");
        if (!TAIL && stage > 0 && elect()) mbar_arrive(base + BAR_EMPTY + ((stage - 1) & 7) * 8);
        stage++;
        a += SLOT >> 4;
        if (a == (base + NA * SLOT) >> 4) a = base >> 4;
        b += SLOT >> 4;
        if (b == (base + BRING + NBS * SLOT) >> 4) b = (base + BRING) >> 4;
        if (more) wait();
    }
    template <Kind K, int NBS, bool INIT, int SB = 1, bool TAIL = false>
    __device__ __forceinline__ void run(float (&d)[56], bool first = true, bool last = true, bool more = true) {
        run<K, NBS, INIT, SB, TAIL>(d, d, first, last, more);
    }
};

__device__ __forceinline__ void pack_all(const float (&d)[56], uint32_t (&p)[28]) {
#pragma unroll
    for (int i = 0; i < 28; i++) p[i] = pack2(d[2 * i], d[2 * i + 1]);
}
template <int I0, int I1>
__device__ __forceinline__ void store_frags(uint8_t* dst, const uint32_t (&p)[28]) {
#pragma unroll
    for (int i = I0; i < I1; i++) stg1(dst + i * 128, p[i]);
}
template <int I0, int I1>
__device__ __forceinline__ void stage_frags(uint32_t lane_addr, const uint32_t (&p)[28]) {
#pragma unroll
    for (int i = I0; i < I1; i += 4) stsm4(lane_addr + i * 128, p[i], p[i + 1], p[i + 2], p[i + 3]);
}
template <class F>
__device__ __forceinline__ void store_out(F frag, int lane, uint32_t slab, const CUtensorMap* m, int c0, int c1) {
    const bool swap = lane & 16;
    const uint32_t addr = slab + (lane & 7) * 224 + ((lane >> 3) ^ ((lane >> 2) & 1)) * 16;
#pragma unroll
    for (int h = 0; h < 2; h++) {
#pragma unroll
        for (int c = 0; c < 14; c += 4) {
            const uint32_t t0 = frag(2 * c + h), t1 = frag(2 * c + 2 + h);
            if (c < 12) {
                const uint32_t t2 = frag(2 * c + 4 + h), t3 = frag(2 * c + 6 + h);
                stsm4(addr + h * 1792 + c * 16, swap ? t1 : t0, swap ? t0 : t1, swap ? t3 : t2, swap ? t2 : t3);
            } else {
                asm volatile("stmatrix.sync.aligned.m8n8.x2.shared.b16 [%0], {%1,%2};" ::"r"(addr + h * 1792 + c * 16), "r"(swap ? t1 : t0), "r"(swap ? t0 : t1) : "memory");
            }
        }
        fence_async_smem();
        __syncwarp();
        if (elect()) tma_st2(m, c0, c1 + 8 * h, slab + h * 1792);
    }
    if (elect()) {
        bulk_commit();
        bulk_wait_read();
    }
}
constexpr int OUT_ROWS = 8;
__host__ __device__ constexpr int tile_of(int t) { return 7 * (t >> 2) + 3 * ((t >> 1) & 1) + 2 * (t & 1); }

struct Role {
    bool H;
    int L, mt, ns, id;
};
template <bool BY_SM>
__device__ __forceinline__ Role decode_role() {
    uint32_t sm;
    if (BY_SM) asm volatile("mov.u32 %0, %%smid;" : "=r"(sm));
    else asm volatile("mov.u32 %0, %%ctaid.x;" : "=r"(sm));
    const int tpc = sm >> 1, q2 = ((tpc - 32) * 37) >> 8;
    const int gpc = tpc < 32 ? tpc & 7 : tpc < 60 ? tpc - 31 - 7 * q2 : 0;
    const int pos = tpc < 32 ? tpc >> 3 : tpc < 60 ? q2 + 4 : tpc - 56;
    Role r;
    r.H = sm >= 128;
    r.L = gpc & 1;
    r.mt = (gpc >> 1) * 4 + (pos >> 1);
    r.ns = (pos & 1) * 2 + (sm & 1);
    r.id = r.H ? sm : gpc * 16 + pos * 2 + (sm & 1);
    return r;
}

template <int I0, int I1>
__device__ __forceinline__ void first_fill(const Maps& maps, const Role& r) {
    if (r.L) {
#pragma unroll
        for (int i = I0; i < I1; i++) {
            const uint32_t bar = full_bar(i), dst = base + BRING + i * SLOT;
            if (i < 6) mbar_expect(bar, SLOT);
            if (i & 1) {
                mbar_arrive(bar);
            } else {
                mbar_expect(bar, SLOT);
                tma_ld2(base + (i >> 1) * SLOT, &maps.m[M_XA], (r.mt >> 3) * 448 + i * 32, (r.mt & 7) * 128, bar);
            }
            if (i < 6) {
                tma_ld4(dst, &maps.m[M_WQK], 0, i * 32, 0, r.ns, bar);
                tma_ld4(dst + 8192, &maps.m[M_WQK], 64, i * 32, 0, r.ns, bar);
            }
        }
    } else if (!r.H) {
#pragma unroll
        for (int i = I0; i < I1; i++) {
            const uint32_t bar = full_bar(i);
            mbar_expect(bar, SLOT);
            tma_ld3(base + i * SLOT, &maps.m[M_XB], i * 64, r.mt * 64, 0, bar);
            mbar_expect(bar, BLOB);
            tma_ld2(base + BRING + bslot_e(i) * SLOT, &maps.m[M_WR], i * 64, r.ns * 112, bar);
        }
    } else {
#pragma unroll 1
        for (int i = I0; i < I1; i++) {
            const uint32_t bar = full_bar(i), dst = base + BRING + i * SLOT;
            mbar_expect(bar, SLOT);
            mbar_expect(bar, SLOT);
            tma_ld4(base + i * SLOT, &maps.m[M_XH], i * 64, 120, 0, 0, bar);
            tma_ld3(dst, &maps.m[M_WV], 0, i * 64, 4 + r.ns, bar);
            tma_ld3(dst + 8192, &maps.m[M_WV], 64, i * 64, 4 + r.ns, bar);
        }
    }
}

template <bool BY_SM>
__global__ void __launch_bounds__(384, 1) fused_kernel(Scratch* sc, Ptrs first, const __grid_constant__ Maps maps) {
    const int warp = __shfl_sync(0xffffffffu, threadIdx.x >> 5, 0);
    const Role role = decode_role<BY_SM>();
    if (warp == OPENER) {
        if (elect()) {
            asm volatile("prefetch.tensormap [%0];" ::"l"(&maps.m[M_XB]) : "memory");
            asm volatile("prefetch.tensormap [%0];" ::"l"(&maps.m[M_XA]) : "memory");
            asm volatile("prefetch.tensormap [%0];" ::"l"(&maps.m[M_WR]) : "memory");
            asm volatile("prefetch.tensormap [%0];" ::"l"(&maps.m[M_WQK]) : "memory");
#pragma unroll
            for (int i = 0; i < 8; i++) mbar_init(base + BAR_FULL + i * 8, 2);
            asm volatile("fence.mbarrier_init.release.cluster;" ::: "memory");
            first_fill<0, LEAD>(maps, role);
        }
    }
    int lane = threadIdx.x & 31;
    asm volatile("" : "+r"(lane));
    const bool roleH = role.H;
    const int roleL = role.L, mt = role.mt, ns = role.ns, bid = role.id;
    const int par = mt >> 3, blk = mt & 7, col = ns * 112;
    if (warp == 9) {
        if (elect()) {
#pragma unroll
            for (int i = 0; i < 8; i++) mbar_init(base + BAR_EMPTY + i * 8, 8);
            asm volatile("fence.mbarrier_init.release.cluster;" ::: "memory");
        }
    } else if (warp == 10) {
        if (elect()) {
#pragma unroll
            for (int i = 0; i < 5; i++) mbar_init(base + BAR_RDY + i * 8, i < 2 ? 4 : 8);
#pragma unroll
            for (int i = 0; i < 2; i++) mbar_init(base + BAR_HALO + i * 8, 8);
            asm volatile("fence.mbarrier_init.release.cluster;" ::: "memory");
        }
    } else if (warp == 11) {
        if (elect()) {
#pragma unroll
            for (int i = 0; i < 3; i++) mbar_init(base + BAR_DEP + i * 8, 1);
            asm volatile("fence.mbarrier_init.release.cluster;" ::: "memory");
        }
    }
    __syncthreads();

    if (__builtin_expect(warp >= 8, 1)) {
        asm volatile("setmaxnreg.dec.sync.aligned.u32 56;");
#define PROF_FEED_A
#define PROF_FEED_B
        if (__builtin_expect(warp == 8, 1)) {
            if (elect()) {
                PROF(129);
                first_fill<LEAD, 7>(maps, role);
                PROF(134);
                Feed<0> f;
                const int row = mt * 128;
                auto c_run = [&](const CUtensorMap* m, int off, int n0, int n1) {
#pragma unroll 1
                    for (int n = n0; n < n1; n++) {
                        const uint32_t bar = f.acquire<NA>();
                        mbar_expect(bar, SLOT);
                        tma_ld2(f.dst, m, (off + skip_own(n, mt)) * 64, row, bar);
                        PROF_FEED_A;
                        f.next<NA>();
                    }
                };
                if (roleH) {
                } else if (!roleL) {
                    f.seek(14, 0);
                    mbar_wait(base + BAR_RDY, 0);
#pragma unroll 1
                    for (int i = 0; i < 4; i++) {
                        const uint32_t bar = f.acquire<NA>();
                        mbar_expect(bar, SLOT);
                        tma_ld2(f.dst, &maps.m[M_CR + (i >> 1)], ((i & 1) * 16 + mt) * 64, row, bar);
                        mbar_arrive(bar);
                        PROF_FEED_A;
                        f.next<NA>();
                    }
                    c_run(&maps.m[M_CR], 0, 0, 15);
                    c_run(&maps.m[M_CI], 0, 0, NBE);
                    wait_dep(2);
#pragma unroll 1
                    for (int i = 0; i < 7; i++) {
                        const uint32_t bar = f.acquire<NA>();
                        mbar_expect(bar, SLOT);
                        bulk_ld(f.dst, sc->o + (size_t)(mt * 7 + i) * SLOT, SLOT, bar);
                        PROF_FEED_A;
                        f.next<NA>();
                    }
                } else {
#pragma unroll 1
                    for (int i = 4; i < 7; i++) {
                        wait_released(2 * i - 8);
                        mbar_expect(full_bar(2 * i), SLOT);
                        tma_ld2(base + i * SLOT, &maps.m[M_XA], par * 448 + i * 64, blk * 128, full_bar(2 * i));
                    }
                    wait_released(7);
                    f.seek(21, 0);
                    c_run(&maps.m[M_CR], 16, 0, 15);
                    c_run(&maps.m[M_CI], 16, 0, 15);
                    c_run(&maps.m[M_CI], 0, NBE, 15);
                }
            }
        } else if (warp == 11) {
            if (elect()) {
                Feed<BRING> f;
                auto blob_run = [&](auto nbs, int quarter, int n0, int n1) {
                    constexpr int N = decltype(nbs)::value;
                    const uint8_t* src = sc->ab + (size_t)(quarter * 64 + ns) * BLOB;
#pragma unroll 1
                    for (int n = n0; n < n1; n++) {
                        const uint32_t bar = f.template acquire<N>();
                        mbar_expect(bar, BLOB);
                        bulk_ld(f.dst, src + skip_own(n, mt) * (4 * BLOB), BLOB, bar);
                        PROF_FEED_B;
                        f.template next<N>();
                    }
                };
                auto w_run = [&](auto nbs, const CUtensorMap* m, int slice, bool no_a) {
                    constexpr int N = decltype(nbs)::value;
#pragma unroll 1
                    for (int i = 0; i < 7; i++) {
                        const uint32_t bar = f.template acquire<N>();
                        mbar_expect(bar, SLOT);
                        tma_ld3(f.dst, m, 0, i * 64, slice, bar);
                        tma_ld3(f.dst + 8192, m, 64, i * 64, slice, bar);
                        if (no_a) mbar_arrive(bar);
                        PROF_FEED_B;
                        f.template next<N>();
                    }
                };
                if (roleH) {
                    f.seek(7, 0);
                    w_run(Int<7>(), &maps.m[M_WV], 8 + ns, true);
                } else if (!roleL) {
                    f.seek(7, bslot_e(7));
#pragma unroll 1
                    for (int i = 0; i < 7; i++) {
                        const uint32_t bar = f.acquire<5>();
                        mbar_expect(bar, BLOB);
                        tma_ld2(f.dst, &maps.m[M_WI], i * 64, col, bar);
                        mbar_arrive(bar);
                        PROF_FEED_B;
                        f.next<5>();
                    }
                    f.seek(18, bslot_e(18));
                    wait_dep(0);
                    blob_run(Int<7>(), 0, 0, 15);
                    wait_dep(1);
                    blob_run(Int<7>(), 2, 0, NBE);
                    w_run(Int<7>(), &maps.m[M_WO], ns, false);
                } else {
                    f.seek(6, 0);
#pragma unroll 1
                    for (int i = 6; i < 14; i++) {
                        const uint32_t bar = f.acquire<6>();
                        mbar_expect(bar, SLOT);
                        tma_ld4(f.dst, &maps.m[M_WQK], 0, i * 32, 0, ns, bar);
                        tma_ld4(f.dst + 8192, &maps.m[M_WQK], 64, i * 32, 0, ns, bar);
                        if (i & 1) mbar_arrive(bar);
                        PROF_FEED_B;
                        f.next<6>();
                    }
                    w_run(Int<6>(), &maps.m[M_WV], 8 + ns, true);
                    wait_dep(0);
                    blob_run(Int<6>(), 1, 0, 15);
                    wait_dep(1);
                    blob_run(Int<6>(), 3, 0, 15);
                    blob_run(Int<6>(), 2, NBE, 15);
                }
            }
        } else if (roleH) {
        } else if (warp == 10) {
            if (elect()) {
                unsigned* epoch_ptr = &sc->epoch[(bid * 4 + 2) * 8];
                const unsigned ep = *epoch_ptr + 1;
                sts1(base + TAG, ep);
                asm volatile("prefetch.tensormap [%0];" ::"l"(&maps.m[M_OUTA + roleL]) : "memory");
                await(sc, CNT_A + roleL * 4 + ns, ep * 16);
                mbar_arrive(base + BAR_DEP);
                PROF(150);
                await(sc, CNT_B + ns, ep * 16);
                mbar_arrive(base + BAR_DEP + 8);
                PROF(151);
                if (!roleL) {
                    await(sc, CNT_O + mt, ep * 4);
                    mbar_arrive(base + BAR_DEP + 16);
                }
                PROF(152);
                *epoch_ptr = ep;
            }
        } else if (!roleL) {
            if (elect()) {
                mbar_wait(base + BAR_RDY, 0);
                PROF(130);
                signal(sc, CNT_A + ns);
                PROF(131);
                mbar_wait(base + BAR_RDY + 8, 0);
                signal(sc, CNT_A + 4 + ns);
                PROF(135);
                mbar_wait(base + BAR_RDY + 32, 0);
                PROF(132);
                signal(sc, CNT_B + ns);
                PROF(133);
            }
        } else {
            const unsigned t_start = clk32();
            unsigned* epoch_ptr = &sc->epoch[(bid * 4 + 1) * 8];
            const unsigned tag = *epoch_ptr + 1;
#pragma unroll 1
            for (int kv = 0; kv < 2; kv++) {
                uint32_t v[14], t[14];
#pragma unroll
                for (int i = 0; i < 14; i++) v[i] = 0;

                if (blk > 0) {
                    const uint8_t* src = sc->halo + (size_t)(((mt - 1) * 4 + ns) * 2 + kv) * (2 * HSLOT) + lane * 16;
                    pause_until(t_start, HALO_DELAY + kv * 3200);
#pragma unroll 1
                    for (int n = 0; n < SPIN_LIMIT; n++) {
                        bool ok = true;
#pragma unroll
                        for (int i = 0; i < 7; i++) ld_tagged(src + i * 512, v[2 * i], t[2 * i], v[2 * i + 1], t[2 * i + 1]);
#pragma unroll
                        for (int i = 0; i < 14; i++) ok = ok && t[i] == tag;
                        if (__all_sync(0xffffffffu, ok)) break;
                    }
                }
#pragma unroll
                for (int i = 0; i < 14; i++) sts1(base + HALO + kv * (8 * HSLOT) + i * 128 + lane * 4, v[i]);
                warp_arrive(base + BAR_HALO + kv * 8);
                if (lane == 0) PROF(142 + kv);
            }
            if (elect()) {
                mbar_wait(base + BAR_RDY + 16, 0);
                PROF(130);
                signal(sc, CNT_O + mt);
                PROF(131);
                *epoch_ptr = tag;
            }
        }
    } else {
        asm volatile("setmaxnreg.inc.sync.aligned.u32 224;");
        Ring r;
        r.wg = warp >> 2;
        r.zero = blockIdx.y;
        const int wg = warp >> 2;
        if (wg) nb_arrive(1, 256);
        r.stage = 0;
        r.wait();
        uint8_t* part = sc->part + (size_t)(ns * 16 + mt) * (2 * BLOB) + warp * 512 + lane * 16;
        uint32_t p[28];

        if (roleH) {
            unsigned* epoch_ptr = &sc->epoch[bid * 4 * 8];
            const unsigned tag = *epoch_ptr + 1;
            uint8_t* hout = sc->halo + (size_t)((warp * 8 + ns) * 2) * (2 * HSLOT) + lane * 16;
            float x0[56], x1[56];
            r.seek(0, 0);
            r.run<XWN, 7, true>(x0);
#pragma unroll 1
            for (int i = 1; i < 7; i++) r.run<XWN, 7, false>(x0);
            r.run<XWN, 7, true>(x1);
            acc_fence(x0);
            pack_all(x0, p);
#pragma unroll
            for (int i = 0; i < 14; i++) st_tagged(hout + (i & 1) * (16 * HSLOT) + (i >> 1) * 512, p[(i >> 1) * 4 + (i & 1)], p[(i >> 1) * 4 + (i & 1) + 2], tag);
#pragma unroll 1
            for (int i = 1; i < 7; i++) r.run<XWN, 7, false>(x1, true, true, i < 6);
            asm volatile("wgmma.wait_group.sync.aligned 0;" ::: "memory");
            acc_fence(x1);
            pack_all(x1, p);
#pragma unroll
            for (int i = 0; i < 28; i++) p[i] = movm(p[i]);
#pragma unroll
            for (int i = 0; i < 14; i++)
                st_tagged(hout + 2 * HSLOT + (i & 1) * (16 * HSLOT) + (i >> 1) * 512, p[(i >> 1) * 4 + (i & 1)], p[(i >> 1) * 4 + (i & 1) + 2], tag);
            if (threadIdx.x == 0) *epoch_ptr = tag;
        } else if (!roleL) {
            uint8_t* blob = sc->ab + (size_t)((wg * 16 + mt) * 4 + ns) * BLOB + (warp & 3) * WSLOT + lane * 4;
            const uint32_t own = base + BRING + wg * SLOT + (warp & 3) * WSLOT + lane * 16;
            float x0[56], x1[56];
            r.seek(0, bslot_e(0));
            r.run<XW, 7, true>(x0);
            r.run<XW, 7, false>(x0);
            r.seek(2, bslot_e(2));
#pragma unroll 1
            for (int i = 2; i < 7; i++) r.run<XW, 5, false>(x0);

            r.seek(7, bslot_e(7));
            r.run<XW, 5, true, -1>(x1);
            acc_fence(x0);
            pack_all(x0, p);
#pragma unroll
            for (int i = 0; i < 2; i++) {
                if (wg == i) store_frags<0, 14>(blob, p);
                else stage_frags<0, 4>(own + 5 * SLOT, p);
                r.run<XW, 5, false, -1>(x1);
                if (wg == i) {
                    store_frags<14, 28>(blob, p);
                    warp_arrive(base + BAR_RDY + i * 8);
                } else {
                    stage_frags<4, 8>(own + 5 * SLOT, p);
                }
                r.run<XW, 5, false, -1>(x1);
            }
            stage_frags<8, 20>(own + 5 * SLOT, p);
            r.run<XW, 5, false, -1>(x1);
            stage_frags<20, 28>(own + 5 * SLOT, p);
            warp_arrive(base + BAR_RDY + 16);
            r.run<XW, 5, false, -1>(x1);

            mbar_wait(base + BAR_RDY + 16, 0);
            fence_async_smem();
            r.seek(14, bslot_e(14));
            r.run<BIG, 7, true>(x0);
            acc_fence(x1);
            pack_all(x1, p);
            wait_released(10);
            stage_frags<0, 28>(own, p);
            warp_arrive(base + BAR_RDY + 24);
            r.run<BIG, 7, false>(x0);
            mbar_wait(base + BAR_RDY + 24, 0);
            fence_async_smem();
            blob += (size_t)128 * BLOB;
#pragma unroll
            for (int i = 0; i < 28; i++) {
                if (i % B_SLICE == 0) r.run<BIG, 7, false>(x0);
                stg1(blob + i * 128, p[i]);
            }
            warp_arrive(base + BAR_RDY + 32);
#pragma unroll 1
            for (int i = 17 + 27 / B_SLICE; i < POUT; i++) r.run<BIG, 7, false>(x0);

            const uint32_t tag = lds1(base + TAG);
            r.seek(POUT, bslot_e(POUT));
            r.run<OUT, 7, true>(x1);
            acc_fence(x0);
            pack_all(x0, p);
#pragma unroll
            for (int k = 0; k < 3; k++) {
                if (k < 2 && wg == k) {
#pragma unroll
                    for (int i = 0; i < 4; i++) st_part(part + i * 4096, p + 4 * i, tag & 1);
                }
                if (k > 0 && wg == k - 1) {
#pragma unroll
                    for (int i = 4; i < 7; i++) st_part(part + i * 4096, p + 4 * i, tag & 1);
                }
                if (k < 2) r.run<OUT, 7, false>(x1);
            }
#pragma unroll
            for (int i = 3; i < 7; i++) r.run<OUT, 7, false, 1, true>(x1, i <= 7 - TURN, i < 7 - TURN || i == 6, i < 6);

            wait_released(ELAST - 6);
            asm volatile("wgmma.wait_group.sync.aligned 0;" ::: "memory");
            acc_fence(x1);
            const uint32_t slab = base + (wg ? BRING + bslot_e(ELAST - 6) * SLOT : ((ELAST - 6) % NA) * SLOT) + (warp & 3) * WSLOT;
            store_out([&](int i) { return pack2(x1[2 * i], x1[2 * i + 1]); }, lane, slab, &maps.m[M_OUTA], par * 896 + col, blk * 128 + warp * 16);
        } else {
            const int g = lane >> 2, tig = lane & 3;
            const uint32_t hin = base + HALO + warp * HSLOT + lane * 4;
            auto publish = [&](const uint32_t (&h)[14], int kv) {
                if (warp < 7) {
#pragma unroll
                    for (int c = 0; c < 14; c++) sts1(hin + HSLOT + c * 128, h[c]);
                    warp_arrive(base + BAR_HALO + kv * 8);
                }
            };
            float y0[56], y1[56], y2[56];
            r.seek(0, 0);
            r.run<QK, 6, true>(y0, y1);
#pragma unroll 1
            for (int i = 1; i < 14; i++) r.run<QK, 6, false>(y0, y1);

            uint32_t m1[8][4], m0[8][4], lo[14], hi[14];
            r.seek(14, bslot_l(14));
            r.run<XWN, 6, true>(y2);
            acc_fence(y0);
            acc_fence(y1);
#pragma unroll
            for (int c = 0; c < 14; c++) hi[c] = pack2(y1[4 * c + 2], y1[4 * c + 3]);
            publish(hi, 0);
            r.run<XWN, 6, false>(y2);
#pragma unroll
            for (int c = 0; c < 14; c++) lo[c] = pack2(y1[4 * c], y1[4 * c + 1]);
#pragma unroll
            for (int t = 0; t < 8; t++) {
                const int c = tile_of(t);
                const bool shared = (t & 3) == 2;
                m1[t][0] = shared ? dup(lo[c], r.zero) : lo[c];
                m1[t][1] = shared ? dup(hi[c], r.zero) : hi[c];
                m1[t][2] = lo[c + 1];
                m1[t][3] = hi[c + 1];
                m0[t][0] = dup(m1[t][0], r.zero);
                m0[t][2] = dup(lo[c + 1], 2 * r.zero);
            }
            PIN;
            r.run<XWN, 6, false>(y2);
            uint32_t q[2][8][2];
#pragma unroll
            for (int b = 0; b < 2; b++) {
                uint32_t v[14];
#pragma unroll
                for (int c = 0; c < 14; c++) v[c] = pack2(y0[4 * c + 2 * b], y0[4 * c + 2 * b + 1]);
#pragma unroll
                for (int t = 0; t < 8; t++) {
                    const int c = tile_of(t);
                    q[b][t][0] = (t & 3) == 2 ? (tig >= 2 ? v[c] : 0u) : v[c];
                    q[b][t][1] = (t & 3) == 1 ? (tig < 2 ? v[c + 1] : 0u) : v[c + 1];
                }
            }
            PIN;
            r.run<XWN, 6, false>(y2);
            mbar_wait(base + BAR_HALO, 0);
#pragma unroll
            for (int t = 0; t < 8; t++) {
                m0[t][1] = lds1(hin + tile_of(t) * 128 + ((t & 3) == 2 ? r.zero : 0u));
                m0[t][3] = lds1(hin + tile_of(t) * 128 + 128);
            }
            r.pin();
            r.take_turn();
            float s[8][4];
#pragma unroll
            for (int step = 0; step < 2; step++) {
#pragma unroll
                for (int i = 0; i < 8; i++) {
                    const int b = 1 - (i >> 2), h = i & 3, t = 2 * h + step;
                    float (&d)[4] = s[2 * h + b];
                    if (step == 0) d[0] = d[1] = d[2] = d[3] = 0.f;
                    mma16816(d, b ? m1[t] : m0[t], q[b][t][0], q[b][t][1]);
                }
            }
            r.pin();
            r.run<XWN, 6, false>(y2, false);

            uint32_t pr[8], mx[4], mx1[4];
            {
                const bool cur0 = g <= 2 * tig, cur1 = g <= 2 * tig + 1;
#pragma unroll
                for (int i = 0; i < 8; i++) {
                    const int c = (i & 1) ? 2 : 0;
                    pr[i] = movm(pack2(cur0 ? s[i][c] : s[i][2 - c], cur1 ? s[i][c + 1] : s[i][3 - c]));
                }
            }
            PIN;
            r.run<XWN, 6, false>(y2);
            const uint32_t curmask = (2 * tig <= g ? 0x0000FFFFu : 0u) | (2 * tig + 1 <= g ? 0xFFFF0000u : 0u);
            {
                const uint32_t keep = (blk == 0 && warp == 0) ? curmask : 0xFFFFFFFFu;
#pragma unroll
                for (int i = 0; i < 4; i++) {
                    pr[2 * i] = (pr[2 * i] & keep) | (0xCF9ECF9Eu & ~keep);
                    mx[i] = max2(__byte_perm(pr[2 * i], pr[2 * i + 1], 0x5410), __byte_perm(pr[2 * i], pr[2 * i + 1], 0x7632));
                }
#pragma unroll
                for (int i = 0; i < 4; i++) mx[i] = max2(mx[i], __shfl_xor_sync(0xffffffffu, mx[i], 1));
#pragma unroll
                for (int i = 0; i < 4; i++) mx1[i] = __shfl_xor_sync(0xffffffffu, mx[i], 2);
            }
            PIN;
            r.run<XWN, 6, false>(y2);
            constexpr float SCL = 0.18898223650461362f * 1.4426950408889634f;
            float e0[8], e1[8], sm[8], sm1[8];
#pragma unroll
            for (int i = 0; i < 8; i++) {
                const uint32_t m2 = max2(mx[i >> 1], mx1[i >> 1]);
                sm[i] = ((i & 1) ? bf_hi(m2) : bf_lo(m2)) * -SCL;
                e0[i] = ex2(fmaf(bf_lo(pr[i]), SCL, sm[i]));
            }

            r.seek(21, bslot_l(21));
            PIN;
            r.run<BIG, 6, true>(y0);
            acc_fence(y2);
#pragma unroll
            for (int c = 0; c < 14; c++) hi[c] = movm(pack2(y2[4 * c + 2], y2[4 * c + 3]));
            PIN;
            r.run<BIG, 6, false>(y0);
            wait_released(18);
            publish(hi, 1);
            r.run<BIG, 6, false>(y0);
#pragma unroll
            for (int i = 0; i < 8; i++) {
                e1[i] = ex2(fmaf(bf_hi(pr[i]), SCL, sm[i]));
                sm[i] = e0[i] + e1[i];
                sm1[i] = __shfl_xor_sync(0xffffffffu, sm[i], 1);
            }
            PIN;
            r.run<BIG, 6, false>(y0);
#pragma unroll
            for (int c = 0; c < 14; c++) lo[c] = movm(pack2(y2[4 * c], y2[4 * c + 1]));
            PIN;
            r.run<BIG, 6, false>(y0);
#pragma unroll
            for (int i = 0; i < 8; i++) {
                sm[i] += sm1[i];
                sm1[i] = __shfl_xor_sync(0xffffffffu, sm[i], 2);
            }
#pragma unroll
            for (int t = 0; t < 8; t++) {
                const int c = tile_of(t);
                const bool shared = (t & 3) == 2;
                m1[t][0] = shared ? dup(lo[c], r.zero) : lo[c];
                m1[t][1] = lo[c + 1];
                m1[t][2] = shared ? dup(hi[c], r.zero) : hi[c];
                m1[t][3] = hi[c + 1];
                m0[t][0] = dup(m1[t][0], r.zero);
                m0[t][1] = dup(lo[c + 1], 2 * r.zero);
            }
            PIN;
            r.run<BIG, 6, false>(y0);
            uint32_t pb[8][2];
#pragma unroll
            for (int i = 0; i < 8; i++) {
                const float inv = rcp(sm[i] + sm1[i]);
                const uint32_t w = pack2(e0[i] * inv, e1[i] * inv);
                pb[i][i & 1] = band(w, curmask);
                pb[i][1 - (i & 1)] = band(w, ~curmask);
            }
            PIN;
            r.run<BIG, 6, false>(y0);
            mbar_wait(base + BAR_HALO + 8, 0);
            const uint32_t vin = warp ? hin : hin + 8 * HSLOT;
#pragma unroll
            for (int t = 0; t < 8; t++) {
                m0[t][2] = lds1(vin + tile_of(t) * 128 + ((t & 3) == 2 ? r.zero : 0u));
                m0[t][3] = lds1(vin + tile_of(t) * 128 + 128);
            }
            r.pin();
            r.take_turn();
            float o[2][8][4];
#pragma unroll
            for (int i = 0; i < 16; i++) {
                const int b = 1 - (i >> 3), t = i & 7;
                float (&d)[4] = o[b][t];
                d[0] = d[1] = d[2] = d[3] = 0.f;
                mma16816(d, b ? m1[t] : m0[t], pb[(t & 6) + b][0], pb[(t & 6) + b][1]);
            }
            r.pin();
            r.run<BIG, 6, false>(y0, false);
            uint8_t* odst = sc->o + (size_t)mt * 7 * SLOT + ns * (14 * 2048) + warp * 256 + lane * 4;
#pragma unroll
            for (int hp = 0; hp < 2; hp++) {
#pragma unroll
                for (int b = 0; b < 2; b++) {
                    const float (&u)[8][4] = o[b];
                    const int t = 4 * hp;
                    uint32_t* w = p + 14 * hp + b;
                    w[0] = pack2(u[t][0], u[t][1]);
                    w[2] = pack2(u[t][2], u[t][3]);
                    w[4] = pack2(u[t + 1][0], u[t + 1][1]);
                    w[6] = pack2(g < 4 ? u[t + 1][2] : u[t + 2][0], g < 4 ? u[t + 1][3] : u[t + 2][1]);
                    w[8] = pack2(u[t + 2][2], u[t + 2][3]);
                    w[10] = pack2(u[t + 3][0], u[t + 3][1]);
                    w[12] = pack2(u[t + 3][2], u[t + 3][3]);
                }
            }
#pragma unroll
            for (int i = 0; i < 28; i++) {
                if (i && i % O_SLICE == 0) r.run<BIG, 6, false>(y0);
                stg1(odst + (i >> 1) * 2048 + (i & 1) * 128, p[i]);
            }
            warp_arrive(base + BAR_RDY + 16);

#pragma unroll 1
            for (int i = 29 + 27 / O_SLICE; i <= LLAST + 1 - TURN; i++) r.run<BIG, 6, false>(y0, true, i <= LLAST - TURN);
            const uint32_t tag = lds1(base + TAG);
#pragma unroll
            for (int i = 0; i < 7; i++) ld_tagged(part + i * 4096, p[4 * i], p[4 * i + 1], p[4 * i + 2], p[4 * i + 3]);
            r.seek(LLAST + 2 - TURN, bslot_l(LLAST + 2 - TURN));
#pragma unroll
            for (int i = 1; i < TURN; i++) r.run<BIG, 6, false, 1, true>(y0, false, i == TURN - 1, i < TURN - 1);
#pragma unroll 1
            for (int n = 0; n < SPIN_LIMIT; n++) {
                uint32_t stale = 0;
#pragma unroll
                for (int i = 0; i < 28; i += 2) stale |= p[i] ^ tag;
                if (__all_sync(0xffffffffu, !(stale & 1))) break;
#pragma unroll
                for (int i = 0; i < 7; i++) ld_tagged(part + i * 4096, p[4 * i], p[4 * i + 1], p[4 * i + 2], p[4 * i + 3]);
            }
            wait_released(LLAST - 6);
            asm volatile("wgmma.wait_group.sync.aligned 0;" ::: "memory");
            acc_fence(y0);
            const uint32_t slab = base + (wg ? HALO : ((LLAST - 6) % NA) * SLOT) + (warp & 3) * WSLOT;
            store_out([&](int i) { return add2(pack2(y0[2 * i], y0[2 * i + 1]), p[i]); }, lane, slab, &maps.m[M_OUTB], 448 + col, mt * 128 + warp * 16);
        }
    }
}

typedef CUresult (*EncodeFn)(CUtensorMap*, CUtensorMapDataType, cuuint32_t, void*, const cuuint64_t*, const cuuint64_t*,
                             const cuuint32_t*, const cuuint32_t*, CUtensorMapInterleave, CUtensorMapSwizzle,
                             CUtensorMapL2promotion, CUtensorMapFloatOOBfill);

struct Dim { uint64_t size, stride; uint32_t box; };
void encode(EncodeFn fn, CUtensorMap* m, const void* ptr, CUtensorMapSwizzle sw, Dim d0, Dim d1, Dim d2 = {0, 0, 0}, Dim d3 = {0, 0, 0}) {
    const cuuint64_t dims[4] = {d0.size, d1.size, d2.size, d3.size};
    const cuuint64_t strides[3] = {d1.stride, d2.stride, d3.stride};
    const cuuint32_t box[4] = {d0.box, d1.box, d2.box, d3.box};
    const cuuint32_t es[4] = {1, 1, 1, 1};
    fn(m, CU_TENSOR_MAP_DATA_TYPE_BFLOAT16, d3.size ? 4 : d2.size ? 3 : 2, const_cast<void*>(ptr), dims, strides, box, es,
       CU_TENSOR_MAP_INTERLEAVE_NONE, sw, CU_TENSOR_MAP_L2_PROMOTION_L2_128B, CU_TENSOR_MAP_FLOAT_OOB_FILL_NONE);
}

}

extern "C" void kernel_launch(void* const* d_in, const int* in_sizes, int n_in, void* d_out, int out_size) {
    (void)in_sizes; (void)n_in; (void)out_size;
    void* fnp = nullptr;
    cudaDriverEntryPointQueryResult st;
    cudaGetDriverEntryPoint("cuTensorMapEncodeTiled", &fnp, cudaEnableDefault, &st);
    EncodeFn fn = (EncodeFn)fnp;
    void* scratch = nullptr;
    cudaGetSymbolAddress(&scratch, g_scratch);
    int dev = 0, sms = 0;
    cudaGetDevice(&dev);
    cudaDeviceGetAttribute(&sms, cudaDevAttrMultiProcessorCount, dev);
    auto kernel = sms == 132 ? fused_kernel<true> : fused_kernel<false>;
    cudaFuncSetAttribute(kernel, cudaFuncAttributeMaxDynamicSharedMemorySize, SMEM_BYTES);

    const CUtensorMapSwizzle S128 = CU_TENSOR_MAP_SWIZZLE_128B, S0 = CU_TENSOR_MAP_SWIZZLE_NONE;
    Maps maps;
    encode(fn, &maps.m[M_XA], d_in[0], S128, {896, 2, 64}, {1024, 1792, 128});
    encode(fn, &maps.m[M_WQK], d_in[1], S128, {112, 2, 64}, {448, 2688, 32}, {3, 896, 2}, {4, 224, 1});
    encode(fn, &maps.m[M_WV], d_in[1], S128, {112, 2, 64}, {448, 2688, 64}, {12, 224, 1});
    encode(fn, &maps.m[M_XH], d_in[0], S128, {448, 2, 64}, {128, 1792, 8}, {8, 128 * 1792, 8}, {2, 896, 2});
    encode(fn, &maps.m[M_WO], d_in[2], S128, {112, 2, 64}, {448, 896, 64}, {4, 224, 1});
    encode(fn, &maps.m[M_XB], d_in[3], S128, {448, 2, 64}, {1024, 896, 64}, {2, 896 * 1024, 2});
    encode(fn, &maps.m[M_CR], d_in[4], S128, {2048, 2, 64}, {2048, 4096, 128});
    encode(fn, &maps.m[M_CI], d_in[5], S128, {2048, 2, 64}, {2048, 4096, 128});
    encode(fn, &maps.m[M_WR], d_in[6], S128, {448, 2, 64}, {448, 896, 112});
    encode(fn, &maps.m[M_WI], d_in[7], S128, {448, 2, 64}, {448, 896, 112});
    encode(fn, &maps.m[M_OUTA], d_out, S0, {1792, 2, 112}, {1024, 3584, OUT_ROWS});
    encode(fn, &maps.m[M_OUTB], d_out, S0, {896, 2, 112}, {2048, 1792, OUT_ROWS});

    const Ptrs first = {{(const uint8_t*)d_in[0], (const uint8_t*)d_in[3], (const uint8_t*)d_in[1], (const uint8_t*)d_in[6]}};
    kernel<<<132, 384, SMEM_BYTES>>>((Scratch*)scratch, first, maps);
}
```

```cpp
#include <cuda.h>
#include <cuda_bf16.h>
#include <cuda_runtime.h>
#include <stdint.h>

namespace {

constexpr uint32_t SLOT = 16384;
constexpr int NA = 7;
constexpr uint32_t BRING = NA * SLOT;
constexpr uint32_t HALO = BRING + 6 * SLOT;
constexpr uint32_t HSLOT = 1792;
constexpr uint32_t WSLOT = 3584;
constexpr uint32_t BLOB = 14336;
constexpr uint32_t BARS = 14 * SLOT;
constexpr uint32_t BAR_FULL = BARS;
constexpr uint32_t BAR_EMPTY = BARS + 64;
constexpr uint32_t BAR_RDY = BARS + 128;
constexpr uint32_t BAR_DEP = BARS + 168;
constexpr uint32_t BAR_HALO = BARS + 192;
constexpr uint32_t TAG = BARS + 208;
constexpr uint32_t SMEM_BYTES = BARS + 256 + 1024;
constexpr uint32_t base = 1024;
constexpr int SPIN_LIMIT = 1 << 16;

#define E_EXTRA 0
#define HALO_K_AT 11
#define HALO_V_AT 18
#define O_SLICE 4
#define B_SLICE 4
#define LEAD 3
#define TURN 3
#define PIN r.pin()
#define OPENER 8
#define MAPPING 2
constexpr int NBE = 13 + E_EXTRA;
constexpr int POUT = 33 + NBE;
constexpr int ELAST = POUT + 6;
constexpr int LLAST = 52 - E_EXTRA;

enum { M_XA, M_XH, M_WQK, M_WV, M_WO, M_XB, M_WR, M_WI, M_CR, M_CI, M_OUTA, M_OUTB, M_COUNT };
struct __align__(64) Maps { CUtensorMap m[M_COUNT]; };

constexpr int CNT_A = 0;
constexpr int CNT_B = 8;
constexpr int CNT_O = 16;
constexpr int CNT_COUNT = 32;

struct Scratch {
    uint8_t ab[64 * 4 * BLOB];
    uint8_t o[16 * 7 * SLOT];
    uint8_t part[64 * 2 * BLOB];
    uint8_t halo[64 * 2 * 2048];
    unsigned cnt[CNT_COUNT * 32];
    unsigned epoch[132 * 4 * 8];
};
__device__ __align__(1024) Scratch g_scratch;

__device__ __forceinline__ unsigned clk32() { unsigned c; asm volatile("mov.u32 %0, %%clock;" : "=r"(c)); return c; }

#define PROF(idx)

__device__ __forceinline__ void mbar_init(uint32_t bar, uint32_t cnt) {
    asm volatile("mbarrier.init.shared::cta.b64 [%0], %1;" ::"r"(bar), "r"(cnt) : "memory");
}
__device__ __forceinline__ void mbar_expect(uint32_t bar, uint32_t bytes) {
    asm volatile("mbarrier.arrive.expect_tx.shared::cta.b64 _, [%0], %1;" ::"r"(bar), "r"(bytes) : "memory");
}
__device__ __forceinline__ void mbar_arrive(uint32_t bar) {
    asm volatile("mbarrier.arrive.shared::cta.b64 _, [%0];" ::"r"(bar) : "memory");
}
__device__ __forceinline__ bool mbar_try(uint32_t bar, uint32_t parity) {
    uint32_t ok;
    asm volatile("{\n.reg .pred p;\nmbarrier.try_wait.parity.shared::cta.b64 p, [%1], %2;\nselp.u32 %0, 1, 0, p;\n}\n"
                 : "=r"(ok) : "r"(bar), "r"(parity) : "memory");
    return ok;
}
__device__ __forceinline__ void mbar_wait(uint32_t bar, uint32_t parity) {
#pragma unroll 1
    for (int n = 0; n < SPIN_LIMIT; n++)
        if (mbar_try(bar, parity)) break;
}
__device__ __forceinline__ bool elect() {
    uint32_t p;
    asm volatile("{\n.reg .pred p;\nelect.sync _|p, 0xffffffff;\nselp.u32 %0, 1, 0, p;\n}\n" : "=r"(p));
    return p;
}
__device__ __forceinline__ void nb_sync(int id, int n) { asm volatile("bar.sync %0, %1;" ::"r"(id), "r"(n) : "memory"); }
__device__ __forceinline__ void nb_arrive(int id, int n) { asm volatile("bar.arrive %0, %1;" ::"r"(id), "r"(n) : "memory"); }
__device__ __forceinline__ void warp_arrive(uint32_t bar) {
    __syncwarp();
    if (elect()) mbar_arrive(bar);
}
__device__ __forceinline__ uint32_t band(uint32_t x, uint32_t m) {
    uint32_t r;
    asm volatile("and.b32 %0, %1, %2;" : "=r"(r) : "r"(x), "r"(m));
    return r;
}
__device__ __forceinline__ uint32_t dup(uint32_t x, uint32_t zero) {
    uint32_t r;
    asm volatile("xor.b32 %0, %1, %2;" : "=r"(r) : "r"(x), "r"(zero));
    return r;
}

__device__ __forceinline__ void tma_ld2(uint32_t dst, const CUtensorMap* m, int c0, int c1, uint32_t bar) {
    asm volatile("cp.async.bulk.tensor.2d.shared::cluster.global.mbarrier::complete_tx::bytes [%0], [%1, {%3, %4}], [%2];"
                 ::"r"(dst), "l"(m), "r"(bar), "r"(c0), "r"(c1) : "memory");
}
__device__ __forceinline__ void tma_ld3(uint32_t dst, const CUtensorMap* m, int c0, int c1, int c2, uint32_t bar) {
    asm volatile("cp.async.bulk.tensor.3d.shared::cluster.global.mbarrier::complete_tx::bytes [%0], [%1, {%3, %4, %5}], [%2];"
                 ::"r"(dst), "l"(m), "r"(bar), "r"(c0), "r"(c1), "r"(c2) : "memory");
}
__device__ __forceinline__ void tma_ld4(uint32_t dst, const CUtensorMap* m, int c0, int c1, int c2, int c3, uint32_t bar) {
    asm volatile("cp.async.bulk.tensor.4d.shared::cluster.global.mbarrier::complete_tx::bytes [%0], [%1, {%3, %4, %5, %6}], [%2];"
                 ::"r"(dst), "l"(m), "r"(bar), "r"(c0), "r"(c1), "r"(c2), "r"(c3) : "memory");
}
__device__ __forceinline__ void bulk_ld(uint32_t dst, const void* src, uint32_t bytes, uint32_t bar) {
    asm volatile("cp.async.bulk.shared::cluster.global.mbarrier::complete_tx::bytes [%0], [%1], %2, [%3];"
                 ::"r"(dst), "l"(src), "r"(bytes), "r"(bar) : "memory");
}
__device__ __forceinline__ void tma_st2(const CUtensorMap* m, int c0, int c1, uint32_t src) {
    asm volatile("cp.async.bulk.tensor.2d.global.shared::cta.bulk_group [%0, {%1, %2}], [%3];"
                 ::"l"(m), "r"(c0), "r"(c1), "r"(src) : "memory");
}
__device__ __forceinline__ void bulk_commit() { asm volatile("cp.async.bulk.commit_group;" ::: "memory"); }
__device__ __forceinline__ void bulk_wait_read() { asm volatile("cp.async.bulk.wait_group.read 0;" ::: "memory"); }
__device__ __forceinline__ void fence_async_smem() { asm volatile("fence.proxy.async.shared::cta;" ::: "memory"); }
__device__ __forceinline__ void fence_async_global() { asm volatile("fence.proxy.async.global;" ::: "memory"); }

__device__ __forceinline__ void signal(Scratch* sc, int idx) {
    asm volatile("fence.proxy.async;\nred.relaxed.gpu.global.add.u32 [%0], 1;" ::"l"(&sc->cnt[idx * 32]) : "memory");
}
__device__ __forceinline__ void await(Scratch* sc, int idx, unsigned target) {
#pragma unroll 1
    for (int n = 0; n < SPIN_LIMIT; n++) {
        unsigned v;
        asm volatile("ld.relaxed.gpu.global.u32 %0, [%1];" : "=r"(v) : "l"(&sc->cnt[idx * 32]) : "memory");
        if ((int)(v - target) >= 0) break;
    }
    asm volatile("fence.acquire.gpu;" ::: "memory");
}
__device__ __forceinline__ void wait_dep(int k) {
    mbar_wait(base + BAR_DEP + k * 8, 0);
    fence_async_global();
}

#define WG_REGS                                                                                                     \
    "{%0,%1,%2,%3,%4,%5,%6,%7,%8,%9,%10,%11,%12,%13,%14,%15,%16,%17,%18,%19,%20,%21,%22,%23,%24,%25,%26,%27,"       \
    "%28,%29,%30,%31,%32,%33,%34,%35,%36,%37,%38,%39,%40,%41,%42,%43,%44,%45,%46,%47,%48,%49,%50,%51,%52,%53,%54,%55}"
#define WG_OPS(C)                                                                                                   \
    C(d[0]), C(d[1]), C(d[2]), C(d[3]), C(d[4]), C(d[5]), C(d[6]), C(d[7]), C(d[8]), C(d[9]), C(d[10]), C(d[11]),   \
    C(d[12]), C(d[13]), C(d[14]), C(d[15]), C(d[16]), C(d[17]), C(d[18]), C(d[19]), C(d[20]), C(d[21]), C(d[22]),   \
    C(d[23]), C(d[24]), C(d[25]), C(d[26]), C(d[27]), C(d[28]), C(d[29]), C(d[30]), C(d[31]), C(d[32]), C(d[33]),   \
    C(d[34]), C(d[35]), C(d[36]), C(d[37]), C(d[38]), C(d[39]), C(d[40]), C(d[41]), C(d[42]), C(d[43]), C(d[44]),   \
    C(d[45]), C(d[46]), C(d[47]), C(d[48]), C(d[49]), C(d[50]), C(d[51]), C(d[52]), C(d[53]), C(d[54]), C(d[55])

template <int TA, int TB, int SB, bool INIT, uint32_t AH, uint32_t BH>
__device__ __forceinline__ void wgmma112(float (&d)[56], uint32_t alo, uint32_t blo) {
    if (INIT) {
        asm volatile("{\n.reg .pred p;\n.reg .b64 da, db;\nsetp.ne.b32 p, 0, 0;\nmov.b64 da, {%56, %61};\nmov.b64 db, {%57, %62};\n"
                     "wgmma.mma_async.sync.aligned.m64n112k16.f32.bf16.bf16 " WG_REGS ", da, db, p, 1, %59, %60, %58;\n}\n"
                     : WG_OPS("=f") : "r"(alo), "r"(blo), "n"(TB), "n"(SB), "n"(TA), "n"(AH), "n"(BH));
    } else {
        asm volatile("{\n.reg .pred p;\n.reg .b64 da, db;\nsetp.ne.b32 p, 1, 0;\nmov.b64 da, {%56, %61};\nmov.b64 db, {%57, %62};\n"
                     "wgmma.mma_async.sync.aligned.m64n112k16.f32.bf16.bf16 " WG_REGS ", da, db, p, 1, %59, %60, %58;\n}\n"
                     : WG_OPS("+f") : "r"(alo), "r"(blo), "n"(TB), "n"(SB), "n"(TA), "n"(AH), "n"(BH));
    }
}
__device__ __forceinline__ void acc_fence(float (&d)[56]) {
#pragma unroll
    for (int i = 0; i < 56; i++) asm volatile("" : "+f"(d[i])::"memory");
}

__device__ __forceinline__ uint32_t pack2(float lo, float hi) {
    uint32_t r;
    asm volatile("cvt.rn.bf16x2.f32 %0, %1, %2;" : "=r"(r) : "f"(hi), "f"(lo));
    return r;
}
__device__ __forceinline__ uint32_t movm(uint32_t a) {
    uint32_t r;
    asm volatile("movmatrix.sync.aligned.m8n8.trans.b16 %0, %1;" : "=r"(r) : "r"(a));
    return r;
}
__device__ __forceinline__ void stsm4(uint32_t addr, uint32_t a, uint32_t b, uint32_t c, uint32_t d) {
    asm volatile("stmatrix.sync.aligned.m8n8.x4.shared.b16 [%0], {%1,%2,%3,%4};" ::"r"(addr), "r"(a), "r"(b), "r"(c), "r"(d) : "memory");
}
__device__ __forceinline__ void sts1(uint32_t addr, uint32_t a) { asm volatile("st.shared.b32 [%0], %1;" ::"r"(addr), "r"(a) : "memory"); }
__device__ __forceinline__ uint32_t lds1(uint32_t addr) {
    uint32_t a;
    asm volatile("ld.shared.b32 %0, [%1];" : "=r"(a) : "r"(addr) : "memory");
    return a;
}
__device__ __forceinline__ void stg1(uint8_t* p, uint32_t a) { asm volatile("st.global.b32 [%0], %1;" ::"l"(p), "r"(a) : "memory"); }
__device__ __forceinline__ void st_part(uint8_t* p, const uint32_t* v, uint32_t parity) {
    asm volatile("{\n.reg .b64 x, y;\nmov.b64 x, {%1, %2};\nmov.b64 y, {%3, %4};\nst.relaxed.gpu.global.v2.b64 [%0], {x, y};\n}\n"
                 ::"l"(p), "r"((v[0] & ~1u) | parity), "r"(v[1]), "r"((v[2] & ~1u) | parity), "r"(v[3]) : "memory");
}
__device__ __forceinline__ void mma16816(float (&d)[4], const uint32_t (&a)[4], uint32_t b0, uint32_t b1) {
    asm volatile("mma.sync.aligned.m16n8k16.row.col.f32.bf16.bf16.f32 {%0,%1,%2,%3}, {%4,%5,%6,%7}, {%8,%9}, {%0,%1,%2,%3};"
                 : "+f"(d[0]), "+f"(d[1]), "+f"(d[2]), "+f"(d[3]) : "r"(a[0]), "r"(a[1]), "r"(a[2]), "r"(a[3]), "r"(b0), "r"(b1));
}
__device__ __forceinline__ uint32_t add2(uint32_t a, uint32_t b) {
    uint32_t r;
    asm("add.rn.bf16x2 %0, %1, %2;" : "=r"(r) : "r"(a), "r"(b));
    return r;
}
__device__ __forceinline__ uint32_t max2(uint32_t a, uint32_t b) {
    uint32_t r;
    asm("max.bf16x2 %0, %1, %2;" : "=r"(r) : "r"(a), "r"(b));
    return r;
}
__device__ __forceinline__ void ld_tagged(const uint8_t* p, uint32_t& a, uint32_t& ta, uint32_t& b, uint32_t& tb) {
    asm volatile("{\n.reg .b64 x, y;\nld.relaxed.gpu.global.v2.b64 {x, y}, [%4];\nmov.b64 {%0, %1}, x;\nmov.b64 {%2, %3}, y;\n}\n"
                 : "=r"(a), "=r"(ta), "=r"(b), "=r"(tb) : "l"(p) : "memory");
}
__device__ __forceinline__ float bf_lo(uint32_t v) { return __uint_as_float(v << 16); }
__device__ __forceinline__ float bf_hi(uint32_t v) { return __uint_as_float(v & 0xFFFF0000u); }
__device__ __forceinline__ float rcp(float x) { float r; asm("rcp.approx.ftz.f32 %0, %1;" : "=f"(r) : "f"(x)); return r; }
__device__ __forceinline__ float ex2(float x) { float r; asm volatile("ex2.approx.ftz.f32 %0, %1;" : "=f"(r) : "f"(x)); return r; }

__device__ __forceinline__ uint32_t full_bar(int stage) { return base + BAR_FULL + (stage & 7) * 8; }
__device__ __forceinline__ void wait_released(int j) { mbar_wait(base + BAR_EMPTY + (j & 7) * 8, (j >> 3) & 1); }

template <int V>
struct Int { static constexpr int value = V; };

__host__ __device__ constexpr int bslot_e(int i) { return (i < 2 || i >= 14) ? (i + 5) % 7 : (i + 1) % 5; }
__host__ __device__ constexpr int bslot_l(int i) { return i % 6; }

template <uint32_t OFF>
struct Feed {
    int stage;
    uint32_t dst;
    __device__ __forceinline__ void seek(int i, int slot) { stage = i; dst = base + OFF + slot * SLOT; }
    template <int N>
    __device__ __forceinline__ uint32_t acquire() { wait_released(stage - N); return full_bar(stage); }
    template <int N>
    __device__ __forceinline__ void next() {
        stage++;
        dst += SLOT;
        if (dst == base + OFF + N * SLOT) dst = base + OFF;
    }
};
__device__ __forceinline__ int skip_own(int n, int mt) { return n == mt ? 15 : n; }

struct Desc { uint32_t lo, hi; };
__host__ __device__ constexpr Desc desc_const(uint32_t lbo, uint32_t sbo, uint32_t mode) { return {(lbo >> 4) << 16, (sbo >> 4) | (mode << 30)}; }
constexpr Desc D_K128 = desc_const(16, 1024, 1);
constexpr Desc D_N128 = desc_const(8192, 1024, 1);
constexpr Desc D_BLOB = desc_const(128, 256, 0);
constexpr Desc D_OT = desc_const(2048, 128, 0);

enum Kind { XW, XWN, QK, BIG, OUT };

struct Ring {
    int stage;
    uint32_t a, b;
    uint32_t wg;
    uint32_t zero;
    __device__ __forceinline__ void seek(int i, int bslot) {
        stage = i;
        a = (base + (i % NA) * SLOT) >> 4;
        b = (base + BRING + bslot * SLOT) >> 4;
    }
    __device__ __forceinline__ void wait() { mbar_wait(full_bar(stage), (stage >> 3) & 1); }
    __device__ __forceinline__ void take_turn() { nb_sync(1 + wg, 256); }
    __device__ __forceinline__ void pin() {
        uint32_t n = 0;
#pragma unroll 1
        do {
            asm volatile("pmevent 7;" ::: "memory");
        } while (n++ < zero);
    }
    template <Kind K, int NBS, bool INIT, int SB = 1, bool TAIL = false>
    __device__ __forceinline__ void run(float (&d)[56], float (&e)[56], bool first = true, bool last = true, bool more = true) {
        if (first) take_turn();
        asm volatile("wgmma.fence.sync.aligned;" ::: "memory");
        if (K == QK) {
            const uint32_t da = D_K128.lo + (base >> 4) + (stage >> 1) * (SLOT >> 4) + (stage & 1) * 4 + wg * 512, db = D_N128.lo + b;
            wgmma112<0, 1, 1, INIT, D_K128.hi, D_N128.hi>(d, da, db);
            wgmma112<0, 1, 1, INIT, D_K128.hi, D_N128.hi>(e, da, db + 256);
            wgmma112<0, 1, 1, false, D_K128.hi, D_N128.hi>(d, da + 2, db + 128);
            wgmma112<0, 1, 1, false, D_K128.hi, D_N128.hi>(e, da + 2, db + 384);
        } else {
            constexpr int TA = K == OUT, TB = K != XW;
            constexpr uint32_t sa = K == OUT ? 256 : 2, sb = K == XW ? 2 : K == BIG ? 224 : 128;
            constexpr Desc A = K == OUT ? D_OT : D_K128, B = K == XW ? D_K128 : K == BIG ? D_BLOB : D_N128;
            const uint32_t da = A.lo + a + wg * (K == OUT ? 64 : 512), db = B.lo + b;
            wgmma112<TA, TB, SB, INIT, A.hi, B.hi>(d, da, db);
            wgmma112<TA, TB, SB, false, A.hi, B.hi>(d, da + sa, db + sb);
            wgmma112<TA, TB, SB, false, A.hi, B.hi>(d, da + 2 * sa, db + 2 * sb);
            wgmma112<TA, TB, SB, false, A.hi, B.hi>(d, da + 3 * sa, db + 3 * sb);
        }
        asm volatile("wgmma.commit_group.sync.aligned;" ::: "memory");
        if (last) nb_arrive(2 - wg, 256);
        if (!TAIL) asm volatile("wgmma.wait_group.sync.aligned 1;" ::: "memory");
        if (!TAIL && stage > 0 && elect()) mbar_arrive(base + BAR_EMPTY + ((stage - 1) & 7) * 8);
        stage++;
        a += SLOT >> 4;
        if (a == (base + NA * SLOT) >> 4) a = base >> 4;
        b += SLOT >> 4;
        if (b == (base + BRING + NBS * SLOT) >> 4) b = (base + BRING) >> 4;
        if (more) wait();
    }
    template <Kind K, int NBS, bool INIT, int SB = 1, bool TAIL = false>
    __device__ __forceinline__ void run(float (&d)[56], bool first = true, bool last = true, bool more = true) {
        run<K, NBS, INIT, SB, TAIL>(d, d, first, last, more);
    }
};

__device__ __forceinline__ void pack_all(const float (&d)[56], uint32_t (&p)[28]) {
#pragma unroll
    for (int i = 0; i < 28; i++) p[i] = pack2(d[2 * i], d[2 * i + 1]);
}
template <int I0, int I1>
__device__ __forceinline__ void store_frags(uint8_t* dst, const uint32_t (&p)[28]) {
#pragma unroll
    for (int i = I0; i < I1; i++) stg1(dst + i * 128, p[i]);
}
template <int I0, int I1>
__device__ __forceinline__ void stage_frags(uint32_t lane_addr, const uint32_t (&p)[28]) {
#pragma unroll
    for (int i = I0; i < I1; i += 4) stsm4(lane_addr + i * 128, p[i], p[i + 1], p[i + 2], p[i + 3]);
}
template <class F>
__device__ __forceinline__ void store_out(F frag, int lane, uint32_t slab, const CUtensorMap* m, int c0, int c1) {
    const bool swap = lane & 16;
    const uint32_t addr = slab + (lane & 7) * 224 + ((lane >> 3) ^ ((lane >> 2) & 1)) * 16;
#pragma unroll
    for (int h = 0; h < 2; h++) {
#pragma unroll
        for (int c = 0; c < 14; c += 4) {
            const uint32_t t0 = frag(2 * c + h), t1 = frag(2 * c + 2 + h);
            if (c < 12) {
                const uint32_t t2 = frag(2 * c + 4 + h), t3 = frag(2 * c + 6 + h);
                stsm4(addr + h * 1792 + c * 16, swap ? t1 : t0, swap ? t0 : t1, swap ? t3 : t2, swap ? t2 : t3);
            } else {
                asm volatile("stmatrix.sync.aligned.m8n8.x2.shared.b16 [%0], {%1,%2};" ::"r"(addr + h * 1792 + c * 16), "r"(swap ? t1 : t0), "r"(swap ? t0 : t1) : "memory");
            }
        }
        fence_async_smem();
        __syncwarp();
        if (elect()) tma_st2(m, c0, c1 + 8 * h, slab + h * 1792);
    }
    if (elect()) {
        bulk_commit();
        bulk_wait_read();
    }
}
__host__ __device__ constexpr int tile_of(int t) { return 7 * (t >> 2) + 3 * ((t >> 1) & 1) + 2 * (t & 1); }

struct Role {
    bool H;
    int L, mt, ns, id;
};
template <bool BY_SM>
__device__ __forceinline__ Role decode_role() {
    uint32_t sm;
    if (BY_SM) asm volatile("mov.u32 %0, %%smid;" : "=r"(sm));
    else asm volatile("mov.u32 %0, %%ctaid.x;" : "=r"(sm));
    const int tpc = sm >> 1, q2 = ((tpc - 32) * 37) >> 8;
    const int gpc = tpc < 32 ? tpc & 7 : tpc < 60 ? tpc - 31 - 7 * q2 : 0;
    const int pos = tpc < 32 ? tpc >> 3 : tpc < 60 ? q2 + 4 : tpc - 56;
    Role r;
    r.H = sm >= 128;
    r.L = gpc & 1;
    r.mt = (gpc >> 1) * 4 + (pos >> 1);
    r.ns = (pos & 1) * 2 + (sm & 1);
    r.id = r.H ? sm : gpc * 16 + pos * 2 + (sm & 1);
    return r;
}

template <int I0, int I1>
__device__ __forceinline__ void first_fill(const Maps& maps, const Role& r) {
    if (r.L) {
#pragma unroll
        for (int i = I0; i < I1; i++) {
            const uint32_t bar = full_bar(i), dst = base + BRING + i * SLOT;
            if (i < 6) mbar_expect(bar, SLOT);
            if (i & 1) {
                mbar_arrive(bar);
            } else {
                mbar_expect(bar, SLOT);
                tma_ld2(base + (i >> 1) * SLOT, &maps.m[M_XA], (r.mt >> 3) * 448 + i * 32, (r.mt & 7) * 128, bar);
            }
            if (i < 6) {
                tma_ld4(dst, &maps.m[M_WQK], 0, i * 32, 0, r.ns, bar);
                tma_ld4(dst + 8192, &maps.m[M_WQK], 64, i * 32, 0, r.ns, bar);
            }
        }
    } else if (!r.H) {
#pragma unroll
        for (int i = I0; i < I1; i++) {
            const uint32_t bar = full_bar(i);
            mbar_expect(bar, SLOT);
            tma_ld3(base + i * SLOT, &maps.m[M_XB], i * 64, r.mt * 64, 0, bar);
            mbar_expect(bar, BLOB);
            tma_ld2(base + BRING + bslot_e(i) * SLOT, &maps.m[M_WR], i * 64, r.ns * 112, bar);
        }
    } else {
#pragma unroll 1
        for (int i = I0; i < I1; i++) {
            const uint32_t bar = full_bar(i), dst = base + BRING + i * SLOT;
            mbar_expect(bar, SLOT);
            mbar_expect(bar, SLOT);
            tma_ld4(base + i * SLOT, &maps.m[M_XH], i * 64, 120, 0, 0, bar);
            tma_ld3(dst, &maps.m[M_WV], 0, i * 64, 4 + r.ns, bar);
            tma_ld3(dst + 8192, &maps.m[M_WV], 64, i * 64, 4 + r.ns, bar);
        }
    }
}

template <bool BY_SM>
__global__ void __launch_bounds__(384, 1) fused_kernel(Scratch* sc, const __grid_constant__ Maps maps) {
    const int warp = __shfl_sync(0xffffffffu, threadIdx.x >> 5, 0);
    const Role role = decode_role<BY_SM>();
    if (warp == OPENER) {
        if (elect()) {
            asm volatile("prefetch.tensormap [%0];" ::"l"(&maps.m[M_XB]) : "memory");
            asm volatile("prefetch.tensormap [%0];" ::"l"(&maps.m[M_XA]) : "memory");
            asm volatile("prefetch.tensormap [%0];" ::"l"(&maps.m[M_WR]) : "memory");
            asm volatile("prefetch.tensormap [%0];" ::"l"(&maps.m[M_WQK]) : "memory");
#pragma unroll
            for (int i = 0; i < 8; i++) mbar_init(base + BAR_FULL + i * 8, 2);
            asm volatile("fence.mbarrier_init.release.cluster;" ::: "memory");
            first_fill<0, LEAD>(maps, role);
        }
    }
    int lane = threadIdx.x & 31;
    asm volatile("" : "+r"(lane));
    const bool roleH = role.H;
    const int roleL = role.L, mt = role.mt, ns = role.ns, bid = role.id;
    const int par = mt >> 3, blk = mt & 7, col = ns * 112;
    if (warp == 9) {
        if (elect()) {
#pragma unroll
            for (int i = 0; i < 8; i++) mbar_init(base + BAR_EMPTY + i * 8, 8);
            asm volatile("fence.mbarrier_init.release.cluster;" ::: "memory");
        }
    } else if (warp == 10) {
        if (elect()) {
#pragma unroll
            for (int i = 0; i < 5; i++) mbar_init(base + BAR_RDY + i * 8, i < 2 ? 4 : 8);
#pragma unroll
            for (int i = 0; i < 2; i++) mbar_init(base + BAR_HALO + i * 8, 8);
            asm volatile("fence.mbarrier_init.release.cluster;" ::: "memory");
        }
    } else if (warp == 11) {
        if (elect()) {
#pragma unroll
            for (int i = 0; i < 3; i++) mbar_init(base + BAR_DEP + i * 8, 1);
            asm volatile("fence.mbarrier_init.release.cluster;" ::: "memory");
        }
    }
    __syncthreads();

    if (__builtin_expect(warp >= 8, 1)) {
        asm volatile("setmaxnreg.dec.sync.aligned.u32 56;");
#define PROF_FEED_A
#define PROF_FEED_B
        if (__builtin_expect(warp == 8, 1)) {
            if (elect()) {
                PROF(129);
                first_fill<LEAD, 7>(maps, role);
                PROF(134);
                Feed<0> f;
                const int row = mt * 128;
                auto c_run = [&](const CUtensorMap* m, int off, int n0, int n1) {
#pragma unroll 1
                    for (int n = n0; n < n1; n++) {
                        const uint32_t bar = f.acquire<NA>();
                        mbar_expect(bar, SLOT);
                        tma_ld2(f.dst, m, (off + skip_own(n, mt)) * 64, row, bar);
                        PROF_FEED_A;
                        f.next<NA>();
                    }
                };
                if (roleH) {
                } else if (!roleL) {
                    f.seek(14, 0);
                    mbar_wait(base + BAR_RDY, 0);
#pragma unroll 1
                    for (int i = 0; i < 4; i++) {
                        const uint32_t bar = f.acquire<NA>();
                        mbar_expect(bar, SLOT);
                        tma_ld2(f.dst, &maps.m[M_CR + (i >> 1)], ((i & 1) * 16 + mt) * 64, row, bar);
                        mbar_arrive(bar);
                        PROF_FEED_A;
                        f.next<NA>();
                    }
                    c_run(&maps.m[M_CR], 0, 0, 15);
                    c_run(&maps.m[M_CI], 0, 0, NBE);
                    wait_dep(2);
#pragma unroll 1
                    for (int i = 0; i < 7; i++) {
                        const uint32_t bar = f.acquire<NA>();
                        mbar_expect(bar, SLOT);
                        bulk_ld(f.dst, sc->o + (size_t)(mt * 7 + i) * SLOT, SLOT, bar);
                        PROF_FEED_A;
                        f.next<NA>();
                    }
                } else {
#pragma unroll 1
                    for (int i = 4; i < 7; i++) {
                        wait_released(2 * i - 8);
                        mbar_expect(full_bar(2 * i), SLOT);
                        tma_ld2(base + i * SLOT, &maps.m[M_XA], par * 448 + i * 64, blk * 128, full_bar(2 * i));
                    }
                    wait_released(HALO_K_AT);
                    mbar_arrive(base + BAR_DEP + 16);
                    f.seek(21, 0);
                    c_run(&maps.m[M_CR], 16, 0, 15);
                    c_run(&maps.m[M_CI], 16, 0, 15);
                    c_run(&maps.m[M_CI], 0, NBE, 15);
                }
            }
        } else if (warp == 11) {
            if (elect()) {
                Feed<BRING> f;
                auto blob_run = [&](auto nbs, int quarter, int n0, int n1) {
                    constexpr int N = decltype(nbs)::value;
                    const uint8_t* src = sc->ab + (size_t)(quarter * 64 + ns) * BLOB;
#pragma unroll 1
                    for (int n = n0; n < n1; n++) {
                        const uint32_t bar = f.template acquire<N>();
                        mbar_expect(bar, BLOB);
                        bulk_ld(f.dst, src + skip_own(n, mt) * (4 * BLOB), BLOB, bar);
                        PROF_FEED_B;
                        f.template next<N>();
                    }
                };
                auto w_run = [&](auto nbs, const CUtensorMap* m, int slice, bool no_a) {
                    constexpr int N = decltype(nbs)::value;
#pragma unroll 1
                    for (int i = 0; i < 7; i++) {
                        const uint32_t bar = f.template acquire<N>();
                        mbar_expect(bar, SLOT);
                        tma_ld3(f.dst, m, 0, i * 64, slice, bar);
                        tma_ld3(f.dst + 8192, m, 64, i * 64, slice, bar);
                        if (no_a) mbar_arrive(bar);
                        PROF_FEED_B;
                        f.template next<N>();
                    }
                };
                if (roleH) {
                    f.seek(7, 0);
                    w_run(Int<7>(), &maps.m[M_WV], 8 + ns, true);
                } else if (!roleL) {
                    f.seek(7, bslot_e(7));
#pragma unroll 1
                    for (int i = 0; i < 7; i++) {
                        const uint32_t bar = f.acquire<5>();
                        mbar_expect(bar, BLOB);
                        tma_ld2(f.dst, &maps.m[M_WI], i * 64, col, bar);
                        mbar_arrive(bar);
                        PROF_FEED_B;
                        f.next<5>();
                    }
                    f.seek(18, bslot_e(18));
                    wait_dep(0);
                    blob_run(Int<7>(), 0, 0, 15);
                    wait_dep(1);
                    blob_run(Int<7>(), 2, 0, NBE);
                    w_run(Int<7>(), &maps.m[M_WO], ns, false);
                } else {
                    f.seek(6, 0);
#pragma unroll 1
                    for (int i = 6; i < 14; i++) {
                        const uint32_t bar = f.acquire<6>();
                        mbar_expect(bar, SLOT);
                        tma_ld4(f.dst, &maps.m[M_WQK], 0, i * 32, 0, ns, bar);
                        tma_ld4(f.dst + 8192, &maps.m[M_WQK], 64, i * 32, 0, ns, bar);
                        if (i & 1) mbar_arrive(bar);
                        PROF_FEED_B;
                        f.next<6>();
                    }
                    w_run(Int<6>(), &maps.m[M_WV], 8 + ns, true);
                    wait_dep(0);
                    blob_run(Int<6>(), 1, 0, 15);
                    wait_dep(1);
                    blob_run(Int<6>(), 3, 0, 15);
                    blob_run(Int<6>(), 2, NBE, 15);
                }
            }
        } else if (roleH) {
        } else if (warp == 10) {
            if (elect()) {
                unsigned* epoch_ptr = &sc->epoch[(bid * 4 + 2) * 8];
                const unsigned ep = *epoch_ptr + 1;
                sts1(base + TAG, ep);
                asm volatile("prefetch.tensormap [%0];" ::"l"(&maps.m[M_OUTA + roleL]) : "memory");
                await(sc, CNT_A + roleL * 4 + ns, ep * 16);
                mbar_arrive(base + BAR_DEP);
                PROF(150);
                await(sc, CNT_B + ns, ep * 16);
                mbar_arrive(base + BAR_DEP + 8);
                PROF(151);
                if (!roleL) {
                    await(sc, CNT_O + mt, ep * 4);
                    mbar_arrive(base + BAR_DEP + 16);
                }
                PROF(152);
                *epoch_ptr = ep;
            }
        } else if (!roleL) {
            if (elect()) {
                mbar_wait(base + BAR_RDY, 0);
                PROF(130);
                signal(sc, CNT_A + ns);
                PROF(131);
                mbar_wait(base + BAR_RDY + 8, 0);
                signal(sc, CNT_A + 4 + ns);
                PROF(135);
                mbar_wait(base + BAR_RDY + 32, 0);
                PROF(132);
                signal(sc, CNT_B + ns);
                PROF(133);
            }
        } else {
            unsigned* epoch_ptr = &sc->epoch[(bid * 4 + 1) * 8];
            const unsigned tag = *epoch_ptr + 1;
#pragma unroll 1
            for (int kv = 0; kv < 2; kv++) {
                uint32_t v[16];
#pragma unroll
                for (int i = 0; i < 16; i++) v[i] = 0;
                if (kv) wait_released(HALO_V_AT);
                else mbar_wait(base + BAR_DEP + 16, 0);
                if (blk > 0) {
                    const uint8_t* src = sc->halo + (size_t)(((mt - 1) * 4 + ns) * 2 + kv) * 2048 + lane * 16;
#pragma unroll 1
                    for (int n = 0; n < SPIN_LIMIT; n++) {
                        uint32_t stale = 0;
#pragma unroll
                        for (int i = 0; i < 4; i++) ld_tagged(src + i * 512, v[4 * i], v[4 * i + 1], v[4 * i + 2], v[4 * i + 3]);
#pragma unroll
                        for (int i = 0; i < 16; i += 2) stale |= v[i] ^ tag;
                        if (__all_sync(0xffffffffu, !(stale & 1))) break;
                    }
#pragma unroll
                    for (int c = 0; c < 14; c += 2) v[c] = (v[c] & ~1u) | ((v[15] >> c) & 1);
                }
#pragma unroll
                for (int i = 0; i < 14; i++) sts1(base + HALO + kv * (8 * HSLOT) + i * 128 + lane * 4, v[i]);
                warp_arrive(base + BAR_HALO + kv * 8);
                if (lane == 0) PROF(142 + kv);
            }
            if (elect()) {
                mbar_wait(base + BAR_RDY + 16, 0);
                PROF(130);
                signal(sc, CNT_O + mt);
                PROF(131);
                *epoch_ptr = tag;
            }
        }
    } else {
        asm volatile("setmaxnreg.inc.sync.aligned.u32 224;");
        Ring r;
        r.wg = warp >> 2;
        r.zero = blockIdx.y;
        const int wg = warp >> 2;
        if (wg) nb_arrive(1, 256);
        r.stage = 0;
        r.wait();
        uint8_t* part = sc->part + (size_t)(ns * 16 + mt) * (2 * BLOB) + warp * 512 + lane * 16;
        uint32_t p[28];

        if (roleH) {
            unsigned* epoch_ptr = &sc->epoch[bid * 4 * 8];
            const unsigned tag = *epoch_ptr + 1;
            uint8_t* hout = sc->halo + (size_t)((warp * 8 + ns) * 2) * 2048 + lane * 16;
            auto send = [&](int kv) {
#pragma unroll
                for (int h = 0; h < 2; h++) {
                    uint32_t v[16];
                    v[14] = v[15] = 0;
#pragma unroll
                    for (int c = 0; c < 14; c++) v[c] = p[2 * c + h];
#pragma unroll
                    for (int c = 0; c < 14; c += 2) v[15] |= (v[c] & 1) << c;
#pragma unroll
                    for (int i = 0; i < 4; i++) st_part(hout + (h * 8 + kv) * 2048 + i * 512, v + 4 * i, tag & 1);
                }
            };
            float x0[56], x1[56];
            r.seek(0, 0);
            r.run<XWN, 7, true>(x0);
#pragma unroll 1
            for (int i = 1; i < 7; i++) r.run<XWN, 7, false>(x0);
            r.run<XWN, 7, true>(x1);
            acc_fence(x0);
            pack_all(x0, p);
            send(0);
#pragma unroll 1
            for (int i = 1; i < 7; i++) r.run<XWN, 7, false>(x1, true, true, i < 6);
            asm volatile("wgmma.wait_group.sync.aligned 0;" ::: "memory");
            acc_fence(x1);
            pack_all(x1, p);
#pragma unroll
            for (int i = 0; i < 28; i++) p[i] = movm(p[i]);
            send(1);
            if (threadIdx.x == 0) *epoch_ptr = tag;
        } else if (!roleL) {
            uint8_t* blob = sc->ab + (size_t)((wg * 16 + mt) * 4 + ns) * BLOB + (warp & 3) * WSLOT + lane * 4;
            const uint32_t own = base + BRING + wg * SLOT + (warp & 3) * WSLOT + lane * 16;
            float x0[56], x1[56];
            r.seek(0, bslot_e(0));
            r.run<XW, 7, true>(x0);
            r.run<XW, 7, false>(x0);
            r.seek(2, bslot_e(2));
#pragma unroll 1
            for (int i = 2; i < 7; i++) r.run<XW, 5, false>(x0);

            r.seek(7, bslot_e(7));
            r.run<XW, 5, true, -1>(x1);
            acc_fence(x0);
            pack_all(x0, p);
#pragma unroll
            for (int i = 0; i < 2; i++) {
                if (wg == i) store_frags<0, 14>(blob, p);
                else stage_frags<0, 4>(own + 5 * SLOT, p);
                r.run<XW, 5, false, -1>(x1);
                if (wg == i) {
                    store_frags<14, 28>(blob, p);
                    warp_arrive(base + BAR_RDY + i * 8);
                } else {
                    stage_frags<4, 8>(own + 5 * SLOT, p);
                }
                r.run<XW, 5, false, -1>(x1);
            }
            stage_frags<8, 20>(own + 5 * SLOT, p);
            r.run<XW, 5, false, -1>(x1);
            stage_frags<20, 28>(own + 5 * SLOT, p);
            warp_arrive(base + BAR_RDY + 16);
            r.run<XW, 5, false, -1>(x1);

            mbar_wait(base + BAR_RDY + 16, 0);
            fence_async_smem();
            r.seek(14, bslot_e(14));
            r.run<BIG, 7, true>(x0);
            acc_fence(x1);
            pack_all(x1, p);
            wait_released(10);
            stage_frags<0, 28>(own, p);
            warp_arrive(base + BAR_RDY + 24);
            r.run<BIG, 7, false>(x0);
            mbar_wait(base + BAR_RDY + 24, 0);
            fence_async_smem();
            blob += (size_t)128 * BLOB;
#pragma unroll
            for (int i = 0; i < 28; i++) {
                if (i % B_SLICE == 0) r.run<BIG, 7, false>(x0);
                stg1(blob + i * 128, p[i]);
            }
            warp_arrive(base + BAR_RDY + 32);
#pragma unroll 1
            for (int i = 17 + 27 / B_SLICE; i < POUT; i++) r.run<BIG, 7, false>(x0);

            const uint32_t tag = lds1(base + TAG);
            r.seek(POUT, bslot_e(POUT));
            r.run<OUT, 7, true>(x1);
            acc_fence(x0);
            pack_all(x0, p);
#pragma unroll
            for (int k = 0; k < 3; k++) {
                if (k < 2 && wg == k) {
#pragma unroll
                    for (int i = 0; i < 4; i++) st_part(part + i * 4096, p + 4 * i, tag & 1);
                }
                if (k > 0 && wg == k - 1) {
#pragma unroll
                    for (int i = 4; i < 7; i++) st_part(part + i * 4096, p + 4 * i, tag & 1);
                }
                if (k < 2) r.run<OUT, 7, false>(x1);
            }
#pragma unroll
            for (int i = 3; i < 7; i++) r.run<OUT, 7, false, 1, true>(x1, i <= 7 - TURN, i < 7 - TURN || i == 6, i < 6);

            wait_released(ELAST - 6);
            asm volatile("wgmma.wait_group.sync.aligned 0;" ::: "memory");
            acc_fence(x1);
            const uint32_t slab = base + (wg ? BRING + bslot_e(ELAST - 6) * SLOT : ((ELAST - 6) % NA) * SLOT) + (warp & 3) * WSLOT;
            store_out([&](int i) { return pack2(x1[2 * i], x1[2 * i + 1]); }, lane, slab, &maps.m[M_OUTA], par * 896 + col, blk * 128 + warp * 16);
        } else {
            const int g = lane >> 2, tig = lane & 3;
            const uint32_t hin = base + HALO + warp * HSLOT + lane * 4;
            auto publish = [&](const uint32_t (&h)[14], int kv) {
                if (warp < 7) {
#pragma unroll
                    for (int c = 0; c < 14; c++) sts1(hin + HSLOT + c * 128, h[c]);
                    warp_arrive(base + BAR_HALO + kv * 8);
                }
            };
            float y0[56], y1[56], y2[56];
            r.seek(0, 0);
            r.run<QK, 6, true>(y0, y1);
#pragma unroll 1
            for (int i = 1; i < 14; i++) r.run<QK, 6, false>(y0, y1);

            uint32_t m1[8][4], m0[8][4], lo[14], hi[14];
            r.seek(14, bslot_l(14));
            r.run<XWN, 6, true>(y2);
            acc_fence(y0);
            acc_fence(y1);
#pragma unroll
            for (int c = 0; c < 14; c++) {
                hi[c] = pack2(y1[4 * c + 2], y1[4 * c + 3]);
                lo[c] = pack2(y1[4 * c], y1[4 * c + 1]);
            }
            publish(hi, 0);
            r.run<XWN, 6, false>(y2);
            uint32_t q[2][8][2];
#pragma unroll
            for (int b = 0; b < 2; b++) {
                uint32_t v[14];
#pragma unroll
                for (int c = 0; c < 14; c++) v[c] = pack2(y0[4 * c + 2 * b], y0[4 * c + 2 * b + 1]);
#pragma unroll
                for (int t = 0; t < 8; t++) {
                    const int c = tile_of(t);
                    q[b][t][0] = (t & 3) == 2 ? (tig >= 2 ? v[c] : 0u) : v[c];
                    q[b][t][1] = (t & 3) == 1 ? (tig < 2 ? v[c + 1] : 0u) : v[c + 1];
                }
            }
            PIN;
            r.run<XWN, 6, false>(y2);
            mbar_wait(base + BAR_HALO, 0);
#pragma unroll
            for (int t = 0; t < 8; t++) {
                const int c = tile_of(t);
                const bool shared = (t & 3) == 2;
                m0[t][1] = lds1(hin + c * 128 + (shared ? r.zero : 0u));
                m0[t][3] = lds1(hin + c * 128 + 128);
                m1[t][0] = shared ? dup(lo[c], r.zero) : lo[c];
                m1[t][1] = shared ? dup(hi[c], r.zero) : hi[c];
                m1[t][2] = lo[c + 1];
                m1[t][3] = hi[c + 1];
                m0[t][0] = dup(m1[t][0], r.zero);
                m0[t][2] = dup(lo[c + 1], 2 * r.zero);
            }
            r.pin();
            r.take_turn();
            float s[8][4];
#pragma unroll
            for (int step = 0; step < 2; step++) {
#pragma unroll
                for (int i = 0; i < 8; i++) {
                    const int b = 1 - (i >> 2), h = i & 3, t = 2 * h + step;
                    float (&d)[4] = s[2 * h + b];
                    if (step == 0) d[0] = d[1] = d[2] = d[3] = 0.f;
                    mma16816(d, b ? m1[t] : m0[t], q[b][t][0], q[b][t][1]);
                }
            }
            r.pin();
            r.run<XWN, 6, false>(y2, false);

            uint32_t pr[8], mx[4], mx1[4];
            {
                const bool cur0 = g <= 2 * tig, cur1 = g <= 2 * tig + 1;
#pragma unroll
                for (int i = 0; i < 8; i++) {
                    const int c = (i & 1) ? 2 : 0;
                    pr[i] = movm(pack2(cur0 ? s[i][c] : s[i][2 - c], cur1 ? s[i][c + 1] : s[i][3 - c]));
                }
            }
            PIN;
            r.run<XWN, 6, false>(y2);
            const uint32_t curmask = (2 * tig <= g ? 0x0000FFFFu : 0u) | (2 * tig + 1 <= g ? 0xFFFF0000u : 0u);
            {
                const uint32_t keep = (blk == 0 && warp == 0) ? curmask : 0xFFFFFFFFu;
#pragma unroll
                for (int i = 0; i < 4; i++) {
                    pr[2 * i] = (pr[2 * i] & keep) | (0xCF9ECF9Eu & ~keep);
                    mx[i] = max2(__byte_perm(pr[2 * i], pr[2 * i + 1], 0x5410), __byte_perm(pr[2 * i], pr[2 * i + 1], 0x7632));
                }
#pragma unroll
                for (int i = 0; i < 4; i++) mx[i] = max2(mx[i], __shfl_xor_sync(0xffffffffu, mx[i], 1));
#pragma unroll
                for (int i = 0; i < 4; i++) mx1[i] = __shfl_xor_sync(0xffffffffu, mx[i], 2);
            }
            PIN;
            r.run<XWN, 6, false>(y2);
            constexpr float SCL = 0.18898223650461362f * 1.4426950408889634f;
            float e0[8], e1[8], sm[8], sm1[8];
#pragma unroll
            for (int i = 0; i < 8; i++) {
                const uint32_t m2 = max2(mx[i >> 1], mx1[i >> 1]);
                sm[i] = ((i & 1) ? bf_hi(m2) : bf_lo(m2)) * -SCL;
                e0[i] = ex2(fmaf(bf_lo(pr[i]), SCL, sm[i]));
            }
            PIN;
            r.run<XWN, 6, false>(y2);
#pragma unroll
            for (int i = 0; i < 8; i++) e1[i] = ex2(fmaf(bf_hi(pr[i]), SCL, sm[i]));

            PIN;
            r.seek(21, bslot_l(21));
            r.run<BIG, 6, true>(y0);
            acc_fence(y2);
#pragma unroll
            for (int c = 0; c < 14; c++) hi[c] = movm(pack2(y2[4 * c + 2], y2[4 * c + 3]));
            PIN;
            r.run<BIG, 6, false>(y0);
#pragma unroll
            for (int i = 0; i < 8; i++) {
                sm[i] = e0[i] + e1[i];
                sm1[i] = __shfl_xor_sync(0xffffffffu, sm[i], 1);
            }
            publish(hi, 1);
            r.run<BIG, 6, false>(y0);
#pragma unroll
            for (int c = 0; c < 14; c++) lo[c] = movm(pack2(y2[4 * c], y2[4 * c + 1]));
            PIN;
            r.run<BIG, 6, false>(y0);
#pragma unroll
            for (int i = 0; i < 8; i++) {
                sm[i] += sm1[i];
                sm1[i] = __shfl_xor_sync(0xffffffffu, sm[i], 2);
            }
#pragma unroll
            for (int t = 0; t < 8; t++) {
                const int c = tile_of(t);
                const bool shared = (t & 3) == 2;
                m1[t][0] = shared ? dup(lo[c], r.zero) : lo[c];
                m1[t][1] = lo[c + 1];
                m1[t][2] = shared ? dup(hi[c], r.zero) : hi[c];
                m1[t][3] = hi[c + 1];
                m0[t][0] = dup(m1[t][0], r.zero);
                m0[t][1] = dup(lo[c + 1], 2 * r.zero);
            }
            PIN;
            r.run<BIG, 6, false>(y0);
#pragma unroll
            for (int i = 0; i < 8; i++) {
                const float inv = rcp(sm[i] + sm1[i]);
                pr[i] = pack2(e0[i] * inv, e1[i] * inv);
            }
            PIN;
            r.run<BIG, 6, false>(y0);
            mbar_wait(base + BAR_HALO + 8, 0);
            const uint32_t vin = warp ? hin : hin + 8 * HSLOT;
            uint32_t pb[8][2];
#pragma unroll
            for (int t = 0; t < 8; t++) {
                m0[t][2] = lds1(vin + tile_of(t) * 128 + ((t & 3) == 2 ? r.zero : 0u));
                m0[t][3] = lds1(vin + tile_of(t) * 128 + 128);
                pb[t][t & 1] = band(pr[t], curmask);
                pb[t][1 - (t & 1)] = band(pr[t], ~curmask);
            }
            r.pin();
            r.take_turn();
            float o[2][8][4];
#pragma unroll
            for (int i = 0; i < 16; i++) {
                const int b = 1 - (i >> 3), t = i & 7;
                float (&d)[4] = o[b][t];
                d[0] = d[1] = d[2] = d[3] = 0.f;
                mma16816(d, b ? m1[t] : m0[t], pb[(t & 6) + b][0], pb[(t & 6) + b][1]);
            }
            r.pin();
            r.run<BIG, 6, false>(y0, false);
            uint8_t* odst = sc->o + (size_t)mt * 7 * SLOT + ns * (14 * 2048) + warp * 256 + lane * 4;
#pragma unroll
            for (int hp = 0; hp < 2; hp++) {
#pragma unroll
                for (int b = 0; b < 2; b++) {
                    const float (&u)[8][4] = o[b];
                    const int t = 4 * hp;
                    uint32_t* w = p + 14 * hp + b;
                    w[0] = pack2(u[t][0], u[t][1]);
                    w[2] = pack2(u[t][2], u[t][3]);
                    w[4] = pack2(u[t + 1][0], u[t + 1][1]);
                    w[6] = pack2(g < 4 ? u[t + 1][2] : u[t + 2][0], g < 4 ? u[t + 1][3] : u[t + 2][1]);
                    w[8] = pack2(u[t + 2][2], u[t + 2][3]);
                    w[10] = pack2(u[t + 3][0], u[t + 3][1]);
                    w[12] = pack2(u[t + 3][2], u[t + 3][3]);
                }
            }
#pragma unroll
            for (int i = 0; i < 28; i++) {
                if (i && i % O_SLICE == 0) r.run<BIG, 6, false>(y0);
                stg1(odst + (i >> 1) * 2048 + (i & 1) * 128, p[i]);
            }
            warp_arrive(base + BAR_RDY + 16);

#pragma unroll 1
            for (int i = 28 + 27 / O_SLICE; i <= LLAST + 1 - TURN; i++) r.run<BIG, 6, false>(y0, true, i <= LLAST - TURN);
            const uint32_t tag = lds1(base + TAG);
#pragma unroll
            for (int i = 0; i < 7; i++) ld_tagged(part + i * 4096, p[4 * i], p[4 * i + 1], p[4 * i + 2], p[4 * i + 3]);
            r.seek(LLAST + 2 - TURN, bslot_l(LLAST + 2 - TURN));
#pragma unroll
            for (int i = 1; i < TURN; i++) r.run<BIG, 6, false, 1, true>(y0, false, i == TURN - 1, i < TURN - 1);
#pragma unroll 1
            for (int n = 0; n < SPIN_LIMIT; n++) {
                uint32_t stale = 0;
#pragma unroll
                for (int i = 0; i < 28; i += 2) stale |= p[i] ^ tag;
                if (__all_sync(0xffffffffu, !(stale & 1))) break;
#pragma unroll
                for (int i = 0; i < 7; i++) ld_tagged(part + i * 4096, p[4 * i], p[4 * i + 1], p[4 * i + 2], p[4 * i + 3]);
            }
            wait_released(LLAST - 6);
            asm volatile("wgmma.wait_group.sync.aligned 0;" ::: "memory");
            acc_fence(y0);
            const uint32_t slab = base + (wg ? HALO : ((LLAST - 6) % NA) * SLOT) + (warp & 3) * WSLOT;
            store_out([&](int i) { return add2(pack2(y0[2 * i], y0[2 * i + 1]), p[i]); }, lane, slab, &maps.m[M_OUTB], 448 + col, mt * 128 + warp * 16);
        }
    }
}

typedef CUresult (*EncodeFn)(CUtensorMap*, CUtensorMapDataType, cuuint32_t, void*, const cuuint64_t*, const cuuint64_t*,
                             const cuuint32_t*, const cuuint32_t*, CUtensorMapInterleave, CUtensorMapSwizzle,
                             CUtensorMapL2promotion, CUtensorMapFloatOOBfill);

struct Dim { uint64_t size, stride; uint32_t box; };
void encode(EncodeFn fn, CUtensorMap* m, const void* ptr, CUtensorMapSwizzle sw, Dim d0, Dim d1, Dim d2 = {0, 0, 0}, Dim d3 = {0, 0, 0}) {
    const cuuint64_t dims[4] = {d0.size, d1.size, d2.size, d3.size};
    const cuuint64_t strides[3] = {d1.stride, d2.stride, d3.stride};
    const cuuint32_t box[4] = {d0.box, d1.box, d2.box, d3.box};
    const cuuint32_t es[4] = {1, 1, 1, 1};
    fn(m, CU_TENSOR_MAP_DATA_TYPE_BFLOAT16, d3.size ? 4 : d2.size ? 3 : 2, const_cast<void*>(ptr), dims, strides, box, es,
       CU_TENSOR_MAP_INTERLEAVE_NONE, sw, CU_TENSOR_MAP_L2_PROMOTION_L2_128B, CU_TENSOR_MAP_FLOAT_OOB_FILL_NONE);
}

}

extern "C" void kernel_launch(void* const* d_in, const int* in_sizes, int n_in, void* d_out, int out_size) {
    (void)in_sizes; (void)n_in; (void)out_size;
    void* fnp = nullptr;
    cudaDriverEntryPointQueryResult st;
    cudaGetDriverEntryPoint("cuTensorMapEncodeTiled", &fnp, cudaEnableDefault, &st);
    EncodeFn fn = (EncodeFn)fnp;
    void* scratch = nullptr;
    cudaGetSymbolAddress(&scratch, g_scratch);
    int dev = 0, sms = 0;
    cudaGetDevice(&dev);
    cudaDeviceGetAttribute(&sms, cudaDevAttrMultiProcessorCount, dev);
    auto kernel = sms == 132 ? fused_kernel<true> : fused_kernel<false>;
    cudaFuncSetAttribute(kernel, cudaFuncAttributeMaxDynamicSharedMemorySize, SMEM_BYTES);

    const CUtensorMapSwizzle S128 = CU_TENSOR_MAP_SWIZZLE_128B, S0 = CU_TENSOR_MAP_SWIZZLE_NONE;
    Maps maps;
    encode(fn, &maps.m[M_XA], d_in[0], S128, {896, 2, 64}, {1024, 1792, 128});
    encode(fn, &maps.m[M_WQK], d_in[1], S128, {112, 2, 64}, {448, 2688, 32}, {3, 896, 2}, {4, 224, 1});
    encode(fn, &maps.m[M_WV], d_in[1], S128, {112, 2, 64}, {448, 2688, 64}, {12, 224, 1});
    encode(fn, &maps.m[M_XH], d_in[0], S128, {448, 2, 64}, {128, 1792, 8}, {8, 128 * 1792, 8}, {2, 896, 2});
    encode(fn, &maps.m[M_WO], d_in[2], S128, {112, 2, 64}, {448, 896, 64}, {4, 224, 1});
    encode(fn, &maps.m[M_XB], d_in[3], S128, {448, 2, 64}, {1024, 896, 64}, {2, 896 * 1024, 2});
    encode(fn, &maps.m[M_CR], d_in[4], S128, {2048, 2, 64}, {2048, 4096, 128});
    encode(fn, &maps.m[M_CI], d_in[5], S128, {2048, 2, 64}, {2048, 4096, 128});
    encode(fn, &maps.m[M_WR], d_in[6], S128, {448, 2, 64}, {448, 896, 112});
    encode(fn, &maps.m[M_WI], d_in[7], S128, {448, 2, 64}, {448, 896, 112});
    encode(fn, &maps.m[M_OUTA], d_out, S0, {1792, 2, 112}, {1024, 3584, 8});
    encode(fn, &maps.m[M_OUTB], d_out, S0, {896, 2, 112}, {2048, 1792, 8});

    kernel<<<132, 384, SMEM_BYTES>>>((Scratch*)scratch, maps);
}
```

```cpp
#include <cuda.h>
#include <cuda_bf16.h>
#include <cuda_runtime.h>
#include <stdint.h>

namespace {

constexpr uint32_t SLOT = 16384;
constexpr int NA = 7;
constexpr uint32_t BRING = NA * SLOT;
constexpr uint32_t HALO = BRING + 6 * SLOT;
constexpr uint32_t HSLOT = 1792;
constexpr uint32_t WSLOT = 3584;
constexpr uint32_t BLOB = 14336;
constexpr uint32_t BARS = 14 * SLOT;
constexpr uint32_t BAR_FULL = BARS;
constexpr uint32_t BAR_EMPTY = BARS + 64;
constexpr uint32_t BAR_RDY = BARS + 128;
constexpr uint32_t BAR_DEP = BARS + 168;
constexpr uint32_t BAR_HALO = BARS + 192;
constexpr uint32_t TAG = BARS + 208;
constexpr uint32_t HSPARE = BARS + 256 + 1024;
constexpr uint32_t SMEM_BYTES = HSPARE + HSLOT;
constexpr uint32_t base = 1024;
constexpr int SPIN_LIMIT = 1 << 16;

#define E_EXTRA 0
#define HALO_K_AT 10
#define HALO_V_AT 19
#define O_SLICE 5
#define B_SLICE 4
#define LEAD 3
#define TURN 3
#define PIN r.pin()
#define OPENER 8
#define MAPPING 2
constexpr int NBE = 13 + E_EXTRA;
constexpr int POUT = 33 + NBE;
constexpr int ELAST = POUT + 6;
constexpr int LLAST = 52 - E_EXTRA;

enum { M_XA, M_XH, M_WQK, M_WV, M_WO, M_XB, M_WR, M_WI, M_CR, M_CI, M_OUTA, M_OUTB, M_COUNT };
struct __align__(64) Maps { CUtensorMap m[M_COUNT]; };

constexpr int CNT_A = 0;
constexpr int CNT_B = 8;
constexpr int CNT_O = 16;
constexpr int CNT_COUNT = 32;

struct Scratch {
    uint8_t ab[64 * 4 * BLOB];
    uint8_t o[16 * 7 * SLOT];
    uint8_t part[64 * 2 * BLOB];
    uint8_t halo[64 * 2 * 2048];
    unsigned cnt[CNT_COUNT * 32];
    unsigned epoch[132 * 4 * 8];
};
__device__ __align__(1024) Scratch g_scratch;

__device__ __forceinline__ unsigned clk32() { unsigned c; asm volatile("mov.u32 %0, %%clock;" : "=r"(c)); return c; }

#define PROF(idx)

__device__ __forceinline__ void mbar_init(uint32_t bar, uint32_t cnt) {
    asm volatile("mbarrier.init.shared::cta.b64 [%0], %1;" ::"r"(bar), "r"(cnt) : "memory");
}
__device__ __forceinline__ void mbar_expect(uint32_t bar, uint32_t bytes) {
    asm volatile("mbarrier.arrive.expect_tx.shared::cta.b64 _, [%0], %1;" ::"r"(bar), "r"(bytes) : "memory");
}
__device__ __forceinline__ void mbar_arrive(uint32_t bar) {
    asm volatile("mbarrier.arrive.shared::cta.b64 _, [%0];" ::"r"(bar) : "memory");
}
__device__ __forceinline__ bool mbar_try(uint32_t bar, uint32_t parity) {
    uint32_t ok;
    asm volatile("{\n.reg .pred p;\nmbarrier.try_wait.parity.shared::cta.b64 p, [%1], %2;\nselp.u32 %0, 1, 0, p;\n}\n"
                 : "=r"(ok) : "r"(bar), "r"(parity) : "memory");
    return ok;
}
__device__ __forceinline__ void mbar_wait(uint32_t bar, uint32_t parity) {
#pragma unroll 1
    for (int n = 0; n < SPIN_LIMIT; n++)
        if (mbar_try(bar, parity)) break;
}
__device__ __forceinline__ bool elect() {
    uint32_t p;
    asm volatile("{\n.reg .pred p;\nelect.sync _|p, 0xffffffff;\nselp.u32 %0, 1, 0, p;\n}\n" : "=r"(p));
    return p;
}
__device__ __forceinline__ void nb_sync(int id, int n) { asm volatile("bar.sync %0, %1;" ::"r"(id), "r"(n) : "memory"); }
__device__ __forceinline__ void nb_arrive(int id, int n) { asm volatile("bar.arrive %0, %1;" ::"r"(id), "r"(n) : "memory"); }
__device__ __forceinline__ void warp_arrive(uint32_t bar) {
    __syncwarp();
    if (elect()) mbar_arrive(bar);
}
__device__ __forceinline__ uint32_t band(uint32_t x, uint32_t m) {
    uint32_t r;
    asm volatile("and.b32 %0, %1, %2;" : "=r"(r) : "r"(x), "r"(m));
    return r;
}
__device__ __forceinline__ uint32_t dup(uint32_t x, uint32_t zero) {
    uint32_t r;
    asm volatile("xor.b32 %0, %1, %2;" : "=r"(r) : "r"(x), "r"(zero));
    return r;
}

__device__ __forceinline__ void tma_ld2(uint32_t dst, const CUtensorMap* m, int c0, int c1, uint32_t bar) {
    asm volatile("cp.async.bulk.tensor.2d.shared::cluster.global.mbarrier::complete_tx::bytes [%0], [%1, {%3, %4}], [%2];"
                 ::"r"(dst), "l"(m), "r"(bar), "r"(c0), "r"(c1) : "memory");
}
__device__ __forceinline__ void tma_ld3(uint32_t dst, const CUtensorMap* m, int c0, int c1, int c2, uint32_t bar) {
    asm volatile("cp.async.bulk.tensor.3d.shared::cluster.global.mbarrier::complete_tx::bytes [%0], [%1, {%3, %4, %5}], [%2];"
                 ::"r"(dst), "l"(m), "r"(bar), "r"(c0), "r"(c1), "r"(c2) : "memory");
}
__device__ __forceinline__ void tma_ld4(uint32_t dst, const CUtensorMap* m, int c0, int c1, int c2, int c3, uint32_t bar) {
    asm volatile("cp.async.bulk.tensor.4d.shared::cluster.global.mbarrier::complete_tx::bytes [%0], [%1, {%3, %4, %5, %6}], [%2];"
                 ::"r"(dst), "l"(m), "r"(bar), "r"(c0), "r"(c1), "r"(c2), "r"(c3) : "memory");
}
__device__ __forceinline__ void bulk_ld(uint32_t dst, const void* src, uint32_t bytes, uint32_t bar) {
    asm volatile("cp.async.bulk.shared::cluster.global.mbarrier::complete_tx::bytes [%0], [%1], %2, [%3];"
                 ::"r"(dst), "l"(src), "r"(bytes), "r"(bar) : "memory");
}
__device__ __forceinline__ void tma_st2(const CUtensorMap* m, int c0, int c1, uint32_t src) {
    asm volatile("cp.async.bulk.tensor.2d.global.shared::cta.bulk_group [%0, {%1, %2}], [%3];"
                 ::"l"(m), "r"(c0), "r"(c1), "r"(src) : "memory");
}
__device__ __forceinline__ void bulk_commit() { asm volatile("cp.async.bulk.commit_group;" ::: "memory"); }
__device__ __forceinline__ void bulk_wait_read() { asm volatile("cp.async.bulk.wait_group.read 0;" ::: "memory"); }
__device__ __forceinline__ void fence_async_smem() { asm volatile("fence.proxy.async.shared::cta;" ::: "memory"); }
__device__ __forceinline__ void fence_async_global() { asm volatile("fence.proxy.async.global;" ::: "memory"); }

__device__ __forceinline__ void signal(Scratch* sc, int idx) {
    asm volatile("fence.proxy.async;\nred.relaxed.gpu.global.add.u32 [%0], 1;" ::"l"(&sc->cnt[idx * 32]) : "memory");
}
__device__ __forceinline__ void await(Scratch* sc, int idx, unsigned target) {
#pragma unroll 1
    for (int n = 0; n < SPIN_LIMIT; n++) {
        unsigned v;
        asm volatile("ld.relaxed.gpu.global.u32 %0, [%1];" : "=r"(v) : "l"(&sc->cnt[idx * 32]) : "memory");
        if ((int)(v - target) >= 0) break;
    }
    asm volatile("fence.acquire.gpu;" ::: "memory");
}
__device__ __forceinline__ void wait_dep(int k) {
    mbar_wait(base + BAR_DEP + k * 8, 0);
    fence_async_global();
}

#define WG_REGS                                                                                                     \
    "{%0,%1,%2,%3,%4,%5,%6,%7,%8,%9,%10,%11,%12,%13,%14,%15,%16,%17,%18,%19,%20,%21,%22,%23,%24,%25,%26,%27,"       \
    "%28,%29,%30,%31,%32,%33,%34,%35,%36,%37,%38,%39,%40,%41,%42,%43,%44,%45,%46,%47,%48,%49,%50,%51,%52,%53,%54,%55}"
#define WG_OPS(C)                                                                                                   \
    C(d[0]), C(d[1]), C(d[2]), C(d[3]), C(d[4]), C(d[5]), C(d[6]), C(d[7]), C(d[8]), C(d[9]), C(d[10]), C(d[11]),   \
    C(d[12]), C(d[13]), C(d[14]), C(d[15]), C(d[16]), C(d[17]), C(d[18]), C(d[19]), C(d[20]), C(d[21]), C(d[22]),   \
    C(d[23]), C(d[24]), C(d[25]), C(d[26]), C(d[27]), C(d[28]), C(d[29]), C(d[30]), C(d[31]), C(d[32]), C(d[33]),   \
    C(d[34]), C(d[35]), C(d[36]), C(d[37]), C(d[38]), C(d[39]), C(d[40]), C(d[41]), C(d[42]), C(d[43]), C(d[44]),   \
    C(d[45]), C(d[46]), C(d[47]), C(d[48]), C(d[49]), C(d[50]), C(d[51]), C(d[52]), C(d[53]), C(d[54]), C(d[55])

template <int TA, int TB, int SB, bool INIT, uint32_t AH, uint32_t BH>
__device__ __forceinline__ void wgmma112(float (&d)[56], uint32_t alo, uint32_t blo) {
    if (INIT) {
        asm volatile("{\n.reg .pred p;\n.reg .b64 da, db;\nsetp.ne.b32 p, 0, 0;\nmov.b64 da, {%56, %61};\nmov.b64 db, {%57, %62};\n"
                     "wgmma.mma_async.sync.aligned.m64n112k16.f32.bf16.bf16 " WG_REGS ", da, db, p, 1, %59, %60, %58;\n}\n"
                     : WG_OPS("=f") : "r"(alo), "r"(blo), "n"(TB), "n"(SB), "n"(TA), "n"(AH), "n"(BH));
    } else {
        asm volatile("{\n.reg .pred p;\n.reg .b64 da, db;\nsetp.ne.b32 p, 1, 0;\nmov.b64 da, {%56, %61};\nmov.b64 db, {%57, %62};\n"
                     "wgmma.mma_async.sync.aligned.m64n112k16.f32.bf16.bf16 " WG_REGS ", da, db, p, 1, %59, %60, %58;\n}\n"
                     : WG_OPS("+f") : "r"(alo), "r"(blo), "n"(TB), "n"(SB), "n"(TA), "n"(AH), "n"(BH));
    }
}
__device__ __forceinline__ void acc_fence(float (&d)[56]) {
#pragma unroll
    for (int i = 0; i < 56; i++) asm volatile("" : "+f"(d[i])::"memory");
}

__device__ __forceinline__ uint32_t pack2(float lo, float hi) {
    uint32_t r;
    asm volatile("cvt.rn.bf16x2.f32 %0, %1, %2;" : "=r"(r) : "f"(hi), "f"(lo));
    return r;
}
__device__ __forceinline__ uint32_t movm(uint32_t a) {
    uint32_t r;
    asm volatile("movmatrix.sync.aligned.m8n8.trans.b16 %0, %1;" : "=r"(r) : "r"(a));
    return r;
}
__device__ __forceinline__ void stsm4(uint32_t addr, uint32_t a, uint32_t b, uint32_t c, uint32_t d) {
    asm volatile("stmatrix.sync.aligned.m8n8.x4.shared.b16 [%0], {%1,%2,%3,%4};" ::"r"(addr), "r"(a), "r"(b), "r"(c), "r"(d) : "memory");
}
__device__ __forceinline__ void sts1(uint32_t addr, uint32_t a) { asm volatile("st.shared.b32 [%0], %1;" ::"r"(addr), "r"(a) : "memory"); }
__device__ __forceinline__ uint32_t lds1(uint32_t addr) {
    uint32_t a;
    asm volatile("ld.shared.b32 %0, [%1];" : "=r"(a) : "r"(addr) : "memory");
    return a;
}
__device__ __forceinline__ void stg1(uint8_t* p, uint32_t a) { asm volatile("st.global.b32 [%0], %1;" ::"l"(p), "r"(a) : "memory"); }
__device__ __forceinline__ void st_part(uint8_t* p, const uint32_t* v, uint32_t parity) {
    asm volatile("{\n.reg .b64 x, y;\nmov.b64 x, {%1, %2};\nmov.b64 y, {%3, %4};\nst.relaxed.gpu.global.v2.b64 [%0], {x, y};\n}\n"
                 ::"l"(p), "r"((v[0] & ~1u) | parity), "r"(v[1]), "r"((v[2] & ~1u) | parity), "r"(v[3]) : "memory");
}
__device__ __forceinline__ void mma16816(float (&d)[4], const uint32_t (&a)[4], uint32_t b0, uint32_t b1) {
    asm volatile("mma.sync.aligned.m16n8k16.row.col.f32.bf16.bf16.f32 {%0,%1,%2,%3}, {%4,%5,%6,%7}, {%8,%9}, {%0,%1,%2,%3};"
                 : "+f"(d[0]), "+f"(d[1]), "+f"(d[2]), "+f"(d[3]) : "r"(a[0]), "r"(a[1]), "r"(a[2]), "r"(a[3]), "r"(b0), "r"(b1));
}
__device__ __forceinline__ uint32_t add2(uint32_t a, uint32_t b) {
    uint32_t r;
    asm("add.rn.bf16x2 %0, %1, %2;" : "=r"(r) : "r"(a), "r"(b));
    return r;
}
__device__ __forceinline__ uint32_t max2(uint32_t a, uint32_t b) {
    uint32_t r;
    asm("max.bf16x2 %0, %1, %2;" : "=r"(r) : "r"(a), "r"(b));
    return r;
}
__device__ __forceinline__ void ld_tagged(const uint8_t* p, uint32_t& a, uint32_t& ta, uint32_t& b, uint32_t& tb) {
    asm volatile("{\n.reg .b64 x, y;\nld.relaxed.gpu.global.v2.b64 {x, y}, [%4];\nmov.b64 {%0, %1}, x;\nmov.b64 {%2, %3}, y;\n}\n"
                 : "=r"(a), "=r"(ta), "=r"(b), "=r"(tb) : "l"(p) : "memory");
}
__device__ __forceinline__ float bf_lo(uint32_t v) { return __uint_as_float(v << 16); }
__device__ __forceinline__ float bf_hi(uint32_t v) { return __uint_as_float(v & 0xFFFF0000u); }
__device__ __forceinline__ float rcp(float x) { float r; asm("rcp.approx.ftz.f32 %0, %1;" : "=f"(r) : "f"(x)); return r; }
__device__ __forceinline__ float ex2(float x) { float r; asm volatile("ex2.approx.ftz.f32 %0, %1;" : "=f"(r) : "f"(x)); return r; }

__device__ __forceinline__ uint32_t full_bar(int stage) { return base + BAR_FULL + (stage & 7) * 8; }
__device__ __forceinline__ void wait_released(int j) { mbar_wait(base + BAR_EMPTY + (j & 7) * 8, (j >> 3) & 1); }

template <int V>
struct Int { static constexpr int value = V; };

__host__ __device__ constexpr int bslot_e(int i) { return (i < 2 || i >= 14) ? (i + 5) % 7 : (i + 1) % 5; }
__host__ __device__ constexpr int bslot_l(int i) { return i % 6; }

template <uint32_t OFF>
struct Feed {
    int stage;
    uint32_t dst;
    __device__ __forceinline__ void seek(int i, int slot) { stage = i; dst = base + OFF + slot * SLOT; }
    template <int N>
    __device__ __forceinline__ uint32_t acquire() { wait_released(stage - N); return full_bar(stage); }
    template <int N>
    __device__ __forceinline__ void next() {
        stage++;
        dst += SLOT;
        if (dst == base + OFF + N * SLOT) dst = base + OFF;
    }
};
__device__ __forceinline__ int skip_own(int n, int mt) { return n == mt ? 15 : n; }

struct Desc { uint32_t lo, hi; };
__host__ __device__ constexpr Desc desc_const(uint32_t lbo, uint32_t sbo, uint32_t mode) { return {(lbo >> 4) << 16, (sbo >> 4) | (mode << 30)}; }
constexpr Desc D_K128 = desc_const(16, 1024, 1);
constexpr Desc D_N128 = desc_const(8192, 1024, 1);
constexpr Desc D_BLOB = desc_const(128, 256, 0);
constexpr Desc D_OT = desc_const(2048, 128, 0);

enum Kind { XW, XWN, QK, BIG, OUT };

struct Ring {
    int stage;
    uint32_t a, b;
    uint32_t wg;
    uint32_t zero;
    __device__ __forceinline__ void seek(int i, int bslot) {
        stage = i;
        a = (base + (i % NA) * SLOT) >> 4;
        b = (base + BRING + bslot * SLOT) >> 4;
    }
    __device__ __forceinline__ void wait() { mbar_wait(full_bar(stage), (stage >> 3) & 1); }
    __device__ __forceinline__ void take_turn() { nb_sync(1 + wg, 256); }
    __device__ __forceinline__ void pin() {
        uint32_t n = 0;
#pragma unroll 1
        do {
            asm volatile("pmevent 7;" ::: "memory");
        } while (n++ < zero);
    }
    template <Kind K, int NBS, bool INIT, int SB = 1, bool TAIL = false>
    __device__ __forceinline__ void run(float (&d)[56], float (&e)[56], bool first = true, bool last = true, bool more = true) {
        if (first) take_turn();
        asm volatile("wgmma.fence.sync.aligned;" ::: "memory");
        if (K == QK) {
            const uint32_t da = D_K128.lo + (base >> 4) + (stage >> 1) * (SLOT >> 4) + (stage & 1) * 4 + wg * 512, db = D_N128.lo + b;
            wgmma112<0, 1, 1, INIT, D_K128.hi, D_N128.hi>(d, da, db);
            wgmma112<0, 1, 1, INIT, D_K128.hi, D_N128.hi>(e, da, db + 256);
            wgmma112<0, 1, 1, false, D_K128.hi, D_N128.hi>(d, da + 2, db + 128);
            wgmma112<0, 1, 1, false, D_K128.hi, D_N128.hi>(e, da + 2, db + 384);
        } else {
            constexpr int TA = K == OUT, TB = K != XW;
            constexpr uint32_t sa = K == OUT ? 256 : 2, sb = K == XW ? 2 : K == BIG ? 224 : 128;
            constexpr Desc A = K == OUT ? D_OT : D_K128, B = K == XW ? D_K128 : K == BIG ? D_BLOB : D_N128;
            const uint32_t da = A.lo + a + wg * (K == OUT ? 64 : 512), db = B.lo + b;
            wgmma112<TA, TB, SB, INIT, A.hi, B.hi>(d, da, db);
            wgmma112<TA, TB, SB, false, A.hi, B.hi>(d, da + sa, db + sb);
            wgmma112<TA, TB, SB, false, A.hi, B.hi>(d, da + 2 * sa, db + 2 * sb);
            wgmma112<TA, TB, SB, false, A.hi, B.hi>(d, da + 3 * sa, db + 3 * sb);
        }
        asm volatile("wgmma.commit_group.sync.aligned;" ::: "memory");
        if (last) nb_arrive(2 - wg, 256);
        if (!TAIL) asm volatile("wgmma.wait_group.sync.aligned 1;" ::: "memory");
        if (!TAIL && stage > 0 && elect()) mbar_arrive(base + BAR_EMPTY + ((stage - 1) & 7) * 8);
        stage++;
        a += SLOT >> 4;
        if (a == (base + NA * SLOT) >> 4) a = base >> 4;
        b += SLOT >> 4;
        if (b == (base + BRING + NBS * SLOT) >> 4) b = (base + BRING) >> 4;
        if (more) wait();
    }
    template <Kind K, int NBS, bool INIT, int SB = 1, bool TAIL = false>
    __device__ __forceinline__ void run(float (&d)[56], bool first = true, bool last = true, bool more = true) {
        run<K, NBS, INIT, SB, TAIL>(d, d, first, last, more);
    }
};

__device__ __forceinline__ void pack_all(const float (&d)[56], uint32_t (&p)[28]) {
#pragma unroll
    for (int i = 0; i < 28; i++) p[i] = pack2(d[2 * i], d[2 * i + 1]);
}
template <int I0, int I1>
__device__ __forceinline__ void store_frags(uint8_t* dst, const uint32_t (&p)[28]) {
#pragma unroll
    for (int i = I0; i < I1; i++) stg1(dst + i * 128, p[i]);
}
template <int I0, int I1>
__device__ __forceinline__ void stage_frags(uint32_t lane_addr, const uint32_t (&p)[28]) {
#pragma unroll
    for (int i = I0; i < I1; i += 4) stsm4(lane_addr + i * 128, p[i], p[i + 1], p[i + 2], p[i + 3]);
}
template <class F>
__device__ __forceinline__ void store_out(F frag, int lane, uint32_t slab, const CUtensorMap* m, int c0, int c1) {
    const bool swap = lane & 16;
    const uint32_t addr = slab + (lane & 7) * 224 + ((lane >> 3) ^ ((lane >> 2) & 1)) * 16;
#pragma unroll
    for (int h = 0; h < 2; h++) {
#pragma unroll
        for (int c = 0; c < 14; c += 4) {
            const uint32_t t0 = frag(2 * c + h), t1 = frag(2 * c + 2 + h);
            if (c < 12) {
                const uint32_t t2 = frag(2 * c + 4 + h), t3 = frag(2 * c + 6 + h);
                stsm4(addr + h * 1792 + c * 16, swap ? t1 : t0, swap ? t0 : t1, swap ? t3 : t2, swap ? t2 : t3);
            } else {
                asm volatile("stmatrix.sync.aligned.m8n8.x2.shared.b16 [%0], {%1,%2};" ::"r"(addr + h * 1792 + c * 16), "r"(swap ? t1 : t0), "r"(swap ? t0 : t1) : "memory");
            }
        }
        fence_async_smem();
        __syncwarp();
        if (elect()) tma_st2(m, c0, c1 + 8 * h, slab + h * 1792);
    }
    if (elect()) {
        bulk_commit();
        bulk_wait_read();
    }
}
__host__ __device__ constexpr int tile_of(int t) { return 7 * (t >> 2) + 3 * ((t >> 1) & 1) + 2 * (t & 1); }

struct Role {
    bool H;
    int L, mt, ns, id;
};
template <bool BY_SM>
__device__ __forceinline__ Role decode_role() {
    uint32_t sm;
    if (BY_SM) asm volatile("mov.u32 %0, %%smid;" : "=r"(sm));
    else asm volatile("mov.u32 %0, %%ctaid.x;" : "=r"(sm));
    const int tpc = sm >> 1, q2 = ((tpc - 32) * 37) >> 8;
    const int gpc = tpc < 32 ? tpc & 7 : tpc < 60 ? tpc - 31 - 7 * q2 : 0;
    const int pos = tpc < 32 ? tpc >> 3 : tpc < 60 ? q2 + 4 : tpc - 56;
    Role r;
    r.H = sm >= 128;
    r.L = gpc & 1;
    r.mt = (gpc >> 1) * 4 + (pos >> 1);
    r.ns = (pos & 1) * 2 + (sm & 1);
    r.id = r.H ? sm : gpc * 16 + pos * 2 + (sm & 1);
    return r;
}

template <int I0, int I1>
__device__ __forceinline__ void first_fill(const Maps& maps, const Role& r) {
    if (r.L) {
#pragma unroll
        for (int i = I0; i < I1; i++) {
            const uint32_t bar = full_bar(i), dst = base + BRING + i * SLOT;
            if (i < 6) mbar_expect(bar, SLOT);
            if (i & 1) {
                mbar_arrive(bar);
            } else {
                mbar_expect(bar, SLOT);
                tma_ld2(base + (i >> 1) * SLOT, &maps.m[M_XA], (r.mt >> 3) * 448 + i * 32, (r.mt & 7) * 128, bar);
            }
            if (i < 6) {
                tma_ld4(dst, &maps.m[M_WQK], 0, i * 32, 0, r.ns, bar);
                tma_ld4(dst + 8192, &maps.m[M_WQK], 64, i * 32, 0, r.ns, bar);
            }
        }
    } else if (!r.H) {
#pragma unroll
        for (int i = I0; i < I1; i++) {
            const uint32_t bar = full_bar(i);
            mbar_expect(bar, SLOT);
            tma_ld3(base + i * SLOT, &maps.m[M_XB], i * 64, r.mt * 64, 0, bar);
            mbar_expect(bar, BLOB);
            tma_ld2(base + BRING + bslot_e(i) * SLOT, &maps.m[M_WR], i * 64, r.ns * 112, bar);
        }
    } else {
#pragma unroll 1
        for (int i = I0; i < I1; i++) {
            const uint32_t bar = full_bar(i), dst = base + BRING + i * SLOT;
            mbar_expect(bar, SLOT);
            mbar_expect(bar, SLOT);
            tma_ld4(base + i * SLOT, &maps.m[M_XH], i * 64, 120, 0, 0, bar);
            tma_ld3(dst, &maps.m[M_WV], 0, i * 64, 4 + r.ns, bar);
            tma_ld3(dst + 8192, &maps.m[M_WV], 64, i * 64, 4 + r.ns, bar);
        }
    }
}

template <bool BY_SM>
__global__ void __launch_bounds__(384, 1) fused_kernel(Scratch* sc, const __grid_constant__ Maps maps) {
    const int warp = __shfl_sync(0xffffffffu, threadIdx.x >> 5, 0);
    const Role role = decode_role<BY_SM>();
    if (warp == OPENER) {
        if (elect()) {
            asm volatile("prefetch.tensormap [%0];" ::"l"(&maps.m[M_XB]) : "memory");
            asm volatile("prefetch.tensormap [%0];" ::"l"(&maps.m[M_XA]) : "memory");
            asm volatile("prefetch.tensormap [%0];" ::"l"(&maps.m[M_WR]) : "memory");
            asm volatile("prefetch.tensormap [%0];" ::"l"(&maps.m[M_WQK]) : "memory");
#pragma unroll
            for (int i = 0; i < 8; i++) mbar_init(base + BAR_FULL + i * 8, 2);
            asm volatile("fence.mbarrier_init.release.cluster;" ::: "memory");
            first_fill<0, LEAD>(maps, role);
        }
    }
    int lane = threadIdx.x & 31;
    asm volatile("" : "+r"(lane));
    const bool roleH = role.H;
    const int roleL = role.L, mt = role.mt, ns = role.ns, bid = role.id;
    const int par = mt >> 3, blk = mt & 7, col = ns * 112;
    if (warp == 9) {
        if (elect()) {
#pragma unroll
            for (int i = 0; i < 8; i++) mbar_init(base + BAR_EMPTY + i * 8, 8);
            asm volatile("fence.mbarrier_init.release.cluster;" ::: "memory");
        }
    } else if (warp == 10) {
        if (elect()) {
#pragma unroll
            for (int i = 0; i < 5; i++) mbar_init(base + BAR_RDY + i * 8, i < 2 ? 4 : 8);
#pragma unroll
            for (int i = 0; i < 2; i++) mbar_init(base + BAR_HALO + i * 8, 9);
            asm volatile("fence.mbarrier_init.release.cluster;" ::: "memory");
        }
    } else if (warp == 11) {
        if (elect()) {
#pragma unroll
            for (int i = 0; i < 3; i++) mbar_init(base + BAR_DEP + i * 8, 1);
            asm volatile("fence.mbarrier_init.release.cluster;" ::: "memory");
        }
    }
    __syncthreads();

    if (__builtin_expect(warp >= 8, 1)) {
        asm volatile("setmaxnreg.dec.sync.aligned.u32 56;");
#define PROF_FEED_A
#define PROF_FEED_B
        if (__builtin_expect(warp == 8, 1)) {
            if (elect()) {
                PROF(129);
                first_fill<LEAD, 7>(maps, role);
                PROF(134);
                Feed<0> f;
                const int row = mt * 128;
                auto c_run = [&](const CUtensorMap* m, int off, int n0, int n1) {
#pragma unroll 1
                    for (int n = n0; n < n1; n++) {
                        const uint32_t bar = f.acquire<NA>();
                        mbar_expect(bar, SLOT);
                        tma_ld2(f.dst, m, (off + skip_own(n, mt)) * 64, row, bar);
                        PROF_FEED_A;
                        f.next<NA>();
                    }
                };
                if (roleH) {
                } else if (!roleL) {
                    f.seek(14, 0);
                    mbar_wait(base + BAR_RDY, 0);
#pragma unroll 1
                    for (int i = 0; i < 4; i++) {
                        const uint32_t bar = f.acquire<NA>();
                        mbar_expect(bar, SLOT);
                        tma_ld2(f.dst, &maps.m[M_CR + (i >> 1)], ((i & 1) * 16 + mt) * 64, row, bar);
                        mbar_arrive(bar);
                        PROF_FEED_A;
                        f.next<NA>();
                    }
                    c_run(&maps.m[M_CR], 0, 0, 15);
                    c_run(&maps.m[M_CI], 0, 0, NBE);
                    wait_dep(2);
#pragma unroll 1
                    for (int i = 0; i < 7; i++) {
                        const uint32_t bar = f.acquire<NA>();
                        mbar_expect(bar, SLOT);
                        bulk_ld(f.dst, sc->o + (size_t)(mt * 7 + i) * SLOT, SLOT, bar);
                        PROF_FEED_A;
                        f.next<NA>();
                    }
                } else {
#pragma unroll 1
                    for (int i = 4; i < 7; i++) {
                        wait_released(2 * i - 8);
                        mbar_expect(full_bar(2 * i), SLOT);
                        tma_ld2(base + i * SLOT, &maps.m[M_XA], par * 448 + i * 64, blk * 128, full_bar(2 * i));
                    }
                    wait_released(HALO_K_AT);
                    mbar_arrive(base + BAR_DEP + 16);
                    f.seek(21, 0);
                    c_run(&maps.m[M_CR], 16, 0, 15);
                    c_run(&maps.m[M_CI], 16, 0, 15);
                    c_run(&maps.m[M_CI], 0, NBE, 15);
                }
            }
        } else if (warp == 11) {
            if (elect()) {
                Feed<BRING> f;
                auto blob_run = [&](auto nbs, int quarter, int n0, int n1) {
                    constexpr int N = decltype(nbs)::value;
                    const uint8_t* src = sc->ab + (size_t)(quarter * 64 + ns) * BLOB;
#pragma unroll 1
                    for (int n = n0; n < n1; n++) {
                        const uint32_t bar = f.template acquire<N>();
                        mbar_expect(bar, BLOB);
                        bulk_ld(f.dst, src + skip_own(n, mt) * (4 * BLOB), BLOB, bar);
                        PROF_FEED_B;
                        f.template next<N>();
                    }
                };
                auto w_run = [&](auto nbs, const CUtensorMap* m, int slice, bool no_a) {
                    constexpr int N = decltype(nbs)::value;
#pragma unroll 1
                    for (int i = 0; i < 7; i++) {
                        const uint32_t bar = f.template acquire<N>();
                        mbar_expect(bar, SLOT);
                        tma_ld3(f.dst, m, 0, i * 64, slice, bar);
                        tma_ld3(f.dst + 8192, m, 64, i * 64, slice, bar);
                        if (no_a) mbar_arrive(bar);
                        PROF_FEED_B;
                        f.template next<N>();
                    }
                };
                if (roleH) {
                    f.seek(7, 0);
                    w_run(Int<7>(), &maps.m[M_WV], 8 + ns, true);
                } else if (!roleL) {
                    f.seek(7, bslot_e(7));
#pragma unroll 1
                    for (int i = 0; i < 7; i++) {
                        const uint32_t bar = f.acquire<5>();
                        mbar_expect(bar, BLOB);
                        tma_ld2(f.dst, &maps.m[M_WI], i * 64, col, bar);
                        mbar_arrive(bar);
                        PROF_FEED_B;
                        f.next<5>();
                    }
                    f.seek(18, bslot_e(18));
                    wait_dep(0);
                    blob_run(Int<7>(), 0, 0, 15);
                    wait_dep(1);
                    blob_run(Int<7>(), 2, 0, NBE);
                    w_run(Int<7>(), &maps.m[M_WO], ns, false);
                } else {
                    f.seek(6, 0);
#pragma unroll 1
                    for (int i = 6; i < 14; i++) {
                        const uint32_t bar = f.acquire<6>();
                        mbar_expect(bar, SLOT);
                        tma_ld4(f.dst, &maps.m[M_WQK], 0, i * 32, 0, ns, bar);
                        tma_ld4(f.dst + 8192, &maps.m[M_WQK], 64, i * 32, 0, ns, bar);
                        if (i & 1) mbar_arrive(bar);
                        PROF_FEED_B;
                        f.next<6>();
                    }
                    w_run(Int<6>(), &maps.m[M_WV], 8 + ns, true);
                    wait_dep(0);
                    blob_run(Int<6>(), 1, 0, 15);
                    wait_dep(1);
                    blob_run(Int<6>(), 3, 0, 15);
                    blob_run(Int<6>(), 2, NBE, 15);
                }
            }
        } else if (roleH) {
        } else if (warp == 10) {
            if (elect()) {
                unsigned* epoch_ptr = &sc->epoch[(bid * 4 + 2) * 8];
                const unsigned ep = *epoch_ptr + 1;
                sts1(base + TAG, ep);
                asm volatile("prefetch.tensormap [%0];" ::"l"(&maps.m[M_OUTA + roleL]) : "memory");
                await(sc, CNT_A + roleL * 4 + ns, ep * 16);
                mbar_arrive(base + BAR_DEP);
                PROF(150);
                await(sc, CNT_B + ns, ep * 16);
                mbar_arrive(base + BAR_DEP + 8);
                PROF(151);
                if (!roleL) {
                    await(sc, CNT_O + mt, ep * 4);
                    mbar_arrive(base + BAR_DEP + 16);
                }
                PROF(152);
                *epoch_ptr = ep;
            }
        } else if (!roleL) {
            if (elect()) {
                mbar_wait(base + BAR_RDY, 0);
                PROF(130);
                signal(sc, CNT_A + ns);
                PROF(131);
                mbar_wait(base + BAR_RDY + 8, 0);
                signal(sc, CNT_A + 4 + ns);
                PROF(135);
                mbar_wait(base + BAR_RDY + 32, 0);
                PROF(132);
                signal(sc, CNT_B + ns);
                PROF(133);
            }
        } else {
            unsigned* epoch_ptr = &sc->epoch[(bid * 4 + 1) * 8];
            const unsigned tag = *epoch_ptr + 1;
#pragma unroll 1
            for (int kv = 0; kv < 2; kv++) {
                uint32_t v[16];
#pragma unroll
                for (int i = 0; i < 16; i++) v[i] = 0;
                if (kv) mbar_wait(base + BAR_HALO, 0), wait_released(HALO_V_AT);
                else mbar_wait(base + BAR_DEP + 16, 0);
                if (blk > 0) {
                    const uint8_t* src = sc->halo + (size_t)(((mt - 1) * 4 + ns) * 2 + kv) * 2048 + lane * 16;
#pragma unroll 1
                    for (int n = 0; n < SPIN_LIMIT; n++) {
                        uint32_t stale = 0;
#pragma unroll
                        for (int i = 0; i < 4; i++) ld_tagged(src + i * 512, v[4 * i], v[4 * i + 1], v[4 * i + 2], v[4 * i + 3]);
#pragma unroll
                        for (int i = 0; i < 16; i += 2) stale |= v[i] ^ tag;
                        if (__all_sync(0xffffffffu, !(stale & 1))) break;
                    }
#pragma unroll
                    for (int c = 0; c < 14; c += 2) v[c] = (v[c] & ~1u) | ((v[15] >> c) & 1);
                }
#pragma unroll
                for (int i = 0; i < 14; i++) sts1(base + HALO + kv * (8 * HSLOT) + i * 128 + lane * 4, v[i]);
                warp_arrive(base + BAR_HALO + kv * 8);
                if (lane == 0) PROF(142 + kv);
            }
            if (elect()) {
                mbar_wait(base + BAR_RDY + 16, 0);
                PROF(130);
                signal(sc, CNT_O + mt);
                PROF(131);
                *epoch_ptr = tag;
            }
        }
    } else {
        asm volatile("setmaxnreg.inc.sync.aligned.u32 224;");
        Ring r;
        r.wg = warp >> 2;
        r.zero = blockIdx.y;
        const int wg = warp >> 2;
        if (wg) nb_arrive(1, 256);
        r.stage = 0;
        r.wait();
        uint8_t* part = sc->part + (size_t)(ns * 16 + mt) * (2 * BLOB) + warp * 512 + lane * 16;
        uint32_t p[28];

        if (roleH) {
            unsigned* epoch_ptr = &sc->epoch[bid * 4 * 8];
            const unsigned tag = *epoch_ptr + 1;
            uint8_t* hout = sc->halo + (size_t)((warp * 8 + ns) * 2) * 2048 + lane * 16;
            auto send = [&](int kv) {
#pragma unroll
                for (int h = 0; h < 2; h++) {
                    uint32_t v[16];
                    v[14] = v[15] = 0;
#pragma unroll
                    for (int c = 0; c < 14; c++) v[c] = p[2 * c + h];
#pragma unroll
                    for (int c = 0; c < 14; c += 2) v[15] |= (v[c] & 1) << c;
#pragma unroll
                    for (int i = 0; i < 4; i++) st_part(hout + (h * 8 + kv) * 2048 + i * 512, v + 4 * i, tag & 1);
                }
            };
            float x0[56], x1[56];
            r.seek(0, 0);
            r.run<XWN, 7, true>(x0);
#pragma unroll 1
            for (int i = 1; i < 7; i++) r.run<XWN, 7, false>(x0);
            r.run<XWN, 7, true>(x1);
            acc_fence(x0);
            pack_all(x0, p);
            send(0);
#pragma unroll 1
            for (int i = 1; i < 7; i++) r.run<XWN, 7, false>(x1, true, true, i < 6);
            asm volatile("wgmma.wait_group.sync.aligned 0;" ::: "memory");
            acc_fence(x1);
            pack_all(x1, p);
#pragma unroll
            for (int i = 0; i < 28; i++) p[i] = movm(p[i]);
            send(1);
            if (threadIdx.x == 0) *epoch_ptr = tag;
        } else if (!roleL) {
            uint8_t* blob = sc->ab + (size_t)((wg * 16 + mt) * 4 + ns) * BLOB + (warp & 3) * WSLOT + lane * 4;
            const uint32_t own = base + BRING + wg * SLOT + (warp & 3) * WSLOT + lane * 16;
            float x0[56], x1[56];
            r.seek(0, bslot_e(0));
            r.run<XW, 7, true>(x0);
            r.run<XW, 7, false>(x0);
            r.seek(2, bslot_e(2));
#pragma unroll 1
            for (int i = 2; i < 7; i++) r.run<XW, 5, false>(x0);

            r.seek(7, bslot_e(7));
            r.run<XW, 5, true, -1>(x1);
            acc_fence(x0);
            pack_all(x0, p);
#pragma unroll
            for (int i = 0; i < 2; i++) {
                if (wg == i) store_frags<0, 14>(blob, p);
                else stage_frags<0, 4>(own + 5 * SLOT, p);
                r.run<XW, 5, false, -1>(x1);
                if (wg == i) {
                    store_frags<14, 28>(blob, p);
                    warp_arrive(base + BAR_RDY + i * 8);
                } else {
                    stage_frags<4, 8>(own + 5 * SLOT, p);
                }
                r.run<XW, 5, false, -1>(x1);
            }
            stage_frags<8, 20>(own + 5 * SLOT, p);
            r.run<XW, 5, false, -1>(x1);
            stage_frags<20, 28>(own + 5 * SLOT, p);
            warp_arrive(base + BAR_RDY + 16);
            r.run<XW, 5, false, -1>(x1);

            mbar_wait(base + BAR_RDY + 16, 0);
            fence_async_smem();
            r.seek(14, bslot_e(14));
            r.run<BIG, 7, true>(x0);
            acc_fence(x1);
            pack_all(x1, p);
            wait_released(10);
            stage_frags<0, 28>(own, p);
            warp_arrive(base + BAR_RDY + 24);
            r.run<BIG, 7, false>(x0);
            mbar_wait(base + BAR_RDY + 24, 0);
            fence_async_smem();
            blob += (size_t)128 * BLOB;
#pragma unroll
            for (int i = 0; i < 28; i++) {
                if (i % B_SLICE == 0) r.run<BIG, 7, false>(x0);
                stg1(blob + i * 128, p[i]);
            }
            warp_arrive(base + BAR_RDY + 32);
#pragma unroll 1
            for (int i = 17 + 27 / B_SLICE; i < POUT; i++) r.run<BIG, 7, false>(x0);

            const uint32_t tag = lds1(base + TAG);
            r.seek(POUT, bslot_e(POUT));
            r.run<OUT, 7, true>(x1);
            acc_fence(x0);
            pack_all(x0, p);
#pragma unroll
            for (int k = 0; k < 3; k++) {
                if (k < 2 && wg == k) {
#pragma unroll
                    for (int i = 0; i < 4; i++) st_part(part + i * 4096, p + 4 * i, tag & 1);
                }
                if (k > 0 && wg == k - 1) {
#pragma unroll
                    for (int i = 4; i < 7; i++) st_part(part + i * 4096, p + 4 * i, tag & 1);
                }
                if (k < 2) r.run<OUT, 7, false>(x1);
            }
#pragma unroll
            for (int i = 3; i < 7; i++) r.run<OUT, 7, false, 1, true>(x1, i <= 7 - TURN, i < 7 - TURN || i == 6, i < 6);

            wait_released(ELAST - 6);
            asm volatile("wgmma.wait_group.sync.aligned 0;" ::: "memory");
            acc_fence(x1);
            const uint32_t slab = base + (wg ? BRING + bslot_e(ELAST - 6) * SLOT : ((ELAST - 6) % NA) * SLOT) + (warp & 3) * WSLOT;
            store_out([&](int i) { return pack2(x1[2 * i], x1[2 * i + 1]); }, lane, slab, &maps.m[M_OUTA], par * 896 + col, blk * 128 + warp * 16);
        } else {
            const int g = lane >> 2, tig = lane & 3;
            const uint32_t hin = base + HALO + warp * HSLOT + lane * 4;
            const uint32_t hpub = warp < 7 ? hin + HSLOT : base + HSPARE + lane * 4;
            auto publish = [&](const uint32_t (&h)[14], int c0, int c1) {
#pragma unroll
                for (int c = 0; c < 14; c++)
                    if (c >= c0 && c < c1) sts1(hpub + c * 128, h[c]);
            };
            float y0[56], y1[56], y2[56];
            r.seek(0, 0);
            r.run<QK, 6, true>(y0, y1);
#pragma unroll 1
            for (int i = 1; i < 14; i++) r.run<QK, 6, false>(y0, y1);

            uint32_t m1[8][4], m0[8][4], lo[14], hi[14], q[2][8][2];
            auto pack_q = [&](int b) {
                uint32_t v[14];
#pragma unroll
                for (int c = 0; c < 14; c++) v[c] = pack2(y0[4 * c + 2 * b], y0[4 * c + 2 * b + 1]);
#pragma unroll
                for (int t = 0; t < 8; t++) {
                    const int c = tile_of(t);
                    q[b][t][0] = (t & 3) == 2 ? (tig >= 2 ? v[c] : 0u) : v[c];
                    q[b][t][1] = (t & 3) == 1 ? (tig < 2 ? v[c + 1] : 0u) : v[c + 1];
                }
            };
            auto fetch = [&](uint32_t src, int hp, int i0) {
#pragma unroll
                for (int t = 4 * hp; t < 4 * hp + 4; t++) {
                    m0[t][i0] = (t & 3) == 2 ? dup(m0[t - 1][3], r.zero) : lds1(src + tile_of(t) * 128);
                    m0[t][3] = lds1(src + tile_of(t) * 128 + 128);
                }
            };
            r.seek(14, bslot_l(14));
            r.run<XWN, 6, true>(y2);
            acc_fence(y0);
            acc_fence(y1);
#pragma unroll
            for (int c = 0; c < 14; c++) hi[c] = pack2(y1[4 * c + 2], y1[4 * c + 3]);
            publish(hi, 0, 7);
            PIN;
            r.run<XWN, 6, false>(y2);
            publish(hi, 7, 14);
            warp_arrive(base + BAR_HALO);
#pragma unroll
            for (int c = 0; c < 14; c++) lo[c] = pack2(y1[4 * c], y1[4 * c + 1]);
#pragma unroll
            for (int t = 0; t < 8; t++) {
                const int c = tile_of(t);
                const bool shared = (t & 3) == 2;
                m1[t][0] = shared ? dup(lo[c], r.zero) : lo[c];
                m1[t][1] = shared ? dup(hi[c], r.zero) : hi[c];
                m1[t][2] = lo[c + 1];
                m1[t][3] = hi[c + 1];
                m0[t][0] = dup(m1[t][0], r.zero);
                m0[t][2] = dup(lo[c + 1], 2 * r.zero);
            }
            PIN;
            r.run<XWN, 6, false>(y2);
            mbar_wait(base + BAR_HALO, 0);
            fetch(hin, 0, 1);
            pack_q(1);
            PIN;
            r.run<XWN, 6, false>(y2);
            fetch(hin, 1, 1);
            pack_q(0);
            r.pin();
            r.take_turn();
            float s[8][4];
#pragma unroll
            for (int step = 0; step < 2; step++) {
#pragma unroll
                for (int i = 0; i < 8; i++) {
                    const int b = 1 - (i >> 2), h = i & 3, t = 2 * h + step;
                    float (&d)[4] = s[2 * h + b];
                    if (step == 0) d[0] = d[1] = d[2] = d[3] = 0.f;
                    mma16816(d, b ? m1[t] : m0[t], q[b][t][0], q[b][t][1]);
                }
            }
            r.pin();
            r.run<XWN, 6, false>(y2, false);

            uint32_t pr[8], mx[4], mx1[4];
            {
                const bool cur0 = g <= 2 * tig, cur1 = g <= 2 * tig + 1;
#pragma unroll
                for (int i = 0; i < 8; i++) {
                    const int c = (i & 1) ? 2 : 0;
                    pr[i] = movm(pack2(cur0 ? s[i][c] : s[i][2 - c], cur1 ? s[i][c + 1] : s[i][3 - c]));
                }
            }
            PIN;
            r.run<XWN, 6, false>(y2);
            const uint32_t curmask = (2 * tig <= g ? 0x0000FFFFu : 0u) | (2 * tig + 1 <= g ? 0xFFFF0000u : 0u);
            {
                const uint32_t keep = (blk == 0 && warp == 0) ? curmask : 0xFFFFFFFFu;
#pragma unroll
                for (int i = 0; i < 4; i++) {
                    pr[2 * i] = (pr[2 * i] & keep) | (0xCF9ECF9Eu & ~keep);
                    mx[i] = max2(__byte_perm(pr[2 * i], pr[2 * i + 1], 0x5410), __byte_perm(pr[2 * i], pr[2 * i + 1], 0x7632));
                    mx1[i] = __shfl_xor_sync(0xffffffffu, mx[i], 1);
                }
            }
            PIN;
            r.run<XWN, 6, false>(y2);
#pragma unroll
            for (int i = 0; i < 4; i++) {
                mx[i] = max2(mx[i], mx1[i]);
                mx1[i] = __shfl_xor_sync(0xffffffffu, mx[i], 2);
            }

            PIN;
            r.seek(21, bslot_l(21));
            r.run<BIG, 6, true>(y0);
            acc_fence(y2);
#pragma unroll
            for (int c = 0; c < 10; c++) hi[c] = movm(pack2(y2[4 * c + 2], y2[4 * c + 3]));
            constexpr float SCL = 0.18898223650461362f * 1.4426950408889634f;
            float e0[8], e1[8], sm[8], sm1[8];
#pragma unroll
            for (int i = 0; i < 8; i++) {
                const uint32_t m2 = max2(mx[i >> 1], mx1[i >> 1]);
                sm[i] = ((i & 1) ? bf_hi(m2) : bf_lo(m2)) * -SCL;
            }
            PIN;
            r.run<BIG, 6, false>(y0);
#pragma unroll
            for (int c = 10; c < 14; c++) hi[c] = movm(pack2(y2[4 * c + 2], y2[4 * c + 3]));
#pragma unroll
            for (int c = 0; c < 4; c++) lo[c] = movm(pack2(y2[4 * c], y2[4 * c + 1]));
#pragma unroll
            for (int i = 0; i < 8; i++) e0[i] = ex2(fmaf(bf_lo(pr[i]), SCL, sm[i]));
            PIN;
            r.run<BIG, 6, false>(y0);
            publish(hi, 0, 10);
#pragma unroll
            for (int i = 0; i < 8; i++) e1[i] = ex2(fmaf(bf_hi(pr[i]), SCL, sm[i]));
            PIN;
            r.run<BIG, 6, false>(y0);
            publish(hi, 10, 14);
            warp_arrive(base + BAR_HALO + 8);
#pragma unroll
            for (int i = 0; i < 8; i++) {
                sm[i] = e0[i] + e1[i];
                sm1[i] = __shfl_xor_sync(0xffffffffu, sm[i], 1);
            }
            PIN;
            r.run<BIG, 6, false>(y0);
#pragma unroll
            for (int c = 4; c < 14; c++) lo[c] = movm(pack2(y2[4 * c], y2[4 * c + 1]));
            PIN;
            r.run<BIG, 6, false>(y0);
#pragma unroll
            for (int i = 0; i < 8; i++) {
                sm[i] += sm1[i];
                sm1[i] = __shfl_xor_sync(0xffffffffu, sm[i], 2);
            }
#pragma unroll
            for (int t = 0; t < 8; t++) {
                const int c = tile_of(t);
                const bool shared = (t & 3) == 2;
                m1[t][0] = shared ? dup(lo[c], r.zero) : lo[c];
                m1[t][1] = lo[c + 1];
                m1[t][2] = shared ? dup(hi[c], r.zero) : hi[c];
                m1[t][3] = hi[c + 1];
                m0[t][0] = dup(m1[t][0], r.zero);
                m0[t][1] = dup(lo[c + 1], 2 * r.zero);
            }
            PIN;
            r.run<BIG, 6, false>(y0);
            mbar_wait(base + BAR_HALO + 8, 0);
            const uint32_t vin = warp ? hin : hin + 8 * HSLOT;
            fetch(vin, 0, 2);
#pragma unroll
            for (int i = 0; i < 8; i++) {
                const float inv = rcp(sm[i] + sm1[i]);
                pr[i] = pack2(e0[i] * inv, e1[i] * inv);
            }
            PIN;
            r.run<BIG, 6, false>(y0);
            fetch(vin, 1, 2);
            uint32_t pb[8][2];
#pragma unroll
            for (int t = 0; t < 8; t++) {
                pb[t][t & 1] = band(pr[t], curmask);
                pb[t][1 - (t & 1)] = band(pr[t], ~curmask);
            }
            r.pin();
            r.take_turn();
            float o[2][8][4];
#pragma unroll
            for (int i = 0; i < 16; i++) {
                const int b = 1 - (i >> 3), t = i & 7;
                float (&d)[4] = o[b][t];
                d[0] = d[1] = d[2] = d[3] = 0.f;
                mma16816(d, b ? m1[t] : m0[t], pb[(t & 6) + b][0], pb[(t & 6) + b][1]);
            }
            r.pin();
            r.run<BIG, 6, false>(y0, false);
            uint8_t* odst = sc->o + (size_t)mt * 7 * SLOT + ns * (14 * 2048) + warp * 256 + lane * 4;
#pragma unroll
            for (int hp = 0; hp < 2; hp++) {
#pragma unroll
                for (int b = 0; b < 2; b++) {
                    const float (&u)[8][4] = o[b];
                    const int t = 4 * hp;
                    uint32_t* w = p + 14 * hp + b;
                    w[0] = pack2(u[t][0], u[t][1]);
                    w[2] = pack2(u[t][2], u[t][3]);
                    w[4] = pack2(u[t + 1][0], u[t + 1][1]);
                    w[6] = pack2(g < 4 ? u[t + 1][2] : u[t + 2][0], g < 4 ? u[t + 1][3] : u[t + 2][1]);
                    w[8] = pack2(u[t + 2][2], u[t + 2][3]);
                    w[10] = pack2(u[t + 3][0], u[t + 3][1]);
                    w[12] = pack2(u[t + 3][2], u[t + 3][3]);
                }
            }
#pragma unroll
            for (int i = 0; i < 28; i++) {
                if (i && i % O_SLICE == 0) r.run<BIG, 6, false>(y0);
                stg1(odst + (i >> 1) * 2048 + (i & 1) * 128, p[i]);
            }
            warp_arrive(base + BAR_RDY + 16);

#pragma unroll 1
            for (int i = 30 + 27 / O_SLICE; i <= LLAST + 1 - TURN; i++) r.run<BIG, 6, false>(y0, true, i <= LLAST - TURN);
            const uint32_t tag = lds1(base + TAG);
#pragma unroll
            for (int i = 0; i < 7; i++) ld_tagged(part + i * 4096, p[4 * i], p[4 * i + 1], p[4 * i + 2], p[4 * i + 3]);
            r.seek(LLAST + 2 - TURN, bslot_l(LLAST + 2 - TURN));
#pragma unroll
            for (int i = 1; i < TURN; i++) r.run<BIG, 6, false, 1, true>(y0, false, i == TURN - 1, i < TURN - 1);
#pragma unroll 1
            for (int n = 0; n < SPIN_LIMIT; n++) {
                uint32_t stale = 0;
#pragma unroll
                for (int i = 0; i < 28; i += 2) stale |= p[i] ^ tag;
                if (__all_sync(0xffffffffu, !(stale & 1))) break;
#pragma unroll
                for (int i = 0; i < 7; i++) ld_tagged(part + i * 4096, p[4 * i], p[4 * i + 1], p[4 * i + 2], p[4 * i + 3]);
            }
            wait_released(LLAST - 6);
            asm volatile("wgmma.wait_group.sync.aligned 0;" ::: "memory");
            acc_fence(y0);
            const uint32_t slab = base + (wg ? HALO : ((LLAST - 6) % NA) * SLOT) + (warp & 3) * WSLOT;
            store_out([&](int i) { return add2(pack2(y0[2 * i], y0[2 * i + 1]), p[i]); }, lane, slab, &maps.m[M_OUTB], 448 + col, mt * 128 + warp * 16);
        }
    }
}

typedef CUresult (*EncodeFn)(CUtensorMap*, CUtensorMapDataType, cuuint32_t, void*, const cuuint64_t*, const cuuint64_t*,
                             const cuuint32_t*, const cuuint32_t*, CUtensorMapInterleave, CUtensorMapSwizzle,
                             CUtensorMapL2promotion, CUtensorMapFloatOOBfill);

struct Dim { uint64_t size, stride; uint32_t box; };
void encode(EncodeFn fn, CUtensorMap* m, const void* ptr, CUtensorMapSwizzle sw, Dim d0, Dim d1, Dim d2 = {0, 0, 0}, Dim d3 = {0, 0, 0}) {
    const cuuint64_t dims[4] = {d0.size, d1.size, d2.size, d3.size};
    const cuuint64_t strides[3] = {d1.stride, d2.stride, d3.stride};
    const cuuint32_t box[4] = {d0.box, d1.box, d2.box, d3.box};
    const cuuint32_t es[4] = {1, 1, 1, 1};
    fn(m, CU_TENSOR_MAP_DATA_TYPE_BFLOAT16, d3.size ? 4 : d2.size ? 3 : 2, const_cast<void*>(ptr), dims, strides, box, es,
       CU_TENSOR_MAP_INTERLEAVE_NONE, sw, CU_TENSOR_MAP_L2_PROMOTION_L2_128B, CU_TENSOR_MAP_FLOAT_OOB_FILL_NONE);
}

}

extern "C" void kernel_launch(void* const* d_in, const int* in_sizes, int n_in, void* d_out, int out_size) {
    (void)in_sizes; (void)n_in; (void)out_size;
    void* fnp = nullptr;
    cudaDriverEntryPointQueryResult st;
    cudaGetDriverEntryPoint("cuTensorMapEncodeTiled", &fnp, cudaEnableDefault, &st);
    EncodeFn fn = (EncodeFn)fnp;
    void* scratch = nullptr;
    cudaGetSymbolAddress(&scratch, g_scratch);
    int dev = 0, sms = 0;
    cudaGetDevice(&dev);
    cudaDeviceGetAttribute(&sms, cudaDevAttrMultiProcessorCount, dev);
    auto kernel = sms == 132 ? fused_kernel<true> : fused_kernel<false>;
    cudaFuncSetAttribute(kernel, cudaFuncAttributeMaxDynamicSharedMemorySize, SMEM_BYTES);

    const CUtensorMapSwizzle S128 = CU_TENSOR_MAP_SWIZZLE_128B, S0 = CU_TENSOR_MAP_SWIZZLE_NONE;
    Maps maps;
    encode(fn, &maps.m[M_XA], d_in[0], S128, {896, 2, 64}, {1024, 1792, 128});
    encode(fn, &maps.m[M_WQK], d_in[1], S128, {112, 2, 64}, {448, 2688, 32}, {3, 896, 2}, {4, 224, 1});
    encode(fn, &maps.m[M_WV], d_in[1], S128, {112, 2, 64}, {448, 2688, 64}, {12, 224, 1});
    encode(fn, &maps.m[M_XH], d_in[0], S128, {448, 2, 64}, {128, 1792, 8}, {8, 128 * 1792, 8}, {2, 896, 2});
    encode(fn, &maps.m[M_WO], d_in[2], S128, {112, 2, 64}, {448, 896, 64}, {4, 224, 1});
    encode(fn, &maps.m[M_XB], d_in[3], S128, {448, 2, 64}, {1024, 896, 64}, {2, 896 * 1024, 2});
    encode(fn, &maps.m[M_CR], d_in[4], S128, {2048, 2, 64}, {2048, 4096, 128});
    encode(fn, &maps.m[M_CI], d_in[5], S128, {2048, 2, 64}, {2048, 4096, 128});
    encode(fn, &maps.m[M_WR], d_in[6], S128, {448, 2, 64}, {448, 896, 112});
    encode(fn, &maps.m[M_WI], d_in[7], S128, {448, 2, 64}, {448, 896, 112});
    encode(fn, &maps.m[M_OUTA], d_out, S0, {1792, 2, 112}, {1024, 3584, 8});
    encode(fn, &maps.m[M_OUTB], d_out, S0, {896, 2, 112}, {2048, 1792, 8});

    kernel<<<132, 384, SMEM_BYTES>>>((Scratch*)scratch, maps);
}
```

```cpp
#include <cuda.h>
#include <cuda_bf16.h>
#include <cuda_runtime.h>
#include <stdint.h>

namespace {

constexpr uint32_t SLOT = 16384;
constexpr int NA = 7;
constexpr uint32_t BRING = NA * SLOT;
constexpr uint32_t HALO = BRING + 6 * SLOT;
constexpr uint32_t HSLOT = 1792;
constexpr uint32_t WSLOT = 3584;
constexpr uint32_t BLOB = 14336;
constexpr uint32_t BARS = 14 * SLOT;
constexpr uint32_t BAR_FULL = BARS;
constexpr uint32_t BAR_EMPTY = BARS + 64;
constexpr uint32_t BAR_RDY = BARS + 128;
constexpr uint32_t BAR_DEP = BARS + 168;
constexpr uint32_t BAR_HALO = BARS + 192;
constexpr uint32_t BAR_PART = BARS + 208;
constexpr uint32_t TAG = BARS + 224;
constexpr uint32_t HSPARE = BARS + 256 + 1024;
constexpr uint32_t SMEM_BYTES = HSPARE + HSLOT;
constexpr uint32_t base = 1024;
constexpr int SPIN_LIMIT = 1 << 16;

#define E_EXTRA 0
#define HALO_K_AT 10
#define HALO_V_AT 19
#define O_SLICE 4
#define B_SLICE 4
#define LEAD 3
#define TURN 3
#define PIN r.pin()
#define OPENER 8
#define MAPPING 2
constexpr int NBE = 13 + E_EXTRA;
constexpr int POUT = 33 + NBE;
constexpr int ELAST = POUT + 6;
constexpr int LLAST = 52 - E_EXTRA;

enum { M_XA, M_XH, M_WQK, M_WV, M_WO, M_XB, M_WR, M_WI, M_CR, M_CI, M_OUTA, M_OUTB, M_COUNT };
struct __align__(64) Maps { CUtensorMap m[M_COUNT]; };

constexpr int CNT_A = 0;
constexpr int CNT_B = 8;
constexpr int CNT_O = 16;
constexpr int CNT_P = 32;
constexpr int CNT_COUNT = 96;

struct Scratch {
    uint8_t ab[64 * 4 * BLOB];
    uint8_t o[16 * 7 * SLOT];
    uint8_t part[64 * 2 * BLOB];
    uint8_t halo[64 * 2 * 2048];
    unsigned cnt[CNT_COUNT * 32];
    unsigned epoch[132 * 4 * 8];
};
__device__ __align__(1024) Scratch g_scratch;

__device__ __forceinline__ unsigned clk32() { unsigned c; asm volatile("mov.u32 %0, %%clock;" : "=r"(c)); return c; }

#define PROF(idx)

__device__ __forceinline__ void mbar_init(uint32_t bar, uint32_t cnt) {
    asm volatile("mbarrier.init.shared::cta.b64 [%0], %1;" ::"r"(bar), "r"(cnt) : "memory");
}
__device__ __forceinline__ void mbar_expect(uint32_t bar, uint32_t bytes) {
    asm volatile("mbarrier.arrive.expect_tx.shared::cta.b64 _, [%0], %1;" ::"r"(bar), "r"(bytes) : "memory");
}
__device__ __forceinline__ void mbar_arrive(uint32_t bar) {
    asm volatile("mbarrier.arrive.shared::cta.b64 _, [%0];" ::"r"(bar) : "memory");
}
__device__ __forceinline__ bool mbar_try(uint32_t bar, uint32_t parity) {
    uint32_t ok;
    asm volatile("{\n.reg .pred p;\nmbarrier.try_wait.parity.shared::cta.b64 p, [%1], %2;\nselp.u32 %0, 1, 0, p;\n}\n"
                 : "=r"(ok) : "r"(bar), "r"(parity) : "memory");
    return ok;
}
__device__ __forceinline__ bool mbar_test(uint32_t bar, uint32_t parity) {
    uint32_t ok;
    asm volatile("{\n.reg .pred p;\nmbarrier.test_wait.parity.shared::cta.b64 p, [%1], %2;\nselp.u32 %0, 1, 0, p;\n}\n"
                 : "=r"(ok) : "r"(bar), "r"(parity) : "memory");
    return ok;
}
__device__ __forceinline__ void mbar_wait(uint32_t bar, uint32_t parity) {
#pragma unroll 1
    for (int n = 0; n < SPIN_LIMIT; n++)
        if (mbar_try(bar, parity)) break;
}
__device__ __forceinline__ bool elect() {
    uint32_t p;
    asm volatile("{\n.reg .pred p;\nelect.sync _|p, 0xffffffff;\nselp.u32 %0, 1, 0, p;\n}\n" : "=r"(p));
    return p;
}
__device__ __forceinline__ void nb_sync(int id, int n) { asm volatile("bar.sync %0, %1;" ::"r"(id), "r"(n) : "memory"); }
__device__ __forceinline__ void nb_arrive(int id, int n) { asm volatile("bar.arrive %0, %1;" ::"r"(id), "r"(n) : "memory"); }
__device__ __forceinline__ void warp_arrive(uint32_t bar) {
    __syncwarp();
    if (elect()) mbar_arrive(bar);
}
__device__ __forceinline__ uint32_t band(uint32_t x, uint32_t m) {
    uint32_t r;
    asm volatile("and.b32 %0, %1, %2;" : "=r"(r) : "r"(x), "r"(m));
    return r;
}
__device__ __forceinline__ uint32_t dup(uint32_t x, uint32_t zero) {
    uint32_t r;
    asm volatile("xor.b32 %0, %1, %2;" : "=r"(r) : "r"(x), "r"(zero));
    return r;
}

__device__ __forceinline__ void tma_ld2(uint32_t dst, const CUtensorMap* m, int c0, int c1, uint32_t bar) {
    asm volatile("cp.async.bulk.tensor.2d.shared::cluster.global.mbarrier::complete_tx::bytes [%0], [%1, {%3, %4}], [%2];"
                 ::"r"(dst), "l"(m), "r"(bar), "r"(c0), "r"(c1) : "memory");
}
__device__ __forceinline__ void tma_ld3(uint32_t dst, const CUtensorMap* m, int c0, int c1, int c2, uint32_t bar) {
    asm volatile("cp.async.bulk.tensor.3d.shared::cluster.global.mbarrier::complete_tx::bytes [%0], [%1, {%3, %4, %5}], [%2];"
                 ::"r"(dst), "l"(m), "r"(bar), "r"(c0), "r"(c1), "r"(c2) : "memory");
}
__device__ __forceinline__ void tma_ld4(uint32_t dst, const CUtensorMap* m, int c0, int c1, int c2, int c3, uint32_t bar) {
    asm volatile("cp.async.bulk.tensor.4d.shared::cluster.global.mbarrier::complete_tx::bytes [%0], [%1, {%3, %4, %5, %6}], [%2];"
                 ::"r"(dst), "l"(m), "r"(bar), "r"(c0), "r"(c1), "r"(c2), "r"(c3) : "memory");
}
__device__ __forceinline__ void bulk_ld(uint32_t dst, const void* src, uint32_t bytes, uint32_t bar) {
    asm volatile("cp.async.bulk.shared::cluster.global.mbarrier::complete_tx::bytes [%0], [%1], %2, [%3];"
                 ::"r"(dst), "l"(src), "r"(bytes), "r"(bar) : "memory");
}
__device__ __forceinline__ void tma_st2(const CUtensorMap* m, int c0, int c1, uint32_t src) {
    asm volatile("cp.async.bulk.tensor.2d.global.shared::cta.bulk_group [%0, {%1, %2}], [%3];"
                 ::"l"(m), "r"(c0), "r"(c1), "r"(src) : "memory");
}
__device__ __forceinline__ void bulk_commit() { asm volatile("cp.async.bulk.commit_group;" ::: "memory"); }
__device__ __forceinline__ void bulk_wait_read() { asm volatile("cp.async.bulk.wait_group.read 0;" ::: "memory"); }
__device__ __forceinline__ void fence_async_smem() { asm volatile("fence.proxy.async.shared::cta;" ::: "memory"); }
__device__ __forceinline__ void fence_async_global() { asm volatile("fence.proxy.async.global;" ::: "memory"); }

__device__ __forceinline__ void signal(Scratch* sc, int idx) {
    asm volatile("fence.proxy.async;\nred.relaxed.gpu.global.add.u32 [%0], 1;" ::"l"(&sc->cnt[idx * 32]) : "memory");
}
__device__ __forceinline__ void await(Scratch* sc, int idx, unsigned target) {
#pragma unroll 1
    for (int n = 0; n < SPIN_LIMIT; n++) {
        unsigned v;
        asm volatile("ld.relaxed.gpu.global.u32 %0, [%1];" : "=r"(v) : "l"(&sc->cnt[idx * 32]) : "memory");
        if ((int)(v - target) >= 0) break;
    }
    asm volatile("fence.acquire.gpu;" ::: "memory");
}
__device__ __forceinline__ void wait_dep(int k) {
    mbar_wait(base + BAR_DEP + k * 8, 0);
    fence_async_global();
}

#define WG_REGS                                                                                                     \
    "{%0,%1,%2,%3,%4,%5,%6,%7,%8,%9,%10,%11,%12,%13,%14,%15,%16,%17,%18,%19,%20,%21,%22,%23,%24,%25,%26,%27,"       \
    "%28,%29,%30,%31,%32,%33,%34,%35,%36,%37,%38,%39,%40,%41,%42,%43,%44,%45,%46,%47,%48,%49,%50,%51,%52,%53,%54,%55}"
#define WG_OPS(C)                                                                                                   \
    C(d[0]), C(d[1]), C(d[2]), C(d[3]), C(d[4]), C(d[5]), C(d[6]), C(d[7]), C(d[8]), C(d[9]), C(d[10]), C(d[11]),   \
    C(d[12]), C(d[13]), C(d[14]), C(d[15]), C(d[16]), C(d[17]), C(d[18]), C(d[19]), C(d[20]), C(d[21]), C(d[22]),   \
    C(d[23]), C(d[24]), C(d[25]), C(d[26]), C(d[27]), C(d[28]), C(d[29]), C(d[30]), C(d[31]), C(d[32]), C(d[33]),   \
    C(d[34]), C(d[35]), C(d[36]), C(d[37]), C(d[38]), C(d[39]), C(d[40]), C(d[41]), C(d[42]), C(d[43]), C(d[44]),   \
    C(d[45]), C(d[46]), C(d[47]), C(d[48]), C(d[49]), C(d[50]), C(d[51]), C(d[52]), C(d[53]), C(d[54]), C(d[55])

template <int TA, int TB, int SB, bool INIT, uint32_t AH, uint32_t BH>
__device__ __forceinline__ void wgmma112(float (&d)[56], uint32_t alo, uint32_t blo) {
    if (INIT) {
        asm volatile("{\n.reg .pred p;\n.reg .b64 da, db;\nsetp.ne.b32 p, 0, 0;\nmov.b64 da, {%56, %61};\nmov.b64 db, {%57, %62};\n"
                     "wgmma.mma_async.sync.aligned.m64n112k16.f32.bf16.bf16 " WG_REGS ", da, db, p, 1, %59, %60, %58;\n}\n"
                     : WG_OPS("=f") : "r"(alo), "r"(blo), "n"(TB), "n"(SB), "n"(TA), "n"(AH), "n"(BH));
    } else {
        asm volatile("{\n.reg .pred p;\n.reg .b64 da, db;\nsetp.ne.b32 p, 1, 0;\nmov.b64 da, {%56, %61};\nmov.b64 db, {%57, %62};\n"
                     "wgmma.mma_async.sync.aligned.m64n112k16.f32.bf16.bf16 " WG_REGS ", da, db, p, 1, %59, %60, %58;\n}\n"
                     : WG_OPS("+f") : "r"(alo), "r"(blo), "n"(TB), "n"(SB), "n"(TA), "n"(AH), "n"(BH));
    }
}
__device__ __forceinline__ void acc_fence(float (&d)[56]) {
#pragma unroll
    for (int i = 0; i < 56; i++) asm volatile("" : "+f"(d[i])::"memory");
}

__device__ __forceinline__ uint32_t pack2(float lo, float hi) {
    uint32_t r;
    asm volatile("cvt.rn.bf16x2.f32 %0, %1, %2;" : "=r"(r) : "f"(hi), "f"(lo));
    return r;
}
__device__ __forceinline__ uint32_t movm(uint32_t a) {
    uint32_t r;
    asm volatile("movmatrix.sync.aligned.m8n8.trans.b16 %0, %1;" : "=r"(r) : "r"(a));
    return r;
}
__device__ __forceinline__ void stsm4(uint32_t addr, uint32_t a, uint32_t b, uint32_t c, uint32_t d) {
    asm volatile("stmatrix.sync.aligned.m8n8.x4.shared.b16 [%0], {%1,%2,%3,%4};" ::"r"(addr), "r"(a), "r"(b), "r"(c), "r"(d) : "memory");
}
__device__ __forceinline__ void sts1(uint32_t addr, uint32_t a) { asm volatile("st.shared.b32 [%0], %1;" ::"r"(addr), "r"(a) : "memory"); }
__device__ __forceinline__ uint32_t lds1(uint32_t addr) {
    uint32_t a;
    asm volatile("ld.shared.b32 %0, [%1];" : "=r"(a) : "r"(addr) : "memory");
    return a;
}
__device__ __forceinline__ void stg1(uint8_t* p, uint32_t a) { asm volatile("st.global.b32 [%0], %1;" ::"l"(p), "r"(a) : "memory"); }
__device__ __forceinline__ void st_part(uint8_t* p, const uint32_t* v, uint32_t parity) {
    asm volatile("{\n.reg .b64 x, y;\nmov.b64 x, {%1, %2};\nmov.b64 y, {%3, %4};\nst.relaxed.gpu.global.v2.b64 [%0], {x, y};\n}\n"
                 ::"l"(p), "r"((v[0] & ~1u) | parity), "r"(v[1]), "r"((v[2] & ~1u) | parity), "r"(v[3]) : "memory");
}
__device__ __forceinline__ void mma16816(float (&d)[4], const uint32_t (&a)[4], uint32_t b0, uint32_t b1) {
    asm volatile("mma.sync.aligned.m16n8k16.row.col.f32.bf16.bf16.f32 {%0,%1,%2,%3}, {%4,%5,%6,%7}, {%8,%9}, {%0,%1,%2,%3};"
                 : "+f"(d[0]), "+f"(d[1]), "+f"(d[2]), "+f"(d[3]) : "r"(a[0]), "r"(a[1]), "r"(a[2]), "r"(a[3]), "r"(b0), "r"(b1));
}
__device__ __forceinline__ uint32_t add2(uint32_t a, uint32_t b) {
    uint32_t r;
    asm("add.rn.bf16x2 %0, %1, %2;" : "=r"(r) : "r"(a), "r"(b));
    return r;
}
__device__ __forceinline__ uint32_t max2(uint32_t a, uint32_t b) {
    uint32_t r;
    asm("max.bf16x2 %0, %1, %2;" : "=r"(r) : "r"(a), "r"(b));
    return r;
}
__device__ __forceinline__ void ld_tagged(const uint8_t* p, uint32_t& a, uint32_t& ta, uint32_t& b, uint32_t& tb) {
    asm volatile("{\n.reg .b64 x, y;\nld.relaxed.gpu.global.v2.b64 {x, y}, [%4];\nmov.b64 {%0, %1}, x;\nmov.b64 {%2, %3}, y;\n}\n"
                 : "=r"(a), "=r"(ta), "=r"(b), "=r"(tb) : "l"(p) : "memory");
}
__device__ __forceinline__ float bf_lo(uint32_t v) { return __uint_as_float(v << 16); }
__device__ __forceinline__ float bf_hi(uint32_t v) { return __uint_as_float(v & 0xFFFF0000u); }
__device__ __forceinline__ float rcp(float x) { float r; asm("rcp.approx.ftz.f32 %0, %1;" : "=f"(r) : "f"(x)); return r; }
__device__ __forceinline__ float ex2(float x) { float r; asm volatile("ex2.approx.ftz.f32 %0, %1;" : "=f"(r) : "f"(x)); return r; }

__device__ __forceinline__ uint32_t full_bar(int stage) { return base + BAR_FULL + (stage & 7) * 8; }
__device__ __forceinline__ void wait_released(int j) { mbar_wait(base + BAR_EMPTY + (j & 7) * 8, (j >> 3) & 1); }

template <int V>
struct Int { static constexpr int value = V; };

__host__ __device__ constexpr int bslot_e(int i) { return (i < 2 || i >= 14) ? (i + 5) % 7 : (i + 1) % 5; }
__host__ __device__ constexpr int bslot_l(int i) { return i % 6; }

template <uint32_t OFF>
struct Feed {
    int stage;
    uint32_t dst;
    __device__ __forceinline__ void seek(int i, int slot) { stage = i; dst = base + OFF + slot * SLOT; }
    template <int N>
    __device__ __forceinline__ uint32_t acquire() { wait_released(stage - N); return full_bar(stage); }
    template <int N>
    __device__ __forceinline__ void next() {
        stage++;
        dst += SLOT;
        if (dst == base + OFF + N * SLOT) dst = base + OFF;
    }
};
__device__ __forceinline__ int skip_own(int n, int mt) { return n == mt ? 15 : n; }

struct Desc { uint32_t lo, hi; };
__host__ __device__ constexpr Desc desc_const(uint32_t lbo, uint32_t sbo, uint32_t mode) { return {(lbo >> 4) << 16, (sbo >> 4) | (mode << 30)}; }
constexpr Desc D_K128 = desc_const(16, 1024, 1);
constexpr Desc D_N128 = desc_const(8192, 1024, 1);
constexpr Desc D_BLOB = desc_const(128, 256, 0);
constexpr Desc D_OT = desc_const(2048, 128, 0);

enum Kind { XW, XWN, QK, BIG, OUT };

struct Ring {
    int stage;
    uint32_t a, b;
    uint32_t wg;
    uint32_t zero;
    __device__ __forceinline__ void seek(int i, int bslot) {
        stage = i;
        a = (base + (i % NA) * SLOT) >> 4;
        b = (base + BRING + bslot * SLOT) >> 4;
    }
    __device__ __forceinline__ void wait() { mbar_wait(full_bar(stage), (stage >> 3) & 1); }
    __device__ __forceinline__ void take_turn() { nb_sync(1 + wg, 256); }
    __device__ __forceinline__ void pin() {
        uint32_t n = 0;
#pragma unroll 1
        do {
            asm volatile("pmevent 7;" ::: "memory");
        } while (n++ < zero);
    }
    template <Kind K, int NBS, bool INIT, int SB = 1, bool TAIL = false>
    __device__ __forceinline__ void run(float (&d)[56], float (&e)[56], bool first = true, bool last = true, bool more = true) {
        if (first) take_turn();
        asm volatile("wgmma.fence.sync.aligned;" ::: "memory");
        if (K == QK) {
            const uint32_t da = D_K128.lo + (base >> 4) + (stage >> 1) * (SLOT >> 4) + (stage & 1) * 4 + wg * 512, db = D_N128.lo + b;
            wgmma112<0, 1, 1, INIT, D_K128.hi, D_N128.hi>(d, da, db);
            wgmma112<0, 1, 1, INIT, D_K128.hi, D_N128.hi>(e, da, db + 256);
            wgmma112<0, 1, 1, false, D_K128.hi, D_N128.hi>(d, da + 2, db + 128);
            wgmma112<0, 1, 1, false, D_K128.hi, D_N128.hi>(e, da + 2, db + 384);
        } else {
            constexpr int TA = K == OUT, TB = K != XW;
            constexpr uint32_t sa = K == OUT ? 256 : 2, sb = K == XW ? 2 : K == BIG ? 224 : 128;
            constexpr Desc A = K == OUT ? D_OT : D_K128, B = K == XW ? D_K128 : K == BIG ? D_BLOB : D_N128;
            const uint32_t da = A.lo + a + wg * (K == OUT ? 64 : 512), db = B.lo + b;
            wgmma112<TA, TB, SB, INIT, A.hi, B.hi>(d, da, db);
            wgmma112<TA, TB, SB, false, A.hi, B.hi>(d, da + sa, db + sb);
            wgmma112<TA, TB, SB, false, A.hi, B.hi>(d, da + 2 * sa, db + 2 * sb);
            wgmma112<TA, TB, SB, false, A.hi, B.hi>(d, da + 3 * sa, db + 3 * sb);
        }
        asm volatile("wgmma.commit_group.sync.aligned;" ::: "memory");
        if (last) nb_arrive(2 - wg, 256);
        if (!TAIL) asm volatile("wgmma.wait_group.sync.aligned 1;" ::: "memory");
        if (!TAIL && stage > 0 && elect()) mbar_arrive(base + BAR_EMPTY + ((stage - 1) & 7) * 8);
        stage++;
        a += SLOT >> 4;
        if (a == (base + NA * SLOT) >> 4) a = base >> 4;
        b += SLOT >> 4;
        if (b == (base + BRING + NBS * SLOT) >> 4) b = (base + BRING) >> 4;
        if (more) wait();
    }
    template <Kind K, int NBS, bool INIT, int SB = 1, bool TAIL = false>
    __device__ __forceinline__ void run(float (&d)[56], bool first = true, bool last = true, bool more = true) {
        run<K, NBS, INIT, SB, TAIL>(d, d, first, last, more);
    }
};

__device__ __forceinline__ void pack_all(const float (&d)[56], uint32_t (&p)[28]) {
#pragma unroll
    for (int i = 0; i < 28; i++) p[i] = pack2(d[2 * i], d[2 * i + 1]);
}
template <int I0, int I1>
__device__ __forceinline__ void store_frags(uint8_t* dst, const uint32_t (&p)[28]) {
#pragma unroll
    for (int i = I0; i < I1; i++) stg1(dst + i * 128, p[i]);
}
template <int I0, int I1>
__device__ __forceinline__ void stage_frags(uint32_t lane_addr, const uint32_t (&p)[28]) {
#pragma unroll
    for (int i = I0; i < I1; i += 4) stsm4(lane_addr + i * 128, p[i], p[i + 1], p[i + 2], p[i + 3]);
}
template <class F>
__device__ __forceinline__ void store_out(F frag, int lane, uint32_t slab, const CUtensorMap* m, int c0, int c1) {
    const bool swap = lane & 16;
    const uint32_t addr = slab + (lane & 7) * 224 + ((lane >> 3) ^ ((lane >> 2) & 1)) * 16;
#pragma unroll
    for (int h = 0; h < 2; h++) {
#pragma unroll
        for (int c = 0; c < 14; c += 4) {
            const uint32_t t0 = frag(2 * c + h), t1 = frag(2 * c + 2 + h);
            if (c < 12) {
                const uint32_t t2 = frag(2 * c + 4 + h), t3 = frag(2 * c + 6 + h);
                stsm4(addr + h * 1792 + c * 16, swap ? t1 : t0, swap ? t0 : t1, swap ? t3 : t2, swap ? t2 : t3);
            } else {
                asm volatile("stmatrix.sync.aligned.m8n8.x2.shared.b16 [%0], {%1,%2};" ::"r"(addr + h * 1792 + c * 16), "r"(swap ? t1 : t0), "r"(swap ? t0 : t1) : "memory");
            }
        }
        fence_async_smem();
        __syncwarp();
        if (elect()) tma_st2(m, c0, c1 + 8 * h, slab + h * 1792);
    }
    if (elect()) {
        bulk_commit();
        bulk_wait_read();
    }
}
__host__ __device__ constexpr int tile_of(int t) { return 7 * (t >> 2) + 3 * ((t >> 1) & 1) + 2 * (t & 1); }

struct Role {
    bool H;
    int L, mt, ns, id;
};
template <bool BY_SM>
__device__ __forceinline__ Role decode_role() {
    uint32_t sm;
    if (BY_SM) asm volatile("mov.u32 %0, %%smid;" : "=r"(sm));
    else asm volatile("mov.u32 %0, %%ctaid.x;" : "=r"(sm));
    const int tpc = sm >> 1, q2 = ((tpc - 32) * 37) >> 8;
    const int gpc = tpc < 32 ? tpc & 7 : tpc < 60 ? tpc - 31 - 7 * q2 : 0;
    const int pos = tpc < 32 ? tpc >> 3 : tpc < 60 ? q2 + 4 : tpc - 56;
    Role r;
    r.H = sm >= 128;
    r.L = gpc & 1;
    r.mt = (gpc >> 1) * 4 + (pos >> 1);
    r.ns = (pos & 1) * 2 + (sm & 1);
    r.id = r.H ? sm : gpc * 16 + pos * 2 + (sm & 1);
    return r;
}

template <int I0, int I1>
__device__ __forceinline__ void first_fill(const Maps& maps, const Role& r) {
    if (r.L) {
#pragma unroll
        for (int i = I0; i < I1; i++) {
            const uint32_t bar = full_bar(i), dst = base + BRING + i * SLOT;
            if (i < 6) mbar_expect(bar, SLOT);
            if (i & 1) {
                mbar_arrive(bar);
            } else {
                mbar_expect(bar, SLOT);
                tma_ld2(base + (i >> 1) * SLOT, &maps.m[M_XA], (r.mt >> 3) * 448 + i * 32, (r.mt & 7) * 128, bar);
            }
            if (i < 6) {
                tma_ld4(dst, &maps.m[M_WQK], 0, i * 32, 0, r.ns, bar);
                tma_ld4(dst + 8192, &maps.m[M_WQK], 64, i * 32, 0, r.ns, bar);
            }
        }
    } else if (!r.H) {
#pragma unroll
        for (int i = I0; i < I1; i++) {
            const uint32_t bar = full_bar(i);
            mbar_expect(bar, SLOT);
            tma_ld3(base + i * SLOT, &maps.m[M_XB], i * 64, r.mt * 64, 0, bar);
            mbar_expect(bar, BLOB);
            tma_ld2(base + BRING + bslot_e(i) * SLOT, &maps.m[M_WR], i * 64, r.ns * 112, bar);
        }
    } else {
#pragma unroll 1
        for (int i = I0; i < I1; i++) {
            const uint32_t bar = full_bar(i), dst = base + BRING + i * SLOT;
            mbar_expect(bar, SLOT);
            mbar_expect(bar, SLOT);
            tma_ld4(base + i * SLOT, &maps.m[M_XH], i * 64, 120, 0, 0, bar);
            tma_ld3(dst, &maps.m[M_WV], 0, i * 64, 4 + r.ns, bar);
            tma_ld3(dst + 8192, &maps.m[M_WV], 64, i * 64, 4 + r.ns, bar);
        }
    }
}

template <bool BY_SM>
__global__ void __launch_bounds__(384, 1) fused_kernel(Scratch* sc, const __grid_constant__ Maps maps) {
    const int warp = __shfl_sync(0xffffffffu, threadIdx.x >> 5, 0);
    const Role role = decode_role<BY_SM>();
    if (warp == OPENER) {
        if (elect()) {
            asm volatile("prefetch.tensormap [%0];" ::"l"(&maps.m[M_XB]) : "memory");
            asm volatile("prefetch.tensormap [%0];" ::"l"(&maps.m[M_XA]) : "memory");
            asm volatile("prefetch.tensormap [%0];" ::"l"(&maps.m[M_WR]) : "memory");
            asm volatile("prefetch.tensormap [%0];" ::"l"(&maps.m[M_WQK]) : "memory");
#pragma unroll
            for (int i = 0; i < 8; i++) mbar_init(base + BAR_FULL + i * 8, 2);
            asm volatile("fence.mbarrier_init.release.cluster;" ::: "memory");
            first_fill<0, LEAD>(maps, role);
        }
    }
    int lane = threadIdx.x & 31;
    asm volatile("" : "+r"(lane));
    const bool roleH = role.H;
    const int roleL = role.L, mt = role.mt, ns = role.ns, bid = role.id;
    const int par = mt >> 3, blk = mt & 7, col = ns * 112;
    if (warp == 9) {
        if (elect()) {
#pragma unroll
            for (int i = 0; i < 8; i++) mbar_init(base + BAR_EMPTY + i * 8, 8);
            asm volatile("fence.mbarrier_init.release.cluster;" ::: "memory");
        }
    } else if (warp == 10) {
        if (elect()) {
#pragma unroll
            for (int i = 0; i < 5; i++) mbar_init(base + BAR_RDY + i * 8, i < 2 ? 4 : 8);
#pragma unroll
            for (int i = 0; i < 2; i++) mbar_init(base + BAR_HALO + i * 8, 9);
            asm volatile("fence.mbarrier_init.release.cluster;" ::: "memory");
        }
    } else if (warp == 11) {
        if (elect()) {
#pragma unroll
            for (int i = 0; i < 3; i++) mbar_init(base + BAR_DEP + i * 8, 1);
#pragma unroll
            for (int i = 0; i < 2; i++) mbar_init(base + BAR_PART + i * 8, 1);
            asm volatile("fence.mbarrier_init.release.cluster;" ::: "memory");
        }
    }
    __syncthreads();

    if (__builtin_expect(warp >= 8, 1)) {
        asm volatile("setmaxnreg.dec.sync.aligned.u32 56;");
#define PROF_FEED_A
#define PROF_FEED_B
        if (__builtin_expect(warp == 8, 1)) {
            if (elect()) {
                PROF(129);
                first_fill<LEAD, 7>(maps, role);
                PROF(134);
                Feed<0> f;
                const int row = mt * 128;
                auto c_run = [&](const CUtensorMap* m, int off, int n0, int n1) {
#pragma unroll 1
                    for (int n = n0; n < n1; n++) {
                        const uint32_t bar = f.acquire<NA>();
                        mbar_expect(bar, SLOT);
                        tma_ld2(f.dst, m, (off + skip_own(n, mt)) * 64, row, bar);
                        PROF_FEED_A;
                        f.next<NA>();
                    }
                };
                if (roleH) {
                } else if (!roleL) {
                    f.seek(14, 0);
                    mbar_wait(base + BAR_RDY, 0);
#pragma unroll 1
                    for (int i = 0; i < 4; i++) {
                        const uint32_t bar = f.acquire<NA>();
                        mbar_expect(bar, SLOT);
                        tma_ld2(f.dst, &maps.m[M_CR + (i >> 1)], ((i & 1) * 16 + mt) * 64, row, bar);
                        mbar_arrive(bar);
                        PROF_FEED_A;
                        f.next<NA>();
                    }
                    c_run(&maps.m[M_CR], 0, 0, 15);
                    c_run(&maps.m[M_CI], 0, 0, NBE);
                    wait_dep(2);
#pragma unroll 1
                    for (int i = 0; i < 7; i++) {
                        const uint32_t bar = f.acquire<NA>();
                        mbar_expect(bar, SLOT);
                        bulk_ld(f.dst, sc->o + (size_t)(mt * 7 + i) * SLOT, SLOT, bar);
                        PROF_FEED_A;
                        f.next<NA>();
                    }
                } else {
#pragma unroll 1
                    for (int i = 4; i < 7; i++) {
                        wait_released(2 * i - 8);
                        mbar_expect(full_bar(2 * i), SLOT);
                        tma_ld2(base + i * SLOT, &maps.m[M_XA], par * 448 + i * 64, blk * 128, full_bar(2 * i));
                    }
                    wait_released(HALO_K_AT);
                    mbar_arrive(base + BAR_DEP + 16);
                    f.seek(21, 0);
                    c_run(&maps.m[M_CR], 16, 0, 15);
                    c_run(&maps.m[M_CI], 16, 0, 15);
                    c_run(&maps.m[M_CI], 0, NBE, 15);
                }
            }
        } else if (warp == 11) {
            if (elect()) {
                Feed<BRING> f;
                auto blob_run = [&](auto nbs, int quarter, int n0, int n1) {
                    constexpr int N = decltype(nbs)::value;
                    const uint8_t* src = sc->ab + (size_t)(quarter * 64 + ns) * BLOB;
#pragma unroll 1
                    for (int n = n0; n < n1; n++) {
                        const uint32_t bar = f.template acquire<N>();
                        mbar_expect(bar, BLOB);
                        bulk_ld(f.dst, src + skip_own(n, mt) * (4 * BLOB), BLOB, bar);
                        PROF_FEED_B;
                        f.template next<N>();
                    }
                };
                auto w_run = [&](auto nbs, const CUtensorMap* m, int slice, bool no_a) {
                    constexpr int N = decltype(nbs)::value;
#pragma unroll 1
                    for (int i = 0; i < 7; i++) {
                        const uint32_t bar = f.template acquire<N>();
                        mbar_expect(bar, SLOT);
                        tma_ld3(f.dst, m, 0, i * 64, slice, bar);
                        tma_ld3(f.dst + 8192, m, 64, i * 64, slice, bar);
                        if (no_a) mbar_arrive(bar);
                        PROF_FEED_B;
                        f.template next<N>();
                    }
                };
                if (roleH) {
                    f.seek(7, 0);
                    w_run(Int<7>(), &maps.m[M_WV], 8 + ns, true);
                } else if (!roleL) {
                    f.seek(7, bslot_e(7));
#pragma unroll 1
                    for (int i = 0; i < 7; i++) {
                        const uint32_t bar = f.acquire<5>();
                        mbar_expect(bar, BLOB);
                        tma_ld2(f.dst, &maps.m[M_WI], i * 64, col, bar);
                        mbar_arrive(bar);
                        PROF_FEED_B;
                        f.next<5>();
                    }
                    f.seek(18, bslot_e(18));
                    wait_dep(0);
                    blob_run(Int<7>(), 0, 0, 15);
                    wait_dep(1);
                    blob_run(Int<7>(), 2, 0, NBE);
                    w_run(Int<7>(), &maps.m[M_WO], ns, false);
                } else {
                    f.seek(6, 0);
#pragma unroll 1
                    for (int i = 6; i < 14; i++) {
                        const uint32_t bar = f.acquire<6>();
                        mbar_expect(bar, SLOT);
                        tma_ld4(f.dst, &maps.m[M_WQK], 0, i * 32, 0, ns, bar);
                        tma_ld4(f.dst + 8192, &maps.m[M_WQK], 64, i * 32, 0, ns, bar);
                        if (i & 1) mbar_arrive(bar);
                        PROF_FEED_B;
                        f.next<6>();
                    }
                    w_run(Int<6>(), &maps.m[M_WV], 8 + ns, true);
                    wait_dep(0);
                    blob_run(Int<6>(), 1, 0, 15);
                    wait_dep(1);
                    blob_run(Int<6>(), 3, 0, 15);
                    blob_run(Int<6>(), 2, NBE, 15);
                }
            }
        } else if (roleH) {
        } else if (warp == 10) {
            if (elect()) {
                unsigned* epoch_ptr = &sc->epoch[(bid * 4 + 2) * 8];
                const unsigned ep = *epoch_ptr + 1;
                sts1(base + TAG, ep);
                asm volatile("prefetch.tensormap [%0];" ::"l"(&maps.m[M_OUTA + roleL]) : "memory");
                await(sc, CNT_A + roleL * 4 + ns, ep * 16);
                mbar_arrive(base + BAR_DEP);
                PROF(150);
                await(sc, CNT_B + ns, ep * 16);
                mbar_arrive(base + BAR_DEP + 8);
                PROF(151);
                if (!roleL) {
                    await(sc, CNT_O + mt, ep * 4);
                    mbar_arrive(base + BAR_DEP + 16);
                } else {
                    await(sc, CNT_P + mt * 4 + ns, ep * 2 - 1);
                    mbar_arrive(base + BAR_PART);
                    PROF(153);
                    await(sc, CNT_P + mt * 4 + ns, ep * 2);
                    mbar_arrive(base + BAR_PART + 8);
                }
                PROF(152);
                *epoch_ptr = ep;
            }
        } else if (!roleL) {
            if (elect()) {
                mbar_wait(base + BAR_RDY, 0);
                PROF(130);
                signal(sc, CNT_A + ns);
                PROF(131);
                mbar_wait(base + BAR_RDY + 8, 0);
                signal(sc, CNT_A + 4 + ns);
                PROF(135);
                mbar_wait(base + BAR_RDY + 32, 0);
                PROF(132);
                signal(sc, CNT_B + ns);
                PROF(133);
            }
        } else {
            unsigned* epoch_ptr = &sc->epoch[(bid * 4 + 1) * 8];
            const unsigned tag = *epoch_ptr + 1;
#pragma unroll 1
            for (int kv = 0; kv < 2; kv++) {
                uint32_t v[16];
#pragma unroll
                for (int i = 0; i < 16; i++) v[i] = 0;
                if (kv) mbar_wait(base + BAR_HALO, 0), wait_released(HALO_V_AT);
                else mbar_wait(base + BAR_DEP + 16, 0);
                if (blk > 0) {
                    const uint8_t* src = sc->halo + (size_t)(((mt - 1) * 4 + ns) * 2 + kv) * 2048 + lane * 16;
#pragma unroll 1
                    for (int n = 0; n < SPIN_LIMIT; n++) {
                        uint32_t stale = 0;
#pragma unroll
                        for (int i = 0; i < 4; i++) ld_tagged(src + i * 512, v[4 * i], v[4 * i + 1], v[4 * i + 2], v[4 * i + 3]);
#pragma unroll
                        for (int i = 0; i < 16; i += 2) stale |= v[i] ^ tag;
                        if (__all_sync(0xffffffffu, !(stale & 1))) break;
                    }
#pragma unroll
                    for (int c = 0; c < 14; c += 2) v[c] = (v[c] & ~1u) | ((v[15] >> c) & 1);
                }
#pragma unroll
                for (int i = 0; i < 14; i++) sts1(base + HALO + kv * (8 * HSLOT) + i * 128 + lane * 4, v[i]);
                warp_arrive(base + BAR_HALO + kv * 8);
                if (lane == 0) PROF(142 + kv);
            }
            if (elect()) {
                mbar_wait(base + BAR_RDY + 16, 0);
                PROF(130);
                signal(sc, CNT_O + mt);
                PROF(131);
                *epoch_ptr = tag;
            }
        }
    } else {
        asm volatile("setmaxnreg.inc.sync.aligned.u32 224;");
        Ring r;
        r.wg = warp >> 2;
        r.zero = blockIdx.y;
        const int wg = warp >> 2;
        if (wg) nb_arrive(1, 256);
        r.stage = 0;
        r.wait();
        uint8_t* part = sc->part + (size_t)(ns * 16 + mt) * (2 * BLOB) + warp * 512 + lane * 16;
        uint32_t p[28];

        if (roleH) {
            unsigned* epoch_ptr = &sc->epoch[bid * 4 * 8];
            const unsigned tag = *epoch_ptr + 1;
            uint8_t* hout = sc->halo + (size_t)((warp * 8 + ns) * 2) * 2048 + lane * 16;
            auto send = [&](int kv) {
#pragma unroll
                for (int h = 0; h < 2; h++) {
                    uint32_t v[16];
                    v[14] = v[15] = 0;
#pragma unroll
                    for (int c = 0; c < 14; c++) v[c] = p[2 * c + h];
#pragma unroll
                    for (int c = 0; c < 14; c += 2) v[15] |= (v[c] & 1) << c;
#pragma unroll
                    for (int i = 0; i < 4; i++) st_part(hout + (h * 8 + kv) * 2048 + i * 512, v + 4 * i, tag & 1);
                }
            };
            float x0[56], x1[56];
            r.seek(0, 0);
            r.run<XWN, 7, true>(x0);
#pragma unroll 1
            for (int i = 1; i < 7; i++) r.run<XWN, 7, false>(x0);
            r.run<XWN, 7, true>(x1);
            acc_fence(x0);
            pack_all(x0, p);
            send(0);
#pragma unroll 1
            for (int i = 1; i < 7; i++) r.run<XWN, 7, false>(x1, true, true, i < 6);
            asm volatile("wgmma.wait_group.sync.aligned 0;" ::: "memory");
            acc_fence(x1);
            pack_all(x1, p);
#pragma unroll
            for (int i = 0; i < 28; i++) p[i] = movm(p[i]);
            send(1);
            if (threadIdx.x == 0) *epoch_ptr = tag;
        } else if (!roleL) {
            uint8_t* blob = sc->ab + (size_t)((wg * 16 + mt) * 4 + ns) * BLOB + (warp & 3) * WSLOT + lane * 4;
            const uint32_t own = base + BRING + wg * SLOT + (warp & 3) * WSLOT + lane * 16;
            float x0[56], x1[56];
            r.seek(0, bslot_e(0));
            r.run<XW, 7, true>(x0);
            r.run<XW, 7, false>(x0);
            r.seek(2, bslot_e(2));
#pragma unroll 1
            for (int i = 2; i < 7; i++) r.run<XW, 5, false>(x0);

            r.seek(7, bslot_e(7));
            r.run<XW, 5, true, -1>(x1);
            acc_fence(x0);
            pack_all(x0, p);
#pragma unroll
            for (int i = 0; i < 2; i++) {
                if (wg == i) store_frags<0, 14>(blob, p);
                else stage_frags<0, 4>(own + 5 * SLOT, p);
                r.run<XW, 5, false, -1>(x1);
                if (wg == i) {
                    store_frags<14, 28>(blob, p);
                    warp_arrive(base + BAR_RDY + i * 8);
                } else {
                    stage_frags<4, 8>(own + 5 * SLOT, p);
                }
                r.run<XW, 5, false, -1>(x1);
            }
            stage_frags<8, 20>(own + 5 * SLOT, p);
            r.run<XW, 5, false, -1>(x1);
            stage_frags<20, 28>(own + 5 * SLOT, p);
            warp_arrive(base + BAR_RDY + 16);
            r.run<XW, 5, false, -1>(x1);

            mbar_wait(base + BAR_RDY + 16, 0);
            fence_async_smem();
            r.seek(14, bslot_e(14));
            r.run<BIG, 7, true>(x0);
            acc_fence(x1);
            pack_all(x1, p);
            wait_released(10);
            stage_frags<0, 28>(own, p);
            warp_arrive(base + BAR_RDY + 24);
            r.run<BIG, 7, false>(x0);
            mbar_wait(base + BAR_RDY + 24, 0);
            fence_async_smem();
            blob += (size_t)128 * BLOB;
#pragma unroll
            for (int i = 0; i < 28; i++) {
                if (i % B_SLICE == 0) r.run<BIG, 7, false>(x0);
                stg1(blob + i * 128, p[i]);
            }
            warp_arrive(base + BAR_RDY + 32);
#pragma unroll 1
            for (int i = 17 + 27 / B_SLICE; i < POUT; i++) r.run<BIG, 7, false>(x0);

            const uint32_t tag = lds1(base + TAG);
            r.seek(POUT, bslot_e(POUT));
            r.run<OUT, 7, true>(x1);
            acc_fence(x0);
            pack_all(x0, p);
#pragma unroll
            for (int k = 0; k < 3; k++) {
                if (k < 2 && wg == k) {
                    if ((warp & 3) == 0 && elect())
                        asm volatile("red.relaxed.gpu.global.add.u32 [%0], 1;" ::"l"(&sc->cnt[(CNT_P + mt * 4 + ns) * 32]) : "memory");
#pragma unroll
                    for (int i = 0; i < 4; i++) st_part(part + i * 4096, p + 4 * i, tag & 1);
                }
                if (k > 0 && wg == k - 1) {
#pragma unroll
                    for (int i = 4; i < 7; i++) st_part(part + i * 4096, p + 4 * i, tag & 1);
                }
                if (k < 2) r.run<OUT, 7, false>(x1);
            }
#pragma unroll
            for (int i = 3; i < 7; i++) r.run<OUT, 7, false, 1, true>(x1, i <= 7 - TURN, i < 7 - TURN || i == 6, i < 6);

            wait_released(ELAST - 6);
            asm volatile("wgmma.wait_group.sync.aligned 0;" ::: "memory");
            acc_fence(x1);
            const uint32_t slab = base + (wg ? BRING + bslot_e(ELAST - 6) * SLOT : ((ELAST - 6) % NA) * SLOT) + (warp & 3) * WSLOT;
            store_out([&](int i) { return pack2(x1[2 * i], x1[2 * i + 1]); }, lane, slab, &maps.m[M_OUTA], par * 896 + col, blk * 128 + warp * 16);
        } else {
            const int g = lane >> 2, tig = lane & 3;
            const uint32_t hin = base + HALO + warp * HSLOT + lane * 4;
            const uint32_t hpub = warp < 7 ? hin + HSLOT : base + HSPARE + lane * 4;
            auto publish = [&](const uint32_t (&h)[14], int c0, int c1) {
#pragma unroll
                for (int c = 0; c < 14; c++)
                    if (c >= c0 && c < c1) sts1(hpub + c * 128, h[c]);
            };
            float y0[56], y1[56], y2[56];
            r.seek(0, 0);
            r.run<QK, 6, true>(y0, y1);
#pragma unroll 1
            for (int i = 1; i < 14; i++) r.run<QK, 6, false>(y0, y1);

            uint32_t m1[8][4], m0[8][4], lo[14], hi[14], q[2][8][2];
            auto pack_q = [&](int b) {
                uint32_t v[14];
#pragma unroll
                for (int c = 0; c < 14; c++) v[c] = pack2(y0[4 * c + 2 * b], y0[4 * c + 2 * b + 1]);
#pragma unroll
                for (int t = 0; t < 8; t++) {
                    const int c = tile_of(t);
                    q[b][t][0] = (t & 3) == 2 ? (tig >= 2 ? v[c] : 0u) : v[c];
                    q[b][t][1] = (t & 3) == 1 ? (tig < 2 ? v[c + 1] : 0u) : v[c + 1];
                }
            };
            auto fetch = [&](uint32_t src, int hp, int i0) {
#pragma unroll
                for (int t = 4 * hp; t < 4 * hp + 4; t++) {
                    m0[t][i0] = (t & 3) == 2 ? dup(m0[t - 1][3], r.zero) : lds1(src + tile_of(t) * 128);
                    m0[t][3] = lds1(src + tile_of(t) * 128 + 128);
                }
            };
            r.seek(14, bslot_l(14));
            r.run<XWN, 6, true>(y2);
            acc_fence(y0);
            acc_fence(y1);
#pragma unroll
            for (int c = 0; c < 14; c++) hi[c] = pack2(y1[4 * c + 2], y1[4 * c + 3]);
            publish(hi, 0, 7);
            PIN;
            r.run<XWN, 6, false>(y2);
            publish(hi, 7, 14);
            warp_arrive(base + BAR_HALO);
#pragma unroll
            for (int c = 0; c < 14; c++) lo[c] = pack2(y1[4 * c], y1[4 * c + 1]);
#pragma unroll
            for (int t = 0; t < 8; t++) {
                const int c = tile_of(t);
                const bool shared = (t & 3) == 2;
                m1[t][0] = shared ? dup(lo[c], r.zero) : lo[c];
                m1[t][1] = shared ? dup(hi[c], r.zero) : hi[c];
                m1[t][2] = lo[c + 1];
                m1[t][3] = hi[c + 1];
                m0[t][0] = dup(m1[t][0], r.zero);
                m0[t][2] = dup(lo[c + 1], 2 * r.zero);
            }
            PIN;
            r.run<XWN, 6, false>(y2);
            mbar_wait(base + BAR_HALO, 0);
            fetch(hin, 0, 1);
            pack_q(1);
            PIN;
            r.run<XWN, 6, false>(y2);
            fetch(hin, 1, 1);
            pack_q(0);
            r.pin();
            r.take_turn();
            float s[8][4];
#pragma unroll
            for (int step = 0; step < 2; step++) {
#pragma unroll
                for (int i = 0; i < 8; i++) {
                    const int b = 1 - (i >> 2), h = i & 3, t = 2 * h + step;
                    float (&d)[4] = s[2 * h + b];
                    if (step == 0) d[0] = d[1] = d[2] = d[3] = 0.f;
                    mma16816(d, b ? m1[t] : m0[t], q[b][t][0], q[b][t][1]);
                }
            }
            r.pin();
            r.run<XWN, 6, false>(y2, false);

            uint32_t pr[8], mx[4], mx1[4];
            {
                const bool cur0 = g <= 2 * tig, cur1 = g <= 2 * tig + 1;
#pragma unroll
                for (int i = 0; i < 8; i++) {
                    const int c = (i & 1) ? 2 : 0;
                    pr[i] = movm(pack2(cur0 ? s[i][c] : s[i][2 - c], cur1 ? s[i][c + 1] : s[i][3 - c]));
                }
            }
            PIN;
            r.run<XWN, 6, false>(y2);
            const uint32_t curmask = (2 * tig <= g ? 0x0000FFFFu : 0u) | (2 * tig + 1 <= g ? 0xFFFF0000u : 0u);
            {
                const uint32_t keep = (blk == 0 && warp == 0) ? curmask : 0xFFFFFFFFu;
#pragma unroll
                for (int i = 0; i < 4; i++) {
                    pr[2 * i] = (pr[2 * i] & keep) | (0xCF9ECF9Eu & ~keep);
                    mx[i] = max2(__byte_perm(pr[2 * i], pr[2 * i + 1], 0x5410), __byte_perm(pr[2 * i], pr[2 * i + 1], 0x7632));
                    mx1[i] = __shfl_xor_sync(0xffffffffu, mx[i], 1);
                }
            }
            PIN;
            r.run<XWN, 6, false>(y2);
#pragma unroll
            for (int i = 0; i < 4; i++) {
                mx[i] = max2(mx[i], mx1[i]);
                mx1[i] = __shfl_xor_sync(0xffffffffu, mx[i], 2);
            }

            PIN;
            r.seek(21, bslot_l(21));
            r.run<BIG, 6, true>(y0);
            acc_fence(y2);
#pragma unroll
            for (int c = 0; c < 10; c++) hi[c] = movm(pack2(y2[4 * c + 2], y2[4 * c + 3]));
            constexpr float SCL = 0.18898223650461362f * 1.4426950408889634f;
            float e0[8], e1[8], sm[8], sm1[8];
#pragma unroll
            for (int i = 0; i < 8; i++) {
                const uint32_t m2 = max2(mx[i >> 1], mx1[i >> 1]);
                sm[i] = ((i & 1) ? bf_hi(m2) : bf_lo(m2)) * -SCL;
            }
            PIN;
            r.run<BIG, 6, false>(y0);
#pragma unroll
            for (int c = 10; c < 14; c++) hi[c] = movm(pack2(y2[4 * c + 2], y2[4 * c + 3]));
#pragma unroll
            for (int c = 0; c < 4; c++) lo[c] = movm(pack2(y2[4 * c], y2[4 * c + 1]));
#pragma unroll
            for (int i = 0; i < 8; i++) e0[i] = ex2(fmaf(bf_lo(pr[i]), SCL, sm[i]));
            PIN;
            r.run<BIG, 6, false>(y0);
            publish(hi, 0, 10);
#pragma unroll
            for (int i = 0; i < 8; i++) e1[i] = ex2(fmaf(bf_hi(pr[i]), SCL, sm[i]));
            PIN;
            r.run<BIG, 6, false>(y0);
            publish(hi, 10, 14);
            warp_arrive(base + BAR_HALO + 8);
#pragma unroll
            for (int i = 0; i < 8; i++) {
                sm[i] = e0[i] + e1[i];
                sm1[i] = __shfl_xor_sync(0xffffffffu, sm[i], 1);
            }
            PIN;
            r.run<BIG, 6, false>(y0);
#pragma unroll
            for (int c = 4; c < 14; c++) lo[c] = movm(pack2(y2[4 * c], y2[4 * c + 1]));
            PIN;
            r.run<BIG, 6, false>(y0);
#pragma unroll
            for (int i = 0; i < 8; i++) {
                sm[i] += sm1[i];
                sm1[i] = __shfl_xor_sync(0xffffffffu, sm[i], 2);
            }
#pragma unroll
            for (int t = 0; t < 8; t++) {
                const int c = tile_of(t);
                const bool shared = (t & 3) == 2;
                m1[t][0] = shared ? dup(lo[c], r.zero) : lo[c];
                m1[t][1] = lo[c + 1];
                m1[t][2] = shared ? dup(hi[c], r.zero) : hi[c];
                m1[t][3] = hi[c + 1];
                m0[t][0] = dup(m1[t][0], r.zero);
                m0[t][1] = dup(lo[c + 1], 2 * r.zero);
            }
            PIN;
            r.run<BIG, 6, false>(y0);
            mbar_wait(base + BAR_HALO + 8, 0);
            const uint32_t vin = warp ? hin : hin + 8 * HSLOT;
            fetch(vin, 0, 2);
#pragma unroll
            for (int i = 0; i < 8; i++) {
                const float inv = rcp(sm[i] + sm1[i]);
                pr[i] = pack2(e0[i] * inv, e1[i] * inv);
            }
            PIN;
            r.run<BIG, 6, false>(y0);
            fetch(vin, 1, 2);
            uint32_t pb[8][2];
#pragma unroll
            for (int t = 0; t < 8; t++) {
                pb[t][t & 1] = band(pr[t], curmask);
                pb[t][1 - (t & 1)] = band(pr[t], ~curmask);
            }
            r.pin();
            r.take_turn();
            float o[2][8][4];
#pragma unroll
            for (int i = 0; i < 16; i++) {
                const int b = 1 - (i >> 3), t = i & 7;
                float (&d)[4] = o[b][t];
                d[0] = d[1] = d[2] = d[3] = 0.f;
                mma16816(d, b ? m1[t] : m0[t], pb[(t & 6) + b][0], pb[(t & 6) + b][1]);
            }
            r.pin();
            r.run<BIG, 6, false>(y0, false);
            uint8_t* odst = sc->o + (size_t)mt * 7 * SLOT + ns * (14 * 2048) + warp * 256 + lane * 4;
#pragma unroll
            for (int hp = 0; hp < 2; hp++) {
#pragma unroll
                for (int b = 0; b < 2; b++) {
                    const float (&u)[8][4] = o[b];
                    const int t = 4 * hp;
                    uint32_t* w = p + 14 * hp + b;
                    w[0] = pack2(u[t][0], u[t][1]);
                    w[2] = pack2(u[t][2], u[t][3]);
                    w[4] = pack2(u[t + 1][0], u[t + 1][1]);
                    w[6] = pack2(g < 4 ? u[t + 1][2] : u[t + 2][0], g < 4 ? u[t + 1][3] : u[t + 2][1]);
                    w[8] = pack2(u[t + 2][2], u[t + 2][3]);
                    w[10] = pack2(u[t + 3][0], u[t + 3][1]);
                    w[12] = pack2(u[t + 3][2], u[t + 3][3]);
                }
            }
#pragma unroll
            for (int i = 0; i < 28; i++) {
                if (i && i % O_SLICE == 0) r.run<BIG, 6, false>(y0);
                stg1(odst + (i >> 1) * 2048 + (i & 1) * 128, p[i]);
            }
            warp_arrive(base + BAR_RDY + 16);

#pragma unroll 1
            for (int i = 30 + 27 / O_SLICE; i <= LLAST + 1 - TURN; i++) r.run<BIG, 6, false>(y0, true, i <= LLAST - TURN);
            const uint32_t tag = lds1(base + TAG);
            if (mbar_test(base + BAR_PART + wg * 8, 0)) {
#pragma unroll
                for (int i = 0; i < 7; i++) ld_tagged(part + i * 4096, p[4 * i], p[4 * i + 1], p[4 * i + 2], p[4 * i + 3]);
            } else {
                p[0] = ~tag;
            }
            r.seek(LLAST + 2 - TURN, bslot_l(LLAST + 2 - TURN));
#pragma unroll
            for (int i = 1; i < TURN; i++) r.run<BIG, 6, false, 1, true>(y0, false, i == TURN - 1, i < TURN - 1);
#pragma unroll 1
            for (int n = 0; n < SPIN_LIMIT; n++) {
                uint32_t stale = 0;
#pragma unroll
                for (int i = 0; i < 28; i += 2) stale |= p[i] ^ tag;
                if (__all_sync(0xffffffffu, !(stale & 1))) break;
                mbar_wait(base + BAR_PART + wg * 8, 0);
#pragma unroll
                for (int i = 0; i < 7; i++) ld_tagged(part + i * 4096, p[4 * i], p[4 * i + 1], p[4 * i + 2], p[4 * i + 3]);
            }
            wait_released(LLAST - 6);
            asm volatile("wgmma.wait_group.sync.aligned 0;" ::: "memory");
            acc_fence(y0);
            const uint32_t slab = base + (wg ? HALO : ((LLAST - 6) % NA) * SLOT) + (warp & 3) * WSLOT;
            store_out([&](int i) { return add2(pack2(y0[2 * i], y0[2 * i + 1]), p[i]); }, lane, slab, &maps.m[M_OUTB], 448 + col, mt * 128 + warp * 16);
        }
    }
}

typedef CUresult (*EncodeFn)(CUtensorMap*, CUtensorMapDataType, cuuint32_t, void*, const cuuint64_t*, const cuuint64_t*,
                             const cuuint32_t*, const cuuint32_t*, CUtensorMapInterleave, CUtensorMapSwizzle,
                             CUtensorMapL2promotion, CUtensorMapFloatOOBfill);

struct Dim { uint64_t size, stride; uint32_t box; };
void encode(EncodeFn fn, CUtensorMap* m, const void* ptr, CUtensorMapSwizzle sw, Dim d0, Dim d1, Dim d2 = {0, 0, 0}, Dim d3 = {0, 0, 0}) {
    const cuuint64_t dims[4] = {d0.size, d1.size, d2.size, d3.size};
    const cuuint64_t strides[3] = {d1.stride, d2.stride, d3.stride};
    const cuuint32_t box[4] = {d0.box, d1.box, d2.box, d3.box};
    const cuuint32_t es[4] = {1, 1, 1, 1};
    fn(m, CU_TENSOR_MAP_DATA_TYPE_BFLOAT16, d3.size ? 4 : d2.size ? 3 : 2, const_cast<void*>(ptr), dims, strides, box, es,
       CU_TENSOR_MAP_INTERLEAVE_NONE, sw, CU_TENSOR_MAP_L2_PROMOTION_L2_128B, CU_TENSOR_MAP_FLOAT_OOB_FILL_NONE);
}

}

extern "C" void kernel_launch(void* const* d_in, const int* in_sizes, int n_in, void* d_out, int out_size) {
    (void)in_sizes; (void)n_in; (void)out_size;
    void* fnp = nullptr;
    cudaDriverEntryPointQueryResult st;
    cudaGetDriverEntryPoint("cuTensorMapEncodeTiled", &fnp, cudaEnableDefault, &st);
    EncodeFn fn = (EncodeFn)fnp;
    void* scratch = nullptr;
    cudaGetSymbolAddress(&scratch, g_scratch);
    int dev = 0, sms = 0;
    cudaGetDevice(&dev);
    cudaDeviceGetAttribute(&sms, cudaDevAttrMultiProcessorCount, dev);
    auto kernel = sms == 132 ? fused_kernel<true> : fused_kernel<false>;
    cudaFuncSetAttribute(kernel, cudaFuncAttributeMaxDynamicSharedMemorySize, SMEM_BYTES);

    const CUtensorMapSwizzle S128 = CU_TENSOR_MAP_SWIZZLE_128B, S0 = CU_TENSOR_MAP_SWIZZLE_NONE;
    Maps maps;
    encode(fn, &maps.m[M_XA], d_in[0], S128, {896, 2, 64}, {1024, 1792, 128});
    encode(fn, &maps.m[M_WQK], d_in[1], S128, {112, 2, 64}, {448, 2688, 32}, {3, 896, 2}, {4, 224, 1});
    encode(fn, &maps.m[M_WV], d_in[1], S128, {112, 2, 64}, {448, 2688, 64}, {12, 224, 1});
    encode(fn, &maps.m[M_XH], d_in[0], S128, {448, 2, 64}, {128, 1792, 8}, {8, 128 * 1792, 8}, {2, 896, 2});
    encode(fn, &maps.m[M_WO], d_in[2], S128, {112, 2, 64}, {448, 896, 64}, {4, 224, 1});
    encode(fn, &maps.m[M_XB], d_in[3], S128, {448, 2, 64}, {1024, 896, 64}, {2, 896 * 1024, 2});
    encode(fn, &maps.m[M_CR], d_in[4], S128, {2048, 2, 64}, {2048, 4096, 128});
    encode(fn, &maps.m[M_CI], d_in[5], S128, {2048, 2, 64}, {2048, 4096, 128});
    encode(fn, &maps.m[M_WR], d_in[6], S128, {448, 2, 64}, {448, 896, 112});
    encode(fn, &maps.m[M_WI], d_in[7], S128, {448, 2, 64}, {448, 896, 112});
    encode(fn, &maps.m[M_OUTA], d_out, S0, {1792, 2, 112}, {1024, 3584, 8});
    encode(fn, &maps.m[M_OUTB], d_out, S0, {896, 2, 112}, {2048, 1792, 8});

    kernel<<<132, 384, SMEM_BYTES>>>((Scratch*)scratch, maps);
}
```

```cpp
#include <cuda.h>
#include <cuda_bf16.h>
#include <cuda_runtime.h>
#include <stdint.h>

namespace {

constexpr uint32_t SLOT = 16384;
constexpr int NA = 7;
constexpr uint32_t BRING = NA * SLOT;
constexpr uint32_t HALO = BRING + 6 * SLOT;
constexpr uint32_t HSLOT = 1792;
constexpr uint32_t WSLOT = 3584;
constexpr uint32_t BLOB = 14336;
constexpr uint32_t BARS = 14 * SLOT;
constexpr uint32_t BAR_FULL = BARS;
constexpr uint32_t BAR_EMPTY = BARS + 64;
constexpr uint32_t BAR_RDY = BARS + 128;
constexpr uint32_t BAR_DEP = BARS + 168;
constexpr uint32_t BAR_HALO = BARS + 192;
constexpr uint32_t BAR_PART = BARS + 208;
constexpr uint32_t TAG = BARS + 224;
constexpr uint32_t HSPARE = BARS + 256 + 1024;
constexpr uint32_t SMEM_BYTES = HSPARE + HSLOT;
constexpr uint32_t base = 1024;
constexpr int SPIN_LIMIT = 1 << 16;

#define E_EXTRA 0
#define HALO_K_AT 10
#define HALO_V_AT 19
#define O_SLICE 4
#define B_SLICE 4
#define LEAD 3
#define TURN 4
#define PIN r.pin()
#define OPENER 8
#define PACE 0
#define MAPPING 2
constexpr int NBE = 13 + E_EXTRA;
constexpr int POUT = 33 + NBE;
constexpr int ELAST = POUT + 6;
constexpr int LLAST = 52 - E_EXTRA;

enum { M_XA, M_XH, M_WQK, M_WV, M_WO, M_XB, M_WR, M_WI, M_CR, M_CI, M_OUTA, M_OUTB, M_COUNT };
struct __align__(64) Maps { CUtensorMap m[M_COUNT]; };

constexpr int CNT_A = 0;
constexpr int CNT_B = 8;
constexpr int CNT_O = 16;
constexpr int CNT_P = 32;
constexpr int CNT_COUNT = 96;

struct Scratch {
    uint8_t ab[64 * 4 * BLOB];
    uint8_t o[16 * 7 * SLOT];
    uint8_t part[64 * 2 * BLOB];
    uint8_t halo[64 * 2 * 2048];
    unsigned cnt[CNT_COUNT * 32];
    unsigned epoch[132 * 4 * 8];
};
__device__ __align__(1024) Scratch g_scratch;

__device__ __forceinline__ unsigned clk32() { unsigned c; asm volatile("mov.u32 %0, %%clock;" : "=r"(c)); return c; }

#define PROF(idx)

__device__ __forceinline__ void mbar_init(uint32_t bar, uint32_t cnt) {
    asm volatile("mbarrier.init.shared::cta.b64 [%0], %1;" ::"r"(bar), "r"(cnt) : "memory");
}
__device__ __forceinline__ void mbar_expect(uint32_t bar, uint32_t bytes) {
    asm volatile("mbarrier.arrive.expect_tx.shared::cta.b64 _, [%0], %1;" ::"r"(bar), "r"(bytes) : "memory");
}
__device__ __forceinline__ void mbar_arrive(uint32_t bar) {
    asm volatile("mbarrier.arrive.shared::cta.b64 _, [%0];" ::"r"(bar) : "memory");
}
__device__ __forceinline__ bool mbar_try(uint32_t bar, uint32_t parity) {
    uint32_t ok;
    asm volatile("{\n.reg .pred p;\nmbarrier.try_wait.parity.shared::cta.b64 p, [%1], %2;\nselp.u32 %0, 1, 0, p;\n}\n"
                 : "=r"(ok) : "r"(bar), "r"(parity) : "memory");
    return ok;
}
__device__ __forceinline__ bool mbar_test(uint32_t bar, uint32_t parity) {
    uint32_t ok;
    asm volatile("{\n.reg .pred p;\nmbarrier.test_wait.parity.shared::cta.b64 p, [%1], %2;\nselp.u32 %0, 1, 0, p;\n}\n"
                 : "=r"(ok) : "r"(bar), "r"(parity) : "memory");
    return ok;
}
__device__ __forceinline__ void mbar_wait(uint32_t bar, uint32_t parity) {
#pragma unroll 1
    for (int n = 0; n < SPIN_LIMIT; n++)
        if (mbar_try(bar, parity)) break;
}
__device__ __forceinline__ bool elect() {
    uint32_t p;
    asm volatile("{\n.reg .pred p;\nelect.sync _|p, 0xffffffff;\nselp.u32 %0, 1, 0, p;\n}\n" : "=r"(p));
    return p;
}
__device__ __forceinline__ void nb_sync(int id, int n) { asm volatile("bar.sync %0, %1;" ::"r"(id), "r"(n) : "memory"); }
__device__ __forceinline__ void nb_arrive(int id, int n) { asm volatile("bar.arrive %0, %1;" ::"r"(id), "r"(n) : "memory"); }
__device__ __forceinline__ void warp_arrive(uint32_t bar) {
    __syncwarp();
    if (elect()) mbar_arrive(bar);
}
__device__ __forceinline__ uint32_t band(uint32_t x, uint32_t m) {
    uint32_t r;
    asm volatile("and.b32 %0, %1, %2;" : "=r"(r) : "r"(x), "r"(m));
    return r;
}
__device__ __forceinline__ uint32_t dup(uint32_t x, uint32_t zero) {
    uint32_t r;
    asm volatile("xor.b32 %0, %1, %2;" : "=r"(r) : "r"(x), "r"(zero));
    return r;
}

__device__ __forceinline__ void tma_ld2(uint32_t dst, const CUtensorMap* m, int c0, int c1, uint32_t bar) {
    asm volatile("cp.async.bulk.tensor.2d.shared::cluster.global.mbarrier::complete_tx::bytes [%0], [%1, {%3, %4}], [%2];"
                 ::"r"(dst), "l"(m), "r"(bar), "r"(c0), "r"(c1) : "memory");
}
__device__ __forceinline__ void tma_ld3(uint32_t dst, const CUtensorMap* m, int c0, int c1, int c2, uint32_t bar) {
    asm volatile("cp.async.bulk.tensor.3d.shared::cluster.global.mbarrier::complete_tx::bytes [%0], [%1, {%3, %4, %5}], [%2];"
                 ::"r"(dst), "l"(m), "r"(bar), "r"(c0), "r"(c1), "r"(c2) : "memory");
}
__device__ __forceinline__ void tma_ld4(uint32_t dst, const CUtensorMap* m, int c0, int c1, int c2, int c3, uint32_t bar) {
    asm volatile("cp.async.bulk.tensor.4d.shared::cluster.global.mbarrier::complete_tx::bytes [%0], [%1, {%3, %4, %5, %6}], [%2];"
                 ::"r"(dst), "l"(m), "r"(bar), "r"(c0), "r"(c1), "r"(c2), "r"(c3) : "memory");
}
__device__ __forceinline__ void bulk_ld(uint32_t dst, const void* src, uint32_t bytes, uint32_t bar) {
    asm volatile("cp.async.bulk.shared::cluster.global.mbarrier::complete_tx::bytes [%0], [%1], %2, [%3];"
                 ::"r"(dst), "l"(src), "r"(bytes), "r"(bar) : "memory");
}
__device__ __forceinline__ void tma_st2(const CUtensorMap* m, int c0, int c1, uint32_t src) {
    asm volatile("cp.async.bulk.tensor.2d.global.shared::cta.bulk_group [%0, {%1, %2}], [%3];"
                 ::"l"(m), "r"(c0), "r"(c1), "r"(src) : "memory");
}
__device__ __forceinline__ void bulk_commit() { asm volatile("cp.async.bulk.commit_group;" ::: "memory"); }
__device__ __forceinline__ void bulk_wait_read() { asm volatile("cp.async.bulk.wait_group.read 0;" ::: "memory"); }
__device__ __forceinline__ void fence_async_smem() { asm volatile("fence.proxy.async.shared::cta;" ::: "memory"); }
__device__ __forceinline__ void fence_async_global() { asm volatile("fence.proxy.async.global;" ::: "memory"); }

__device__ __forceinline__ void signal(Scratch* sc, int idx) {
    asm volatile("fence.proxy.async;\nred.relaxed.gpu.global.add.u32 [%0], 1;" ::"l"(&sc->cnt[idx * 32]) : "memory");
}
__device__ __forceinline__ unsigned peek(const unsigned* p) {
    unsigned v;
    asm volatile("ld.relaxed.gpu.global.u32 %0, [%1];" : "=r"(v) : "l"(p) : "memory");
    return v;
}
__device__ __forceinline__ void await(Scratch* sc, int idx, unsigned target) {
    const unsigned* p = &sc->cnt[idx * 32];
#pragma unroll 1
    for (int n = 0; n < SPIN_LIMIT; n++)
        if ((int)(peek(p) - target) >= 0) break;
    asm volatile("fence.acquire.gpu;" ::: "memory");
}
__device__ __forceinline__ void wait_dep(int k) {
    mbar_wait(base + BAR_DEP + k * 8, 0);
    fence_async_global();
}

#define WG_REGS                                                                                                     \
    "{%0,%1,%2,%3,%4,%5,%6,%7,%8,%9,%10,%11,%12,%13,%14,%15,%16,%17,%18,%19,%20,%21,%22,%23,%24,%25,%26,%27,"       \
    "%28,%29,%30,%31,%32,%33,%34,%35,%36,%37,%38,%39,%40,%41,%42,%43,%44,%45,%46,%47,%48,%49,%50,%51,%52,%53,%54,%55}"
#define WG_OPS(C)                                                                                                   \
    C(d[0]), C(d[1]), C(d[2]), C(d[3]), C(d[4]), C(d[5]), C(d[6]), C(d[7]), C(d[8]), C(d[9]), C(d[10]), C(d[11]),   \
    C(d[12]), C(d[13]), C(d[14]), C(d[15]), C(d[16]), C(d[17]), C(d[18]), C(d[19]), C(d[20]), C(d[21]), C(d[22]),   \
    C(d[23]), C(d[24]), C(d[25]), C(d[26]), C(d[27]), C(d[28]), C(d[29]), C(d[30]), C(d[31]), C(d[32]), C(d[33]),   \
    C(d[34]), C(d[35]), C(d[36]), C(d[37]), C(d[38]), C(d[39]), C(d[40]), C(d[41]), C(d[42]), C(d[43]), C(d[44]),   \
    C(d[45]), C(d[46]), C(d[47]), C(d[48]), C(d[49]), C(d[50]), C(d[51]), C(d[52]), C(d[53]), C(d[54]), C(d[55])

template <int TA, int TB, int SB, bool INIT, uint32_t AH, uint32_t BH>
__device__ __forceinline__ void wgmma112(float (&d)[56], uint32_t alo, uint32_t blo) {
    if (INIT) {
        asm volatile("{\n.reg .pred p;\n.reg .b64 da, db;\nsetp.ne.b32 p, 0, 0;\nmov.b64 da, {%56, %61};\nmov.b64 db, {%57, %62};\n"
                     "wgmma.mma_async.sync.aligned.m64n112k16.f32.bf16.bf16 " WG_REGS ", da, db, p, 1, %59, %60, %58;\n}\n"
                     : WG_OPS("=f") : "r"(alo), "r"(blo), "n"(TB), "n"(SB), "n"(TA), "n"(AH), "n"(BH));
    } else {
        asm volatile("{\n.reg .pred p;\n.reg .b64 da, db;\nsetp.ne.b32 p, 1, 0;\nmov.b64 da, {%56, %61};\nmov.b64 db, {%57, %62};\n"
                     "wgmma.mma_async.sync.aligned.m64n112k16.f32.bf16.bf16 " WG_REGS ", da, db, p, 1, %59, %60, %58;\n}\n"
                     : WG_OPS("+f") : "r"(alo), "r"(blo), "n"(TB), "n"(SB), "n"(TA), "n"(AH), "n"(BH));
    }
}
__device__ __forceinline__ void acc_fence(float (&d)[56]) {
#pragma unroll
    for (int i = 0; i < 56; i++) asm volatile("" : "+f"(d[i])::"memory");
}

__device__ __forceinline__ uint32_t pack2(float lo, float hi) {
    uint32_t r;
    asm volatile("cvt.rn.bf16x2.f32 %0, %1, %2;" : "=r"(r) : "f"(hi), "f"(lo));
    return r;
}
__device__ __forceinline__ uint32_t movm(uint32_t a) {
    uint32_t r;
    asm volatile("movmatrix.sync.aligned.m8n8.trans.b16 %0, %1;" : "=r"(r) : "r"(a));
    return r;
}
__device__ __forceinline__ void stsm4(uint32_t addr, uint32_t a, uint32_t b, uint32_t c, uint32_t d) {
    asm volatile("stmatrix.sync.aligned.m8n8.x4.shared.b16 [%0], {%1,%2,%3,%4};" ::"r"(addr), "r"(a), "r"(b), "r"(c), "r"(d) : "memory");
}
__device__ __forceinline__ void sts1(uint32_t addr, uint32_t a) { asm volatile("st.shared.b32 [%0], %1;" ::"r"(addr), "r"(a) : "memory"); }
__device__ __forceinline__ uint32_t lds1(uint32_t addr) {
    uint32_t a;
    asm volatile("ld.shared.b32 %0, [%1];" : "=r"(a) : "r"(addr) : "memory");
    return a;
}
__device__ __forceinline__ void stg1(uint8_t* p, uint32_t a) { asm volatile("st.global.b32 [%0], %1;" ::"l"(p), "r"(a) : "memory"); }
__device__ __forceinline__ void st_part(uint8_t* p, const uint32_t* v, uint32_t parity) {
    asm volatile("{\n.reg .b64 x, y;\nmov.b64 x, {%1, %2};\nmov.b64 y, {%3, %4};\nst.relaxed.gpu.global.v2.b64 [%0], {x, y};\n}\n"
                 ::"l"(p), "r"((v[0] & ~1u) | parity), "r"(v[1]), "r"((v[2] & ~1u) | parity), "r"(v[3]) : "memory");
}
__device__ __forceinline__ void mma16816(float (&d)[4], const uint32_t (&a)[4], uint32_t b0, uint32_t b1) {
    asm volatile("mma.sync.aligned.m16n8k16.row.col.f32.bf16.bf16.f32 {%0,%1,%2,%3}, {%4,%5,%6,%7}, {%8,%9}, {%0,%1,%2,%3};"
                 : "+f"(d[0]), "+f"(d[1]), "+f"(d[2]), "+f"(d[3]) : "r"(a[0]), "r"(a[1]), "r"(a[2]), "r"(a[3]), "r"(b0), "r"(b1));
}
__device__ __forceinline__ uint32_t add2(uint32_t a, uint32_t b) {
    uint32_t r;
    asm("add.rn.bf16x2 %0, %1, %2;" : "=r"(r) : "r"(a), "r"(b));
    return r;
}
__device__ __forceinline__ uint32_t max2(uint32_t a, uint32_t b) {
    uint32_t r;
    asm("max.bf16x2 %0, %1, %2;" : "=r"(r) : "r"(a), "r"(b));
    return r;
}
__device__ __forceinline__ void ld_tagged(const uint8_t* p, uint32_t& a, uint32_t& ta, uint32_t& b, uint32_t& tb) {
    asm volatile("{\n.reg .b64 x, y;\nld.relaxed.gpu.global.v2.b64 {x, y}, [%4];\nmov.b64 {%0, %1}, x;\nmov.b64 {%2, %3}, y;\n}\n"
                 : "=r"(a), "=r"(ta), "=r"(b), "=r"(tb) : "l"(p) : "memory");
}
__device__ __forceinline__ float bf_lo(uint32_t v) { return __uint_as_float(v << 16); }
__device__ __forceinline__ float bf_hi(uint32_t v) { return __uint_as_float(v & 0xFFFF0000u); }
__device__ __forceinline__ float rcp(float x) { float r; asm("rcp.approx.ftz.f32 %0, %1;" : "=f"(r) : "f"(x)); return r; }
__device__ __forceinline__ float ex2(float x) { float r; asm volatile("ex2.approx.ftz.f32 %0, %1;" : "=f"(r) : "f"(x)); return r; }

__device__ __forceinline__ uint32_t full_bar(int stage) { return base + BAR_FULL + (stage & 7) * 8; }
__device__ __forceinline__ void wait_released(int j) { mbar_wait(base + BAR_EMPTY + (j & 7) * 8, (j >> 3) & 1); }

template <int V>
struct Int { static constexpr int value = V; };

__host__ __device__ constexpr int bslot_e(int i) { return (i < 2 || i >= 14) ? (i + 5) % 7 : (i + 1) % 5; }
__host__ __device__ constexpr int bslot_l(int i) { return i % 6; }

template <uint32_t OFF>
struct Feed {
    int stage;
    uint32_t dst;
    __device__ __forceinline__ void seek(int i, int slot) { stage = i; dst = base + OFF + slot * SLOT; }
    template <int N>
    __device__ __forceinline__ uint32_t acquire() { wait_released(stage - N); return full_bar(stage); }
    template <int N>
    __device__ __forceinline__ void next() {
        stage++;
        dst += SLOT;
        if (dst == base + OFF + N * SLOT) dst = base + OFF;
    }
};
__device__ __forceinline__ int skip_own(int n, int mt) { return n == mt ? 15 : n; }

struct Desc { uint32_t lo, hi; };
__host__ __device__ constexpr Desc desc_const(uint32_t lbo, uint32_t sbo, uint32_t mode) { return {(lbo >> 4) << 16, (sbo >> 4) | (mode << 30)}; }
constexpr Desc D_K128 = desc_const(16, 1024, 1);
constexpr Desc D_N128 = desc_const(8192, 1024, 1);
constexpr Desc D_BLOB = desc_const(128, 256, 0);
constexpr Desc D_OT = desc_const(2048, 128, 0);

enum Kind { XW, XWN, QK, BIG, OUT };

struct Ring {
    int stage;
    uint32_t a, b;
    uint32_t wg;
    uint32_t zero;
    __device__ __forceinline__ void seek(int i, int bslot) {
        stage = i;
        a = (base + (i % NA) * SLOT) >> 4;
        b = (base + BRING + bslot * SLOT) >> 4;
    }
    __device__ __forceinline__ void wait() { mbar_wait(full_bar(stage), (stage >> 3) & 1); }
    __device__ __forceinline__ void take_turn() { nb_sync(1 + wg, 256); }
    __device__ __forceinline__ void pin() {
        uint32_t n = 0;
#pragma unroll 1
        do {
            asm volatile("pmevent 7;" ::: "memory");
        } while (n++ < zero);
    }
    template <Kind K, int NBS, bool INIT, int SB = 1, bool TAIL = false>
    __device__ __forceinline__ void run(float (&d)[56], float (&e)[56], bool first = true, bool last = true, bool more = true) {
        if (first) take_turn();
        asm volatile("wgmma.fence.sync.aligned;" ::: "memory");
        if (K == QK) {
            const uint32_t da = D_K128.lo + (base >> 4) + (stage >> 1) * (SLOT >> 4) + (stage & 1) * 4 + wg * 512, db = D_N128.lo + b;
            wgmma112<0, 1, 1, INIT, D_K128.hi, D_N128.hi>(d, da, db);
            wgmma112<0, 1, 1, INIT, D_K128.hi, D_N128.hi>(e, da, db + 256);
            wgmma112<0, 1, 1, false, D_K128.hi, D_N128.hi>(d, da + 2, db + 128);
            wgmma112<0, 1, 1, false, D_K128.hi, D_N128.hi>(e, da + 2, db + 384);
        } else {
            constexpr int TA = K == OUT, TB = K != XW;
            constexpr uint32_t sa = K == OUT ? 256 : 2, sb = K == XW ? 2 : K == BIG ? 224 : 128;
            constexpr Desc A = K == OUT ? D_OT : D_K128, B = K == XW ? D_K128 : K == BIG ? D_BLOB : D_N128;
            const uint32_t da = A.lo + a + wg * (K == OUT ? 64 : 512), db = B.lo + b;
            wgmma112<TA, TB, SB, INIT, A.hi, B.hi>(d, da, db);
            wgmma112<TA, TB, SB, false, A.hi, B.hi>(d, da + sa, db + sb);
            wgmma112<TA, TB, SB, false, A.hi, B.hi>(d, da + 2 * sa, db + 2 * sb);
            wgmma112<TA, TB, SB, false, A.hi, B.hi>(d, da + 3 * sa, db + 3 * sb);
        }
        asm volatile("wgmma.commit_group.sync.aligned;" ::: "memory");
        if (last) nb_arrive(2 - wg, 256);
        if (!TAIL) asm volatile("wgmma.wait_group.sync.aligned 1;" ::: "memory");
        if (!TAIL && stage > 0 && elect()) mbar_arrive(base + BAR_EMPTY + ((stage - 1) & 7) * 8);
        stage++;
        a += SLOT >> 4;
        if (a == (base + NA * SLOT) >> 4) a = base >> 4;
        b += SLOT >> 4;
        if (b == (base + BRING + NBS * SLOT) >> 4) b = (base + BRING) >> 4;
        if (more) wait();
    }
    template <Kind K, int NBS, bool INIT, int SB = 1, bool TAIL = false>
    __device__ __forceinline__ void run(float (&d)[56], bool first = true, bool last = true, bool more = true) {
        run<K, NBS, INIT, SB, TAIL>(d, d, first, last, more);
    }
};

__device__ __forceinline__ void pack_all(const float (&d)[56], uint32_t (&p)[28]) {
#pragma unroll
    for (int i = 0; i < 28; i++) p[i] = pack2(d[2 * i], d[2 * i + 1]);
}
template <int I0, int I1>
__device__ __forceinline__ void store_frags(uint8_t* dst, const uint32_t (&p)[28]) {
#pragma unroll
    for (int i = I0; i < I1; i++) stg1(dst + i * 128, p[i]);
}
template <int I0, int I1>
__device__ __forceinline__ void stage_frags(uint32_t lane_addr, const uint32_t (&p)[28]) {
#pragma unroll
    for (int i = I0; i < I1; i += 4) stsm4(lane_addr + i * 128, p[i], p[i + 1], p[i + 2], p[i + 3]);
}
template <class F>
__device__ __forceinline__ void store_out(F frag, int lane, uint32_t slab, const CUtensorMap* m, int c0, int c1) {
    const bool swap = lane & 16;
    const uint32_t addr = slab + (lane & 7) * 224 + ((lane >> 3) ^ ((lane >> 2) & 1)) * 16;
#pragma unroll
    for (int h = 0; h < 2; h++) {
#pragma unroll
        for (int c = 0; c < 14; c += 4) {
            const uint32_t t0 = frag(2 * c + h), t1 = frag(2 * c + 2 + h);
            if (c < 12) {
                const uint32_t t2 = frag(2 * c + 4 + h), t3 = frag(2 * c + 6 + h);
                stsm4(addr + h * 1792 + c * 16, swap ? t1 : t0, swap ? t0 : t1, swap ? t3 : t2, swap ? t2 : t3);
            } else {
                asm volatile("stmatrix.sync.aligned.m8n8.x2.shared.b16 [%0], {%1,%2};" ::"r"(addr + h * 1792 + c * 16), "r"(swap ? t1 : t0), "r"(swap ? t0 : t1) : "memory");
            }
        }
        fence_async_smem();
        __syncwarp();
        if (elect()) tma_st2(m, c0, c1 + 8 * h, slab + h * 1792);
    }
    if (elect()) {
        bulk_commit();
        bulk_wait_read();
    }
}
__host__ __device__ constexpr int tile_of(int t) { return 7 * (t >> 2) + 3 * ((t >> 1) & 1) + 2 * (t & 1); }

struct Role {
    bool H;
    int L, mt, ns, id;
};
template <bool BY_SM>
__device__ __forceinline__ Role decode_role() {
    uint32_t sm;
    if (BY_SM) asm volatile("mov.u32 %0, %%smid;" : "=r"(sm));
    else asm volatile("mov.u32 %0, %%ctaid.x;" : "=r"(sm));
    const int tpc = sm >> 1, q2 = ((tpc - 32) * 37) >> 8;
    const int gpc = tpc < 32 ? tpc & 7 : tpc < 60 ? tpc - 31 - 7 * q2 : 0;
    const int pos = tpc < 32 ? tpc >> 3 : tpc < 60 ? q2 + 4 : tpc - 56;
    Role r;
    r.H = sm >= 128;
    r.L = gpc & 1;
    r.mt = (gpc >> 1) * 4 + (pos >> 1);
    r.ns = (pos & 1) * 2 + (sm & 1);
    r.id = r.H ? sm : gpc * 16 + pos * 2 + (sm & 1);
    return r;
}

template <int I0, int I1>
__device__ __forceinline__ void first_fill(const Maps& maps, const Role& r, unsigned t0) {
    auto pace = [&](int i) {
        if (PACE && I0) while (clk32() - t0 < i * PACE) {}
    };
    if (r.L) {
#pragma unroll
        for (int i = I0; i < I1; i++) {
            const uint32_t bar = full_bar(i), dst = base + BRING + i * SLOT;
            pace(i);
            if (i < 6) mbar_expect(bar, SLOT);
            if (i & 1) {
                mbar_arrive(bar);
            } else {
                mbar_expect(bar, SLOT);
                tma_ld2(base + (i >> 1) * SLOT, &maps.m[M_XA], (r.mt >> 3) * 448 + i * 32, (r.mt & 7) * 128, bar);
            }
            if (i < 6) {
                tma_ld4(dst, &maps.m[M_WQK], 0, i * 32, 0, r.ns, bar);
                tma_ld4(dst + 8192, &maps.m[M_WQK], 64, i * 32, 0, r.ns, bar);
            }
        }
    } else if (!r.H) {
#pragma unroll
        for (int i = I0; i < I1; i++) {
            const uint32_t bar = full_bar(i);
            pace(i);
            mbar_expect(bar, SLOT);
            tma_ld3(base + i * SLOT, &maps.m[M_XB], i * 64, r.mt * 64, 0, bar);
            mbar_expect(bar, BLOB);
            tma_ld2(base + BRING + bslot_e(i) * SLOT, &maps.m[M_WR], i * 64, r.ns * 112, bar);
        }
    } else {
#pragma unroll 1
        for (int i = I0; i < I1; i++) {
            const uint32_t bar = full_bar(i), dst = base + BRING + i * SLOT;
            pace(i);
            mbar_expect(bar, SLOT);
            mbar_expect(bar, SLOT);
            tma_ld4(base + i * SLOT, &maps.m[M_XH], i * 64, 120, 0, 0, bar);
            tma_ld3(dst, &maps.m[M_WV], 0, i * 64, 4 + r.ns, bar);
            tma_ld3(dst + 8192, &maps.m[M_WV], 64, i * 64, 4 + r.ns, bar);
        }
    }
}

template <bool BY_SM>
__global__ void __launch_bounds__(384, 1) fused_kernel(Scratch* sc, const __grid_constant__ Maps maps) {
    const int warp = __shfl_sync(0xffffffffu, threadIdx.x >> 5, 0);
    const Role role = decode_role<BY_SM>();
    const unsigned t_open = PACE ? clk32() : 0;
    if (warp == OPENER) {
        if (elect()) {
            asm volatile("prefetch.tensormap [%0];" ::"l"(&maps.m[M_XB]) : "memory");
            asm volatile("prefetch.tensormap [%0];" ::"l"(&maps.m[M_XA]) : "memory");
            asm volatile("prefetch.tensormap [%0];" ::"l"(&maps.m[M_WR]) : "memory");
            asm volatile("prefetch.tensormap [%0];" ::"l"(&maps.m[M_WQK]) : "memory");
#pragma unroll
            for (int i = 0; i < 8; i++) mbar_init(base + BAR_FULL + i * 8, 2);
            asm volatile("fence.mbarrier_init.release.cluster;" ::: "memory");
            first_fill<0, LEAD>(maps, role, 0);
        }
    }
    int lane = threadIdx.x & 31;
    asm volatile("" : "+r"(lane));
    const bool roleH = role.H;
    const int roleL = role.L, mt = role.mt, ns = role.ns, bid = role.id;
    const int par = mt >> 3, blk = mt & 7, col = ns * 112;
    if (warp == 9) {
        if (elect()) {
#pragma unroll
            for (int i = 0; i < 8; i++) mbar_init(base + BAR_EMPTY + i * 8, 8);
            asm volatile("fence.mbarrier_init.release.cluster;" ::: "memory");
        }
    } else if (warp == 10) {
        if (elect()) {
#pragma unroll
            for (int i = 0; i < 5; i++) mbar_init(base + BAR_RDY + i * 8, i < 2 ? 4 : 8);
#pragma unroll
            for (int i = 0; i < 2; i++) mbar_init(base + BAR_HALO + i * 8, 9);
            asm volatile("fence.mbarrier_init.release.cluster;" ::: "memory");
        }
    } else if (warp == 11) {
        if (elect()) {
#pragma unroll
            for (int i = 0; i < 3; i++) mbar_init(base + BAR_DEP + i * 8, 1);
#pragma unroll
            for (int i = 0; i < 2; i++) mbar_init(base + BAR_PART + i * 8, 1);
            asm volatile("fence.mbarrier_init.release.cluster;" ::: "memory");
        }
    }
    __syncthreads();

    if (__builtin_expect(warp >= 8, 1)) {
        asm volatile("setmaxnreg.dec.sync.aligned.u32 56;");
#define PROF_FEED_A
#define PROF_FEED_B
        if (__builtin_expect(warp == 8, 1)) {
            if (elect()) {
                PROF(129);
                first_fill<LEAD, 7>(maps, role, t_open);
                PROF(134);
                Feed<0> f;
                const int row = mt * 128;
                auto c_run = [&](const CUtensorMap* m, int off, int n0, int n1) {
#pragma unroll 1
                    for (int n = n0; n < n1; n++) {
                        const uint32_t bar = f.acquire<NA>();
                        mbar_expect(bar, SLOT);
                        tma_ld2(f.dst, m, (off + skip_own(n, mt)) * 64, row, bar);
                        PROF_FEED_A;
                        f.next<NA>();
                    }
                };
                if (roleH) {
                } else if (!roleL) {
                    f.seek(14, 0);
                    mbar_wait(base + BAR_RDY, 0);
#pragma unroll 1
                    for (int i = 0; i < 4; i++) {
                        const uint32_t bar = f.acquire<NA>();
                        mbar_expect(bar, SLOT);
                        tma_ld2(f.dst, &maps.m[M_CR + (i >> 1)], ((i & 1) * 16 + mt) * 64, row, bar);
                        mbar_arrive(bar);
                        PROF_FEED_A;
                        f.next<NA>();
                    }
                    c_run(&maps.m[M_CR], 0, 0, 15);
                    c_run(&maps.m[M_CI], 0, 0, NBE);
                    wait_dep(2);
#pragma unroll 1
                    for (int i = 0; i < 7; i++) {
                        const uint32_t bar = f.acquire<NA>();
                        mbar_expect(bar, SLOT);
                        bulk_ld(f.dst, sc->o + (size_t)(mt * 7 + i) * SLOT, SLOT, bar);
                        PROF_FEED_A;
                        f.next<NA>();
                    }
                } else {
#pragma unroll 1
                    for (int i = 4; i < 7; i++) {
                        wait_released(2 * i - 8);
                        mbar_expect(full_bar(2 * i), SLOT);
                        tma_ld2(base + i * SLOT, &maps.m[M_XA], par * 448 + i * 64, blk * 128, full_bar(2 * i));
                    }
                    wait_released(HALO_K_AT);
                    mbar_arrive(base + BAR_DEP + 16);
                    f.seek(21, 0);
                    c_run(&maps.m[M_CR], 16, 0, 15);
                    c_run(&maps.m[M_CI], 16, 0, 15);
                    c_run(&maps.m[M_CI], 0, NBE, 15);
                }
            }
        } else if (warp == 11) {
            if (elect()) {
                Feed<BRING> f;
                auto blob_run = [&](auto nbs, int quarter, int n0, int n1) {
                    constexpr int N = decltype(nbs)::value;
                    const uint8_t* src = sc->ab + (size_t)(quarter * 64 + ns) * BLOB;
#pragma unroll 1
                    for (int n = n0; n < n1; n++) {
                        const uint32_t bar = f.template acquire<N>();
                        mbar_expect(bar, BLOB);
                        bulk_ld(f.dst, src + skip_own(n, mt) * (4 * BLOB), BLOB, bar);
                        PROF_FEED_B;
                        f.template next<N>();
                    }
                };
                auto w_run = [&](auto nbs, const CUtensorMap* m, int slice, bool no_a) {
                    constexpr int N = decltype(nbs)::value;
#pragma unroll 1
                    for (int i = 0; i < 7; i++) {
                        const uint32_t bar = f.template acquire<N>();
                        mbar_expect(bar, SLOT);
                        tma_ld3(f.dst, m, 0, i * 64, slice, bar);
                        tma_ld3(f.dst + 8192, m, 64, i * 64, slice, bar);
                        if (no_a) mbar_arrive(bar);
                        PROF_FEED_B;
                        f.template next<N>();
                    }
                };
                if (roleH) {
                    f.seek(7, 0);
                    w_run(Int<7>(), &maps.m[M_WV], 8 + ns, true);
                } else if (!roleL) {
                    f.seek(7, bslot_e(7));
#pragma unroll 1
                    for (int i = 0; i < 7; i++) {
                        const uint32_t bar = f.acquire<5>();
                        mbar_expect(bar, BLOB);
                        tma_ld2(f.dst, &maps.m[M_WI], i * 64, col, bar);
                        mbar_arrive(bar);
                        PROF_FEED_B;
                        f.next<5>();
                    }
                    f.seek(18, bslot_e(18));
                    wait_dep(0);
                    blob_run(Int<7>(), 0, 0, 15);
                    wait_dep(1);
                    blob_run(Int<7>(), 2, 0, NBE);
                    w_run(Int<7>(), &maps.m[M_WO], ns, false);
                } else {
                    f.seek(6, 0);
#pragma unroll 1
                    for (int i = 6; i < 14; i++) {
                        const uint32_t bar = f.acquire<6>();
                        mbar_expect(bar, SLOT);
                        tma_ld4(f.dst, &maps.m[M_WQK], 0, i * 32, 0, ns, bar);
                        tma_ld4(f.dst + 8192, &maps.m[M_WQK], 64, i * 32, 0, ns, bar);
                        if (i & 1) mbar_arrive(bar);
                        PROF_FEED_B;
                        f.next<6>();
                    }
                    w_run(Int<6>(), &maps.m[M_WV], 8 + ns, true);
                    wait_dep(0);
                    blob_run(Int<6>(), 1, 0, 15);
                    wait_dep(1);
                    blob_run(Int<6>(), 3, 0, 15);
                    blob_run(Int<6>(), 2, NBE, 15);
                }
            }
        } else if (roleH) {
            if (elect()) {
                wait_released(warp == 9 ? 0 : 7);
#pragma unroll 1
                for (int i = 0; i < 7; i++) {
                    if (warp == 9) {
                        asm volatile("cp.async.bulk.prefetch.tensor.2d.L2.global [%0, {%1, %2}];" ::"l"(&maps.m[M_WI]), "r"(i * 64), "r"(col) : "memory");
                    } else {
                        asm volatile("cp.async.bulk.prefetch.tensor.3d.L2.global [%0, {%1, %2, %3}];" ::"l"(&maps.m[M_WO]), "r"(0), "r"(i * 64), "r"(ns) : "memory");
                        asm volatile("cp.async.bulk.prefetch.tensor.3d.L2.global [%0, {%1, %2, %3}];" ::"l"(&maps.m[M_WO]), "r"(64), "r"(i * 64), "r"(ns) : "memory");
                    }
                }
            }
        } else if (warp == 10) {
            if (elect()) {
                unsigned* epoch_ptr = &sc->epoch[(bid * 4 + 2) * 8];
                const unsigned ep = *epoch_ptr + 1;
                sts1(base + TAG, ep);
                asm volatile("prefetch.tensormap [%0];" ::"l"(&maps.m[M_OUTA + roleL]) : "memory");
                await(sc, CNT_A + roleL * 4 + ns, ep * 16);
                mbar_arrive(base + BAR_DEP);
                PROF(150);
                await(sc, CNT_B + ns, ep * 16);
                mbar_arrive(base + BAR_DEP + 8);
                PROF(151);
                if (!roleL) {
                    await(sc, CNT_O + mt, ep * 4);
                    mbar_arrive(base + BAR_DEP + 16);
                } else {
                    await(sc, CNT_P + mt * 4 + ns, ep * 2 - 1);
                    mbar_arrive(base + BAR_PART);
                    PROF(153);
                    await(sc, CNT_P + mt * 4 + ns, ep * 2);
                    mbar_arrive(base + BAR_PART + 8);
                }
                PROF(152);
                *epoch_ptr = ep;
            }
        } else if (!roleL) {
            if (elect()) {
                mbar_wait(base + BAR_RDY, 0);
                PROF(130);
                signal(sc, CNT_A + ns);
                PROF(131);
                mbar_wait(base + BAR_RDY + 8, 0);
                signal(sc, CNT_A + 4 + ns);
                PROF(135);
                mbar_wait(base + BAR_RDY + 32, 0);
                PROF(132);
                signal(sc, CNT_B + ns);
                PROF(133);
            }
        } else {
            unsigned* epoch_ptr = &sc->epoch[(bid * 4 + 1) * 8];
            const unsigned tag = *epoch_ptr + 1;
#pragma unroll 1
            for (int kv = 0; kv < 2; kv++) {
                uint32_t v[16];
#pragma unroll
                for (int i = 0; i < 16; i++) v[i] = 0;
                if (kv) mbar_wait(base + BAR_HALO, 0), wait_released(HALO_V_AT);
                else mbar_wait(base + BAR_DEP + 16, 0);
                if (blk > 0) {
                    const uint8_t* src = sc->halo + (size_t)(((mt - 1) * 4 + ns) * 2 + kv) * 2048 + lane * 16;
#pragma unroll 1
                    for (int n = 0; n < SPIN_LIMIT; n++) {
                        uint32_t stale = 0;
#pragma unroll
                        for (int i = 0; i < 4; i++) ld_tagged(src + i * 512, v[4 * i], v[4 * i + 1], v[4 * i + 2], v[4 * i + 3]);
#pragma unroll
                        for (int i = 0; i < 16; i += 2) stale |= v[i] ^ tag;
                        if (__all_sync(0xffffffffu, !(stale & 1))) break;
                    }
#pragma unroll
                    for (int c = 0; c < 14; c += 2) v[c] = (v[c] & ~1u) | ((v[15] >> c) & 1);
                }
#pragma unroll
                for (int i = 0; i < 14; i++) sts1(base + HALO + kv * (8 * HSLOT) + i * 128 + lane * 4, v[i]);
                warp_arrive(base + BAR_HALO + kv * 8);
                if (lane == 0) PROF(142 + kv);
            }
            if (elect()) {
                mbar_wait(base + BAR_RDY + 16, 0);
                PROF(130);
                signal(sc, CNT_O + mt);
                PROF(131);
                *epoch_ptr = tag;
            }
        }
    } else {
        asm volatile("setmaxnreg.inc.sync.aligned.u32 224;");
        Ring r;
        r.wg = warp >> 2;
        r.zero = blockIdx.y;
        const int wg = warp >> 2;
        if (wg) nb_arrive(1, 256);
        r.stage = 0;
        r.wait();
        uint8_t* part = sc->part + (size_t)(ns * 16 + mt) * (2 * BLOB) + warp * 512 + lane * 16;
        uint32_t p[28];

        if (roleH) {
            unsigned* epoch_ptr = &sc->epoch[bid * 4 * 8];
            const unsigned tag = *epoch_ptr + 1;
            uint8_t* hout = sc->halo + (size_t)((warp * 8 + ns) * 2) * 2048 + lane * 16;
            auto send = [&](int kv) {
#pragma unroll
                for (int h = 0; h < 2; h++) {
                    uint32_t v[16];
                    v[14] = v[15] = 0;
#pragma unroll
                    for (int c = 0; c < 14; c++) v[c] = p[2 * c + h];
#pragma unroll
                    for (int c = 0; c < 14; c += 2) v[15] |= (v[c] & 1) << c;
#pragma unroll
                    for (int i = 0; i < 4; i++) st_part(hout + (h * 8 + kv) * 2048 + i * 512, v + 4 * i, tag & 1);
                }
            };
            float x0[56], x1[56];
            r.seek(0, 0);
            r.run<XWN, 7, true>(x0);
#pragma unroll 1
            for (int i = 1; i < 7; i++) r.run<XWN, 7, false>(x0);
            r.run<XWN, 7, true>(x1);
            acc_fence(x0);
            pack_all(x0, p);
            send(0);
#pragma unroll 1
            for (int i = 1; i < 7; i++) r.run<XWN, 7, false>(x1, true, true, i < 6);
            asm volatile("wgmma.wait_group.sync.aligned 0;" ::: "memory");
            acc_fence(x1);
            pack_all(x1, p);
#pragma unroll
            for (int i = 0; i < 28; i++) p[i] = movm(p[i]);
            send(1);
            if (threadIdx.x == 0) *epoch_ptr = tag;
        } else if (!roleL) {
            uint8_t* blob = sc->ab + (size_t)((wg * 16 + mt) * 4 + ns) * BLOB + (warp & 3) * WSLOT + lane * 4;
            const uint32_t own = base + BRING + wg * SLOT + (warp & 3) * WSLOT + lane * 16;
            float x0[56], x1[56];
            r.seek(0, bslot_e(0));
            r.run<XW, 7, true>(x0);
            r.run<XW, 7, false>(x0);
            r.seek(2, bslot_e(2));
#pragma unroll 1
            for (int i = 2; i < 7; i++) r.run<XW, 5, false>(x0);

            r.seek(7, bslot_e(7));
            r.run<XW, 5, true, -1>(x1);
            acc_fence(x0);
            pack_all(x0, p);
#pragma unroll
            for (int i = 0; i < 2; i++) {
                if (wg == i) store_frags<0, 14>(blob, p);
                else stage_frags<0, 4>(own + 5 * SLOT, p);
                r.run<XW, 5, false, -1>(x1);
                if (wg == i) {
                    store_frags<14, 28>(blob, p);
                    warp_arrive(base + BAR_RDY + i * 8);
                } else {
                    stage_frags<4, 8>(own + 5 * SLOT, p);
                }
                r.run<XW, 5, false, -1>(x1);
            }
            stage_frags<8, 20>(own + 5 * SLOT, p);
            r.run<XW, 5, false, -1>(x1);
            stage_frags<20, 28>(own + 5 * SLOT, p);
            warp_arrive(base + BAR_RDY + 16);
            r.run<XW, 5, false, -1>(x1);

            mbar_wait(base + BAR_RDY + 16, 0);
            fence_async_smem();
            r.seek(14, bslot_e(14));
            r.run<BIG, 7, true>(x0);
            acc_fence(x1);
            pack_all(x1, p);
            wait_released(10);
            stage_frags<0, 28>(own, p);
            warp_arrive(base + BAR_RDY + 24);
            r.run<BIG, 7, false>(x0);
            mbar_wait(base + BAR_RDY + 24, 0);
            fence_async_smem();
            blob += (size_t)128 * BLOB;
#pragma unroll
            for (int i = 0; i < 28; i++) {
                if (i % B_SLICE == 0) r.run<BIG, 7, false>(x0);
                stg1(blob + i * 128, p[i]);
            }
            warp_arrive(base + BAR_RDY + 32);
#pragma unroll 1
            for (int i = 17 + 27 / B_SLICE; i < POUT; i++) r.run<BIG, 7, false>(x0);

            const uint32_t tag = lds1(base + TAG);
            r.seek(POUT, bslot_e(POUT));
            r.run<OUT, 7, true>(x1);
            acc_fence(x0);
            pack_all(x0, p);
#pragma unroll
            for (int k = 0; k < 3; k++) {
                if (k < 2 && wg == k) {
                    if ((warp & 3) == 0 && elect())
                        asm volatile("red.relaxed.gpu.global.add.u32 [%0], 1;" ::"l"(&sc->cnt[(CNT_P + mt * 4 + ns) * 32]) : "memory");
#pragma unroll
                    for (int i = 0; i < 4; i++) st_part(part + i * 4096, p + 4 * i, tag & 1);
                }
                if (k > 0 && wg == k - 1) {
#pragma unroll
                    for (int i = 4; i < 7; i++) st_part(part + i * 4096, p + 4 * i, tag & 1);
                }
                if (k < 2) r.run<OUT, 7, false>(x1);
            }
#pragma unroll
            for (int i = 3; i < 7; i++) r.run<OUT, 7, false, 1, true>(x1, i <= 7 - TURN, i < 7 - TURN || i == 6, i < 6);

            wait_released(ELAST - 6);
            asm volatile("wgmma.wait_group.sync.aligned 0;" ::: "memory");
            acc_fence(x1);
            const uint32_t slab = base + (wg ? BRING + bslot_e(ELAST - 6) * SLOT : ((ELAST - 6) % NA) * SLOT) + (warp & 3) * WSLOT;
            store_out([&](int i) { return pack2(x1[2 * i], x1[2 * i + 1]); }, lane, slab, &maps.m[M_OUTA], par * 896 + col, blk * 128 + warp * 16);
        } else {
            const int g = lane >> 2, tig = lane & 3;
            const uint32_t hin = base + HALO + warp * HSLOT + lane * 4;
            const uint32_t hpub = warp < 7 ? hin + HSLOT : base + HSPARE + lane * 4;
            auto publish = [&](const uint32_t (&h)[14], int c0, int c1) {
#pragma unroll
                for (int c = 0; c < 14; c++)
                    if (c >= c0 && c < c1) sts1(hpub + c * 128, h[c]);
            };
            float y0[56], y1[56], y2[56];
            r.seek(0, 0);
            r.run<QK, 6, true>(y0, y1);
#pragma unroll 1
            for (int i = 1; i < 14; i++) r.run<QK, 6, false>(y0, y1);

            uint32_t m1[8][4], m0[8][4], lo[14], hi[14], q[2][8][2];
            auto pack_q = [&](int b) {
                uint32_t v[14];
#pragma unroll
                for (int c = 0; c < 14; c++) v[c] = pack2(y0[4 * c + 2 * b], y0[4 * c + 2 * b + 1]);
#pragma unroll
                for (int t = 0; t < 8; t++) {
                    const int c = tile_of(t);
                    q[b][t][0] = (t & 3) == 2 ? (tig >= 2 ? v[c] : 0u) : v[c];
                    q[b][t][1] = (t & 3) == 1 ? (tig < 2 ? v[c + 1] : 0u) : v[c + 1];
                }
            };
            auto fetch = [&](uint32_t src, int hp, int i0) {
#pragma unroll
                for (int t = 4 * hp; t < 4 * hp + 4; t++) {
                    m0[t][i0] = (t & 3) == 2 ? dup(m0[t - 1][3], r.zero) : lds1(src + tile_of(t) * 128);
                    m0[t][3] = lds1(src + tile_of(t) * 128 + 128);
                }
            };
            r.seek(14, bslot_l(14));
            r.run<XWN, 6, true>(y2);
            acc_fence(y0);
            acc_fence(y1);
#pragma unroll
            for (int c = 0; c < 14; c++) hi[c] = pack2(y1[4 * c + 2], y1[4 * c + 3]);
            publish(hi, 0, 7);
            PIN;
            r.run<XWN, 6, false>(y2);
            publish(hi, 7, 14);
            warp_arrive(base + BAR_HALO);
#pragma unroll
            for (int c = 0; c < 14; c++) lo[c] = pack2(y1[4 * c], y1[4 * c + 1]);
#pragma unroll
            for (int t = 0; t < 8; t++) {
                const int c = tile_of(t);
                const bool shared = (t & 3) == 2;
                m1[t][0] = shared ? dup(lo[c], r.zero) : lo[c];
                m1[t][1] = shared ? dup(hi[c], r.zero) : hi[c];
                m1[t][2] = lo[c + 1];
                m1[t][3] = hi[c + 1];
                m0[t][0] = dup(m1[t][0], r.zero);
                m0[t][2] = dup(lo[c + 1], 2 * r.zero);
            }
            PIN;
            r.run<XWN, 6, false>(y2);
            mbar_wait(base + BAR_HALO, 0);
            fetch(hin, 0, 1);
            pack_q(1);
            PIN;
            r.run<XWN, 6, false>(y2);
            fetch(hin, 1, 1);
            pack_q(0);
            r.pin();
            r.take_turn();
            float s[8][4];
#pragma unroll
            for (int step = 0; step < 2; step++) {
#pragma unroll
                for (int i = 0; i < 8; i++) {
                    const int b = 1 - (i >> 2), h = i & 3, t = 2 * h + step;
                    float (&d)[4] = s[2 * h + b];
                    if (step == 0) d[0] = d[1] = d[2] = d[3] = 0.f;
                    mma16816(d, b ? m1[t] : m0[t], q[b][t][0], q[b][t][1]);
                }
            }
            r.pin();
            r.run<XWN, 6, false>(y2, false);

            uint32_t pr[8], mx[4], mx1[4];
            {
                const bool cur0 = g <= 2 * tig, cur1 = g <= 2 * tig + 1;
#pragma unroll
                for (int i = 0; i < 8; i++) {
                    const int c = (i & 1) ? 2 : 0;
                    pr[i] = movm(pack2(cur0 ? s[i][c] : s[i][2 - c], cur1 ? s[i][c + 1] : s[i][3 - c]));
                }
            }
            PIN;
            r.run<XWN, 6, false>(y2);
            const uint32_t curmask = (2 * tig <= g ? 0x0000FFFFu : 0u) | (2 * tig + 1 <= g ? 0xFFFF0000u : 0u);
            {
                const uint32_t keep = (blk == 0 && warp == 0) ? curmask : 0xFFFFFFFFu;
#pragma unroll
                for (int i = 0; i < 4; i++) {
                    pr[2 * i] = (pr[2 * i] & keep) | (0xCF9ECF9Eu & ~keep);
                    mx[i] = max2(__byte_perm(pr[2 * i], pr[2 * i + 1], 0x5410), __byte_perm(pr[2 * i], pr[2 * i + 1], 0x7632));
                    mx1[i] = __shfl_xor_sync(0xffffffffu, mx[i], 1);
                }
            }
            PIN;
            r.run<XWN, 6, false>(y2);
#pragma unroll
            for (int i = 0; i < 4; i++) {
                mx[i] = max2(mx[i], mx1[i]);
                mx1[i] = __shfl_xor_sync(0xffffffffu, mx[i], 2);
            }

            PIN;
            r.seek(21, bslot_l(21));
            r.run<BIG, 6, true>(y0);
            acc_fence(y2);
#pragma unroll
            for (int c = 0; c < 10; c++) hi[c] = movm(pack2(y2[4 * c + 2], y2[4 * c + 3]));
            constexpr float SCL = 0.18898223650461362f * 1.4426950408889634f;
            float e0[8], e1[8], sm[8], sm1[8];
#pragma unroll
            for (int i = 0; i < 8; i++) {
                const uint32_t m2 = max2(mx[i >> 1], mx1[i >> 1]);
                sm[i] = ((i & 1) ? bf_hi(m2) : bf_lo(m2)) * -SCL;
            }
            PIN;
            r.run<BIG, 6, false>(y0);
#pragma unroll
            for (int c = 10; c < 14; c++) hi[c] = movm(pack2(y2[4 * c + 2], y2[4 * c + 3]));
#pragma unroll
            for (int c = 0; c < 4; c++) lo[c] = movm(pack2(y2[4 * c], y2[4 * c + 1]));
#pragma unroll
            for (int i = 0; i < 8; i++) e0[i] = ex2(fmaf(bf_lo(pr[i]), SCL, sm[i]));
            PIN;
            r.run<BIG, 6, false>(y0);
            publish(hi, 0, 10);
#pragma unroll
            for (int i = 0; i < 8; i++) e1[i] = ex2(fmaf(bf_hi(pr[i]), SCL, sm[i]));
            PIN;
            r.run<BIG, 6, false>(y0);
            publish(hi, 10, 14);
            warp_arrive(base + BAR_HALO + 8);
#pragma unroll
            for (int i = 0; i < 8; i++) {
                sm[i] = e0[i] + e1[i];
                sm1[i] = __shfl_xor_sync(0xffffffffu, sm[i], 1);
            }
            PIN;
            r.run<BIG, 6, false>(y0);
#pragma unroll
            for (int c = 4; c < 14; c++) lo[c] = movm(pack2(y2[4 * c], y2[4 * c + 1]));
            PIN;
            r.run<BIG, 6, false>(y0);
#pragma unroll
            for (int i = 0; i < 8; i++) {
                sm[i] += sm1[i];
                sm1[i] = __shfl_xor_sync(0xffffffffu, sm[i], 2);
            }
#pragma unroll
            for (int t = 0; t < 8; t++) {
                const int c = tile_of(t);
                const bool shared = (t & 3) == 2;
                m1[t][0] = shared ? dup(lo[c], r.zero) : lo[c];
                m1[t][1] = lo[c + 1];
                m1[t][2] = shared ? dup(hi[c], r.zero) : hi[c];
                m1[t][3] = hi[c + 1];
                m0[t][0] = dup(m1[t][0], r.zero);
                m0[t][1] = dup(lo[c + 1], 2 * r.zero);
            }
            PIN;
            r.run<BIG, 6, false>(y0);
            mbar_wait(base + BAR_HALO + 8, 0);
            const uint32_t vin = warp ? hin : hin + 8 * HSLOT;
            fetch(vin, 0, 2);
#pragma unroll
            for (int i = 0; i < 8; i++) {
                const float inv = rcp(sm[i] + sm1[i]);
                pr[i] = pack2(e0[i] * inv, e1[i] * inv);
            }
            PIN;
            r.run<BIG, 6, false>(y0);
            fetch(vin, 1, 2);
            uint32_t pb[8][2];
#pragma unroll
            for (int t = 0; t < 8; t++) {
                pb[t][t & 1] = band(pr[t], curmask);
                pb[t][1 - (t & 1)] = band(pr[t], ~curmask);
            }
            r.pin();
            r.take_turn();
            float o[2][8][4];
#pragma unroll
            for (int i = 0; i < 16; i++) {
                const int b = 1 - (i >> 3), t = i & 7;
                float (&d)[4] = o[b][t];
                d[0] = d[1] = d[2] = d[3] = 0.f;
                mma16816(d, b ? m1[t] : m0[t], pb[(t & 6) + b][0], pb[(t & 6) + b][1]);
            }
            r.pin();
            r.run<BIG, 6, false>(y0, false);
            uint8_t* odst = sc->o + (size_t)mt * 7 * SLOT + ns * (14 * 2048) + warp * 256 + lane * 4;
#pragma unroll
            for (int hp = 0; hp < 2; hp++) {
#pragma unroll
                for (int b = 0; b < 2; b++) {
                    const float (&u)[8][4] = o[b];
                    const int t = 4 * hp;
                    uint32_t* w = p + 14 * hp + b;
                    w[0] = pack2(u[t][0], u[t][1]);
                    w[2] = pack2(u[t][2], u[t][3]);
                    w[4] = pack2(u[t + 1][0], u[t + 1][1]);
                    w[6] = pack2(g < 4 ? u[t + 1][2] : u[t + 2][0], g < 4 ? u[t + 1][3] : u[t + 2][1]);
                    w[8] = pack2(u[t + 2][2], u[t + 2][3]);
                    w[10] = pack2(u[t + 3][0], u[t + 3][1]);
                    w[12] = pack2(u[t + 3][2], u[t + 3][3]);
                }
            }
#pragma unroll
            for (int i = 0; i < 28; i++) {
                if (i && i % O_SLICE == 0) r.run<BIG, 6, false>(y0);
                stg1(odst + (i >> 1) * 2048 + (i & 1) * 128, p[i]);
            }
            warp_arrive(base + BAR_RDY + 16);

#pragma unroll 1
            for (int i = 30 + 27 / O_SLICE; i <= LLAST + 1 - TURN; i++) r.run<BIG, 6, false>(y0, true, i <= LLAST - TURN);
            const uint32_t tag = lds1(base + TAG);
            if (mbar_test(base + BAR_PART + wg * 8, 0)) {
#pragma unroll
                for (int i = 0; i < 7; i++) ld_tagged(part + i * 4096, p[4 * i], p[4 * i + 1], p[4 * i + 2], p[4 * i + 3]);
            } else {
                p[0] = ~tag;
            }
            r.seek(LLAST + 2 - TURN, bslot_l(LLAST + 2 - TURN));
#pragma unroll
            for (int i = 1; i < TURN; i++) r.run<BIG, 6, false, 1, true>(y0, false, i == TURN - 1, i < TURN - 1);
#pragma unroll 1
            for (int n = 0; n < SPIN_LIMIT; n++) {
                uint32_t stale = 0;
#pragma unroll
                for (int i = 0; i < 28; i += 2) stale |= p[i] ^ tag;
                if (__all_sync(0xffffffffu, !(stale & 1))) break;
                mbar_wait(base + BAR_PART + wg * 8, 0);
#pragma unroll
                for (int i = 0; i < 7; i++) ld_tagged(part + i * 4096, p[4 * i], p[4 * i + 1], p[4 * i + 2], p[4 * i + 3]);
            }
            wait_released(LLAST - 6);
            asm volatile("wgmma.wait_group.sync.aligned 0;" ::: "memory");
            acc_fence(y0);
            const uint32_t slab = base + (wg ? HALO : ((LLAST - 6) % NA) * SLOT) + (warp & 3) * WSLOT;
            store_out([&](int i) { return add2(pack2(y0[2 * i], y0[2 * i + 1]), p[i]); }, lane, slab, &maps.m[M_OUTB], 448 + col, mt * 128 + warp * 16);
        }
    }
}

typedef CUresult (*EncodeFn)(CUtensorMap*, CUtensorMapDataType, cuuint32_t, void*, const cuuint64_t*, const cuuint64_t*,
                             const cuuint32_t*, const cuuint32_t*, CUtensorMapInterleave, CUtensorMapSwizzle,
                             CUtensorMapL2promotion, CUtensorMapFloatOOBfill);

struct Dim { uint64_t size, stride; uint32_t box; };
void encode(EncodeFn fn, CUtensorMap* m, const void* ptr, CUtensorMapSwizzle sw, Dim d0, Dim d1, Dim d2 = {0, 0, 0}, Dim d3 = {0, 0, 0}) {
    const cuuint64_t dims[4] = {d0.size, d1.size, d2.size, d3.size};
    const cuuint64_t strides[3] = {d1.stride, d2.stride, d3.stride};
    const cuuint32_t box[4] = {d0.box, d1.box, d2.box, d3.box};
    const cuuint32_t es[4] = {1, 1, 1, 1};
    fn(m, CU_TENSOR_MAP_DATA_TYPE_BFLOAT16, d3.size ? 4 : d2.size ? 3 : 2, const_cast<void*>(ptr), dims, strides, box, es,
       CU_TENSOR_MAP_INTERLEAVE_NONE, sw, CU_TENSOR_MAP_L2_PROMOTION_L2_128B, CU_TENSOR_MAP_FLOAT_OOB_FILL_NONE);
}

}

extern "C" void kernel_launch(void* const* d_in, const int* in_sizes, int n_in, void* d_out, int out_size) {
    (void)in_sizes; (void)n_in; (void)out_size;
    void* fnp = nullptr;
    cudaDriverEntryPointQueryResult st;
    cudaGetDriverEntryPoint("cuTensorMapEncodeTiled", &fnp, cudaEnableDefault, &st);
    EncodeFn fn = (EncodeFn)fnp;
    void* scratch = nullptr;
    cudaGetSymbolAddress(&scratch, g_scratch);
    int dev = 0, sms = 0;
    cudaGetDevice(&dev);
    cudaDeviceGetAttribute(&sms, cudaDevAttrMultiProcessorCount, dev);
    auto kernel = sms == 132 ? fused_kernel<true> : fused_kernel<false>;
    cudaFuncSetAttribute(kernel, cudaFuncAttributeMaxDynamicSharedMemorySize, SMEM_BYTES);

    const CUtensorMapSwizzle S128 = CU_TENSOR_MAP_SWIZZLE_128B, S0 = CU_TENSOR_MAP_SWIZZLE_NONE;
    Maps maps;
    encode(fn, &maps.m[M_XA], d_in[0], S128, {896, 2, 64}, {1024, 1792, 128});
    encode(fn, &maps.m[M_WQK], d_in[1], S128, {112, 2, 64}, {448, 2688, 32}, {3, 896, 2}, {4, 224, 1});
    encode(fn, &maps.m[M_WV], d_in[1], S128, {112, 2, 64}, {448, 2688, 64}, {12, 224, 1});
    encode(fn, &maps.m[M_XH], d_in[0], S128, {448, 2, 64}, {128, 1792, 8}, {8, 128 * 1792, 8}, {2, 896, 2});
    encode(fn, &maps.m[M_WO], d_in[2], S128, {112, 2, 64}, {448, 896, 64}, {4, 224, 1});
    encode(fn, &maps.m[M_XB], d_in[3], S128, {448, 2, 64}, {1024, 896, 64}, {2, 896 * 1024, 2});
    encode(fn, &maps.m[M_CR], d_in[4], S128, {2048, 2, 64}, {2048, 4096, 128});
    encode(fn, &maps.m[M_CI], d_in[5], S128, {2048, 2, 64}, {2048, 4096, 128});
    encode(fn, &maps.m[M_WR], d_in[6], S128, {448, 2, 64}, {448, 896, 112});
    encode(fn, &maps.m[M_WI], d_in[7], S128, {448, 2, 64}, {448, 896, 112});
    encode(fn, &maps.m[M_OUTA], d_out, S0, {1792, 2, 112}, {1024, 3584, 8});
    encode(fn, &maps.m[M_OUTB], d_out, S0, {896, 2, 112}, {2048, 1792, 8});

    kernel<<<132, 384, SMEM_BYTES>>>((Scratch*)scratch, maps);
}
```

```cpp
#include <cuda.h>
#include <cuda_bf16.h>
#include <cuda_runtime.h>
#include <stdint.h>

namespace {

constexpr uint32_t SLOT = 16384;
constexpr int NA = 7;
constexpr uint32_t BRING = NA * SLOT;
constexpr uint32_t HALO = BRING + 6 * SLOT;
constexpr uint32_t HSLOT = 1792;
constexpr uint32_t WSLOT = 3584;
constexpr uint32_t BLOB = 14336;
constexpr uint32_t BARS = 14 * SLOT;
constexpr uint32_t BAR_FULL = BARS;
constexpr uint32_t BAR_EMPTY = BARS + 64;
constexpr uint32_t BAR_RDY = BARS + 128;
constexpr uint32_t BAR_DEP = BARS + 168;
constexpr uint32_t BAR_HALO = BARS + 192;
constexpr uint32_t BAR_PART = BARS + 208;
constexpr uint32_t TAG = BARS + 224;
constexpr uint32_t HSPARE = BARS + 256 + 1024;
constexpr uint32_t SMEM_BYTES = HSPARE + HSLOT;
constexpr uint32_t base = 1024;
constexpr int SPIN_LIMIT = 1 << 16;

#define E_EXTRA 0
#define HALO_K_AT 10
#define HALO_V_AT 19
#define O_SLICE 4
#define B_SLICE 4
#define LEAD 3
#define TURN 4
#define PIN r.pin()
#define OPENER 8
#define PACE 500
#define MAPPING 2
constexpr int NBE = 13 + E_EXTRA;
constexpr int POUT = 33 + NBE;
constexpr int ELAST = POUT + 6;
constexpr int LLAST = 52 - E_EXTRA;

enum { M_XB, M_XA, M_XH, M_WR, M_WQK, M_WV, M_WO, M_WI, M_CR, M_CI, M_OUTA, M_OUTB, M_COUNT };
struct __align__(64) Maps { CUtensorMap m[M_COUNT]; };

constexpr int CNT_A = 0;
constexpr int CNT_B = 8;
constexpr int CNT_O = 16;
constexpr int CNT_P = 32;
constexpr int CNT_COUNT = 96;

struct Scratch {
    uint8_t ab[64 * 4 * BLOB];
    uint8_t o[16 * 7 * SLOT];
    uint8_t part[64 * 2 * BLOB];
    uint8_t halo[64 * 2 * 2048];
    unsigned cnt[CNT_COUNT * 32];
    unsigned epoch[132 * 4 * 8];
};
__device__ __align__(1024) Scratch g_scratch;

__device__ __forceinline__ unsigned clk32() { unsigned c; asm volatile("mov.u32 %0, %%clock;" : "=r"(c)); return c; }

#define PROF(idx)

__device__ __forceinline__ void mbar_init(uint32_t bar, uint32_t cnt) {
    asm volatile("mbarrier.init.shared::cta.b64 [%0], %1;" ::"r"(bar), "r"(cnt) : "memory");
}
__device__ __forceinline__ void mbar_expect(uint32_t bar, uint32_t bytes) {
    asm volatile("mbarrier.arrive.expect_tx.shared::cta.b64 _, [%0], %1;" ::"r"(bar), "r"(bytes) : "memory");
}
__device__ __forceinline__ void mbar_arrive(uint32_t bar) {
    asm volatile("mbarrier.arrive.shared::cta.b64 _, [%0];" ::"r"(bar) : "memory");
}
__device__ __forceinline__ bool mbar_try(uint32_t bar, uint32_t parity) {
    uint32_t ok;
    asm volatile("{\n.reg .pred p;\nmbarrier.try_wait.parity.shared::cta.b64 p, [%1], %2;\nselp.u32 %0, 1, 0, p;\n}\n"
                 : "=r"(ok) : "r"(bar), "r"(parity) : "memory");
    return ok;
}
__device__ __forceinline__ bool mbar_test(uint32_t bar, uint32_t parity) {
    uint32_t ok;
    asm volatile("{\n.reg .pred p;\nmbarrier.test_wait.parity.shared::cta.b64 p, [%1], %2;\nselp.u32 %0, 1, 0, p;\n}\n"
                 : "=r"(ok) : "r"(bar), "r"(parity) : "memory");
    return ok;
}
__device__ __forceinline__ void mbar_wait(uint32_t bar, uint32_t parity) {
#pragma unroll 1
    for (int n = 0; n < SPIN_LIMIT; n++)
        if (mbar_try(bar, parity)) break;
}
__device__ __forceinline__ bool elect() {
    uint32_t p;
    asm volatile("{\n.reg .pred p;\nelect.sync _|p, 0xffffffff;\nselp.u32 %0, 1, 0, p;\n}\n" : "=r"(p));
    return p;
}
__device__ __forceinline__ void nb_sync(int id, int n) { asm volatile("bar.sync %0, %1;" ::"r"(id), "r"(n) : "memory"); }
__device__ __forceinline__ void nb_arrive(int id, int n) { asm volatile("bar.arrive %0, %1;" ::"r"(id), "r"(n) : "memory"); }
__device__ __forceinline__ void warp_arrive(uint32_t bar) {
    __syncwarp();
    if (elect()) mbar_arrive(bar);
}
__device__ __forceinline__ uint32_t band(uint32_t x, uint32_t m) {
    uint32_t r;
    asm volatile("and.b32 %0, %1, %2;" : "=r"(r) : "r"(x), "r"(m));
    return r;
}
__device__ __forceinline__ uint32_t dup(uint32_t x, uint32_t zero) {
    uint32_t r;
    asm volatile("xor.b32 %0, %1, %2;" : "=r"(r) : "r"(x), "r"(zero));
    return r;
}

__device__ __forceinline__ void tma_ld2(uint32_t dst, const CUtensorMap* m, int c0, int c1, uint32_t bar) {
    asm volatile("cp.async.bulk.tensor.2d.shared::cluster.global.mbarrier::complete_tx::bytes [%0], [%1, {%3, %4}], [%2];"
                 ::"r"(dst), "l"(m), "r"(bar), "r"(c0), "r"(c1) : "memory");
}
__device__ __forceinline__ void tma_ld4(uint32_t dst, const CUtensorMap* m, int c0, int c1, int c2, int c3, uint32_t bar) {
    asm volatile("cp.async.bulk.tensor.4d.shared::cluster.global.mbarrier::complete_tx::bytes [%0], [%1, {%3, %4, %5, %6}], [%2];"
                 ::"r"(dst), "l"(m), "r"(bar), "r"(c0), "r"(c1), "r"(c2), "r"(c3) : "memory");
}
__device__ __forceinline__ void bulk_ld(uint32_t dst, const void* src, uint32_t bytes, uint32_t bar) {
    asm volatile("cp.async.bulk.shared::cluster.global.mbarrier::complete_tx::bytes [%0], [%1], %2, [%3];"
                 ::"r"(dst), "l"(src), "r"(bytes), "r"(bar) : "memory");
}
__device__ __forceinline__ void tma_st2(const CUtensorMap* m, int c0, int c1, uint32_t src) {
    asm volatile("cp.async.bulk.tensor.2d.global.shared::cta.bulk_group [%0, {%1, %2}], [%3];"
                 ::"l"(m), "r"(c0), "r"(c1), "r"(src) : "memory");
}
__device__ __forceinline__ void bulk_commit() { asm volatile("cp.async.bulk.commit_group;" ::: "memory"); }
__device__ __forceinline__ void bulk_wait_read() { asm volatile("cp.async.bulk.wait_group.read 0;" ::: "memory"); }
__device__ __forceinline__ void fence_async_smem() { asm volatile("fence.proxy.async.shared::cta;" ::: "memory"); }
__device__ __forceinline__ void fence_async_global() { asm volatile("fence.proxy.async.global;" ::: "memory"); }

__device__ __forceinline__ void signal(Scratch* sc, int idx) {
    asm volatile("fence.proxy.async;\nred.relaxed.gpu.global.add.u32 [%0], 1;" ::"l"(&sc->cnt[idx * 32]) : "memory");
}
__device__ __forceinline__ unsigned peek(const unsigned* p) {
    unsigned v;
    asm volatile("ld.relaxed.gpu.global.u32 %0, [%1];" : "=r"(v) : "l"(p) : "memory");
    return v;
}
__device__ __forceinline__ void await(Scratch* sc, int idx, unsigned target) {
    const unsigned* p = &sc->cnt[idx * 32];
#pragma unroll 1
    for (int n = 0; n < SPIN_LIMIT; n++)
        if ((int)(peek(p) - target) >= 0) break;
    asm volatile("fence.acquire.gpu;" ::: "memory");
}
__device__ __forceinline__ void wait_dep(int k) {
    mbar_wait(base + BAR_DEP + k * 8, 0);
    fence_async_global();
}

#define WG_REGS                                                                                                     \
    "{%0,%1,%2,%3,%4,%5,%6,%7,%8,%9,%10,%11,%12,%13,%14,%15,%16,%17,%18,%19,%20,%21,%22,%23,%24,%25,%26,%27,"       \
    "%28,%29,%30,%31,%32,%33,%34,%35,%36,%37,%38,%39,%40,%41,%42,%43,%44,%45,%46,%47,%48,%49,%50,%51,%52,%53,%54,%55}"
#define WG_OPS(C)                                                                                                   \
    C(d[0]), C(d[1]), C(d[2]), C(d[3]), C(d[4]), C(d[5]), C(d[6]), C(d[7]), C(d[8]), C(d[9]), C(d[10]), C(d[11]),   \
    C(d[12]), C(d[13]), C(d[14]), C(d[15]), C(d[16]), C(d[17]), C(d[18]), C(d[19]), C(d[20]), C(d[21]), C(d[22]),   \
    C(d[23]), C(d[24]), C(d[25]), C(d[26]), C(d[27]), C(d[28]), C(d[29]), C(d[30]), C(d[31]), C(d[32]), C(d[33]),   \
    C(d[34]), C(d[35]), C(d[36]), C(d[37]), C(d[38]), C(d[39]), C(d[40]), C(d[41]), C(d[42]), C(d[43]), C(d[44]),   \
    C(d[45]), C(d[46]), C(d[47]), C(d[48]), C(d[49]), C(d[50]), C(d[51]), C(d[52]), C(d[53]), C(d[54]), C(d[55])

template <int TA, int TB, int SB, bool INIT, uint32_t AH, uint32_t BH>
__device__ __forceinline__ void wgmma112(float (&d)[56], uint32_t alo, uint32_t blo) {
    if (INIT) {
        asm volatile("{\n.reg .pred p;\n.reg .b64 da, db;\nsetp.ne.b32 p, 0, 0;\nmov.b64 da, {%56, %61};\nmov.b64 db, {%57, %62};\n"
                     "wgmma.mma_async.sync.aligned.m64n112k16.f32.bf16.bf16 " WG_REGS ", da, db, p, 1, %59, %60, %58;\n}\n"
                     : WG_OPS("=f") : "r"(alo), "r"(blo), "n"(TB), "n"(SB), "n"(TA), "n"(AH), "n"(BH));
    } else {
        asm volatile("{\n.reg .pred p;\n.reg .b64 da, db;\nsetp.ne.b32 p, 1, 0;\nmov.b64 da, {%56, %61};\nmov.b64 db, {%57, %62};\n"
                     "wgmma.mma_async.sync.aligned.m64n112k16.f32.bf16.bf16 " WG_REGS ", da, db, p, 1, %59, %60, %58;\n}\n"
                     : WG_OPS("+f") : "r"(alo), "r"(blo), "n"(TB), "n"(SB), "n"(TA), "n"(AH), "n"(BH));
    }
}
__device__ __forceinline__ void acc_fence(float (&d)[56]) {
#pragma unroll
    for (int i = 0; i < 56; i++) asm volatile("" : "+f"(d[i])::"memory");
}

__device__ __forceinline__ uint32_t pack2(float lo, float hi) {
    uint32_t r;
    asm volatile("cvt.rn.bf16x2.f32 %0, %1, %2;" : "=r"(r) : "f"(hi), "f"(lo));
    return r;
}
__device__ __forceinline__ uint32_t movm(uint32_t a) {
    uint32_t r;
    asm volatile("movmatrix.sync.aligned.m8n8.trans.b16 %0, %1;" : "=r"(r) : "r"(a));
    return r;
}
__device__ __forceinline__ void stsm4(uint32_t addr, uint32_t a, uint32_t b, uint32_t c, uint32_t d) {
    asm volatile("stmatrix.sync.aligned.m8n8.x4.shared.b16 [%0], {%1,%2,%3,%4};" ::"r"(addr), "r"(a), "r"(b), "r"(c), "r"(d) : "memory");
}
__device__ __forceinline__ void sts1(uint32_t addr, uint32_t a) { asm volatile("st.shared.b32 [%0], %1;" ::"r"(addr), "r"(a) : "memory"); }
__device__ __forceinline__ uint32_t lds1(uint32_t addr) {
    uint32_t a;
    asm volatile("ld.shared.b32 %0, [%1];" : "=r"(a) : "r"(addr) : "memory");
    return a;
}
__device__ __forceinline__ void stg1(uint8_t* p, uint32_t a) { asm volatile("st.global.b32 [%0], %1;" ::"l"(p), "r"(a) : "memory"); }
__device__ __forceinline__ void st_part(uint8_t* p, const uint32_t* v, uint32_t parity) {
    asm volatile("{\n.reg .b64 x, y;\nmov.b64 x, {%1, %2};\nmov.b64 y, {%3, %4};\nst.relaxed.gpu.global.v2.b64 [%0], {x, y};\n}\n"
                 ::"l"(p), "r"((v[0] & ~1u) | parity), "r"(v[1]), "r"((v[2] & ~1u) | parity), "r"(v[3]) : "memory");
}
__device__ __forceinline__ void mma16816(float (&d)[4], const uint32_t (&a)[4], uint32_t b0, uint32_t b1) {
    asm volatile("mma.sync.aligned.m16n8k16.row.col.f32.bf16.bf16.f32 {%0,%1,%2,%3}, {%4,%5,%6,%7}, {%8,%9}, {%0,%1,%2,%3};"
                 : "+f"(d[0]), "+f"(d[1]), "+f"(d[2]), "+f"(d[3]) : "r"(a[0]), "r"(a[1]), "r"(a[2]), "r"(a[3]), "r"(b0), "r"(b1));
}
__device__ __forceinline__ uint32_t add2(uint32_t a, uint32_t b) {
    uint32_t r;
    asm("add.rn.bf16x2 %0, %1, %2;" : "=r"(r) : "r"(a), "r"(b));
    return r;
}
__device__ __forceinline__ uint32_t max2(uint32_t a, uint32_t b) {
    uint32_t r;
    asm("max.bf16x2 %0, %1, %2;" : "=r"(r) : "r"(a), "r"(b));
    return r;
}
__device__ __forceinline__ void ld_tagged(const uint8_t* p, uint32_t& a, uint32_t& ta, uint32_t& b, uint32_t& tb) {
    asm volatile("{\n.reg .b64 x, y;\nld.relaxed.gpu.global.v2.b64 {x, y}, [%4];\nmov.b64 {%0, %1}, x;\nmov.b64 {%2, %3}, y;\n}\n"
                 : "=r"(a), "=r"(ta), "=r"(b), "=r"(tb) : "l"(p) : "memory");
}
__device__ __forceinline__ float bf_lo(uint32_t v) { return __uint_as_float(v << 16); }
__device__ __forceinline__ float bf_hi(uint32_t v) { return __uint_as_float(v & 0xFFFF0000u); }
__device__ __forceinline__ float rcp(float x) { float r; asm("rcp.approx.ftz.f32 %0, %1;" : "=f"(r) : "f"(x)); return r; }
__device__ __forceinline__ float ex2(float x) { float r; asm volatile("ex2.approx.ftz.f32 %0, %1;" : "=f"(r) : "f"(x)); return r; }

__device__ __forceinline__ uint32_t full_bar(int stage) { return base + BAR_FULL + (stage & 7) * 8; }
__device__ __forceinline__ void wait_released(int j) { mbar_wait(base + BAR_EMPTY + (j & 7) * 8, (j >> 3) & 1); }

template <int V>
struct Int { static constexpr int value = V; };

__host__ __device__ constexpr int bslot_e(int i) { return (i < 2 || i >= 14) ? (i + 5) % 7 : (i + 1) % 5; }
__host__ __device__ constexpr int bslot_l(int i) { return i % 6; }

template <uint32_t OFF>
struct Feed {
    int stage;
    uint32_t dst;
    __device__ __forceinline__ void seek(int i, int slot) { stage = i; dst = base + OFF + slot * SLOT; }
    template <int N>
    __device__ __forceinline__ uint32_t acquire() { wait_released(stage - N); return full_bar(stage); }
    template <int N>
    __device__ __forceinline__ void next() {
        stage++;
        dst += SLOT;
        if (dst == base + OFF + N * SLOT) dst = base + OFF;
    }
};
__device__ __forceinline__ int skip_own(int n, int mt) { return n == mt ? 15 : n; }

struct Desc { uint32_t lo, hi; };
__host__ __device__ constexpr Desc desc_const(uint32_t lbo, uint32_t sbo, uint32_t mode) { return {(lbo >> 4) << 16, (sbo >> 4) | (mode << 30)}; }
constexpr Desc D_K128 = desc_const(16, 1024, 1);
constexpr Desc D_N128 = desc_const(8192, 1024, 1);
constexpr Desc D_BLOB = desc_const(128, 256, 0);
constexpr Desc D_OT = desc_const(2048, 128, 0);

enum Kind { XW, XWN, QK, BIG, OUT };

struct Ring {
    int stage;
    uint32_t a, b;
    uint32_t wg;
    uint32_t zero;
    __device__ __forceinline__ void seek(int i, int bslot) {
        stage = i;
        a = (base + (i % NA) * SLOT) >> 4;
        b = (base + BRING + bslot * SLOT) >> 4;
    }
    __device__ __forceinline__ void wait() { mbar_wait(full_bar(stage), (stage >> 3) & 1); }
    __device__ __forceinline__ void take_turn() { nb_sync(1 + wg, 256); }
    __device__ __forceinline__ void pin() {
        uint32_t n = 0;
#pragma unroll 1
        do {
            asm volatile("pmevent 7;" ::: "memory");
        } while (n++ < zero);
    }
    template <Kind K, int NBS, bool INIT, int SB = 1, bool TAIL = false>
    __device__ __forceinline__ void run(float (&d)[56], float (&e)[56], bool first = true, bool last = true, bool more = true) {
        if (first) take_turn();
        asm volatile("wgmma.fence.sync.aligned;" ::: "memory");
        if (K == QK) {
            const uint32_t da = D_K128.lo + (base >> 4) + (stage >> 1) * (SLOT >> 4) + (stage & 1) * 4 + wg * 512, db = D_N128.lo + b;
            wgmma112<0, 1, 1, INIT, D_K128.hi, D_N128.hi>(d, da, db);
            wgmma112<0, 1, 1, INIT, D_K128.hi, D_N128.hi>(e, da, db + 256);
            wgmma112<0, 1, 1, false, D_K128.hi, D_N128.hi>(d, da + 2, db + 128);
            wgmma112<0, 1, 1, false, D_K128.hi, D_N128.hi>(e, da + 2, db + 384);
        } else {
            constexpr int TA = K == OUT, TB = K != XW;
            constexpr uint32_t sa = K == OUT ? 256 : 2, sb = K == XW ? 2 : K == BIG ? 224 : 128;
            constexpr Desc A = K == OUT ? D_OT : D_K128, B = K == XW ? D_K128 : K == BIG ? D_BLOB : D_N128;
            const uint32_t da = A.lo + a + wg * (K == OUT ? 64 : 512), db = B.lo + b;
            wgmma112<TA, TB, SB, INIT, A.hi, B.hi>(d, da, db);
            wgmma112<TA, TB, SB, false, A.hi, B.hi>(d, da + sa, db + sb);
            wgmma112<TA, TB, SB, false, A.hi, B.hi>(d, da + 2 * sa, db + 2 * sb);
            wgmma112<TA, TB, SB, false, A.hi, B.hi>(d, da + 3 * sa, db + 3 * sb);
        }
        asm volatile("wgmma.commit_group.sync.aligned;" ::: "memory");
        if (last) nb_arrive(2 - wg, 256);
        if (!TAIL) asm volatile("wgmma.wait_group.sync.aligned 1;" ::: "memory");
        if (!TAIL && stage > 0 && elect()) mbar_arrive(base + BAR_EMPTY + ((stage - 1) & 7) * 8);
        stage++;
        a += SLOT >> 4;
        if (a == (base + NA * SLOT) >> 4) a = base >> 4;
        b += SLOT >> 4;
        if (b == (base + BRING + NBS * SLOT) >> 4) b = (base + BRING) >> 4;
        if (more) wait();
    }
    template <Kind K, int NBS, bool INIT, int SB = 1, bool TAIL = false>
    __device__ __forceinline__ void run(float (&d)[56], bool first = true, bool last = true, bool more = true) {
        run<K, NBS, INIT, SB, TAIL>(d, d, first, last, more);
    }
};

__device__ __forceinline__ void pack_all(const float (&d)[56], uint32_t (&p)[28]) {
#pragma unroll
    for (int i = 0; i < 28; i++) p[i] = pack2(d[2 * i], d[2 * i + 1]);
}
template <int I0, int I1>
__device__ __forceinline__ void store_frags(uint8_t* dst, const uint32_t (&p)[28]) {
#pragma unroll
    for (int i = I0; i < I1; i++) stg1(dst + i * 128, p[i]);
}
template <int I0, int I1>
__device__ __forceinline__ void stage_frags(uint32_t lane_addr, const uint32_t (&p)[28]) {
#pragma unroll
    for (int i = I0; i < I1; i += 4) stsm4(lane_addr + i * 128, p[i], p[i + 1], p[i + 2], p[i + 3]);
}
template <class F>
__device__ __forceinline__ void store_out(F frag, int lane, uint32_t slab, const CUtensorMap* m, int c0, int c1) {
    const bool swap = lane & 16;
    const uint32_t addr = slab + (lane & 7) * 224 + ((lane >> 3) ^ ((lane >> 2) & 1)) * 16;
#pragma unroll
    for (int h = 0; h < 2; h++) {
#pragma unroll
        for (int c = 0; c < 14; c += 4) {
            const uint32_t t0 = frag(2 * c + h), t1 = frag(2 * c + 2 + h);
            if (c < 12) {
                const uint32_t t2 = frag(2 * c + 4 + h), t3 = frag(2 * c + 6 + h);
                stsm4(addr + h * 1792 + c * 16, swap ? t1 : t0, swap ? t0 : t1, swap ? t3 : t2, swap ? t2 : t3);
            } else {
                asm volatile("stmatrix.sync.aligned.m8n8.x2.shared.b16 [%0], {%1,%2};" ::"r"(addr + h * 1792 + c * 16), "r"(swap ? t1 : t0), "r"(swap ? t0 : t1) : "memory");
            }
        }
        fence_async_smem();
        __syncwarp();
        if (elect()) tma_st2(m, c0, c1 + 8 * h, slab + h * 1792);
    }
    if (elect()) {
        bulk_commit();
        bulk_wait_read();
    }
}
__host__ __device__ constexpr int tile_of(int t) { return 7 * (t >> 2) + 3 * ((t >> 1) & 1) + 2 * (t & 1); }

struct Role {
    bool H;
    int L, mt, ns, id;
};
template <bool BY_SM>
__device__ __forceinline__ Role decode_role() {
    uint32_t sm;
    if (BY_SM) asm volatile("mov.u32 %0, %%smid;" : "=r"(sm));
    else asm volatile("mov.u32 %0, %%ctaid.x;" : "=r"(sm));
    const int tpc = sm >> 1, q2 = ((tpc - 32) * 37) >> 8;
    const int gpc = tpc < 32 ? tpc & 7 : tpc < 60 ? tpc - 31 - 7 * q2 : 0;
    const int pos = tpc < 32 ? tpc >> 3 : tpc < 60 ? q2 + 4 : tpc - 56;
    Role r;
    r.H = sm >= 128;
    r.L = gpc & 1;
    r.mt = (gpc >> 1) * 4 + (pos >> 1);
    r.ns = (pos & 1) * 2 + (sm & 1);
    r.id = r.H ? sm : gpc * 16 + pos * 2 + (sm & 1);
    return r;
}

template <bool PACED>
__device__ __forceinline__ void first_fill(const Maps& maps, const Role& r, int i0, int i1, unsigned t0) {
    const bool E = !r.L && !r.H;
    const CUtensorMap* ma = &maps.m[r.H ? 2 : r.L];
    const int a0 = r.L ? (r.mt >> 3) * 448 : 0, a1 = r.L ? (r.mt & 7) * 128 : r.H ? 120 : r.mt * 64;
    const int b3 = E ? 0 : r.H ? 4 + r.ns : r.ns;
#pragma unroll 1
    for (int i = i0; i < i1; i++) {
        if (PACED) while (clk32() - t0 < i * PACE) {}
        const uint32_t bar = full_bar(i);
        const int k = (i * 64) >> r.L;
        const bool has_a = !(i & r.L), has_b = i < 7 - r.L;
        const uint32_t dst = base + BRING + (E ? (0x2104365u >> (4 * i)) & 7 : i) * SLOT;
        mbar_expect(bar, (has_a ? SLOT : 0) + (has_b ? (E ? BLOB : SLOT) : 0));
        if (has_a) tma_ld4(base + (i >> r.L) * SLOT, ma, a0 + k, a1, 0, 0, bar);
        if (has_b) {
            tma_ld4(dst, ma + 3, E ? k : 0, E ? r.ns * 112 : k, 0, b3, bar);
            if (!E) tma_ld4(dst + 8192, ma + 3, 64, k, 0, b3, bar);
            mbar_arrive(bar);
        }
    }
}
static_assert(bslot_e(0) == 5 && bslot_e(1) == 6 && bslot_e(2) == 3 && bslot_e(3) == 4 && bslot_e(4) == 0 && bslot_e(6) == 2, "");

template <bool BY_SM>
__global__ void __launch_bounds__(384, 1) fused_kernel(Scratch* sc, const __grid_constant__ Maps maps) {
    const unsigned t_open = clk32();
    const int warp = __shfl_sync(0xffffffffu, threadIdx.x >> 5, 0);
    if (warp == OPENER) {
        if (elect()) {
#pragma unroll
            for (int i = 0; i < LEAD; i++) mbar_init(base + BAR_FULL + i * 8, 2);
            asm volatile("fence.mbarrier_init.release.cluster;" ::: "memory");
            first_fill<false>(maps, decode_role<BY_SM>(), 0, LEAD, 0);
        }
    }
    if (warp == 9) {
        if (elect()) {
#pragma unroll
            for (int i = 0; i < 8; i++) mbar_init(base + BAR_EMPTY + i * 8, 8);
            asm volatile("fence.mbarrier_init.release.cluster;" ::: "memory");
        }
    } else if (warp == 10) {
        if (elect()) {
#pragma unroll
            for (int i = 0; i < 5; i++) mbar_init(base + BAR_RDY + i * 8, i < 2 ? 4 : 8);
#pragma unroll
            for (int i = 0; i < 2; i++) mbar_init(base + BAR_HALO + i * 8, 9);
            asm volatile("fence.mbarrier_init.release.cluster;" ::: "memory");
        }
    } else if (warp == 11) {
        if (elect()) {
#pragma unroll
            for (int i = LEAD; i < 8; i++) mbar_init(base + BAR_FULL + i * 8, 2);
#pragma unroll
            for (int i = 0; i < 3; i++) mbar_init(base + BAR_DEP + i * 8, 1);
#pragma unroll
            for (int i = 0; i < 2; i++) mbar_init(base + BAR_PART + i * 8, 1);
            asm volatile("fence.mbarrier_init.release.cluster;" ::: "memory");
        }
    }
    __syncthreads();

    const Role role = decode_role<BY_SM>();
    int lane = threadIdx.x & 31;
    asm volatile("" : "+r"(lane));
    const bool roleH = role.H;
    const int roleL = role.L, mt = role.mt, ns = role.ns, bid = role.id;
    const int par = mt >> 3, blk = mt & 7, col = ns * 112;

    if (__builtin_expect(warp >= 8, 1)) {
        asm volatile("setmaxnreg.dec.sync.aligned.u32 56;");
#define PROF_FEED_A
#define PROF_FEED_B
        if (__builtin_expect(warp == 8, 1)) {
            if (elect()) {
                PROF(129);
                first_fill<true>(maps, role, LEAD, 7, t_open);
                PROF(134);
                Feed<0> f;
                const int row = mt * 128;
                auto c_run = [&](const CUtensorMap* m, int off, int n0, int n1) {
#pragma unroll 1
                    for (int n = n0; n < n1; n++) {
                        const uint32_t bar = f.acquire<NA>();
                        mbar_expect(bar, SLOT);
                        tma_ld2(f.dst, m, (off + skip_own(n, mt)) * 64, row, bar);
                        PROF_FEED_A;
                        f.next<NA>();
                    }
                };
                if (roleH) {
                } else if (!roleL) {
                    f.seek(14, 0);
                    mbar_wait(base + BAR_RDY, 0);
#pragma unroll 1
                    for (int i = 0; i < 4; i++) {
                        const uint32_t bar = f.acquire<NA>();
                        mbar_expect(bar, SLOT);
                        tma_ld2(f.dst, &maps.m[M_CR + (i >> 1)], ((i & 1) * 16 + mt) * 64, row, bar);
                        mbar_arrive(bar);
                        PROF_FEED_A;
                        f.next<NA>();
                    }
                    c_run(&maps.m[M_CR], 0, 0, 15);
                    c_run(&maps.m[M_CI], 0, 0, NBE);
                    wait_dep(2);
#pragma unroll 1
                    for (int i = 0; i < 7; i++) {
                        const uint32_t bar = f.acquire<NA>();
                        mbar_expect(bar, SLOT);
                        bulk_ld(f.dst, sc->o + (size_t)(mt * 7 + i) * SLOT, SLOT, bar);
                        PROF_FEED_A;
                        f.next<NA>();
                    }
                } else {
#pragma unroll 1
                    for (int i = 4; i < 7; i++) {
                        wait_released(2 * i - 8);
                        mbar_expect(full_bar(2 * i), SLOT);
                        tma_ld4(base + i * SLOT, &maps.m[M_XA], par * 448 + i * 64, blk * 128, 0, 0, full_bar(2 * i));
                    }
                    wait_released(HALO_K_AT);
                    mbar_arrive(base + BAR_DEP + 16);
                    f.seek(21, 0);
                    c_run(&maps.m[M_CR], 16, 0, 15);
                    c_run(&maps.m[M_CI], 16, 0, 15);
                    c_run(&maps.m[M_CI], 0, NBE, 15);
                }
            }
        } else if (warp == 11) {
            if (elect()) {
                Feed<BRING> f;
                auto blob_run = [&](auto nbs, int quarter, int n0, int n1) {
                    constexpr int N = decltype(nbs)::value;
                    const uint8_t* src = sc->ab + (size_t)(quarter * 64 + ns) * BLOB;
#pragma unroll 1
                    for (int n = n0; n < n1; n++) {
                        const uint32_t bar = f.template acquire<N>();
                        mbar_expect(bar, BLOB);
                        bulk_ld(f.dst, src + skip_own(n, mt) * (4 * BLOB), BLOB, bar);
                        PROF_FEED_B;
                        f.template next<N>();
                    }
                };
                auto w_run = [&](auto nbs, const CUtensorMap* m, int slice, bool no_a) {
                    constexpr int N = decltype(nbs)::value;
#pragma unroll 1
                    for (int i = 0; i < 7; i++) {
                        const uint32_t bar = f.template acquire<N>();
                        mbar_expect(bar, SLOT);
                        tma_ld4(f.dst, m, 0, i * 64, 0, slice, bar);
                        tma_ld4(f.dst + 8192, m, 64, i * 64, 0, slice, bar);
                        if (no_a) mbar_arrive(bar);
                        PROF_FEED_B;
                        f.template next<N>();
                    }
                };
                if (roleH) {
                    f.seek(7, 0);
                    w_run(Int<7>(), &maps.m[M_WV], 8 + ns, true);
                } else if (!roleL) {
                    f.seek(7, bslot_e(7));
#pragma unroll 1
                    for (int i = 0; i < 7; i++) {
                        const uint32_t bar = f.acquire<5>();
                        mbar_expect(bar, BLOB);
                        tma_ld2(f.dst, &maps.m[M_WI], i * 64, col, bar);
                        mbar_arrive(bar);
                        PROF_FEED_B;
                        f.next<5>();
                    }
                    f.seek(18, bslot_e(18));
                    wait_dep(0);
                    blob_run(Int<7>(), 0, 0, 15);
                    wait_dep(1);
                    blob_run(Int<7>(), 2, 0, NBE);
                    w_run(Int<7>(), &maps.m[M_WO], ns, false);
                } else {
                    f.seek(6, 0);
#pragma unroll 1
                    for (int i = 6; i < 14; i++) {
                        const uint32_t bar = f.acquire<6>();
                        mbar_expect(bar, SLOT);
                        tma_ld4(f.dst, &maps.m[M_WQK], 0, i * 32, 0, ns, bar);
                        tma_ld4(f.dst + 8192, &maps.m[M_WQK], 64, i * 32, 0, ns, bar);
                        if (i & 1) mbar_arrive(bar);
                        PROF_FEED_B;
                        f.next<6>();
                    }
                    w_run(Int<6>(), &maps.m[M_WV], 8 + ns, true);
                    wait_dep(0);
                    blob_run(Int<6>(), 1, 0, 15);
                    wait_dep(1);
                    blob_run(Int<6>(), 3, 0, 15);
                    blob_run(Int<6>(), 2, NBE, 15);
                }
            }
        } else if (roleH) {
            if (elect()) {
                wait_released(warp == 9 ? 0 : 7);
#pragma unroll 1
                for (int i = 0; i < 7; i++) {
                    if (warp == 9) {
                        asm volatile("cp.async.bulk.prefetch.tensor.2d.L2.global [%0, {%1, %2}];" ::"l"(&maps.m[M_WI]), "r"(i * 64), "r"(col) : "memory");
                    } else {
                        asm volatile("cp.async.bulk.prefetch.tensor.4d.L2.global [%0, {%1, %2, 0, %3}];" ::"l"(&maps.m[M_WO]), "r"(0), "r"(i * 64), "r"(ns) : "memory");
                        asm volatile("cp.async.bulk.prefetch.tensor.4d.L2.global [%0, {%1, %2, 0, %3}];" ::"l"(&maps.m[M_WO]), "r"(64), "r"(i * 64), "r"(ns) : "memory");
                    }
                }
            }
        } else if (warp == 10) {
            if (elect()) {
                unsigned* epoch_ptr = &sc->epoch[(bid * 4 + 2) * 8];
                const unsigned ep = *epoch_ptr + 1;
                sts1(base + TAG, ep);
                asm volatile("prefetch.tensormap [%0];" ::"l"(&maps.m[M_OUTA + roleL]) : "memory");
                await(sc, CNT_A + roleL * 4 + ns, ep * 16);
                mbar_arrive(base + BAR_DEP);
                PROF(150);
                await(sc, CNT_B + ns, ep * 16);
                mbar_arrive(base + BAR_DEP + 8);
                PROF(151);
                if (!roleL) {
                    await(sc, CNT_O + mt, ep * 4);
                    mbar_arrive(base + BAR_DEP + 16);
                } else {
                    await(sc, CNT_P + mt * 4 + ns, ep * 2 - 1);
                    mbar_arrive(base + BAR_PART);
                    PROF(153);
                    await(sc, CNT_P + mt * 4 + ns, ep * 2);
                    mbar_arrive(base + BAR_PART + 8);
                }
                PROF(152);
                *epoch_ptr = ep;
            }
        } else if (!roleL) {
            if (elect()) {
                mbar_wait(base + BAR_RDY, 0);
                PROF(130);
                signal(sc, CNT_A + ns);
                PROF(131);
                mbar_wait(base + BAR_RDY + 8, 0);
                signal(sc, CNT_A + 4 + ns);
                PROF(135);
                mbar_wait(base + BAR_RDY + 32, 0);
                PROF(132);
                signal(sc, CNT_B + ns);
                PROF(133);
            }
        } else {
            unsigned* epoch_ptr = &sc->epoch[(bid * 4 + 1) * 8];
            const unsigned tag = *epoch_ptr + 1;
#pragma unroll 1
            for (int kv = 0; kv < 2; kv++) {
                uint32_t v[16];
#pragma unroll
                for (int i = 0; i < 16; i++) v[i] = 0;
                if (kv) mbar_wait(base + BAR_HALO, 0), wait_released(HALO_V_AT);
                else mbar_wait(base + BAR_DEP + 16, 0);
                if (blk > 0) {
                    const uint8_t* src = sc->halo + (size_t)(((mt - 1) * 4 + ns) * 2 + kv) * 2048 + lane * 16;
#pragma unroll 1
                    for (int n = 0; n < SPIN_LIMIT; n++) {
                        uint32_t stale = 0;
#pragma unroll
                        for (int i = 0; i < 4; i++) ld_tagged(src + i * 512, v[4 * i], v[4 * i + 1], v[4 * i + 2], v[4 * i + 3]);
#pragma unroll
                        for (int i = 0; i < 16; i += 2) stale |= v[i] ^ tag;
                        if (__all_sync(0xffffffffu, !(stale & 1))) break;
                    }
#pragma unroll
                    for (int c = 0; c < 14; c += 2) v[c] = (v[c] & ~1u) | ((v[15] >> c) & 1);
                }
#pragma unroll
                for (int i = 0; i < 14; i++) sts1(base + HALO + kv * (8 * HSLOT) + i * 128 + lane * 4, v[i]);
                warp_arrive(base + BAR_HALO + kv * 8);
                if (lane == 0) PROF(142 + kv);
            }
            if (elect()) {
                mbar_wait(base + BAR_RDY + 16, 0);
                PROF(130);
                signal(sc, CNT_O + mt);
                PROF(131);
                *epoch_ptr = tag;
            }
        }
    } else {
        asm volatile("setmaxnreg.inc.sync.aligned.u32 224;");
        Ring r;
        r.wg = warp >> 2;
        r.zero = blockIdx.y;
        const int wg = warp >> 2;
        if (wg) nb_arrive(1, 256);
        r.stage = 0;
        r.wait();
        uint8_t* part = sc->part + (size_t)(ns * 16 + mt) * (2 * BLOB) + warp * 512 + lane * 16;
        uint32_t p[28];

        if (roleH) {
            unsigned* epoch_ptr = &sc->epoch[bid * 4 * 8];
            const unsigned tag = *epoch_ptr + 1;
            uint8_t* hout = sc->halo + (size_t)((warp * 8 + ns) * 2) * 2048 + lane * 16;
            auto send = [&](int kv) {
#pragma unroll
                for (int h = 0; h < 2; h++) {
                    uint32_t v[16];
                    v[14] = v[15] = 0;
#pragma unroll
                    for (int c = 0; c < 14; c++) v[c] = p[2 * c + h];
#pragma unroll
                    for (int c = 0; c < 14; c += 2) v[15] |= (v[c] & 1) << c;
#pragma unroll
                    for (int i = 0; i < 4; i++) st_part(hout + (h * 8 + kv) * 2048 + i * 512, v + 4 * i, tag & 1);
                }
            };
            float x0[56], x1[56];
            r.seek(0, 0);
            r.run<XWN, 7, true>(x0);
#pragma unroll 1
            for (int i = 1; i < 7; i++) r.run<XWN, 7, false>(x0);
            r.run<XWN, 7, true>(x1);
            acc_fence(x0);
            pack_all(x0, p);
            send(0);
#pragma unroll 1
            for (int i = 1; i < 7; i++) r.run<XWN, 7, false>(x1, true, true, i < 6);
            asm volatile("wgmma.wait_group.sync.aligned 0;" ::: "memory");
            acc_fence(x1);
            pack_all(x1, p);
#pragma unroll
            for (int i = 0; i < 28; i++) p[i] = movm(p[i]);
            send(1);
            if (threadIdx.x == 0) *epoch_ptr = tag;
        } else if (!roleL) {
            uint8_t* blob = sc->ab + (size_t)((wg * 16 + mt) * 4 + ns) * BLOB + (warp & 3) * WSLOT + lane * 4;
            const uint32_t own = base + BRING + wg * SLOT + (warp & 3) * WSLOT + lane * 16;
            float x0[56], x1[56];
            r.seek(0, bslot_e(0));
            r.run<XW, 7, true>(x0);
            r.run<XW, 7, false>(x0);
            r.seek(2, bslot_e(2));
#pragma unroll 1
            for (int i = 2; i < 7; i++) r.run<XW, 5, false>(x0);

            r.seek(7, bslot_e(7));
            r.run<XW, 5, true, -1>(x1);
            acc_fence(x0);
            pack_all(x0, p);
#pragma unroll
            for (int i = 0; i < 2; i++) {
                if (wg == i) store_frags<0, 14>(blob, p);
                else stage_frags<0, 4>(own + 5 * SLOT, p);
                r.run<XW, 5, false, -1>(x1);
                if (wg == i) {
                    store_frags<14, 28>(blob, p);
                    warp_arrive(base + BAR_RDY + i * 8);
                } else {
                    stage_frags<4, 8>(own + 5 * SLOT, p);
                }
                r.run<XW, 5, false, -1>(x1);
            }
            stage_frags<8, 20>(own + 5 * SLOT, p);
            r.run<XW, 5, false, -1>(x1);
            stage_frags<20, 28>(own + 5 * SLOT, p);
            warp_arrive(base + BAR_RDY + 16);
            r.run<XW, 5, false, -1>(x1);

            mbar_wait(base + BAR_RDY + 16, 0);
            fence_async_smem();
            r.seek(14, bslot_e(14));
            r.run<BIG, 7, true>(x0);
            acc_fence(x1);
            pack_all(x1, p);
            wait_released(10);
            stage_frags<0, 28>(own, p);
            warp_arrive(base + BAR_RDY + 24);
            r.run<BIG, 7, false>(x0);
            mbar_wait(base + BAR_RDY + 24, 0);
            fence_async_smem();
            blob += (size_t)128 * BLOB;
#pragma unroll
            for (int i = 0; i < 28; i++) {
                if (i % B_SLICE == 0) r.run<BIG, 7, false>(x0);
                stg1(blob + i * 128, p[i]);
            }
            warp_arrive(base + BAR_RDY + 32);
#pragma unroll 1
            for (int i = 17 + 27 / B_SLICE; i < POUT; i++) r.run<BIG, 7, false>(x0);

            const uint32_t tag = lds1(base + TAG);
            r.seek(POUT, bslot_e(POUT));
            r.run<OUT, 7, true>(x1);
            acc_fence(x0);
            pack_all(x0, p);
#pragma unroll
            for (int k = 0; k < 3; k++) {
                if (k < 2 && wg == k) {
                    if ((warp & 3) == 0 && elect())
                        asm volatile("red.relaxed.gpu.global.add.u32 [%0], 1;" ::"l"(&sc->cnt[(CNT_P + mt * 4 + ns) * 32]) : "memory");
#pragma unroll
                    for (int i = 0; i < 4; i++) st_part(part + i * 4096, p + 4 * i, tag & 1);
                }
                if (k > 0 && wg == k - 1) {
#pragma unroll
                    for (int i = 4; i < 7; i++) st_part(part + i * 4096, p + 4 * i, tag & 1);
                }
                if (k < 2) r.run<OUT, 7, false>(x1);
            }
#pragma unroll
            for (int i = 3; i < 7; i++) r.run<OUT, 7, false, 1, true>(x1, i <= 7 - TURN, i < 7 - TURN || i == 6, i < 6);

            wait_released(ELAST - 6);
            asm volatile("wgmma.wait_group.sync.aligned 0;" ::: "memory");
            acc_fence(x1);
            const uint32_t slab = base + (wg ? BRING + bslot_e(ELAST - 6) * SLOT : ((ELAST - 6) % NA) * SLOT) + (warp & 3) * WSLOT;
            store_out([&](int i) { return pack2(x1[2 * i], x1[2 * i + 1]); }, lane, slab, &maps.m[M_OUTA], par * 896 + col, blk * 128 + warp * 16);
        } else {
            const int g = lane >> 2, tig = lane & 3;
            const uint32_t hin = base + HALO + warp * HSLOT + lane * 4;
            const uint32_t hpub = warp < 7 ? hin + HSLOT : base + HSPARE + lane * 4;
            auto publish = [&](const uint32_t (&h)[14], int c0, int c1) {
#pragma unroll
                for (int c = 0; c < 14; c++)
                    if (c >= c0 && c < c1) sts1(hpub + c * 128, h[c]);
            };
            float y0[56], y1[56], y2[56];
            r.seek(0, 0);
            r.run<QK, 6, true>(y0, y1);
#pragma unroll 1
            for (int i = 1; i < 14; i++) r.run<QK, 6, false>(y0, y1);

            uint32_t m1[8][4], m0[8][4], lo[14], hi[14], q[2][8][2];
            auto pack_q = [&](int b) {
                uint32_t v[14];
#pragma unroll
                for (int c = 0; c < 14; c++) v[c] = pack2(y0[4 * c + 2 * b], y0[4 * c + 2 * b + 1]);
#pragma unroll
                for (int t = 0; t < 8; t++) {
                    const int c = tile_of(t);
                    q[b][t][0] = (t & 3) == 2 ? (tig >= 2 ? v[c] : 0u) : v[c];
                    q[b][t][1] = (t & 3) == 1 ? (tig < 2 ? v[c + 1] : 0u) : v[c + 1];
                }
            };
            auto fetch = [&](uint32_t src, int hp, int i0) {
#pragma unroll
                for (int t = 4 * hp; t < 4 * hp + 4; t++) {
                    m0[t][i0] = (t & 3) == 2 ? dup(m0[t - 1][3], r.zero) : lds1(src + tile_of(t) * 128);
                    m0[t][3] = lds1(src + tile_of(t) * 128 + 128);
                }
            };
            r.seek(14, bslot_l(14));
            r.run<XWN, 6, true>(y2);
            acc_fence(y0);
            acc_fence(y1);
#pragma unroll
            for (int c = 0; c < 14; c++) hi[c] = pack2(y1[4 * c + 2], y1[4 * c + 3]);
            publish(hi, 0, 7);
            PIN;
            r.run<XWN, 6, false>(y2);
            publish(hi, 7, 14);
            warp_arrive(base + BAR_HALO);
#pragma unroll
            for (int c = 0; c < 14; c++) lo[c] = pack2(y1[4 * c], y1[4 * c + 1]);
#pragma unroll
            for (int t = 0; t < 8; t++) {
                const int c = tile_of(t);
                const bool shared = (t & 3) == 2;
                m1[t][0] = shared ? dup(lo[c], r.zero) : lo[c];
                m1[t][1] = shared ? dup(hi[c], r.zero) : hi[c];
                m1[t][2] = lo[c + 1];
                m1[t][3] = hi[c + 1];
                m0[t][0] = dup(m1[t][0], r.zero);
                m0[t][2] = dup(lo[c + 1], 2 * r.zero);
            }
            PIN;
            r.run<XWN, 6, false>(y2);
            mbar_wait(base + BAR_HALO, 0);
            fetch(hin, 0, 1);
            pack_q(1);
            PIN;
            r.run<XWN, 6, false>(y2);
            fetch(hin, 1, 1);
            pack_q(0);
            r.pin();
            r.take_turn();
            float s[8][4];
#pragma unroll
            for (int step = 0; step < 2; step++) {
#pragma unroll
                for (int i = 0; i < 8; i++) {
                    const int b = 1 - (i >> 2), h = i & 3, t = 2 * h + step;
                    float (&d)[4] = s[2 * h + b];
                    if (step == 0) d[0] = d[1] = d[2] = d[3] = 0.f;
                    mma16816(d, b ? m1[t] : m0[t], q[b][t][0], q[b][t][1]);
                }
            }
            r.pin();
            r.run<XWN, 6, false>(y2, false);

            uint32_t pr[8], mx[4], mx1[4];
            {
                const bool cur0 = g <= 2 * tig, cur1 = g <= 2 * tig + 1;
#pragma unroll
                for (int i = 0; i < 8; i++) {
                    const int c = (i & 1) ? 2 : 0;
                    pr[i] = movm(pack2(cur0 ? s[i][c] : s[i][2 - c], cur1 ? s[i][c + 1] : s[i][3 - c]));
                }
            }
            PIN;
            r.run<XWN, 6, false>(y2);
            const uint32_t curmask = (2 * tig <= g ? 0x0000FFFFu : 0u) | (2 * tig + 1 <= g ? 0xFFFF0000u : 0u);
            {
                const uint32_t keep = (blk == 0 && warp == 0) ? curmask : 0xFFFFFFFFu;
#pragma unroll
                for (int i = 0; i < 4; i++) {
                    pr[2 * i] = (pr[2 * i] & keep) | (0xCF9ECF9Eu & ~keep);
                    mx[i] = max2(__byte_perm(pr[2 * i], pr[2 * i + 1], 0x5410), __byte_perm(pr[2 * i], pr[2 * i + 1], 0x7632));
                    mx1[i] = __shfl_xor_sync(0xffffffffu, mx[i], 1);
                }
            }
            PIN;
            r.run<XWN, 6, false>(y2);
#pragma unroll
            for (int i = 0; i < 4; i++) {
                mx[i] = max2(mx[i], mx1[i]);
                mx1[i] = __shfl_xor_sync(0xffffffffu, mx[i], 2);
            }

            PIN;
            r.seek(21, bslot_l(21));
            r.run<BIG, 6, true>(y0);
            acc_fence(y2);
#pragma unroll
            for (int c = 0; c < 10; c++) hi[c] = movm(pack2(y2[4 * c + 2], y2[4 * c + 3]));
            constexpr float SCL = 0.18898223650461362f * 1.4426950408889634f;
            float e0[8], e1[8], sm[8], sm1[8];
#pragma unroll
            for (int i = 0; i < 8; i++) {
                const uint32_t m2 = max2(mx[i >> 1], mx1[i >> 1]);
                sm[i] = ((i & 1) ? bf_hi(m2) : bf_lo(m2)) * -SCL;
            }
            PIN;
            r.run<BIG, 6, false>(y0);
#pragma unroll
            for (int c = 10; c < 14; c++) hi[c] = movm(pack2(y2[4 * c + 2], y2[4 * c + 3]));
#pragma unroll
            for (int c = 0; c < 4; c++) lo[c] = movm(pack2(y2[4 * c], y2[4 * c + 1]));
#pragma unroll
            for (int i = 0; i < 8; i++) e0[i] = ex2(fmaf(bf_lo(pr[i]), SCL, sm[i]));
            PIN;
            r.run<BIG, 6, false>(y0);
            publish(hi, 0, 10);
#pragma unroll
            for (int i = 0; i < 8; i++) e1[i] = ex2(fmaf(bf_hi(pr[i]), SCL, sm[i]));
            PIN;
            r.run<BIG, 6, false>(y0);
            publish(hi, 10, 14);
            warp_arrive(base + BAR_HALO + 8);
#pragma unroll
            for (int i = 0; i < 8; i++) {
                sm[i] = e0[i] + e1[i];
                sm1[i] = __shfl_xor_sync(0xffffffffu, sm[i], 1);
            }
            PIN;
            r.run<BIG, 6, false>(y0);
#pragma unroll
            for (int c = 4; c < 14; c++) lo[c] = movm(pack2(y2[4 * c], y2[4 * c + 1]));
            PIN;
            r.run<BIG, 6, false>(y0);
#pragma unroll
            for (int i = 0; i < 8; i++) {
                sm[i] += sm1[i];
                sm1[i] = __shfl_xor_sync(0xffffffffu, sm[i], 2);
            }
#pragma unroll
            for (int t = 0; t < 8; t++) {
                const int c = tile_of(t);
                const bool shared = (t & 3) == 2;
                m1[t][0] = shared ? dup(lo[c], r.zero) : lo[c];
                m1[t][1] = lo[c + 1];
                m1[t][2] = shared ? dup(hi[c], r.zero) : hi[c];
                m1[t][3] = hi[c + 1];
                m0[t][0] = dup(m1[t][0], r.zero);
                m0[t][1] = dup(lo[c + 1], 2 * r.zero);
            }
            PIN;
            r.run<BIG, 6, false>(y0);
            mbar_wait(base + BAR_HALO + 8, 0);
            const uint32_t vin = warp ? hin : hin + 8 * HSLOT;
            fetch(vin, 0, 2);
#pragma unroll
            for (int i = 0; i < 8; i++) {
                const float inv = rcp(sm[i] + sm1[i]);
                pr[i] = pack2(e0[i] * inv, e1[i] * inv);
            }
            PIN;
            r.run<BIG, 6, false>(y0);
            fetch(vin, 1, 2);
            uint32_t pb[8][2];
#pragma unroll
            for (int t = 0; t < 8; t++) {
                pb[t][t & 1] = band(pr[t], curmask);
                pb[t][1 - (t & 1)] = band(pr[t], ~curmask);
            }
            r.pin();
            r.take_turn();
            float o[2][8][4];
#pragma unroll
            for (int i = 0; i < 16; i++) {
                const int b = 1 - (i >> 3), t = i & 7;
                float (&d)[4] = o[b][t];
                d[0] = d[1] = d[2] = d[3] = 0.f;
                mma16816(d, b ? m1[t] : m0[t], pb[(t & 6) + b][0], pb[(t & 6) + b][1]);
            }
            r.pin();
            r.run<BIG, 6, false>(y0, false);
            uint8_t* odst = sc->o + (size_t)mt * 7 * SLOT + ns * (14 * 2048) + warp * 256 + lane * 4;
#pragma unroll
            for (int hp = 0; hp < 2; hp++) {
#pragma unroll
                for (int b = 0; b < 2; b++) {
                    const float (&u)[8][4] = o[b];
                    const int t = 4 * hp;
                    uint32_t* w = p + 14 * hp + b;
                    w[0] = pack2(u[t][0], u[t][1]);
                    w[2] = pack2(u[t][2], u[t][3]);
                    w[4] = pack2(u[t + 1][0], u[t + 1][1]);
                    w[6] = pack2(g < 4 ? u[t + 1][2] : u[t + 2][0], g < 4 ? u[t + 1][3] : u[t + 2][1]);
                    w[8] = pack2(u[t + 2][2], u[t + 2][3]);
                    w[10] = pack2(u[t + 3][0], u[t + 3][1]);
                    w[12] = pack2(u[t + 3][2], u[t + 3][3]);
                }
            }
#pragma unroll
            for (int i = 0; i < 28; i++) {
                if (i && i % O_SLICE == 0) r.run<BIG, 6, false>(y0);
                stg1(odst + (i >> 1) * 2048 + (i & 1) * 128, p[i]);
            }
            warp_arrive(base + BAR_RDY + 16);

#pragma unroll 1
            for (int i = 30 + 27 / O_SLICE; i <= LLAST + 1 - TURN; i++) r.run<BIG, 6, false>(y0, true, i <= LLAST - TURN);
            const uint32_t tag = lds1(base + TAG);
            if (mbar_test(base + BAR_PART + wg * 8, 0)) {
#pragma unroll
                for (int i = 0; i < 7; i++) ld_tagged(part + i * 4096, p[4 * i], p[4 * i + 1], p[4 * i + 2], p[4 * i + 3]);
            } else {
                p[0] = ~tag;
            }
            r.seek(LLAST + 2 - TURN, bslot_l(LLAST + 2 - TURN));
#pragma unroll
            for (int i = 1; i < TURN; i++) r.run<BIG, 6, false, 1, true>(y0, false, i == TURN - 1, i < TURN - 1);
#pragma unroll 1
            for (int n = 0; n < SPIN_LIMIT; n++) {
                uint32_t stale = 0;
#pragma unroll
                for (int i = 0; i < 28; i += 2) stale |= p[i] ^ tag;
                if (__all_sync(0xffffffffu, !(stale & 1))) break;
                mbar_wait(base + BAR_PART + wg * 8, 0);
#pragma unroll
                for (int i = 0; i < 7; i++) ld_tagged(part + i * 4096, p[4 * i], p[4 * i + 1], p[4 * i + 2], p[4 * i + 3]);
            }
            wait_released(LLAST - 6);
            asm volatile("wgmma.wait_group.sync.aligned 0;" ::: "memory");
            acc_fence(y0);
            const uint32_t slab = base + (wg ? HALO : ((LLAST - 6) % NA) * SLOT) + (warp & 3) * WSLOT;
            store_out([&](int i) { return add2(pack2(y0[2 * i], y0[2 * i + 1]), p[i]); }, lane, slab, &maps.m[M_OUTB], 448 + col, mt * 128 + warp * 16);
        }
    }
}

typedef CUresult (*EncodeFn)(CUtensorMap*, CUtensorMapDataType, cuuint32_t, void*, const cuuint64_t*, const cuuint64_t*,
                             const cuuint32_t*, const cuuint32_t*, CUtensorMapInterleave, CUtensorMapSwizzle,
                             CUtensorMapL2promotion, CUtensorMapFloatOOBfill);

struct Dim { uint64_t size, stride; uint32_t box; };
void encode(EncodeFn fn, CUtensorMap* m, const void* ptr, CUtensorMapSwizzle sw, Dim d0, Dim d1, Dim d2 = {0, 0, 0}, Dim d3 = {0, 0, 0}) {
    const cuuint64_t dims[4] = {d0.size, d1.size, d2.size, d3.size};
    const cuuint64_t strides[3] = {d1.stride, d2.stride, d3.stride};
    const cuuint32_t box[4] = {d0.box, d1.box, d2.box, d3.box};
    const cuuint32_t es[4] = {1, 1, 1, 1};
    fn(m, CU_TENSOR_MAP_DATA_TYPE_BFLOAT16, d3.size ? 4 : d2.size ? 3 : 2, const_cast<void*>(ptr), dims, strides, box, es,
       CU_TENSOR_MAP_INTERLEAVE_NONE, sw, CU_TENSOR_MAP_L2_PROMOTION_L2_128B, CU_TENSOR_MAP_FLOAT_OOB_FILL_NONE);
}

}

extern "C" void kernel_launch(void* const* d_in, const int* in_sizes, int n_in, void* d_out, int out_size) {
    (void)in_sizes; (void)n_in; (void)out_size;
    void* fnp = nullptr;
    cudaDriverEntryPointQueryResult st;
    cudaGetDriverEntryPoint("cuTensorMapEncodeTiled", &fnp, cudaEnableDefault, &st);
    EncodeFn fn = (EncodeFn)fnp;
    void* scratch = nullptr;
    cudaGetSymbolAddress(&scratch, g_scratch);
    int dev = 0, sms = 0;
    cudaGetDevice(&dev);
    cudaDeviceGetAttribute(&sms, cudaDevAttrMultiProcessorCount, dev);
    auto kernel = sms == 132 ? fused_kernel<true> : fused_kernel<false>;
    cudaFuncSetAttribute(kernel, cudaFuncAttributeMaxDynamicSharedMemorySize, SMEM_BYTES);

    const CUtensorMapSwizzle S128 = CU_TENSOR_MAP_SWIZZLE_128B, S0 = CU_TENSOR_MAP_SWIZZLE_NONE;
    const Dim one = {1, 16, 1};
    Maps maps;
    encode(fn, &maps.m[M_XA], d_in[0], S128, {896, 2, 64}, {1024, 1792, 128}, one, one);
    encode(fn, &maps.m[M_WQK], d_in[1], S128, {112, 2, 64}, {448, 2688, 32}, {3, 896, 2}, {4, 224, 1});
    encode(fn, &maps.m[M_WV], d_in[1], S128, {112, 2, 64}, {448, 2688, 64}, one, {12, 224, 1});
    encode(fn, &maps.m[M_XH], d_in[0], S128, {448, 2, 64}, {128, 1792, 8}, {8, 128 * 1792, 8}, {2, 896, 2});
    encode(fn, &maps.m[M_WO], d_in[2], S128, {112, 2, 64}, {448, 896, 64}, one, {4, 224, 1});
    encode(fn, &maps.m[M_XB], d_in[3], S128, {448, 2, 64}, {1024, 896, 64}, {2, 896 * 1024, 2}, one);
    encode(fn, &maps.m[M_CR], d_in[4], S128, {2048, 2, 64}, {2048, 4096, 128});
    encode(fn, &maps.m[M_CI], d_in[5], S128, {2048, 2, 64}, {2048, 4096, 128});
    encode(fn, &maps.m[M_WR], d_in[6], S128, {448, 2, 64}, {448, 896, 112}, one, one);
    encode(fn, &maps.m[M_WI], d_in[7], S128, {448, 2, 64}, {448, 896, 112});
    encode(fn, &maps.m[M_OUTA], d_out, S0, {1792, 2, 112}, {1024, 3584, 8});
    encode(fn, &maps.m[M_OUTB], d_out, S0, {896, 2, 112}, {2048, 1792, 8});

    kernel<<<132, 384, SMEM_BYTES>>>((Scratch*)scratch, maps);
}
```

```cpp
#include <cuda.h>
#include <cuda_bf16.h>
#include <cuda_runtime.h>
#include <stdint.h>

namespace {

constexpr uint32_t SLOT = 16384;
constexpr int NA = 7;
constexpr uint32_t BRING = NA * SLOT;
constexpr uint32_t HALO = BRING + 6 * SLOT;
constexpr uint32_t HSLOT = 1792;
constexpr uint32_t WSLOT = 3584;
constexpr uint32_t BLOB = 14336;
constexpr uint32_t BARS = 14 * SLOT;
constexpr uint32_t BAR_FULL = BARS;
constexpr uint32_t BAR_EMPTY = BARS + 64;
constexpr uint32_t BAR_RDY = BARS + 128;
constexpr uint32_t BAR_DEP = BARS + 168;
constexpr uint32_t BAR_HALO = BARS + 192;
constexpr uint32_t BAR_PART = BARS + 208;
constexpr uint32_t BAR_B0 = BARS + 224;
constexpr uint32_t TAG = BARS + 232;
constexpr uint32_t HSPARE = BARS + 256 + 1024;
constexpr uint32_t SMEM_BYTES = HSPARE + HSLOT;
constexpr uint32_t base = 1024;
constexpr int SPIN_LIMIT = 1 << 16;

#define E_EXTRA 0
#define HALO_K_AT 10
#define HALO_V_AT 19
#define O_SLICE 4
#define B_SLICE 4
#define LEAD 3
#define TURN 4
#define PIN r.pin()
#define PACE 450
#define MAPPING 2
constexpr int NBE = 13 + E_EXTRA;
constexpr int POUT = 33 + NBE;
constexpr int ELAST = POUT + 6;
constexpr int LLAST = 52 - E_EXTRA;

enum { M_XB, M_XA, M_XH, M_WR, M_WQK, M_WV, M_WO, M_WI, M_CR, M_CI, M_OUTA, M_OUTB, M_COUNT };
struct __align__(64) Maps { CUtensorMap m[M_COUNT]; };

constexpr int CNT_A = 0;
constexpr int CNT_B = 8;
constexpr int CNT_O = 16;
constexpr int CNT_P = 32;
constexpr int CNT_COUNT = 96;

struct Scratch {
    uint8_t ab[64 * 4 * BLOB];
    uint8_t o[16 * 7 * SLOT];
    uint8_t part[64 * 2 * BLOB];
    uint8_t halo[64 * 2 * 2048];
    unsigned cnt[CNT_COUNT * 32];
    unsigned epoch[132 * 4 * 8];
};
__device__ __align__(1024) Scratch g_scratch;

__device__ __forceinline__ unsigned clk32() { unsigned c; asm volatile("mov.u32 %0, %%clock;" : "=r"(c)); return c; }

#define PROF(idx)

__device__ __forceinline__ void mbar_init(uint32_t bar, uint32_t cnt) {
    asm volatile("mbarrier.init.shared::cta.b64 [%0], %1;" ::"r"(bar), "r"(cnt) : "memory");
}
__device__ __forceinline__ void mbar_expect(uint32_t bar, uint32_t bytes) {
    asm volatile("mbarrier.arrive.expect_tx.shared::cta.b64 _, [%0], %1;" ::"r"(bar), "r"(bytes) : "memory");
}
__device__ __forceinline__ void mbar_arrive(uint32_t bar) {
    asm volatile("mbarrier.arrive.shared::cta.b64 _, [%0];" ::"r"(bar) : "memory");
}
__device__ __forceinline__ bool mbar_try(uint32_t bar, uint32_t parity) {
    uint32_t ok;
    asm volatile("{\n.reg .pred p;\nmbarrier.try_wait.parity.shared::cta.b64 p, [%1], %2;\nselp.u32 %0, 1, 0, p;\n}\n"
                 : "=r"(ok) : "r"(bar), "r"(parity) : "memory");
    return ok;
}
__device__ __forceinline__ bool mbar_test(uint32_t bar, uint32_t parity) {
    uint32_t ok;
    asm volatile("{\n.reg .pred p;\nmbarrier.test_wait.parity.shared::cta.b64 p, [%1], %2;\nselp.u32 %0, 1, 0, p;\n}\n"
                 : "=r"(ok) : "r"(bar), "r"(parity) : "memory");
    return ok;
}
__device__ __forceinline__ void mbar_wait(uint32_t bar, uint32_t parity) {
#pragma unroll 1
    for (int n = 0; n < SPIN_LIMIT; n++)
        if (mbar_try(bar, parity)) break;
}
__device__ __forceinline__ bool elect() {
    uint32_t p;
    asm volatile("{\n.reg .pred p;\nelect.sync _|p, 0xffffffff;\nselp.u32 %0, 1, 0, p;\n}\n" : "=r"(p));
    return p;
}
__device__ __forceinline__ void nb_sync(int id, int n) { asm volatile("bar.sync %0, %1;" ::"r"(id), "r"(n) : "memory"); }
__device__ __forceinline__ void nb_arrive(int id, int n) { asm volatile("bar.arrive %0, %1;" ::"r"(id), "r"(n) : "memory"); }
__device__ __forceinline__ void warp_arrive(uint32_t bar) {
    __syncwarp();
    if (elect()) mbar_arrive(bar);
}
__device__ __forceinline__ uint32_t band(uint32_t x, uint32_t m) {
    uint32_t r;
    asm volatile("and.b32 %0, %1, %2;" : "=r"(r) : "r"(x), "r"(m));
    return r;
}
__device__ __forceinline__ uint32_t dup(uint32_t x, uint32_t zero) {
    uint32_t r;
    asm volatile("xor.b32 %0, %1, %2;" : "=r"(r) : "r"(x), "r"(zero));
    return r;
}

__device__ __forceinline__ void tma_ld2(uint32_t dst, const CUtensorMap* m, int c0, int c1, uint32_t bar) {
    asm volatile("cp.async.bulk.tensor.2d.shared::cluster.global.mbarrier::complete_tx::bytes [%0], [%1, {%3, %4}], [%2];"
                 ::"r"(dst), "l"(m), "r"(bar), "r"(c0), "r"(c1) : "memory");
}
__device__ __forceinline__ void tma_ld4(uint32_t dst, const CUtensorMap* m, int c0, int c1, int c2, int c3, uint32_t bar) {
    asm volatile("cp.async.bulk.tensor.4d.shared::cluster.global.mbarrier::complete_tx::bytes [%0], [%1, {%3, %4, %5, %6}], [%2];"
                 ::"r"(dst), "l"(m), "r"(bar), "r"(c0), "r"(c1), "r"(c2), "r"(c3) : "memory");
}
__device__ __forceinline__ void bulk_ld(uint32_t dst, const void* src, uint32_t bytes, uint32_t bar) {
    asm volatile("cp.async.bulk.shared::cluster.global.mbarrier::complete_tx::bytes [%0], [%1], %2, [%3];"
                 ::"r"(dst), "l"(src), "r"(bytes), "r"(bar) : "memory");
}
__device__ __forceinline__ void tma_st2(const CUtensorMap* m, int c0, int c1, uint32_t src) {
    asm volatile("cp.async.bulk.tensor.2d.global.shared::cta.bulk_group [%0, {%1, %2}], [%3];"
                 ::"l"(m), "r"(c0), "r"(c1), "r"(src) : "memory");
}
__device__ __forceinline__ void bulk_commit() { asm volatile("cp.async.bulk.commit_group;" ::: "memory"); }
__device__ __forceinline__ void bulk_wait_read() { asm volatile("cp.async.bulk.wait_group.read 0;" ::: "memory"); }
__device__ __forceinline__ void fence_async_smem() { asm volatile("fence.proxy.async.shared::cta;" ::: "memory"); }
__device__ __forceinline__ void fence_async_global() { asm volatile("fence.proxy.async.global;" ::: "memory"); }

__device__ __forceinline__ void signal(Scratch* sc, int idx) {
    asm volatile("fence.proxy.async;\nred.relaxed.gpu.global.add.u32 [%0], 1;" ::"l"(&sc->cnt[idx * 32]) : "memory");
}
__device__ __forceinline__ unsigned peek(const unsigned* p) {
    unsigned v;
    asm volatile("ld.relaxed.gpu.global.u32 %0, [%1];" : "=r"(v) : "l"(p) : "memory");
    return v;
}
__device__ __forceinline__ void await(Scratch* sc, int idx, unsigned target) {
    const unsigned* p = &sc->cnt[idx * 32];
#pragma unroll 1
    for (int n = 0; n < SPIN_LIMIT; n++)
        if ((int)(peek(p) - target) >= 0) break;
    asm volatile("fence.acquire.gpu;" ::: "memory");
}
__device__ __forceinline__ void wait_dep(int k) {
    mbar_wait(base + BAR_DEP + k * 8, 0);
    fence_async_global();
}

#define WG_REGS                                                                                                     \
    "{%0,%1,%2,%3,%4,%5,%6,%7,%8,%9,%10,%11,%12,%13,%14,%15,%16,%17,%18,%19,%20,%21,%22,%23,%24,%25,%26,%27,"       \
    "%28,%29,%30,%31,%32,%33,%34,%35,%36,%37,%38,%39,%40,%41,%42,%43,%44,%45,%46,%47,%48,%49,%50,%51,%52,%53,%54,%55}"
#define WG_OPS(C)                                                                                                   \
    C(d[0]), C(d[1]), C(d[2]), C(d[3]), C(d[4]), C(d[5]), C(d[6]), C(d[7]), C(d[8]), C(d[9]), C(d[10]), C(d[11]),   \
    C(d[12]), C(d[13]), C(d[14]), C(d[15]), C(d[16]), C(d[17]), C(d[18]), C(d[19]), C(d[20]), C(d[21]), C(d[22]),   \
    C(d[23]), C(d[24]), C(d[25]), C(d[26]), C(d[27]), C(d[28]), C(d[29]), C(d[30]), C(d[31]), C(d[32]), C(d[33]),   \
    C(d[34]), C(d[35]), C(d[36]), C(d[37]), C(d[38]), C(d[39]), C(d[40]), C(d[41]), C(d[42]), C(d[43]), C(d[44]),   \
    C(d[45]), C(d[46]), C(d[47]), C(d[48]), C(d[49]), C(d[50]), C(d[51]), C(d[52]), C(d[53]), C(d[54]), C(d[55])

template <int TA, int TB, int SB, bool INIT, uint32_t AH, uint32_t BH>
__device__ __forceinline__ void wgmma112(float (&d)[56], uint32_t alo, uint32_t blo) {
    if (INIT) {
        asm volatile("{\n.reg .pred p;\n.reg .b64 da, db;\nsetp.ne.b32 p, 0, 0;\nmov.b64 da, {%56, %61};\nmov.b64 db, {%57, %62};\n"
                     "wgmma.mma_async.sync.aligned.m64n112k16.f32.bf16.bf16 " WG_REGS ", da, db, p, 1, %59, %60, %58;\n}\n"
                     : WG_OPS("=f") : "r"(alo), "r"(blo), "n"(TB), "n"(SB), "n"(TA), "n"(AH), "n"(BH));
    } else {
        asm volatile("{\n.reg .pred p;\n.reg .b64 da, db;\nsetp.ne.b32 p, 1, 0;\nmov.b64 da, {%56, %61};\nmov.b64 db, {%57, %62};\n"
                     "wgmma.mma_async.sync.aligned.m64n112k16.f32.bf16.bf16 " WG_REGS ", da, db, p, 1, %59, %60, %58;\n}\n"
                     : WG_OPS("+f") : "r"(alo), "r"(blo), "n"(TB), "n"(SB), "n"(TA), "n"(AH), "n"(BH));
    }
}
__device__ __forceinline__ void acc_fence(float (&d)[56]) {
#pragma unroll
    for (int i = 0; i < 56; i++) asm volatile("" : "+f"(d[i])::"memory");
}

__device__ __forceinline__ uint32_t pack2(float lo, float hi) {
    uint32_t r;
    asm volatile("cvt.rn.bf16x2.f32 %0, %1, %2;" : "=r"(r) : "f"(hi), "f"(lo));
    return r;
}
__device__ __forceinline__ uint32_t movm(uint32_t a) {
    uint32_t r;
    asm volatile("movmatrix.sync.aligned.m8n8.trans.b16 %0, %1;" : "=r"(r) : "r"(a));
    return r;
}
__device__ __forceinline__ void stsm4(uint32_t addr, uint32_t a, uint32_t b, uint32_t c, uint32_t d) {
    asm volatile("stmatrix.sync.aligned.m8n8.x4.shared.b16 [%0], {%1,%2,%3,%4};" ::"r"(addr), "r"(a), "r"(b), "r"(c), "r"(d) : "memory");
}
__device__ __forceinline__ void sts1(uint32_t addr, uint32_t a) { asm volatile("st.shared.b32 [%0], %1;" ::"r"(addr), "r"(a) : "memory"); }
__device__ __forceinline__ uint32_t lds1(uint32_t addr) {
    uint32_t a;
    asm volatile("ld.shared.b32 %0, [%1];" : "=r"(a) : "r"(addr) : "memory");
    return a;
}
__device__ __forceinline__ void stg1(uint8_t* p, uint32_t a) { asm volatile("st.global.b32 [%0], %1;" ::"l"(p), "r"(a) : "memory"); }
__device__ __forceinline__ void st_part(uint8_t* p, const uint32_t* v, uint32_t parity) {
    asm volatile("{\n.reg .b64 x, y;\nmov.b64 x, {%1, %2};\nmov.b64 y, {%3, %4};\nst.relaxed.gpu.global.v2.b64 [%0], {x, y};\n}\n"
                 ::"l"(p), "r"((v[0] & ~1u) | parity), "r"(v[1]), "r"((v[2] & ~1u) | parity), "r"(v[3]) : "memory");
}
__device__ __forceinline__ void mma16816(float (&d)[4], const uint32_t (&a)[4], uint32_t b0, uint32_t b1) {
    asm volatile("mma.sync.aligned.m16n8k16.row.col.f32.bf16.bf16.f32 {%0,%1,%2,%3}, {%4,%5,%6,%7}, {%8,%9}, {%0,%1,%2,%3};"
                 : "+f"(d[0]), "+f"(d[1]), "+f"(d[2]), "+f"(d[3]) : "r"(a[0]), "r"(a[1]), "r"(a[2]), "r"(a[3]), "r"(b0), "r"(b1));
}
__device__ __forceinline__ uint32_t add2(uint32_t a, uint32_t b) {
    uint32_t r;
    asm("add.rn.bf16x2 %0, %1, %2;" : "=r"(r) : "r"(a), "r"(b));
    return r;
}
__device__ __forceinline__ uint32_t max2(uint32_t a, uint32_t b) {
    uint32_t r;
    asm("max.bf16x2 %0, %1, %2;" : "=r"(r) : "r"(a), "r"(b));
    return r;
}
__device__ __forceinline__ void ld_tagged(const uint8_t* p, uint32_t& a, uint32_t& ta, uint32_t& b, uint32_t& tb) {
    asm volatile("{\n.reg .b64 x, y;\nld.relaxed.gpu.global.v2.b64 {x, y}, [%4];\nmov.b64 {%0, %1}, x;\nmov.b64 {%2, %3}, y;\n}\n"
                 : "=r"(a), "=r"(ta), "=r"(b), "=r"(tb) : "l"(p) : "memory");
}
__device__ __forceinline__ float bf_lo(uint32_t v) { return __uint_as_float(v << 16); }
__device__ __forceinline__ float bf_hi(uint32_t v) { return __uint_as_float(v & 0xFFFF0000u); }
__device__ __forceinline__ float rcp(float x) { float r; asm("rcp.approx.ftz.f32 %0, %1;" : "=f"(r) : "f"(x)); return r; }
__device__ __forceinline__ float ex2(float x) { float r; asm volatile("ex2.approx.ftz.f32 %0, %1;" : "=f"(r) : "f"(x)); return r; }

__device__ __forceinline__ uint32_t full_bar(int stage) { return base + BAR_FULL + (stage & 7) * 8; }
__device__ __forceinline__ void wait_released(int j) { mbar_wait(base + BAR_EMPTY + (j & 7) * 8, (j >> 3) & 1); }

template <int V>
struct Int { static constexpr int value = V; };

__host__ __device__ constexpr int bslot_e(int i) { return (i < 2 || i >= 14) ? (i + 5) % 7 : (i + 1) % 5; }
__host__ __device__ constexpr int bslot_l(int i) { return i % 6; }

template <uint32_t OFF>
struct Feed {
    int stage;
    uint32_t dst;
    __device__ __forceinline__ void seek(int i, int slot) { stage = i; dst = base + OFF + slot * SLOT; }
    template <int N>
    __device__ __forceinline__ uint32_t acquire() { wait_released(stage - N); return full_bar(stage); }
    template <int N>
    __device__ __forceinline__ void next() {
        stage++;
        dst += SLOT;
        if (dst == base + OFF + N * SLOT) dst = base + OFF;
    }
};
__device__ __forceinline__ int skip_own(int n, int mt) { return n == mt ? 15 : n; }

struct Desc { uint32_t lo, hi; };
__host__ __device__ constexpr Desc desc_const(uint32_t lbo, uint32_t sbo, uint32_t mode) { return {(lbo >> 4) << 16, (sbo >> 4) | (mode << 30)}; }
constexpr Desc D_K128 = desc_const(16, 1024, 1);
constexpr Desc D_N128 = desc_const(8192, 1024, 1);
constexpr Desc D_BLOB = desc_const(128, 256, 0);
constexpr Desc D_OT = desc_const(2048, 128, 0);

enum Kind { XW, XWN, QK, BIG, OUT };

struct Ring {
    int stage;
    uint32_t a, b;
    uint32_t wg;
    uint32_t zero;
    __device__ __forceinline__ void seek(int i, int bslot) {
        stage = i;
        a = (base + (i % NA) * SLOT) >> 4;
        b = (base + BRING + bslot * SLOT) >> 4;
    }
    __device__ __forceinline__ void wait() { mbar_wait(full_bar(stage), (stage >> 3) & 1); }
    __device__ __forceinline__ void take_turn() { nb_sync(1 + wg, 256); }
    __device__ __forceinline__ void pin() {
        uint32_t n = 0;
#pragma unroll 1
        do {
            asm volatile("pmevent 7;" ::: "memory");
        } while (n++ < zero);
    }
    template <Kind K, int NBS, bool INIT, int SB = 1, bool TAIL = false>
    __device__ __forceinline__ void run(float (&d)[56], float (&e)[56], bool first = true, bool last = true, bool more = true) {
        if (first) take_turn();
        asm volatile("wgmma.fence.sync.aligned;" ::: "memory");
        if (K == QK) {
            const uint32_t da = D_K128.lo + (base >> 4) + (stage >> 1) * (SLOT >> 4) + (stage & 1) * 4 + wg * 512, db = D_N128.lo + b;
            wgmma112<0, 1, 1, INIT, D_K128.hi, D_N128.hi>(d, da, db);
            wgmma112<0, 1, 1, INIT, D_K128.hi, D_N128.hi>(e, da, db + 256);
            wgmma112<0, 1, 1, false, D_K128.hi, D_N128.hi>(d, da + 2, db + 128);
            wgmma112<0, 1, 1, false, D_K128.hi, D_N128.hi>(e, da + 2, db + 384);
        } else {
            constexpr int TA = K == OUT, TB = K != XW;
            constexpr uint32_t sa = K == OUT ? 256 : 2, sb = K == XW ? 2 : K == BIG ? 224 : 128;
            constexpr Desc A = K == OUT ? D_OT : D_K128, B = K == XW ? D_K128 : K == BIG ? D_BLOB : D_N128;
            const uint32_t da = A.lo + a + wg * (K == OUT ? 64 : 512), db = B.lo + b;
            wgmma112<TA, TB, SB, INIT, A.hi, B.hi>(d, da, db);
            wgmma112<TA, TB, SB, false, A.hi, B.hi>(d, da + sa, db + sb);
            wgmma112<TA, TB, SB, false, A.hi, B.hi>(d, da + 2 * sa, db + 2 * sb);
            wgmma112<TA, TB, SB, false, A.hi, B.hi>(d, da + 3 * sa, db + 3 * sb);
        }
        asm volatile("wgmma.commit_group.sync.aligned;" ::: "memory");
        if (last) nb_arrive(2 - wg, 256);
        if (!TAIL) asm volatile("wgmma.wait_group.sync.aligned 1;" ::: "memory");
        if (!TAIL && stage > 0 && elect()) mbar_arrive(base + BAR_EMPTY + ((stage - 1) & 7) * 8);
        stage++;
        a += SLOT >> 4;
        if (a == (base + NA * SLOT) >> 4) a = base >> 4;
        b += SLOT >> 4;
        if (b == (base + BRING + NBS * SLOT) >> 4) b = (base + BRING) >> 4;
        if (more) wait();
    }
    template <Kind K, int NBS, bool INIT, int SB = 1, bool TAIL = false>
    __device__ __forceinline__ void run(float (&d)[56], bool first = true, bool last = true, bool more = true) {
        run<K, NBS, INIT, SB, TAIL>(d, d, first, last, more);
    }
};

__device__ __forceinline__ void pack_all(const float (&d)[56], uint32_t (&p)[28]) {
#pragma unroll
    for (int i = 0; i < 28; i++) p[i] = pack2(d[2 * i], d[2 * i + 1]);
}
template <int I0, int I1>
__device__ __forceinline__ void store_frags(uint8_t* dst, const uint32_t (&p)[28]) {
#pragma unroll
    for (int i = I0; i < I1; i++) stg1(dst + i * 128, p[i]);
}
template <int I0, int I1>
__device__ __forceinline__ void stage_frags(uint32_t lane_addr, const uint32_t (&p)[28]) {
#pragma unroll
    for (int i = I0; i < I1; i += 4) stsm4(lane_addr + i * 128, p[i], p[i + 1], p[i + 2], p[i + 3]);
}
template <class F>
__device__ __forceinline__ void store_out(F frag, int lane, uint32_t slab, const CUtensorMap* m, int c0, int c1) {
    const bool swap = lane & 16;
    const uint32_t addr = slab + (lane & 7) * 224 + ((lane >> 3) ^ ((lane >> 2) & 1)) * 16;
#pragma unroll
    for (int h = 0; h < 2; h++) {
#pragma unroll
        for (int c = 0; c < 14; c += 4) {
            const uint32_t t0 = frag(2 * c + h), t1 = frag(2 * c + 2 + h);
            if (c < 12) {
                const uint32_t t2 = frag(2 * c + 4 + h), t3 = frag(2 * c + 6 + h);
                stsm4(addr + h * 1792 + c * 16, swap ? t1 : t0, swap ? t0 : t1, swap ? t3 : t2, swap ? t2 : t3);
            } else {
                asm volatile("stmatrix.sync.aligned.m8n8.x2.shared.b16 [%0], {%1,%2};" ::"r"(addr + h * 1792 + c * 16), "r"(swap ? t1 : t0), "r"(swap ? t0 : t1) : "memory");
            }
        }
        fence_async_smem();
        __syncwarp();
        if (elect()) tma_st2(m, c0, c1 + 8 * h, slab + h * 1792);
    }
    if (elect()) {
        bulk_commit();
        bulk_wait_read();
    }
}
__host__ __device__ constexpr int tile_of(int t) { return 7 * (t >> 2) + 3 * ((t >> 1) & 1) + 2 * (t & 1); }

struct Role {
    bool H;
    int L, mt, ns, id;
};
template <bool BY_SM>
__device__ __forceinline__ Role decode_role() {
    uint32_t sm;
    if (BY_SM) asm volatile("mov.u32 %0, %%smid;" : "=r"(sm));
    else asm volatile("mov.u32 %0, %%ctaid.x;" : "=r"(sm));
    const int tpc = sm >> 1, q2 = ((tpc - 32) * 37) >> 8;
    const int gpc = tpc < 32 ? tpc & 7 : tpc < 60 ? tpc - 31 - 7 * q2 : 0;
    const int pos = tpc < 32 ? tpc >> 3 : tpc < 60 ? q2 + 4 : tpc - 56;
    Role r;
    r.H = sm >= 128;
    r.L = gpc & 1;
    r.mt = (gpc >> 1) * 4 + (pos >> 1);
    r.ns = (pos & 1) * 2 + (sm & 1);
    r.id = r.H ? sm : gpc * 16 + pos * 2 + (sm & 1);
    return r;
}

template <bool PACED>
__device__ __forceinline__ void first_fill(const Maps& maps, const Role& r, int i0, int i1, unsigned t0) {
    const bool E = !r.L && !r.H;
    const CUtensorMap* ma = &maps.m[r.H ? 2 : r.L];
    const int a0 = r.L ? (r.mt >> 3) * 448 : 0, a1 = r.L ? (r.mt & 7) * 128 : r.H ? 120 : r.mt * 64;
    const int b3 = E ? 0 : r.H ? 4 + r.ns : r.ns;
#pragma unroll 1
    for (int i = i0; i < i1; i++) {
        if (PACED) while (clk32() - t0 < i * PACE) {}
        const uint32_t bar = full_bar(i);
        const int k = (i * 64) >> r.L;
        const bool has_a = !(i & r.L), has_b = i < 7 - r.L;
        const uint32_t dst = base + BRING + (E ? (0x2104365u >> (4 * i)) & 7 : i) * SLOT;
        mbar_expect(bar, (has_a ? SLOT : 0) + (has_b ? (E ? BLOB : SLOT) : 0));
        if (has_a) tma_ld4(base + (i >> r.L) * SLOT, ma, a0 + k, a1, 0, 0, bar);
        if (has_b) {
            tma_ld4(dst, ma + 3, E ? k : 0, E ? r.ns * 112 : k, 0, b3, bar);
            if (!E) tma_ld4(dst + 8192, ma + 3, 64, k, 0, b3, bar);
            mbar_arrive(bar);
        }
    }
}
static_assert(bslot_e(0) == 5 && bslot_e(1) == 6 && bslot_e(2) == 3 && bslot_e(3) == 4 && bslot_e(4) == 0 && bslot_e(6) == 2, "");

template <bool BY_SM>
__global__ void __launch_bounds__(384, 1) fused_kernel(Scratch* sc, const __grid_constant__ Maps maps) {
    const unsigned t_open = clk32();
    const int warp = __shfl_sync(0xffffffffu, threadIdx.x >> 5, 0);
    if (warp == 8) {
        if (elect()) {
            mbar_init(base + BAR_FULL, 2);
            const Role r = decode_role<BY_SM>();
            mbar_expect(full_bar(0), SLOT);
            tma_ld4(base, &maps.m[r.H ? 2 : r.L], r.L ? (r.mt >> 3) * 448 : 0, r.L ? (r.mt & 7) * 128 : r.H ? 120 : r.mt * 64, 0, 0, full_bar(0));
            mbar_arrive(full_bar(0));
#pragma unroll
            for (int i = 1; i < LEAD; i++) mbar_init(base + BAR_FULL + i * 8, 2);
            asm volatile("fence.mbarrier_init.release.cluster;" ::: "memory");
            first_fill<false>(maps, decode_role<BY_SM>(), 1, LEAD, 0);
        }
    } else if (warp == 11) {
        if (elect()) {
            mbar_init(base + BAR_B0, 1);
            const Role r = decode_role<BY_SM>();
            const bool E = !r.L && !r.H;
            const CUtensorMap* mb = &maps.m[r.H ? 5 : 3 + r.L];
            const int b3 = E ? 0 : r.H ? 4 + r.ns : r.ns;
            mbar_expect(base + BAR_B0, E ? BLOB : SLOT);
            tma_ld4(base + BRING + (E ? bslot_e(0) * SLOT : 0), mb, 0, E ? r.ns * 112 : 0, 0, b3, base + BAR_B0);
            if (!E) tma_ld4(base + BRING + 8192, mb, 64, 0, 0, b3, base + BAR_B0);
            asm volatile("fence.mbarrier_init.release.cluster;" ::: "memory");
        }
    }
    if (warp == 9) {
        if (elect()) {
#pragma unroll
            for (int i = 0; i < 8; i++) mbar_init(base + BAR_EMPTY + i * 8, 8);
            asm volatile("fence.mbarrier_init.release.cluster;" ::: "memory");
        }
    } else if (warp == 10) {
        if (elect()) {
#pragma unroll
            for (int i = 0; i < 5; i++) mbar_init(base + BAR_RDY + i * 8, i < 2 ? 4 : 8);
#pragma unroll
            for (int i = 0; i < 2; i++) mbar_init(base + BAR_HALO + i * 8, 9);
            asm volatile("fence.mbarrier_init.release.cluster;" ::: "memory");
        }
    } else if (warp == 1) {
        if (elect()) {
#pragma unroll
            for (int i = LEAD; i < 8; i++) mbar_init(base + BAR_FULL + i * 8, 2);
#pragma unroll
            for (int i = 0; i < 3; i++) mbar_init(base + BAR_DEP + i * 8, 1);
#pragma unroll
            for (int i = 0; i < 2; i++) mbar_init(base + BAR_PART + i * 8, 1);
            asm volatile("fence.mbarrier_init.release.cluster;" ::: "memory");
        }
    }
    __syncthreads();

    const Role role = decode_role<BY_SM>();
    int lane = threadIdx.x & 31;
    asm volatile("" : "+r"(lane));
    const bool roleH = role.H;
    const int roleL = role.L, mt = role.mt, ns = role.ns, bid = role.id;
    const int par = mt >> 3, blk = mt & 7, col = ns * 112;

    if (__builtin_expect(warp >= 8, 1)) {
        asm volatile("setmaxnreg.dec.sync.aligned.u32 56;");
#define PROF_FEED_A
#define PROF_FEED_B
        if (__builtin_expect(warp == 8, 1)) {
            if (elect()) {
                PROF(129);
                first_fill<true>(maps, role, LEAD, 7, t_open);
                PROF(134);
                Feed<0> f;
                const int row = mt * 128;
                auto c_run = [&](const CUtensorMap* m, int off, int n0, int n1) {
#pragma unroll 1
                    for (int n = n0; n < n1; n++) {
                        const uint32_t bar = f.acquire<NA>();
                        mbar_expect(bar, SLOT);
                        tma_ld2(f.dst, m, (off + skip_own(n, mt)) * 64, row, bar);
                        PROF_FEED_A;
                        f.next<NA>();
                    }
                };
                if (roleH) {
                } else if (!roleL) {
                    f.seek(14, 0);
                    mbar_wait(base + BAR_RDY, 0);
#pragma unroll 1
                    for (int i = 0; i < 4; i++) {
                        const uint32_t bar = f.acquire<NA>();
                        mbar_expect(bar, SLOT);
                        tma_ld2(f.dst, &maps.m[M_CR + (i >> 1)], ((i & 1) * 16 + mt) * 64, row, bar);
                        mbar_arrive(bar);
                        PROF_FEED_A;
                        f.next<NA>();
                    }
                    c_run(&maps.m[M_CR], 0, 0, 15);
                    c_run(&maps.m[M_CI], 0, 0, NBE);
                    wait_dep(2);
#pragma unroll 1
                    for (int i = 0; i < 7; i++) {
                        const uint32_t bar = f.acquire<NA>();
                        mbar_expect(bar, SLOT);
                        bulk_ld(f.dst, sc->o + (size_t)(mt * 7 + i) * SLOT, SLOT, bar);
                        PROF_FEED_A;
                        f.next<NA>();
                    }
                } else {
#pragma unroll 1
                    for (int i = 4; i < 7; i++) {
                        wait_released(2 * i - 8);
                        mbar_expect(full_bar(2 * i), SLOT);
                        tma_ld4(base + i * SLOT, &maps.m[M_XA], par * 448 + i * 64, blk * 128, 0, 0, full_bar(2 * i));
                    }
                    wait_released(HALO_K_AT);
                    mbar_arrive(base + BAR_DEP + 16);
                    f.seek(21, 0);
                    c_run(&maps.m[M_CR], 16, 0, 15);
                    c_run(&maps.m[M_CI], 16, 0, 15);
                    c_run(&maps.m[M_CI], 0, NBE, 15);
                }
            }
        } else if (warp == 11) {
            if (elect()) {
                Feed<BRING> f;
                auto blob_run = [&](auto nbs, int quarter, int n0, int n1) {
                    constexpr int N = decltype(nbs)::value;
                    const uint8_t* src = sc->ab + (size_t)(quarter * 64 + ns) * BLOB;
#pragma unroll 1
                    for (int n = n0; n < n1; n++) {
                        const uint32_t bar = f.template acquire<N>();
                        mbar_expect(bar, BLOB);
                        bulk_ld(f.dst, src + skip_own(n, mt) * (4 * BLOB), BLOB, bar);
                        PROF_FEED_B;
                        f.template next<N>();
                    }
                };
                auto w_run = [&](auto nbs, const CUtensorMap* m, int slice, bool no_a) {
                    constexpr int N = decltype(nbs)::value;
#pragma unroll 1
                    for (int i = 0; i < 7; i++) {
                        const uint32_t bar = f.template acquire<N>();
                        mbar_expect(bar, SLOT);
                        tma_ld4(f.dst, m, 0, i * 64, 0, slice, bar);
                        tma_ld4(f.dst + 8192, m, 64, i * 64, 0, slice, bar);
                        if (no_a) mbar_arrive(bar);
                        PROF_FEED_B;
                        f.template next<N>();
                    }
                };
                if (roleH) {
                    f.seek(7, 0);
                    w_run(Int<7>(), &maps.m[M_WV], 8 + ns, true);
                } else if (!roleL) {
                    f.seek(7, bslot_e(7));
#pragma unroll 1
                    for (int i = 0; i < 7; i++) {
                        const uint32_t bar = f.acquire<5>();
                        mbar_expect(bar, BLOB);
                        tma_ld2(f.dst, &maps.m[M_WI], i * 64, col, bar);
                        mbar_arrive(bar);
                        PROF_FEED_B;
                        f.next<5>();
                    }
                    f.seek(18, bslot_e(18));
                    wait_dep(0);
                    blob_run(Int<7>(), 0, 0, 15);
                    wait_dep(1);
                    blob_run(Int<7>(), 2, 0, NBE);
                    w_run(Int<7>(), &maps.m[M_WO], ns, false);
                } else {
                    f.seek(6, 0);
#pragma unroll 1
                    for (int i = 6; i < 14; i++) {
                        const uint32_t bar = f.acquire<6>();
                        mbar_expect(bar, SLOT);
                        tma_ld4(f.dst, &maps.m[M_WQK], 0, i * 32, 0, ns, bar);
                        tma_ld4(f.dst + 8192, &maps.m[M_WQK], 64, i * 32, 0, ns, bar);
                        if (i & 1) mbar_arrive(bar);
                        PROF_FEED_B;
                        f.next<6>();
                    }
                    w_run(Int<6>(), &maps.m[M_WV], 8 + ns, true);
                    wait_dep(0);
                    blob_run(Int<6>(), 1, 0, 15);
                    wait_dep(1);
                    blob_run(Int<6>(), 3, 0, 15);
                    blob_run(Int<6>(), 2, NBE, 15);
                }
            }
        } else if (roleH) {
            if (elect()) {
                wait_released(warp == 9 ? 0 : 7);
#pragma unroll 1
                for (int i = 0; i < 7; i++) {
                    if (warp == 9) {
                        asm volatile("cp.async.bulk.prefetch.tensor.2d.L2.global [%0, {%1, %2}];" ::"l"(&maps.m[M_WI]), "r"(i * 64), "r"(col) : "memory");
                    } else {
                        asm volatile("cp.async.bulk.prefetch.tensor.4d.L2.global [%0, {%1, %2, 0, %3}];" ::"l"(&maps.m[M_WO]), "r"(0), "r"(i * 64), "r"(ns) : "memory");
                        asm volatile("cp.async.bulk.prefetch.tensor.4d.L2.global [%0, {%1, %2, 0, %3}];" ::"l"(&maps.m[M_WO]), "r"(64), "r"(i * 64), "r"(ns) : "memory");
                    }
                }
            }
        } else if (warp == 10) {
            if (elect()) {
                unsigned* epoch_ptr = &sc->epoch[(bid * 4 + 2) * 8];
                const unsigned ep = *epoch_ptr + 1;
                sts1(base + TAG, ep);
                asm volatile("prefetch.tensormap [%0];" ::"l"(&maps.m[M_OUTA + roleL]) : "memory");
                await(sc, CNT_A + roleL * 4 + ns, ep * 16);
                mbar_arrive(base + BAR_DEP);
                PROF(150);
                await(sc, CNT_B + ns, ep * 16);
                mbar_arrive(base + BAR_DEP + 8);
                PROF(151);
                if (!roleL) {
                    await(sc, CNT_O + mt, ep * 4);
                    mbar_arrive(base + BAR_DEP + 16);
                } else {
                    await(sc, CNT_P + mt * 4 + ns, ep * 2 - 1);
                    mbar_arrive(base + BAR_PART);
                    PROF(153);
                    await(sc, CNT_P + mt * 4 + ns, ep * 2);
                    mbar_arrive(base + BAR_PART + 8);
                }
                PROF(152);
                *epoch_ptr = ep;
            }
        } else if (!roleL) {
            if (elect()) {
                mbar_wait(base + BAR_RDY, 0);
                PROF(130);
                signal(sc, CNT_A + ns);
                PROF(131);
                mbar_wait(base + BAR_RDY + 8, 0);
                signal(sc, CNT_A + 4 + ns);
                PROF(135);
                mbar_wait(base + BAR_RDY + 32, 0);
                PROF(132);
                signal(sc, CNT_B + ns);
                PROF(133);
            }
        } else {
            unsigned* epoch_ptr = &sc->epoch[(bid * 4 + 1) * 8];
            const unsigned tag = *epoch_ptr + 1;
#pragma unroll 1
            for (int kv = 0; kv < 2; kv++) {
                uint32_t v[16];
#pragma unroll
                for (int i = 0; i < 16; i++) v[i] = 0;
                if (kv) mbar_wait(base + BAR_HALO, 0), wait_released(HALO_V_AT);
                else mbar_wait(base + BAR_DEP + 16, 0);
                if (blk > 0) {
                    const uint8_t* src = sc->halo + (size_t)(((mt - 1) * 4 + ns) * 2 + kv) * 2048 + lane * 16;
#pragma unroll 1
                    for (int n = 0; n < SPIN_LIMIT; n++) {
                        uint32_t stale = 0;
#pragma unroll
                        for (int i = 0; i < 4; i++) ld_tagged(src + i * 512, v[4 * i], v[4 * i + 1], v[4 * i + 2], v[4 * i + 3]);
#pragma unroll
                        for (int i = 0; i < 16; i += 2) stale |= v[i] ^ tag;
                        if (__all_sync(0xffffffffu, !(stale & 1))) break;
                    }
#pragma unroll
                    for (int c = 0; c < 14; c += 2) v[c] = (v[c] & ~1u) | ((v[15] >> c) & 1);
                }
#pragma unroll
                for (int i = 0; i < 14; i++) sts1(base + HALO + kv * (8 * HSLOT) + i * 128 + lane * 4, v[i]);
                warp_arrive(base + BAR_HALO + kv * 8);
                if (lane == 0) PROF(142 + kv);
            }
            if (elect()) {
                mbar_wait(base + BAR_RDY + 16, 0);
                PROF(130);
                signal(sc, CNT_O + mt);
                PROF(131);
                *epoch_ptr = tag;
            }
        }
    } else {
        asm volatile("setmaxnreg.inc.sync.aligned.u32 224;");
        Ring r;
        r.wg = warp >> 2;
        r.zero = blockIdx.y;
        const int wg = warp >> 2;
        if (wg) nb_arrive(1, 256);
        r.stage = 0;
        mbar_wait(base + BAR_B0, 0);
        r.wait();
        uint8_t* part = sc->part + (size_t)(ns * 16 + mt) * (2 * BLOB) + warp * 512 + lane * 16;
        uint32_t p[28];

        if (roleH) {
            unsigned* epoch_ptr = &sc->epoch[bid * 4 * 8];
            const unsigned tag = *epoch_ptr + 1;
            uint8_t* hout = sc->halo + (size_t)((warp * 8 + ns) * 2) * 2048 + lane * 16;
            auto send = [&](int kv) {
#pragma unroll
                for (int h = 0; h < 2; h++) {
                    uint32_t v[16];
                    v[14] = v[15] = 0;
#pragma unroll
                    for (int c = 0; c < 14; c++) v[c] = p[2 * c + h];
#pragma unroll
                    for (int c = 0; c < 14; c += 2) v[15] |= (v[c] & 1) << c;
#pragma unroll
                    for (int i = 0; i < 4; i++) st_part(hout + (h * 8 + kv) * 2048 + i * 512, v + 4 * i, tag & 1);
                }
            };
            float x0[56], x1[56];
            r.seek(0, 0);
            r.run<XWN, 7, true>(x0);
#pragma unroll 1
            for (int i = 1; i < 7; i++) r.run<XWN, 7, false>(x0);
            r.run<XWN, 7, true>(x1);
            acc_fence(x0);
            pack_all(x0, p);
            send(0);
#pragma unroll 1
            for (int i = 1; i < 7; i++) r.run<XWN, 7, false>(x1, true, true, i < 6);
            asm volatile("wgmma.wait_group.sync.aligned 0;" ::: "memory");
            acc_fence(x1);
            pack_all(x1, p);
#pragma unroll
            for (int i = 0; i < 28; i++) p[i] = movm(p[i]);
            send(1);
            if (threadIdx.x == 0) *epoch_ptr = tag;
        } else if (!roleL) {
            uint8_t* blob = sc->ab + (size_t)((wg * 16 + mt) * 4 + ns) * BLOB + (warp & 3) * WSLOT + lane * 4;
            const uint32_t own = base + BRING + wg * SLOT + (warp & 3) * WSLOT + lane * 16;
            float x0[56], x1[56];
            r.seek(0, bslot_e(0));
            r.run<XW, 7, true>(x0);
            r.run<XW, 7, false>(x0);
            r.seek(2, bslot_e(2));
#pragma unroll 1
            for (int i = 2; i < 7; i++) r.run<XW, 5, false>(x0);

            r.seek(7, bslot_e(7));
            r.run<XW, 5, true, -1>(x1);
            acc_fence(x0);
            pack_all(x0, p);
#pragma unroll
            for (int i = 0; i < 2; i++) {
                if (wg == i) store_frags<0, 14>(blob, p);
                else stage_frags<0, 4>(own + 5 * SLOT, p);
                r.run<XW, 5, false, -1>(x1);
                if (wg == i) {
                    store_frags<14, 28>(blob, p);
                    warp_arrive(base + BAR_RDY + i * 8);
                } else {
                    stage_frags<4, 8>(own + 5 * SLOT, p);
                }
                r.run<XW, 5, false, -1>(x1);
            }
            stage_frags<8, 20>(own + 5 * SLOT, p);
            r.run<XW, 5, false, -1>(x1);
            stage_frags<20, 28>(own + 5 * SLOT, p);
            warp_arrive(base + BAR_RDY + 16);
            r.run<XW, 5, false, -1>(x1);

            mbar_wait(base + BAR_RDY + 16, 0);
            fence_async_smem();
            r.seek(14, bslot_e(14));
            r.run<BIG, 7, true>(x0);
            acc_fence(x1);
            pack_all(x1, p);
            wait_released(10);
            stage_frags<0, 28>(own, p);
            warp_arrive(base + BAR_RDY + 24);
            r.run<BIG, 7, false>(x0);
            mbar_wait(base + BAR_RDY + 24, 0);
            fence_async_smem();
            blob += (size_t)128 * BLOB;
#pragma unroll
            for (int i = 0; i < 28; i++) {
                if (i % B_SLICE == 0) r.run<BIG, 7, false>(x0);
                stg1(blob + i * 128, p[i]);
            }
            warp_arrive(base + BAR_RDY + 32);
#pragma unroll 1
            for (int i = 17 + 27 / B_SLICE; i < POUT; i++) r.run<BIG, 7, false>(x0);

            const uint32_t tag = lds1(base + TAG);
            r.seek(POUT, bslot_e(POUT));
            r.run<OUT, 7, true>(x1);
            acc_fence(x0);
            pack_all(x0, p);
#pragma unroll
            for (int k = 0; k < 3; k++) {
                if (k < 2 && wg == k) {
                    if ((warp & 3) == 0 && elect())
                        asm volatile("red.relaxed.gpu.global.add.u32 [%0], 1;" ::"l"(&sc->cnt[(CNT_P + mt * 4 + ns) * 32]) : "memory");
#pragma unroll
                    for (int i = 0; i < 4; i++) st_part(part + i * 4096, p + 4 * i, tag & 1);
                }
                if (k > 0 && wg == k - 1) {
#pragma unroll
                    for (int i = 4; i < 7; i++) st_part(part + i * 4096, p + 4 * i, tag & 1);
                }
                if (k < 2) r.run<OUT, 7, false>(x1);
            }
#pragma unroll
            for (int i = 3; i < 7; i++) r.run<OUT, 7, false, 1, true>(x1, i <= 7 - TURN, i < 7 - TURN || i == 6, i < 6);

            wait_released(ELAST - 6);
            asm volatile("wgmma.wait_group.sync.aligned 0;" ::: "memory");
            acc_fence(x1);
            const uint32_t slab = base + (wg ? BRING + bslot_e(ELAST - 6) * SLOT : ((ELAST - 6) % NA) * SLOT) + (warp & 3) * WSLOT;
            store_out([&](int i) { return pack2(x1[2 * i], x1[2 * i + 1]); }, lane, slab, &maps.m[M_OUTA], par * 896 + col, blk * 128 + warp * 16);
        } else {
            const int g = lane >> 2, tig = lane & 3;
            const uint32_t hin = base + HALO + warp * HSLOT + lane * 4;
            const uint32_t hpub = warp < 7 ? hin + HSLOT : base + HSPARE + lane * 4;
            auto publish = [&](const uint32_t (&h)[14], int c0, int c1) {
#pragma unroll
                for (int c = 0; c < 14; c++)
                    if (c >= c0 && c < c1) sts1(hpub + c * 128, h[c]);
            };
            float y0[56], y1[56], y2[56];
            r.seek(0, 0);
            r.run<QK, 6, true>(y0, y1);
#pragma unroll 1
            for (int i = 1; i < 14; i++) r.run<QK, 6, false>(y0, y1);

            uint32_t m1[8][4], m0[8][4], lo[14], hi[14], q[2][8][2];
            auto pack_q = [&](int b) {
                uint32_t v[14];
#pragma unroll
                for (int c = 0; c < 14; c++) v[c] = pack2(y0[4 * c + 2 * b], y0[4 * c + 2 * b + 1]);
#pragma unroll
                for (int t = 0; t < 8; t++) {
                    const int c = tile_of(t);
                    q[b][t][0] = (t & 3) == 2 ? (tig >= 2 ? v[c] : 0u) : v[c];
                    q[b][t][1] = (t & 3) == 1 ? (tig < 2 ? v[c + 1] : 0u) : v[c + 1];
                }
            };
            auto fetch = [&](uint32_t src, int hp, int i0) {
#pragma unroll
                for (int t = 4 * hp; t < 4 * hp + 4; t++) {
                    m0[t][i0] = (t & 3) == 2 ? dup(m0[t - 1][3], r.zero) : lds1(src + tile_of(t) * 128);
                    m0[t][3] = lds1(src + tile_of(t) * 128 + 128);
                }
            };
            r.seek(14, bslot_l(14));
            r.run<XWN, 6, true>(y2);
            acc_fence(y0);
            acc_fence(y1);
#pragma unroll
            for (int c = 0; c < 14; c++) hi[c] = pack2(y1[4 * c + 2], y1[4 * c + 3]);
            publish(hi, 0, 7);
            PIN;
            r.run<XWN, 6, false>(y2);
            publish(hi, 7, 14);
            warp_arrive(base + BAR_HALO);
#pragma unroll
            for (int c = 0; c < 14; c++) lo[c] = pack2(y1[4 * c], y1[4 * c + 1]);
#pragma unroll
            for (int t = 0; t < 8; t++) {
                const int c = tile_of(t);
                const bool shared = (t & 3) == 2;
                m1[t][0] = shared ? dup(lo[c], r.zero) : lo[c];
                m1[t][1] = shared ? dup(hi[c], r.zero) : hi[c];
                m1[t][2] = lo[c + 1];
                m1[t][3] = hi[c + 1];
                m0[t][0] = dup(m1[t][0], r.zero);
                m0[t][2] = dup(lo[c + 1], 2 * r.zero);
            }
            PIN;
            r.run<XWN, 6, false>(y2);
            mbar_wait(base + BAR_HALO, 0);
            fetch(hin, 0, 1);
            pack_q(1);
            PIN;
            r.run<XWN, 6, false>(y2);
            fetch(hin, 1, 1);
            pack_q(0);
            r.pin();
            r.take_turn();
            float s[8][4];
#pragma unroll
            for (int step = 0; step < 2; step++) {
#pragma unroll
                for (int i = 0; i < 8; i++) {
                    const int b = 1 - (i >> 2), h = i & 3, t = 2 * h + step;
                    float (&d)[4] = s[2 * h + b];
                    if (step == 0) d[0] = d[1] = d[2] = d[3] = 0.f;
                    mma16816(d, b ? m1[t] : m0[t], q[b][t][0], q[b][t][1]);
                }
            }
            r.pin();
            r.run<XWN, 6, false>(y2, false);

            uint32_t pr[8], mx[4], mx1[4];
            {
                const bool cur0 = g <= 2 * tig, cur1 = g <= 2 * tig + 1;
#pragma unroll
                for (int i = 0; i < 8; i++) {
                    const int c = (i & 1) ? 2 : 0;
                    pr[i] = movm(pack2(cur0 ? s[i][c] : s[i][2 - c], cur1 ? s[i][c + 1] : s[i][3 - c]));
                }
            }
            PIN;
            r.run<XWN, 6, false>(y2);
            const uint32_t curmask = (2 * tig <= g ? 0x0000FFFFu : 0u) | (2 * tig + 1 <= g ? 0xFFFF0000u : 0u);
            {
                const uint32_t keep = (blk == 0 && warp == 0) ? curmask : 0xFFFFFFFFu;
#pragma unroll
                for (int i = 0; i < 4; i++) {
                    pr[2 * i] = (pr[2 * i] & keep) | (0xCF9ECF9Eu & ~keep);
                    mx[i] = max2(__byte_perm(pr[2 * i], pr[2 * i + 1], 0x5410), __byte_perm(pr[2 * i], pr[2 * i + 1], 0x7632));
                    mx1[i] = __shfl_xor_sync(0xffffffffu, mx[i], 1);
                }
            }
            PIN;
            r.run<XWN, 6, false>(y2);
#pragma unroll
            for (int i = 0; i < 4; i++) {
                mx[i] = max2(mx[i], mx1[i]);
                mx1[i] = __shfl_xor_sync(0xffffffffu, mx[i], 2);
            }

            PIN;
            r.seek(21, bslot_l(21));
            r.run<BIG, 6, true>(y0);
            acc_fence(y2);
#pragma unroll
            for (int c = 0; c < 10; c++) hi[c] = movm(pack2(y2[4 * c + 2], y2[4 * c + 3]));
            constexpr float SCL = 0.18898223650461362f * 1.4426950408889634f;
            float e0[8], e1[8], sm[8], sm1[8];
#pragma unroll
            for (int i = 0; i < 8; i++) {
                const uint32_t m2 = max2(mx[i >> 1], mx1[i >> 1]);
                sm[i] = ((i & 1) ? bf_hi(m2) : bf_lo(m2)) * -SCL;
            }
            PIN;
            r.run<BIG, 6, false>(y0);
#pragma unroll
            for (int c = 10; c < 14; c++) hi[c] = movm(pack2(y2[4 * c + 2], y2[4 * c + 3]));
#pragma unroll
            for (int c = 0; c < 4; c++) lo[c] = movm(pack2(y2[4 * c], y2[4 * c + 1]));
#pragma unroll
            for (int i = 0; i < 8; i++) e0[i] = ex2(fmaf(bf_lo(pr[i]), SCL, sm[i]));
            PIN;
            r.run<BIG, 6, false>(y0);
            publish(hi, 0, 10);
#pragma unroll
            for (int i = 0; i < 8; i++) e1[i] = ex2(fmaf(bf_hi(pr[i]), SCL, sm[i]));
            PIN;
            r.run<BIG, 6, false>(y0);
            publish(hi, 10, 14);
            warp_arrive(base + BAR_HALO + 8);
#pragma unroll
            for (int i = 0; i < 8; i++) {
                sm[i] = e0[i] + e1[i];
                sm1[i] = __shfl_xor_sync(0xffffffffu, sm[i], 1);
            }
            PIN;
            r.run<BIG, 6, false>(y0);
#pragma unroll
            for (int c = 4; c < 14; c++) lo[c] = movm(pack2(y2[4 * c], y2[4 * c + 1]));
            PIN;
            r.run<BIG, 6, false>(y0);
#pragma unroll
            for (int i = 0; i < 8; i++) {
                sm[i] += sm1[i];
                sm1[i] = __shfl_xor_sync(0xffffffffu, sm[i], 2);
            }
#pragma unroll
            for (int t = 0; t < 8; t++) {
                const int c = tile_of(t);
                const bool shared = (t & 3) == 2;
                m1[t][0] = shared ? dup(lo[c], r.zero) : lo[c];
                m1[t][1] = lo[c + 1];
                m1[t][2] = shared ? dup(hi[c], r.zero) : hi[c];
                m1[t][3] = hi[c + 1];
                m0[t][0] = dup(m1[t][0], r.zero);
                m0[t][1] = dup(lo[c + 1], 2 * r.zero);
            }
            PIN;
            r.run<BIG, 6, false>(y0);
            mbar_wait(base + BAR_HALO + 8, 0);
            const uint32_t vin = warp ? hin : hin + 8 * HSLOT;
            fetch(vin, 0, 2);
#pragma unroll
            for (int i = 0; i < 8; i++) {
                const float inv = rcp(sm[i] + sm1[i]);
                pr[i] = pack2(e0[i] * inv, e1[i] * inv);
            }
            PIN;
            r.run<BIG, 6, false>(y0);
            fetch(vin, 1, 2);
            uint32_t pb[8][2];
#pragma unroll
            for (int t = 0; t < 8; t++) {
                pb[t][t & 1] = band(pr[t], curmask);
                pb[t][1 - (t & 1)] = band(pr[t], ~curmask);
            }
            r.pin();
            r.take_turn();
            float o[2][8][4];
#pragma unroll
            for (int i = 0; i < 16; i++) {
                const int b = 1 - (i >> 3), t = i & 7;
                float (&d)[4] = o[b][t];
                d[0] = d[1] = d[2] = d[3] = 0.f;
                mma16816(d, b ? m1[t] : m0[t], pb[(t & 6) + b][0], pb[(t & 6) + b][1]);
            }
            r.pin();
            r.run<BIG, 6, false>(y0, false);
            uint8_t* odst = sc->o + (size_t)mt * 7 * SLOT + ns * (14 * 2048) + warp * 256 + lane * 4;
#pragma unroll
            for (int hp = 0; hp < 2; hp++) {
#pragma unroll
                for (int b = 0; b < 2; b++) {
                    const float (&u)[8][4] = o[b];
                    const int t = 4 * hp;
                    uint32_t* w = p + 14 * hp + b;
                    w[0] = pack2(u[t][0], u[t][1]);
                    w[2] = pack2(u[t][2], u[t][3]);
                    w[4] = pack2(u[t + 1][0], u[t + 1][1]);
                    w[6] = pack2(g < 4 ? u[t + 1][2] : u[t + 2][0], g < 4 ? u[t + 1][3] : u[t + 2][1]);
                    w[8] = pack2(u[t + 2][2], u[t + 2][3]);
                    w[10] = pack2(u[t + 3][0], u[t + 3][1]);
                    w[12] = pack2(u[t + 3][2], u[t + 3][3]);
                }
            }
#pragma unroll
            for (int i = 0; i < 28; i++) {
                if (i && i % O_SLICE == 0) r.run<BIG, 6, false>(y0);
                stg1(odst + (i >> 1) * 2048 + (i & 1) * 128, p[i]);
            }
            warp_arrive(base + BAR_RDY + 16);

#pragma unroll 1
            for (int i = 30 + 27 / O_SLICE; i <= LLAST + 1 - TURN; i++) r.run<BIG, 6, false>(y0, true, i <= LLAST - TURN);
            const uint32_t tag = lds1(base + TAG);
            if (mbar_test(base + BAR_PART + wg * 8, 0)) {
#pragma unroll
                for (int i = 0; i < 7; i++) ld_tagged(part + i * 4096, p[4 * i], p[4 * i + 1], p[4 * i + 2], p[4 * i + 3]);
            } else {
                p[0] = ~tag;
            }
            r.seek(LLAST + 2 - TURN, bslot_l(LLAST + 2 - TURN));
#pragma unroll
            for (int i = 1; i < TURN; i++) r.run<BIG, 6, false, 1, true>(y0, false, i == TURN - 1, i < TURN - 1);
#pragma unroll 1
            for (int n = 0; n < SPIN_LIMIT; n++) {
                uint32_t stale = 0;
#pragma unroll
                for (int i = 0; i < 28; i += 2) stale |= p[i] ^ tag;
                if (__all_sync(0xffffffffu, !(stale & 1))) break;
                mbar_wait(base + BAR_PART + wg * 8, 0);
#pragma unroll
                for (int i = 0; i < 7; i++) ld_tagged(part + i * 4096, p[4 * i], p[4 * i + 1], p[4 * i + 2], p[4 * i + 3]);
            }
            wait_released(LLAST - 6);
            asm volatile("wgmma.wait_group.sync.aligned 0;" ::: "memory");
            acc_fence(y0);
            const uint32_t slab = base + (wg ? HALO : ((LLAST - 6) % NA) * SLOT) + (warp & 3) * WSLOT;
            store_out([&](int i) { return add2(pack2(y0[2 * i], y0[2 * i + 1]), p[i]); }, lane, slab, &maps.m[M_OUTB], 448 + col, mt * 128 + warp * 16);
        }
    }
}

typedef CUresult (*EncodeFn)(CUtensorMap*, CUtensorMapDataType, cuuint32_t, void*, const cuuint64_t*, const cuuint64_t*,
                             const cuuint32_t*, const cuuint32_t*, CUtensorMapInterleave, CUtensorMapSwizzle,
                             CUtensorMapL2promotion, CUtensorMapFloatOOBfill);

struct Dim { uint64_t size, stride; uint32_t box; };
void encode(EncodeFn fn, CUtensorMap* m, const void* ptr, CUtensorMapSwizzle sw, Dim d0, Dim d1, Dim d2 = {0, 0, 0}, Dim d3 = {0, 0, 0}) {
    const cuuint64_t dims[4] = {d0.size, d1.size, d2.size, d3.size};
    const cuuint64_t strides[3] = {d1.stride, d2.stride, d3.stride};
    const cuuint32_t box[4] = {d0.box, d1.box, d2.box, d3.box};
    const cuuint32_t es[4] = {1, 1, 1, 1};
    fn(m, CU_TENSOR_MAP_DATA_TYPE_BFLOAT16, d3.size ? 4 : d2.size ? 3 : 2, const_cast<void*>(ptr), dims, strides, box, es,
       CU_TENSOR_MAP_INTERLEAVE_NONE, sw, CU_TENSOR_MAP_L2_PROMOTION_L2_128B, CU_TENSOR_MAP_FLOAT_OOB_FILL_NONE);
}

}

extern "C" void kernel_launch(void* const* d_in, const int* in_sizes, int n_in, void* d_out, int out_size) {
    (void)in_sizes; (void)n_in; (void)out_size;
    void* fnp = nullptr;
    cudaDriverEntryPointQueryResult st;
    cudaGetDriverEntryPoint("cuTensorMapEncodeTiled", &fnp, cudaEnableDefault, &st);
    EncodeFn fn = (EncodeFn)fnp;
    void* scratch = nullptr;
    cudaGetSymbolAddress(&scratch, g_scratch);
    int dev = 0, sms = 0;
    cudaGetDevice(&dev);
    cudaDeviceGetAttribute(&sms, cudaDevAttrMultiProcessorCount, dev);
    auto kernel = sms == 132 ? fused_kernel<true> : fused_kernel<false>;
    cudaFuncSetAttribute(kernel, cudaFuncAttributeMaxDynamicSharedMemorySize, SMEM_BYTES);

    const CUtensorMapSwizzle S128 = CU_TENSOR_MAP_SWIZZLE_128B, S0 = CU_TENSOR_MAP_SWIZZLE_NONE;
    const Dim one = {1, 16, 1};
    Maps maps;
    encode(fn, &maps.m[M_XA], d_in[0], S128, {896, 2, 64}, {1024, 1792, 128}, one, one);
    encode(fn, &maps.m[M_WQK], d_in[1], S128, {112, 2, 64}, {448, 2688, 32}, {3, 896, 2}, {4, 224, 1});
    encode(fn, &maps.m[M_WV], d_in[1], S128, {112, 2, 64}, {448, 2688, 64}, one, {12, 224, 1});
    encode(fn, &maps.m[M_XH], d_in[0], S128, {448, 2, 64}, {128, 1792, 8}, {8, 128 * 1792, 8}, {2, 896, 2});
    encode(fn, &maps.m[M_WO], d_in[2], S128, {112, 2, 64}, {448, 896, 64}, one, {4, 224, 1});
    encode(fn, &maps.m[M_XB], d_in[3], S128, {448, 2, 64}, {1024, 896, 64}, {2, 896 * 1024, 2}, one);
    encode(fn, &maps.m[M_CR], d_in[4], S128, {2048, 2, 64}, {2048, 4096, 128});
    encode(fn, &maps.m[M_CI], d_in[5], S128, {2048, 2, 64}, {2048, 4096, 128});
    encode(fn, &maps.m[M_WR], d_in[6], S128, {448, 2, 64}, {448, 896, 112}, one, one);
    encode(fn, &maps.m[M_WI], d_in[7], S128, {448, 2, 64}, {448, 896, 112});
    encode(fn, &maps.m[M_OUTA], d_out, S0, {1792, 2, 112}, {1024, 3584, 8});
    encode(fn, &maps.m[M_OUTB], d_out, S0, {896, 2, 112}, {2048, 1792, 8});

    kernel<<<132, 384, SMEM_BYTES>>>((Scratch*)scratch, maps);
}
```

```cpp
#include <cuda.h>
#include <cuda_bf16.h>
#include <cuda_runtime.h>
#include <stdint.h>

namespace {

constexpr uint32_t SLOT = 16384;
constexpr int NA = 7;
constexpr uint32_t BRING = NA * SLOT;
constexpr uint32_t HALO = BRING + 6 * SLOT;
constexpr uint32_t HSLOT = 1792;
constexpr uint32_t WSLOT = 3584;
constexpr uint32_t BLOB = 14336;
constexpr uint32_t BARS = 14 * SLOT;
constexpr uint32_t BAR_FULL = BARS;
constexpr uint32_t BAR_EMPTY = BARS + 64;
constexpr uint32_t BAR_RDY = BARS + 128;
constexpr uint32_t BAR_DEP = BARS + 168;
constexpr uint32_t BAR_HALO = BARS + 192;
constexpr uint32_t BAR_PART = BARS + 208;
constexpr uint32_t TAG = BARS + 224;
constexpr uint32_t HSPARE = BARS + 256 + 1024;
constexpr uint32_t SMEM_BYTES = HSPARE + HSLOT;
constexpr uint32_t base = 1024;
constexpr int SPIN_LIMIT = 1 << 16;

#define E_EXTRA 0
#define HALO_K_AT 10
#define HALO_V_AT 19
#define O_SLICE 4
#define B_SLICE 4
#define LEAD 3
#define TURN 4
#define PIN r.pin()
#define PACE 450
#define MAPPING 2
constexpr int NBE = 13 + E_EXTRA;
constexpr int POUT = 33 + NBE;
constexpr int ELAST = POUT + 6;
constexpr int LLAST = 52 - E_EXTRA;

enum { M_XB, M_XA, M_XH, M_WR, M_WQK, M_WV, M_WO, M_WI, M_CR, M_CI, M_OUTA, M_OUTB, M_COUNT };
struct __align__(16) Role {
    int a1, b1, b3;
    uint32_t bits;
};
struct __align__(64) Maps {
    CUtensorMap m[M_COUNT];
    Role role[132];
};

constexpr int CNT_A = 0;
constexpr int CNT_B = 8;
constexpr int CNT_O = 16;
constexpr int CNT_P = 32;
constexpr int CNT_COUNT = 96;

struct Scratch {
    uint8_t ab[64 * 4 * BLOB];
    uint8_t o[16 * 7 * SLOT];
    uint8_t part[64 * 2 * BLOB];
    uint8_t halo[64 * 2 * 2048];
    unsigned cnt[CNT_COUNT * 32];
    unsigned epoch[132 * 4 * 8];
};
__device__ __align__(1024) Scratch g_scratch;

__device__ __forceinline__ unsigned clk32() { unsigned c; asm volatile("mov.u32 %0, %%clock;" : "=r"(c)); return c; }

#define PROF(idx)

__device__ __forceinline__ void mbar_init(uint32_t bar, uint32_t cnt) {
    asm volatile("mbarrier.init.shared::cta.b64 [%0], %1;" ::"r"(bar), "r"(cnt) : "memory");
}
__device__ __forceinline__ void mbar_expect(uint32_t bar, uint32_t bytes) {
    asm volatile("mbarrier.arrive.expect_tx.shared::cta.b64 _, [%0], %1;" ::"r"(bar), "r"(bytes) : "memory");
}
__device__ __forceinline__ void mbar_arrive(uint32_t bar) {
    asm volatile("mbarrier.arrive.shared::cta.b64 _, [%0];" ::"r"(bar) : "memory");
}
__device__ __forceinline__ bool mbar_try(uint32_t bar, uint32_t parity) {
    uint32_t ok;
    asm volatile("{\n.reg .pred p;\nmbarrier.try_wait.parity.shared::cta.b64 p, [%1], %2;\nselp.u32 %0, 1, 0, p;\n}\n"
                 : "=r"(ok) : "r"(bar), "r"(parity) : "memory");
    return ok;
}
__device__ __forceinline__ bool mbar_test(uint32_t bar, uint32_t parity) {
    uint32_t ok;
    asm volatile("{\n.reg .pred p;\nmbarrier.test_wait.parity.shared::cta.b64 p, [%1], %2;\nselp.u32 %0, 1, 0, p;\n}\n"
                 : "=r"(ok) : "r"(bar), "r"(parity) : "memory");
    return ok;
}
__device__ __forceinline__ void mbar_wait(uint32_t bar, uint32_t parity) {
#pragma unroll 1
    for (int n = 0; n < SPIN_LIMIT; n++)
        if (mbar_try(bar, parity)) break;
}
__device__ __forceinline__ bool elect() {
    uint32_t p;
    asm volatile("{\n.reg .pred p;\nelect.sync _|p, 0xffffffff;\nselp.u32 %0, 1, 0, p;\n}\n" : "=r"(p));
    return p;
}
__device__ __forceinline__ void nb_sync(int id, int n) { asm volatile("bar.sync %0, %1;" ::"r"(id), "r"(n) : "memory"); }
__device__ __forceinline__ void nb_arrive(int id, int n) { asm volatile("bar.arrive %0, %1;" ::"r"(id), "r"(n) : "memory"); }
__device__ __forceinline__ void warp_arrive(uint32_t bar) {
    __syncwarp();
    if (elect()) mbar_arrive(bar);
}
__device__ __forceinline__ uint32_t band(uint32_t x, uint32_t m) {
    uint32_t r;
    asm volatile("and.b32 %0, %1, %2;" : "=r"(r) : "r"(x), "r"(m));
    return r;
}
__device__ __forceinline__ uint32_t dup(uint32_t x, uint32_t zero) {
    uint32_t r;
    asm volatile("xor.b32 %0, %1, %2;" : "=r"(r) : "r"(x), "r"(zero));
    return r;
}

__device__ __forceinline__ void tma_ld2(uint32_t dst, const CUtensorMap* m, int c0, int c1, uint32_t bar) {
    asm volatile("cp.async.bulk.tensor.2d.shared::cluster.global.mbarrier::complete_tx::bytes [%0], [%1, {%3, %4}], [%2];"
                 ::"r"(dst), "l"(m), "r"(bar), "r"(c0), "r"(c1) : "memory");
}
__device__ __forceinline__ void tma_ld4(uint32_t dst, const CUtensorMap* m, int c0, int c1, int c2, int c3, uint32_t bar) {
    asm volatile("cp.async.bulk.tensor.4d.shared::cluster.global.mbarrier::complete_tx::bytes [%0], [%1, {%3, %4, %5, %6}], [%2];"
                 ::"r"(dst), "l"(m), "r"(bar), "r"(c0), "r"(c1), "r"(c2), "r"(c3) : "memory");
}
__device__ __forceinline__ void bulk_ld(uint32_t dst, const void* src, uint32_t bytes, uint32_t bar) {
    asm volatile("cp.async.bulk.shared::cluster.global.mbarrier::complete_tx::bytes [%0], [%1], %2, [%3];"
                 ::"r"(dst), "l"(src), "r"(bytes), "r"(bar) : "memory");
}
__device__ __forceinline__ void tma_st2(const CUtensorMap* m, int c0, int c1, uint32_t src) {
    asm volatile("cp.async.bulk.tensor.2d.global.shared::cta.bulk_group [%0, {%1, %2}], [%3];"
                 ::"l"(m), "r"(c0), "r"(c1), "r"(src) : "memory");
}
__device__ __forceinline__ void bulk_commit() { asm volatile("cp.async.bulk.commit_group;" ::: "memory"); }
__device__ __forceinline__ void bulk_wait_read() { asm volatile("cp.async.bulk.wait_group.read 0;" ::: "memory"); }
__device__ __forceinline__ void fence_async_smem() { asm volatile("fence.proxy.async.shared::cta;" ::: "memory"); }
__device__ __forceinline__ void fence_async_global() { asm volatile("fence.proxy.async.global;" ::: "memory"); }

__device__ __forceinline__ void signal(Scratch* sc, int idx) {
    asm volatile("fence.proxy.async;\nred.relaxed.gpu.global.add.u32 [%0], 1;" ::"l"(&sc->cnt[idx * 32]) : "memory");
}
__device__ __forceinline__ unsigned peek(const unsigned* p) {
    unsigned v;
    asm volatile("ld.relaxed.gpu.global.u32 %0, [%1];" : "=r"(v) : "l"(p) : "memory");
    return v;
}
__device__ __forceinline__ void await(Scratch* sc, int idx, unsigned target) {
    const unsigned* p = &sc->cnt[idx * 32];
#pragma unroll 1
    for (int n = 0; n < SPIN_LIMIT; n++)
        if ((int)(peek(p) - target) >= 0) break;
    asm volatile("fence.acquire.gpu;" ::: "memory");
}
__device__ __forceinline__ void wait_dep(int k) {
    mbar_wait(base + BAR_DEP + k * 8, 0);
    fence_async_global();
}

#define WG_REGS                                                                                                     \
    "{%0,%1,%2,%3,%4,%5,%6,%7,%8,%9,%10,%11,%12,%13,%14,%15,%16,%17,%18,%19,%20,%21,%22,%23,%24,%25,%26,%27,"       \
    "%28,%29,%30,%31,%32,%33,%34,%35,%36,%37,%38,%39,%40,%41,%42,%43,%44,%45,%46,%47,%48,%49,%50,%51,%52,%53,%54,%55}"
#define WG_OPS(C)                                                                                                   \
    C(d[0]), C(d[1]), C(d[2]), C(d[3]), C(d[4]), C(d[5]), C(d[6]), C(d[7]), C(d[8]), C(d[9]), C(d[10]), C(d[11]),   \
    C(d[12]), C(d[13]), C(d[14]), C(d[15]), C(d[16]), C(d[17]), C(d[18]), C(d[19]), C(d[20]), C(d[21]), C(d[22]),   \
    C(d[23]), C(d[24]), C(d[25]), C(d[26]), C(d[27]), C(d[28]), C(d[29]), C(d[30]), C(d[31]), C(d[32]), C(d[33]),   \
    C(d[34]), C(d[35]), C(d[36]), C(d[37]), C(d[38]), C(d[39]), C(d[40]), C(d[41]), C(d[42]), C(d[43]), C(d[44]),   \
    C(d[45]), C(d[46]), C(d[47]), C(d[48]), C(d[49]), C(d[50]), C(d[51]), C(d[52]), C(d[53]), C(d[54]), C(d[55])

template <int TA, int TB, int SB, bool INIT, uint32_t AH, uint32_t BH>
__device__ __forceinline__ void wgmma112(float (&d)[56], uint32_t alo, uint32_t blo) {
    if (INIT) {
        asm volatile("{\n.reg .pred p;\n.reg .b64 da, db;\nsetp.ne.b32 p, 0, 0;\nmov.b64 da, {%56, %61};\nmov.b64 db, {%57, %62};\n"
                     "wgmma.mma_async.sync.aligned.m64n112k16.f32.bf16.bf16 " WG_REGS ", da, db, p, 1, %59, %60, %58;\n}\n"
                     : WG_OPS("=f") : "r"(alo), "r"(blo), "n"(TB), "n"(SB), "n"(TA), "n"(AH), "n"(BH));
    } else {
        asm volatile("{\n.reg .pred p;\n.reg .b64 da, db;\nsetp.ne.b32 p, 1, 0;\nmov.b64 da, {%56, %61};\nmov.b64 db, {%57, %62};\n"
                     "wgmma.mma_async.sync.aligned.m64n112k16.f32.bf16.bf16 " WG_REGS ", da, db, p, 1, %59, %60, %58;\n}\n"
                     : WG_OPS("+f") : "r"(alo), "r"(blo), "n"(TB), "n"(SB), "n"(TA), "n"(AH), "n"(BH));
    }
}
__device__ __forceinline__ void acc_fence(float (&d)[56]) {
#pragma unroll
    for (int i = 0; i < 56; i++) asm volatile("" : "+f"(d[i])::"memory");
}

__device__ __forceinline__ uint32_t pack2(float lo, float hi) {
    uint32_t r;
    asm volatile("cvt.rn.bf16x2.f32 %0, %1, %2;" : "=r"(r) : "f"(hi), "f"(lo));
    return r;
}
__device__ __forceinline__ uint32_t movm(uint32_t a) {
    uint32_t r;
    asm volatile("movmatrix.sync.aligned.m8n8.trans.b16 %0, %1;" : "=r"(r) : "r"(a));
    return r;
}
__device__ __forceinline__ void stsm4(uint32_t addr, uint32_t a, uint32_t b, uint32_t c, uint32_t d) {
    asm volatile("stmatrix.sync.aligned.m8n8.x4.shared.b16 [%0], {%1,%2,%3,%4};" ::"r"(addr), "r"(a), "r"(b), "r"(c), "r"(d) : "memory");
}
__device__ __forceinline__ void sts1(uint32_t addr, uint32_t a) { asm volatile("st.shared.b32 [%0], %1;" ::"r"(addr), "r"(a) : "memory"); }
__device__ __forceinline__ uint32_t lds1(uint32_t addr) {
    uint32_t a;
    asm volatile("ld.shared.b32 %0, [%1];" : "=r"(a) : "r"(addr) : "memory");
    return a;
}
__device__ __forceinline__ void stg1(uint8_t* p, uint32_t a) { asm volatile("st.global.b32 [%0], %1;" ::"l"(p), "r"(a) : "memory"); }
__device__ __forceinline__ void st_part(uint8_t* p, const uint32_t* v, uint32_t parity) {
    asm volatile("{\n.reg .b64 x, y;\nmov.b64 x, {%1, %2};\nmov.b64 y, {%3, %4};\nst.relaxed.gpu.global.v2.b64 [%0], {x, y};\n}\n"
                 ::"l"(p), "r"((v[0] & ~1u) | parity), "r"(v[1]), "r"((v[2] & ~1u) | parity), "r"(v[3]) : "memory");
}
__device__ __forceinline__ void mma16816(float (&d)[4], const uint32_t (&a)[4], uint32_t b0, uint32_t b1) {
    asm volatile("mma.sync.aligned.m16n8k16.row.col.f32.bf16.bf16.f32 {%0,%1,%2,%3}, {%4,%5,%6,%7}, {%8,%9}, {%0,%1,%2,%3};"
                 : "+f"(d[0]), "+f"(d[1]), "+f"(d[2]), "+f"(d[3]) : "r"(a[0]), "r"(a[1]), "r"(a[2]), "r"(a[3]), "r"(b0), "r"(b1));
}
__device__ __forceinline__ uint32_t add2(uint32_t a, uint32_t b) {
    uint32_t r;
    asm("add.rn.bf16x2 %0, %1, %2;" : "=r"(r) : "r"(a), "r"(b));
    return r;
}
__device__ __forceinline__ uint32_t max2(uint32_t a, uint32_t b) {
    uint32_t r;
    asm("max.bf16x2 %0, %1, %2;" : "=r"(r) : "r"(a), "r"(b));
    return r;
}
__device__ __forceinline__ void ld_tagged(const uint8_t* p, uint32_t& a, uint32_t& ta, uint32_t& b, uint32_t& tb) {
    asm volatile("{\n.reg .b64 x, y;\nld.relaxed.gpu.global.v2.b64 {x, y}, [%4];\nmov.b64 {%0, %1}, x;\nmov.b64 {%2, %3}, y;\n}\n"
                 : "=r"(a), "=r"(ta), "=r"(b), "=r"(tb) : "l"(p) : "memory");
}
__device__ __forceinline__ float bf_lo(uint32_t v) { return __uint_as_float(v << 16); }
__device__ __forceinline__ float bf_hi(uint32_t v) { return __uint_as_float(v & 0xFFFF0000u); }
__device__ __forceinline__ float rcp(float x) { float r; asm("rcp.approx.ftz.f32 %0, %1;" : "=f"(r) : "f"(x)); return r; }
__device__ __forceinline__ float ex2(float x) { float r; asm volatile("ex2.approx.ftz.f32 %0, %1;" : "=f"(r) : "f"(x)); return r; }

__device__ __forceinline__ uint32_t full_bar(int stage) { return base + BAR_FULL + (stage & 7) * 8; }
__device__ __forceinline__ void wait_released(int j) { mbar_wait(base + BAR_EMPTY + (j & 7) * 8, (j >> 3) & 1); }

template <int V>
struct Int { static constexpr int value = V; };

__host__ __device__ constexpr int bslot_e(int i) { return (i < 2 || i >= 14) ? (i + 5) % 7 : (i + 1) % 5; }
__host__ __device__ constexpr int bslot_l(int i) { return i % 6; }

template <uint32_t OFF>
struct Feed {
    int stage;
    uint32_t dst;
    __device__ __forceinline__ void seek(int i, int slot) { stage = i; dst = base + OFF + slot * SLOT; }
    template <int N>
    __device__ __forceinline__ uint32_t acquire() { wait_released(stage - N); return full_bar(stage); }
    template <int N>
    __device__ __forceinline__ void next() {
        stage++;
        dst += SLOT;
        if (dst == base + OFF + N * SLOT) dst = base + OFF;
    }
};
__device__ __forceinline__ int skip_own(int n, int mt) { return n == mt ? 15 : n; }

struct Desc { uint32_t lo, hi; };
__host__ __device__ constexpr Desc desc_const(uint32_t lbo, uint32_t sbo, uint32_t mode) { return {(lbo >> 4) << 16, (sbo >> 4) | (mode << 30)}; }
constexpr Desc D_K128 = desc_const(16, 1024, 1);
constexpr Desc D_N128 = desc_const(8192, 1024, 1);
constexpr Desc D_BLOB = desc_const(128, 256, 0);
constexpr Desc D_OT = desc_const(2048, 128, 0);

enum Kind { XW, XWN, QK, BIG, OUT };

struct Ring {
    int stage;
    uint32_t a, b;
    uint32_t wg;
    uint32_t zero;
    __device__ __forceinline__ void seek(int i, int bslot) {
        stage = i;
        a = (base + (i % NA) * SLOT) >> 4;
        b = (base + BRING + bslot * SLOT) >> 4;
    }
    __device__ __forceinline__ void wait() { mbar_wait(full_bar(stage), (stage >> 3) & 1); }
    __device__ __forceinline__ void take_turn() { nb_sync(1 + wg, 256); }
    __device__ __forceinline__ void pin() {
        uint32_t n = 0;
#pragma unroll 1
        do {
            asm volatile("pmevent 7;" ::: "memory");
        } while (n++ < zero);
    }
    template <Kind K, int NBS, bool INIT, int SB = 1, bool TAIL = false>
    __device__ __forceinline__ void run(float (&d)[56], float (&e)[56], bool first = true, bool last = true, bool more = true) {
        if (first) take_turn();
        asm volatile("wgmma.fence.sync.aligned;" ::: "memory");
        if (K == QK) {
            const uint32_t da = D_K128.lo + (base >> 4) + (stage >> 1) * (SLOT >> 4) + (stage & 1) * 4 + wg * 512, db = D_N128.lo + b;
            wgmma112<0, 1, 1, INIT, D_K128.hi, D_N128.hi>(d, da, db);
            wgmma112<0, 1, 1, INIT, D_K128.hi, D_N128.hi>(e, da, db + 256);
            wgmma112<0, 1, 1, false, D_K128.hi, D_N128.hi>(d, da + 2, db + 128);
            wgmma112<0, 1, 1, false, D_K128.hi, D_N128.hi>(e, da + 2, db + 384);
        } else {
            constexpr int TA = K == OUT, TB = K != XW;
            constexpr uint32_t sa = K == OUT ? 256 : 2, sb = K == XW ? 2 : K == BIG ? 224 : 128;
            constexpr Desc A = K == OUT ? D_OT : D_K128, B = K == XW ? D_K128 : K == BIG ? D_BLOB : D_N128;
            const uint32_t da = A.lo + a + wg * (K == OUT ? 64 : 512), db = B.lo + b;
            wgmma112<TA, TB, SB, INIT, A.hi, B.hi>(d, da, db);
            wgmma112<TA, TB, SB, false, A.hi, B.hi>(d, da + sa, db + sb);
            wgmma112<TA, TB, SB, false, A.hi, B.hi>(d, da + 2 * sa, db + 2 * sb);
            wgmma112<TA, TB, SB, false, A.hi, B.hi>(d, da + 3 * sa, db + 3 * sb);
        }
        asm volatile("wgmma.commit_group.sync.aligned;" ::: "memory");
        if (last) nb_arrive(2 - wg, 256);
        if (!TAIL) asm volatile("wgmma.wait_group.sync.aligned 1;" ::: "memory");
        if (!TAIL && stage > 0 && elect()) mbar_arrive(base + BAR_EMPTY + ((stage - 1) & 7) * 8);
        stage++;
        a += SLOT >> 4;
        if (a == (base + NA * SLOT) >> 4) a = base >> 4;
        b += SLOT >> 4;
        if (b == (base + BRING + NBS * SLOT) >> 4) b = (base + BRING) >> 4;
        if (more) wait();
    }
    template <Kind K, int NBS, bool INIT, int SB = 1, bool TAIL = false>
    __device__ __forceinline__ void run(float (&d)[56], bool first = true, bool last = true, bool more = true) {
        run<K, NBS, INIT, SB, TAIL>(d, d, first, last, more);
    }
};

__device__ __forceinline__ void pack_all(const float (&d)[56], uint32_t (&p)[28]) {
#pragma unroll
    for (int i = 0; i < 28; i++) p[i] = pack2(d[2 * i], d[2 * i + 1]);
}
template <int I0, int I1>
__device__ __forceinline__ void store_frags(uint8_t* dst, const uint32_t (&p)[28]) {
#pragma unroll
    for (int i = I0; i < I1; i++) stg1(dst + i * 128, p[i]);
}
template <int I0, int I1>
__device__ __forceinline__ void stage_frags(uint32_t lane_addr, const uint32_t (&p)[28]) {
#pragma unroll
    for (int i = I0; i < I1; i += 4) stsm4(lane_addr + i * 128, p[i], p[i + 1], p[i + 2], p[i + 3]);
}
template <class F>
__device__ __forceinline__ void store_out(F frag, int lane, uint32_t slab, const CUtensorMap* m, int c0, int c1) {
    const bool swap = lane & 16;
    const uint32_t addr = slab + (lane & 7) * 224 + ((lane >> 3) ^ ((lane >> 2) & 1)) * 16;
#pragma unroll
    for (int h = 0; h < 2; h++) {
#pragma unroll
        for (int c = 0; c < 14; c += 4) {
            const uint32_t t0 = frag(2 * c + h), t1 = frag(2 * c + 2 + h);
            if (c < 12) {
                const uint32_t t2 = frag(2 * c + 4 + h), t3 = frag(2 * c + 6 + h);
                stsm4(addr + h * 1792 + c * 16, swap ? t1 : t0, swap ? t0 : t1, swap ? t3 : t2, swap ? t2 : t3);
            } else {
                asm volatile("stmatrix.sync.aligned.m8n8.x2.shared.b16 [%0], {%1,%2};" ::"r"(addr + h * 1792 + c * 16), "r"(swap ? t1 : t0), "r"(swap ? t0 : t1) : "memory");
            }
        }
        fence_async_smem();
        __syncwarp();
        if (elect()) tma_st2(m, c0, c1 + 8 * h, slab + h * 1792);
    }
    if (elect()) {
        bulk_commit();
        bulk_wait_read();
    }
}
__host__ __device__ constexpr int tile_of(int t) { return 7 * (t >> 2) + 3 * ((t >> 1) & 1) + 2 * (t & 1); }

__device__ __forceinline__ void first_fill(const Maps& maps, const Role& r, int i) {
    const uint32_t off = (r.bits >> 9) & 0x180;
    const int L = (off >> 7) & 1;
    const bool E = off == 0;
    const CUtensorMap* ma = reinterpret_cast<const CUtensorMap*>(reinterpret_cast<const uint8_t*>(maps.m) + off);
    const uint32_t bar = full_bar(i);
    const int k = (i * 64) >> L;
    const bool has_a = !(i & L), has_b = i < 7 - L;
    const uint32_t dst = base + BRING + (E ? (0x2104365u >> (4 * i)) & 7 : i) * SLOT;
    mbar_expect(bar, (has_a ? SLOT : 0) + (has_b ? (E ? BLOB : SLOT) : 0));
    if (has_a) tma_ld4(base + (i >> L) * SLOT, ma, (r.bits & 0x1FF) + k, r.a1, 0, 0, bar);
    if (has_b) {
        tma_ld4(dst, ma + 3, E ? k : 0, E ? r.b1 : k, 0, r.b3, bar);
        if (!E) tma_ld4(dst + 8192, ma + 3, 64, k, 0, r.b3, bar);
        mbar_arrive(bar);
    }
}
static_assert(bslot_e(0) == 5 && bslot_e(1) == 6 && bslot_e(2) == 3 && bslot_e(3) == 4 && bslot_e(4) == 0 && bslot_e(6) == 2, "");

template <bool BY_SM>
__global__ void __launch_bounds__(384, 1) fused_kernel(Scratch* sc, const __grid_constant__ Maps maps) {
    uint32_t sm = blockIdx.x;
    if (BY_SM) asm("mov.u32 %0, %%smid;" : "=r"(sm));
    const Role role = maps.role[sm];
    const int warp = __shfl_sync(0xffffffffu, threadIdx.x >> 5, 0);
    const unsigned t_open = clk32();
    if (warp == 8) {
        if (elect()) {
#pragma unroll
            for (int i = 0; i < LEAD; i++) mbar_init(base + BAR_FULL + i * 8, 2);
            asm volatile("fence.mbarrier_init.release.cluster;" ::: "memory");
            first_fill(maps, role, 0);
#pragma unroll 1
            for (int i = 1 + blockIdx.y; i < LEAD; i++) first_fill(maps, role, i);
        }
    }
    if (warp == 9) {
        if (elect()) {
#pragma unroll
            for (int i = 0; i < 8; i++) mbar_init(base + BAR_EMPTY + i * 8, 8);
            asm volatile("fence.mbarrier_init.release.cluster;" ::: "memory");
        }
    } else if (warp == 10) {
        if (elect()) {
#pragma unroll
            for (int i = 0; i < 5; i++) mbar_init(base + BAR_RDY + i * 8, i < 2 ? 4 : 8);
#pragma unroll
            for (int i = 0; i < 2; i++) mbar_init(base + BAR_HALO + i * 8, 9);
            asm volatile("fence.mbarrier_init.release.cluster;" ::: "memory");
        }
    } else if (warp == 11) {
        if (elect()) {
#pragma unroll
            for (int i = LEAD; i < 8; i++) mbar_init(base + BAR_FULL + i * 8, 2);
#pragma unroll
            for (int i = 0; i < 3; i++) mbar_init(base + BAR_DEP + i * 8, 1);
#pragma unroll
            for (int i = 0; i < 2; i++) mbar_init(base + BAR_PART + i * 8, 1);
            asm volatile("fence.mbarrier_init.release.cluster;" ::: "memory");
        }
    }
    __syncthreads();

    int lane = threadIdx.x & 31;
    asm volatile("" : "+r"(lane));
    const bool roleH = role.bits & (1u << 17);
    const int roleL = (role.bits >> 16) & 1, mt = (role.bits >> 18) & 15, ns = (role.bits >> 22) & 3, bid = role.bits >> 24;
    const int par = mt >> 3, blk = mt & 7, col = ns * 112;

    if (__builtin_expect(warp >= 8, 1)) {
        asm volatile("setmaxnreg.dec.sync.aligned.u32 56;");
#define PROF_FEED_A
#define PROF_FEED_B
        if (__builtin_expect(warp == 8, 1)) {
            if (elect()) {
                PROF(129);
#pragma unroll 1
                for (int i = LEAD; i < 7; i++) {
                    while (clk32() - t_open < i * PACE) {}
                    first_fill(maps, role, i);
                }
                PROF(134);
                Feed<0> f;
                const int row = mt * 128;
                auto c_run = [&](const CUtensorMap* m, int off, int n0, int n1) {
#pragma unroll 1
                    for (int n = n0; n < n1; n++) {
                        const uint32_t bar = f.acquire<NA>();
                        mbar_expect(bar, SLOT);
                        tma_ld2(f.dst, m, (off + skip_own(n, mt)) * 64, row, bar);
                        PROF_FEED_A;
                        f.next<NA>();
                    }
                };
                if (roleH) {
                } else if (!roleL) {
                    f.seek(14, 0);
                    mbar_wait(base + BAR_RDY, 0);
#pragma unroll 1
                    for (int i = 0; i < 4; i++) {
                        const uint32_t bar = f.acquire<NA>();
                        mbar_expect(bar, SLOT);
                        tma_ld2(f.dst, &maps.m[M_CR + (i >> 1)], ((i & 1) * 16 + mt) * 64, row, bar);
                        mbar_arrive(bar);
                        PROF_FEED_A;
                        f.next<NA>();
                    }
                    c_run(&maps.m[M_CR], 0, 0, 15);
                    c_run(&maps.m[M_CI], 0, 0, NBE);
                    wait_dep(2);
#pragma unroll 1
                    for (int i = 0; i < 7; i++) {
                        const uint32_t bar = f.acquire<NA>();
                        mbar_expect(bar, SLOT);
                        bulk_ld(f.dst, sc->o + (size_t)(mt * 7 + i) * SLOT, SLOT, bar);
                        PROF_FEED_A;
                        f.next<NA>();
                    }
                } else {
#pragma unroll 1
                    for (int i = 4; i < 7; i++) {
                        wait_released(2 * i - 8);
                        mbar_expect(full_bar(2 * i), SLOT);
                        tma_ld4(base + i * SLOT, &maps.m[M_XA], par * 448 + i * 64, blk * 128, 0, 0, full_bar(2 * i));
                    }
                    wait_released(HALO_K_AT);
                    mbar_arrive(base + BAR_DEP + 16);
                    f.seek(21, 0);
                    c_run(&maps.m[M_CR], 16, 0, 15);
                    c_run(&maps.m[M_CI], 16, 0, 15);
                    c_run(&maps.m[M_CI], 0, NBE, 15);
                }
            }
        } else if (warp == 11) {
            if (elect()) {
                Feed<BRING> f;
                auto blob_run = [&](auto nbs, int quarter, int n0, int n1) {
                    constexpr int N = decltype(nbs)::value;
                    const uint8_t* src = sc->ab + (size_t)(quarter * 64 + ns) * BLOB;
#pragma unroll 1
                    for (int n = n0; n < n1; n++) {
                        const uint32_t bar = f.template acquire<N>();
                        mbar_expect(bar, BLOB);
                        bulk_ld(f.dst, src + skip_own(n, mt) * (4 * BLOB), BLOB, bar);
                        PROF_FEED_B;
                        f.template next<N>();
                    }
                };
                auto w_run = [&](auto nbs, const CUtensorMap* m, int slice, bool no_a) {
                    constexpr int N = decltype(nbs)::value;
#pragma unroll 1
                    for (int i = 0; i < 7; i++) {
                        const uint32_t bar = f.template acquire<N>();
                        mbar_expect(bar, SLOT);
                        tma_ld4(f.dst, m, 0, i * 64, 0, slice, bar);
                        tma_ld4(f.dst + 8192, m, 64, i * 64, 0, slice, bar);
                        if (no_a) mbar_arrive(bar);
                        PROF_FEED_B;
                        f.template next<N>();
                    }
                };
                if (roleH) {
                    f.seek(7, 0);
                    w_run(Int<7>(), &maps.m[M_WV], 8 + ns, true);
                } else if (!roleL) {
                    f.seek(7, bslot_e(7));
#pragma unroll 1
                    for (int i = 0; i < 7; i++) {
                        const uint32_t bar = f.acquire<5>();
                        mbar_expect(bar, BLOB);
                        tma_ld2(f.dst, &maps.m[M_WI], i * 64, col, bar);
                        mbar_arrive(bar);
                        PROF_FEED_B;
                        f.next<5>();
                    }
                    f.seek(18, bslot_e(18));
                    wait_dep(0);
                    blob_run(Int<7>(), 0, 0, 15);
                    wait_dep(1);
                    blob_run(Int<7>(), 2, 0, NBE);
                    w_run(Int<7>(), &maps.m[M_WO], ns, false);
                } else {
                    f.seek(6, 0);
#pragma unroll 1
                    for (int i = 6; i < 14; i++) {
                        const uint32_t bar = f.acquire<6>();
                        mbar_expect(bar, SLOT);
                        tma_ld4(f.dst, &maps.m[M_WQK], 0, i * 32, 0, ns, bar);
                        tma_ld4(f.dst + 8192, &maps.m[M_WQK], 64, i * 32, 0, ns, bar);
                        if (i & 1) mbar_arrive(bar);
                        PROF_FEED_B;
                        f.next<6>();
                    }
                    w_run(Int<6>(), &maps.m[M_WV], 8 + ns, true);
                    wait_dep(0);
                    blob_run(Int<6>(), 1, 0, 15);
                    wait_dep(1);
                    blob_run(Int<6>(), 3, 0, 15);
                    blob_run(Int<6>(), 2, NBE, 15);
                }
            }
        } else if (roleH) {
            if (elect()) {
                wait_released(warp == 9 ? 0 : 7);
#pragma unroll 1
                for (int i = 0; i < 7; i++) {
                    if (warp == 9) {
                        asm volatile("cp.async.bulk.prefetch.tensor.2d.L2.global [%0, {%1, %2}];" ::"l"(&maps.m[M_WI]), "r"(i * 64), "r"(col) : "memory");
                    } else {
                        asm volatile("cp.async.bulk.prefetch.tensor.4d.L2.global [%0, {%1, %2, 0, %3}];" ::"l"(&maps.m[M_WO]), "r"(0), "r"(i * 64), "r"(ns) : "memory");
                        asm volatile("cp.async.bulk.prefetch.tensor.4d.L2.global [%0, {%1, %2, 0, %3}];" ::"l"(&maps.m[M_WO]), "r"(64), "r"(i * 64), "r"(ns) : "memory");
                    }
                }
            }
        } else if (warp == 10) {
            if (elect()) {
                unsigned* epoch_ptr = &sc->epoch[(bid * 4 + 2) * 8];
                const unsigned ep = *epoch_ptr + 1;
                sts1(base + TAG, ep);
                asm volatile("prefetch.tensormap [%0];" ::"l"(&maps.m[M_OUTA + roleL]) : "memory");
                await(sc, CNT_A + roleL * 4 + ns, ep * 16);
                mbar_arrive(base + BAR_DEP);
                PROF(150);
                await(sc, CNT_B + ns, ep * 16);
                mbar_arrive(base + BAR_DEP + 8);
                PROF(151);
                if (!roleL) {
                    await(sc, CNT_O + mt, ep * 4);
                    mbar_arrive(base + BAR_DEP + 16);
                } else {
                    await(sc, CNT_P + mt * 4 + ns, ep * 2 - 1);
                    mbar_arrive(base + BAR_PART);
                    PROF(153);
                    await(sc, CNT_P + mt * 4 + ns, ep * 2);
                    mbar_arrive(base + BAR_PART + 8);
                }
                PROF(152);
                *epoch_ptr = ep;
            }
        } else if (!roleL) {
            if (elect()) {
                mbar_wait(base + BAR_RDY, 0);
                PROF(130);
                signal(sc, CNT_A + ns);
                PROF(131);
                mbar_wait(base + BAR_RDY + 8, 0);
                signal(sc, CNT_A + 4 + ns);
                PROF(135);
                mbar_wait(base + BAR_RDY + 32, 0);
                PROF(132);
                signal(sc, CNT_B + ns);
                PROF(133);
            }
        } else {
            unsigned* epoch_ptr = &sc->epoch[(bid * 4 + 1) * 8];
            const unsigned tag = *epoch_ptr + 1;
#pragma unroll 1
            for (int kv = 0; kv < 2; kv++) {
                uint32_t v[16];
#pragma unroll
                for (int i = 0; i < 16; i++) v[i] = 0;
                if (kv) mbar_wait(base + BAR_HALO, 0), wait_released(HALO_V_AT);
                else mbar_wait(base + BAR_DEP + 16, 0);
                if (blk > 0) {
                    const uint8_t* src = sc->halo + (size_t)(((mt - 1) * 4 + ns) * 2 + kv) * 2048 + lane * 16;
#pragma unroll 1
                    for (int n = 0; n < SPIN_LIMIT; n++) {
                        uint32_t stale = 0;
#pragma unroll
                        for (int i = 0; i < 4; i++) ld_tagged(src + i * 512, v[4 * i], v[4 * i + 1], v[4 * i + 2], v[4 * i + 3]);
#pragma unroll
                        for (int i = 0; i < 16; i += 2) stale |= v[i] ^ tag;
                        if (__all_sync(0xffffffffu, !(stale & 1))) break;
                    }
#pragma unroll
                    for (int c = 0; c < 14; c += 2) v[c] = (v[c] & ~1u) | ((v[15] >> c) & 1);
                }
#pragma unroll
                for (int i = 0; i < 14; i++) sts1(base + HALO + kv * (8 * HSLOT) + i * 128 + lane * 4, v[i]);
                warp_arrive(base + BAR_HALO + kv * 8);
                if (lane == 0) PROF(142 + kv);
            }
            if (elect()) {
                mbar_wait(base + BAR_RDY + 16, 0);
                PROF(130);
                signal(sc, CNT_O + mt);
                PROF(131);
                *epoch_ptr = tag;
            }
        }
    } else {
        asm volatile("setmaxnreg.inc.sync.aligned.u32 224;");
        Ring r;
        r.wg = warp >> 2;
        r.zero = blockIdx.y;
        const int wg = warp >> 2;
        if (wg) nb_arrive(1, 256);
        r.stage = 0;
        r.wait();
        uint8_t* part = sc->part + (size_t)(ns * 16 + mt) * (2 * BLOB) + warp * 512 + lane * 16;
        uint32_t p[28];

        if (roleH) {
            unsigned* epoch_ptr = &sc->epoch[bid * 4 * 8];
            const unsigned tag = *epoch_ptr + 1;
            uint8_t* hout = sc->halo + (size_t)((warp * 8 + ns) * 2) * 2048 + lane * 16;
            auto send = [&](int kv) {
#pragma unroll
                for (int h = 0; h < 2; h++) {
                    uint32_t v[16];
                    v[14] = v[15] = 0;
#pragma unroll
                    for (int c = 0; c < 14; c++) v[c] = p[2 * c + h];
#pragma unroll
                    for (int c = 0; c < 14; c += 2) v[15] |= (v[c] & 1) << c;
#pragma unroll
                    for (int i = 0; i < 4; i++) st_part(hout + (h * 8 + kv) * 2048 + i * 512, v + 4 * i, tag & 1);
                }
            };
            float x0[56], x1[56];
            r.seek(0, 0);
            r.run<XWN, 7, true>(x0);
#pragma unroll 1
            for (int i = 1; i < 7; i++) r.run<XWN, 7, false>(x0);
            r.run<XWN, 7, true>(x1);
            acc_fence(x0);
            pack_all(x0, p);
            send(0);
#pragma unroll 1
            for (int i = 1; i < 7; i++) r.run<XWN, 7, false>(x1, true, true, i < 6);
            asm volatile("wgmma.wait_group.sync.aligned 0;" ::: "memory");
            acc_fence(x1);
            pack_all(x1, p);
#pragma unroll
            for (int i = 0; i < 28; i++) p[i] = movm(p[i]);
            send(1);
            if (threadIdx.x == 0) *epoch_ptr = tag;
        } else if (!roleL) {
            uint8_t* blob = sc->ab + (size_t)((wg * 16 + mt) * 4 + ns) * BLOB + (warp & 3) * WSLOT + lane * 4;
            const uint32_t own = base + BRING + wg * SLOT + (warp & 3) * WSLOT + lane * 16;
            float x0[56], x1[56];
            r.seek(0, bslot_e(0));
            r.run<XW, 7, true>(x0);
            r.run<XW, 7, false>(x0);
            r.seek(2, bslot_e(2));
#pragma unroll 1
            for (int i = 2; i < 7; i++) r.run<XW, 5, false>(x0);

            r.seek(7, bslot_e(7));
            r.run<XW, 5, true, -1>(x1);
            acc_fence(x0);
            pack_all(x0, p);
#pragma unroll
            for (int i = 0; i < 2; i++) {
                if (wg == i) store_frags<0, 14>(blob, p);
                else stage_frags<0, 4>(own + 5 * SLOT, p);
                r.run<XW, 5, false, -1>(x1);
                if (wg == i) {
                    store_frags<14, 28>(blob, p);
                    warp_arrive(base + BAR_RDY + i * 8);
                } else {
                    stage_frags<4, 8>(own + 5 * SLOT, p);
                }
                r.run<XW, 5, false, -1>(x1);
            }
            stage_frags<8, 20>(own + 5 * SLOT, p);
            r.run<XW, 5, false, -1>(x1);
            stage_frags<20, 28>(own + 5 * SLOT, p);
            warp_arrive(base + BAR_RDY + 16);
            r.run<XW, 5, false, -1>(x1);

            mbar_wait(base + BAR_RDY + 16, 0);
            fence_async_smem();
            r.seek(14, bslot_e(14));
            r.run<BIG, 7, true>(x0);
            acc_fence(x1);
            pack_all(x1, p);
            wait_released(10);
            stage_frags<0, 28>(own, p);
            warp_arrive(base + BAR_RDY + 24);
            r.run<BIG, 7, false>(x0);
            mbar_wait(base + BAR_RDY + 24, 0);
            fence_async_smem();
            blob += (size_t)128 * BLOB;
#pragma unroll
            for (int i = 0; i < 28; i++) {
                if (i % B_SLICE == 0) r.run<BIG, 7, false>(x0);
                stg1(blob + i * 128, p[i]);
            }
            warp_arrive(base + BAR_RDY + 32);
#pragma unroll 1
            for (int i = 17 + 27 / B_SLICE; i < POUT; i++) r.run<BIG, 7, false>(x0);

            const uint32_t tag = lds1(base + TAG);
            r.seek(POUT, bslot_e(POUT));
            r.run<OUT, 7, true>(x1);
            acc_fence(x0);
            pack_all(x0, p);
#pragma unroll
            for (int k = 0; k < 3; k++) {
                if (k < 2 && wg == k) {
                    if ((warp & 3) == 0 && elect())
                        asm volatile("red.relaxed.gpu.global.add.u32 [%0], 1;" ::"l"(&sc->cnt[(CNT_P + mt * 4 + ns) * 32]) : "memory");
#pragma unroll
                    for (int i = 0; i < 4; i++) st_part(part + i * 4096, p + 4 * i, tag & 1);
                }
                if (k > 0 && wg == k - 1) {
#pragma unroll
                    for (int i = 4; i < 7; i++) st_part(part + i * 4096, p + 4 * i, tag & 1);
                }
                if (k < 2) r.run<OUT, 7, false>(x1);
            }
#pragma unroll
            for (int i = 3; i < 7; i++) r.run<OUT, 7, false, 1, true>(x1, i <= 7 - TURN, i < 7 - TURN || i == 6, i < 6);

            wait_released(ELAST - 6);
            asm volatile("wgmma.wait_group.sync.aligned 0;" ::: "memory");
            acc_fence(x1);
            const uint32_t slab = base + (wg ? BRING + bslot_e(ELAST - 6) * SLOT : ((ELAST - 6) % NA) * SLOT) + (warp & 3) * WSLOT;
            store_out([&](int i) { return pack2(x1[2 * i], x1[2 * i + 1]); }, lane, slab, &maps.m[M_OUTA], par * 896 + col, blk * 128 + warp * 16);
        } else {
            const int g = lane >> 2, tig = lane & 3;
            const uint32_t hin = base + HALO + warp * HSLOT + lane * 4;
            const uint32_t hpub = warp < 7 ? hin + HSLOT : base + HSPARE + lane * 4;
            auto publish = [&](const uint32_t (&h)[14], int c0, int c1) {
#pragma unroll
                for (int c = 0; c < 14; c++)
                    if (c >= c0 && c < c1) sts1(hpub + c * 128, h[c]);
            };
            float y0[56], y1[56], y2[56];
            r.seek(0, 0);
            r.run<QK, 6, true>(y0, y1);
#pragma unroll 1
            for (int i = 1; i < 14; i++) r.run<QK, 6, false>(y0, y1);

            uint32_t m1[8][4], m0[8][4], lo[14], hi[14], q[2][8][2];
            auto pack_q = [&](int b) {
                uint32_t v[14];
#pragma unroll
                for (int c = 0; c < 14; c++) v[c] = pack2(y0[4 * c + 2 * b], y0[4 * c + 2 * b + 1]);
#pragma unroll
                for (int t = 0; t < 8; t++) {
                    const int c = tile_of(t);
                    q[b][t][0] = (t & 3) == 2 ? (tig >= 2 ? v[c] : 0u) : v[c];
                    q[b][t][1] = (t & 3) == 1 ? (tig < 2 ? v[c + 1] : 0u) : v[c + 1];
                }
            };
            auto fetch = [&](uint32_t src, int hp, int i0) {
#pragma unroll
                for (int t = 4 * hp; t < 4 * hp + 4; t++) {
                    m0[t][i0] = (t & 3) == 2 ? dup(m0[t - 1][3], r.zero) : lds1(src + tile_of(t) * 128);
                    m0[t][3] = lds1(src + tile_of(t) * 128 + 128);
                }
            };
            r.seek(14, bslot_l(14));
            r.run<XWN, 6, true>(y2);
            acc_fence(y0);
            acc_fence(y1);
#pragma unroll
            for (int c = 0; c < 14; c++) hi[c] = pack2(y1[4 * c + 2], y1[4 * c + 3]);
            publish(hi, 0, 7);
            PIN;
            r.run<XWN, 6, false>(y2);
            publish(hi, 7, 14);
            warp_arrive(base + BAR_HALO);
#pragma unroll
            for (int c = 0; c < 14; c++) lo[c] = pack2(y1[4 * c], y1[4 * c + 1]);
#pragma unroll
            for (int t = 0; t < 8; t++) {
                const int c = tile_of(t);
                const bool shared = (t & 3) == 2;
                m1[t][0] = shared ? dup(lo[c], r.zero) : lo[c];
                m1[t][1] = shared ? dup(hi[c], r.zero) : hi[c];
                m1[t][2] = lo[c + 1];
                m1[t][3] = hi[c + 1];
                m0[t][0] = dup(m1[t][0], r.zero);
                m0[t][2] = dup(lo[c + 1], 2 * r.zero);
            }
            PIN;
            r.run<XWN, 6, false>(y2);
            mbar_wait(base + BAR_HALO, 0);
            fetch(hin, 0, 1);
            pack_q(1);
            PIN;
            r.run<XWN, 6, false>(y2);
            fetch(hin, 1, 1);
            pack_q(0);
            r.pin();
            r.take_turn();
            float s[8][4];
#pragma unroll
            for (int step = 0; step < 2; step++) {
#pragma unroll
                for (int i = 0; i < 8; i++) {
                    const int b = 1 - (i >> 2), h = i & 3, t = 2 * h + step;
                    float (&d)[4] = s[2 * h + b];
                    if (step == 0) d[0] = d[1] = d[2] = d[3] = 0.f;
                    mma16816(d, b ? m1[t] : m0[t], q[b][t][0], q[b][t][1]);
                }
            }
            r.pin();
            r.run<XWN, 6, false>(y2, false);

            uint32_t pr[8], mx[4], mx1[4];
            {
                const bool cur0 = g <= 2 * tig, cur1 = g <= 2 * tig + 1;
#pragma unroll
                for (int i = 0; i < 8; i++) {
                    const int c = (i & 1) ? 2 : 0;
                    pr[i] = movm(pack2(cur0 ? s[i][c] : s[i][2 - c], cur1 ? s[i][c + 1] : s[i][3 - c]));
                }
            }
            PIN;
            r.run<XWN, 6, false>(y2);
            const uint32_t curmask = (2 * tig <= g ? 0x0000FFFFu : 0u) | (2 * tig + 1 <= g ? 0xFFFF0000u : 0u);
            {
                const uint32_t keep = (blk == 0 && warp == 0) ? curmask : 0xFFFFFFFFu;
#pragma unroll
                for (int i = 0; i < 4; i++) {
                    pr[2 * i] = (pr[2 * i] & keep) | (0xCF9ECF9Eu & ~keep);
                    mx[i] = max2(__byte_perm(pr[2 * i], pr[2 * i + 1], 0x5410), __byte_perm(pr[2 * i], pr[2 * i + 1], 0x7632));
                    mx1[i] = __shfl_xor_sync(0xffffffffu, mx[i], 1);
                }
            }
            PIN;
            r.run<XWN, 6, false>(y2);
#pragma unroll
            for (int i = 0; i < 4; i++) {
                mx[i] = max2(mx[i], mx1[i]);
                mx1[i] = __shfl_xor_sync(0xffffffffu, mx[i], 2);
            }

            PIN;
            r.seek(21, bslot_l(21));
            r.run<BIG, 6, true>(y0);
            acc_fence(y2);
#pragma unroll
            for (int c = 0; c < 10; c++) hi[c] = movm(pack2(y2[4 * c + 2], y2[4 * c + 3]));
            constexpr float SCL = 0.18898223650461362f * 1.4426950408889634f;
            float e0[8], e1[8], sm[8], sm1[8];
#pragma unroll
            for (int i = 0; i < 8; i++) {
                const uint32_t m2 = max2(mx[i >> 1], mx1[i >> 1]);
                sm[i] = ((i & 1) ? bf_hi(m2) : bf_lo(m2)) * -SCL;
            }
            PIN;
            r.run<BIG, 6, false>(y0);
#pragma unroll
            for (int c = 10; c < 14; c++) hi[c] = movm(pack2(y2[4 * c + 2], y2[4 * c + 3]));
#pragma unroll
            for (int c = 0; c < 4; c++) lo[c] = movm(pack2(y2[4 * c], y2[4 * c + 1]));
#pragma unroll
            for (int i = 0; i < 8; i++) e0[i] = ex2(fmaf(bf_lo(pr[i]), SCL, sm[i]));
            PIN;
            r.run<BIG, 6, false>(y0);
            publish(hi, 0, 10);
#pragma unroll
            for (int i = 0; i < 8; i++) e1[i] = ex2(fmaf(bf_hi(pr[i]), SCL, sm[i]));
            PIN;
            r.run<BIG, 6, false>(y0);
            publish(hi, 10, 14);
            warp_arrive(base + BAR_HALO + 8);
#pragma unroll
            for (int i = 0; i < 8; i++) {
                sm[i] = e0[i] + e1[i];
                sm1[i] = __shfl_xor_sync(0xffffffffu, sm[i], 1);
            }
            PIN;
            r.run<BIG, 6, false>(y0);
#pragma unroll
            for (int c = 4; c < 14; c++) lo[c] = movm(pack2(y2[4 * c], y2[4 * c + 1]));
            PIN;
            r.run<BIG, 6, false>(y0);
#pragma unroll
            for (int i = 0; i < 8; i++) {
                sm[i] += sm1[i];
                sm1[i] = __shfl_xor_sync(0xffffffffu, sm[i], 2);
            }
#pragma unroll
            for (int t = 0; t < 8; t++) {
                const int c = tile_of(t);
                const bool shared = (t & 3) == 2;
                m1[t][0] = shared ? dup(lo[c], r.zero) : lo[c];
                m1[t][1] = lo[c + 1];
                m1[t][2] = shared ? dup(hi[c], r.zero) : hi[c];
                m1[t][3] = hi[c + 1];
                m0[t][0] = dup(m1[t][0], r.zero);
                m0[t][1] = dup(lo[c + 1], 2 * r.zero);
            }
            PIN;
            r.run<BIG, 6, false>(y0);
            mbar_wait(base + BAR_HALO + 8, 0);
            const uint32_t vin = warp ? hin : hin + 8 * HSLOT;
            fetch(vin, 0, 2);
#pragma unroll
            for (int i = 0; i < 8; i++) {
                const float inv = rcp(sm[i] + sm1[i]);
                pr[i] = pack2(e0[i] * inv, e1[i] * inv);
            }
            PIN;
            r.run<BIG, 6, false>(y0);
            fetch(vin, 1, 2);
            uint32_t pb[8][2];
#pragma unroll
            for (int t = 0; t < 8; t++) {
                pb[t][t & 1] = band(pr[t], curmask);
                pb[t][1 - (t & 1)] = band(pr[t], ~curmask);
            }
            r.pin();
            r.take_turn();
            float o[2][8][4];
#pragma unroll
            for (int i = 0; i < 16; i++) {
                const int b = 1 - (i >> 3), t = i & 7;
                float (&d)[4] = o[b][t];
                d[0] = d[1] = d[2] = d[3] = 0.f;
                mma16816(d, b ? m1[t] : m0[t], pb[(t & 6) + b][0], pb[(t & 6) + b][1]);
            }
            r.pin();
            r.run<BIG, 6, false>(y0, false);
            uint8_t* odst = sc->o + (size_t)mt * 7 * SLOT + ns * (14 * 2048) + warp * 256 + lane * 4;
#pragma unroll
            for (int hp = 0; hp < 2; hp++) {
#pragma unroll
                for (int b = 0; b < 2; b++) {
                    const float (&u)[8][4] = o[b];
                    const int t = 4 * hp;
                    uint32_t* w = p + 14 * hp + b;
                    w[0] = pack2(u[t][0], u[t][1]);
                    w[2] = pack2(u[t][2], u[t][3]);
                    w[4] = pack2(u[t + 1][0], u[t + 1][1]);
                    w[6] = pack2(g < 4 ? u[t + 1][2] : u[t + 2][0], g < 4 ? u[t + 1][3] : u[t + 2][1]);
                    w[8] = pack2(u[t + 2][2], u[t + 2][3]);
                    w[10] = pack2(u[t + 3][0], u[t + 3][1]);
                    w[12] = pack2(u[t + 3][2], u[t + 3][3]);
                }
            }
#pragma unroll
            for (int i = 0; i < 28; i++) {
                if (i && i % O_SLICE == 0) r.run<BIG, 6, false>(y0);
                stg1(odst + (i >> 1) * 2048 + (i & 1) * 128, p[i]);
            }
            warp_arrive(base + BAR_RDY + 16);

#pragma unroll 1
            for (int i = 30 + 27 / O_SLICE; i <= LLAST + 1 - TURN; i++) r.run<BIG, 6, false>(y0, true, i <= LLAST - TURN);
            const uint32_t tag = lds1(base + TAG);
            if (mbar_test(base + BAR_PART + wg * 8, 0)) {
#pragma unroll
                for (int i = 0; i < 7; i++) ld_tagged(part + i * 4096, p[4 * i], p[4 * i + 1], p[4 * i + 2], p[4 * i + 3]);
            } else {
                p[0] = ~tag;
            }
            r.seek(LLAST + 2 - TURN, bslot_l(LLAST + 2 - TURN));
#pragma unroll
            for (int i = 1; i < TURN; i++) r.run<BIG, 6, false, 1, true>(y0, false, i == TURN - 1, i < TURN - 1);
#pragma unroll 1
            for (int n = 0; n < SPIN_LIMIT; n++) {
                uint32_t stale = 0;
#pragma unroll
                for (int i = 0; i < 28; i += 2) stale |= p[i] ^ tag;
                if (__all_sync(0xffffffffu, !(stale & 1))) break;
                mbar_wait(base + BAR_PART + wg * 8, 0);
#pragma unroll
                for (int i = 0; i < 7; i++) ld_tagged(part + i * 4096, p[4 * i], p[4 * i + 1], p[4 * i + 2], p[4 * i + 3]);
            }
            wait_released(LLAST - 6);
            asm volatile("wgmma.wait_group.sync.aligned 0;" ::: "memory");
            acc_fence(y0);
            const uint32_t slab = base + (wg ? HALO : ((LLAST - 6) % NA) * SLOT) + (warp & 3) * WSLOT;
            store_out([&](int i) { return add2(pack2(y0[2 * i], y0[2 * i + 1]), p[i]); }, lane, slab, &maps.m[M_OUTB], 448 + col, mt * 128 + warp * 16);
        }
    }
}

typedef CUresult (*EncodeFn)(CUtensorMap*, CUtensorMapDataType, cuuint32_t, void*, const cuuint64_t*, const cuuint64_t*,
                             const cuuint32_t*, const cuuint32_t*, CUtensorMapInterleave, CUtensorMapSwizzle,
                             CUtensorMapL2promotion, CUtensorMapFloatOOBfill);

struct Dim { uint64_t size, stride; uint32_t box; };
void encode(EncodeFn fn, CUtensorMap* m, const void* ptr, CUtensorMapSwizzle sw, Dim d0, Dim d1, Dim d2 = {0, 0, 0}, Dim d3 = {0, 0, 0}) {
    const cuuint64_t dims[4] = {d0.size, d1.size, d2.size, d3.size};
    const cuuint64_t strides[3] = {d1.stride, d2.stride, d3.stride};
    const cuuint32_t box[4] = {d0.box, d1.box, d2.box, d3.box};
    const cuuint32_t es[4] = {1, 1, 1, 1};
    fn(m, CU_TENSOR_MAP_DATA_TYPE_BFLOAT16, d3.size ? 4 : d2.size ? 3 : 2, const_cast<void*>(ptr), dims, strides, box, es,
       CU_TENSOR_MAP_INTERLEAVE_NONE, sw, CU_TENSOR_MAP_L2_PROMOTION_L2_128B, CU_TENSOR_MAP_FLOAT_OOB_FILL_NONE);
}

}

extern "C" void kernel_launch(void* const* d_in, const int* in_sizes, int n_in, void* d_out, int out_size) {
    (void)in_sizes; (void)n_in; (void)out_size;
    void* fnp = nullptr;
    cudaDriverEntryPointQueryResult st;
    cudaGetDriverEntryPoint("cuTensorMapEncodeTiled", &fnp, cudaEnableDefault, &st);
    EncodeFn fn = (EncodeFn)fnp;
    void* scratch = nullptr;
    cudaGetSymbolAddress(&scratch, g_scratch);
    int dev = 0, sms = 0;
    cudaGetDevice(&dev);
    cudaDeviceGetAttribute(&sms, cudaDevAttrMultiProcessorCount, dev);
    auto kernel = sms == 132 ? fused_kernel<true> : fused_kernel<false>;
    cudaFuncSetAttribute(kernel, cudaFuncAttributeMaxDynamicSharedMemorySize, SMEM_BYTES);

    const CUtensorMapSwizzle S128 = CU_TENSOR_MAP_SWIZZLE_128B, S0 = CU_TENSOR_MAP_SWIZZLE_NONE;
    const Dim one = {1, 16, 1};
    Maps maps;
    encode(fn, &maps.m[M_XA], d_in[0], S128, {896, 2, 64}, {1024, 1792, 128}, one, one);
    encode(fn, &maps.m[M_WQK], d_in[1], S128, {112, 2, 64}, {448, 2688, 32}, {3, 896, 2}, {4, 224, 1});
    encode(fn, &maps.m[M_WV], d_in[1], S128, {112, 2, 64}, {448, 2688, 64}, one, {12, 224, 1});
    encode(fn, &maps.m[M_XH], d_in[0], S128, {448, 2, 64}, {128, 1792, 8}, {8, 128 * 1792, 8}, {2, 896, 2});
    encode(fn, &maps.m[M_WO], d_in[2], S128, {112, 2, 64}, {448, 896, 64}, one, {4, 224, 1});
    encode(fn, &maps.m[M_XB], d_in[3], S128, {448, 2, 64}, {1024, 896, 64}, {2, 896 * 1024, 2}, one);
    encode(fn, &maps.m[M_CR], d_in[4], S128, {2048, 2, 64}, {2048, 4096, 128});
    encode(fn, &maps.m[M_CI], d_in[5], S128, {2048, 2, 64}, {2048, 4096, 128});
    encode(fn, &maps.m[M_WR], d_in[6], S128, {448, 2, 64}, {448, 896, 112}, one, one);
    encode(fn, &maps.m[M_WI], d_in[7], S128, {448, 2, 64}, {448, 896, 112});
    encode(fn, &maps.m[M_OUTA], d_out, S0, {1792, 2, 112}, {1024, 3584, 8});
    encode(fn, &maps.m[M_OUTB], d_out, S0, {896, 2, 112}, {2048, 1792, 8});

    for (int sm = 0; sm < 132; sm++) {
        const int tpc = sm >> 1;
        const int gpc = tpc < 32 ? tpc & 7 : tpc < 60 ? (tpc - 32) % 7 + 1 : 0;
        const int pos = tpc < 32 ? tpc >> 3 : tpc < 60 ? (tpc - 32) / 7 + 4 : tpc - 56;
        const bool H = sm >= 128;
        const int L = gpc & 1, mt = H ? 0 : (gpc >> 1) * 4 + (pos >> 1);
        const int ns = (pos & 1) * 2 + (sm & 1), id = H ? sm : gpc * 16 + pos * 2 + (sm & 1);
        Role& r = maps.role[sm];
        r.a1 = H ? 120 : L ? (mt & 7) * 128 : mt * 64;
        r.b1 = ns * 112;
        r.b3 = H ? 4 + ns : L ? ns : 0;
        r.bits = (L ? (mt >> 3) * 448 : 0) | (uint32_t)((H ? 2 : L) * 128) << 9 | mt << 18 | ns << 22 | (uint32_t)id << 24;
    }

    kernel<<<132, 384, SMEM_BYTES>>>((Scratch*)scratch, maps);
}
```

```cpp
#include <cuda.h>
#include <cuda_bf16.h>
#include <cuda_runtime.h>
#include <stdint.h>

namespace {

constexpr uint32_t SLOT = 16384;
constexpr int NA = 7;
constexpr uint32_t BRING = NA * SLOT;
constexpr uint32_t HALO = BRING + 6 * SLOT;
constexpr uint32_t HSLOT = 1792;
constexpr uint32_t WSLOT = 3584;
constexpr uint32_t BLOB = 14336;
constexpr uint32_t BARS = 14 * SLOT;
constexpr uint32_t BAR_FULL = BARS;
constexpr uint32_t BAR_EMPTY = BARS + 64;
constexpr uint32_t BAR_RDY = BARS + 128;
constexpr uint32_t BAR_DEP = BARS + 168;
constexpr uint32_t BAR_HALO = BARS + 192;
constexpr uint32_t BAR_PART = BARS + 208;
constexpr uint32_t TAG = BARS + 224;
constexpr uint32_t HSPARE = BARS + 256 + 1024;
constexpr uint32_t SMEM_BYTES = HSPARE + HSLOT;
constexpr uint32_t base = 1024;
constexpr int SPIN_LIMIT = 1 << 16;

#define E_EXTRA 0
#define HALO_K_AT 10
#define HALO_V_AT 19
#define O_SLICE 4
#define B_SLICE 4
#define LEAD 3
#define TURN 4
#define PIN r.pin()
#define PACE 450
#define MAPPING 2
constexpr int NBE = 13 + E_EXTRA;
constexpr int POUT = 33 + NBE;
constexpr int ELAST = POUT + 6;
constexpr int LLAST = 52 - E_EXTRA;

enum { M_XB, M_XA, M_XH, M_WR, M_WQK, M_WV, M_WO, M_WI, M_CR, M_CI, M_OUTA, M_OUTB, M_COUNT };
struct __align__(64) Maps { CUtensorMap m[M_COUNT]; };

constexpr int CNT_A = 0;
constexpr int CNT_B = 8;
constexpr int CNT_O = 16;
constexpr int CNT_P = 32;
constexpr int CNT_COUNT = 96;

struct Scratch {
    uint8_t ab[64 * 4 * BLOB];
    uint8_t o[16 * 7 * SLOT];
    uint8_t part[64 * 2 * BLOB];
    uint8_t halo[64 * 2 * 2048];
    unsigned cnt[CNT_COUNT * 32];
    unsigned epoch[132 * 4 * 8];
};
__device__ __align__(1024) Scratch g_scratch;

__device__ __forceinline__ unsigned clk32() { unsigned c; asm volatile("mov.u32 %0, %%clock;" : "=r"(c)); return c; }

#define PROF(idx)

__device__ __forceinline__ void mbar_init(uint32_t bar, uint32_t cnt) {
    asm volatile("mbarrier.init.shared::cta.b64 [%0], %1;" ::"r"(bar), "r"(cnt) : "memory");
}
__device__ __forceinline__ void mbar_expect(uint32_t bar, uint32_t bytes) {
    asm volatile("mbarrier.arrive.expect_tx.shared::cta.b64 _, [%0], %1;" ::"r"(bar), "r"(bytes) : "memory");
}
__device__ __forceinline__ void mbar_arrive(uint32_t bar) {
    asm volatile("mbarrier.arrive.shared::cta.b64 _, [%0];" ::"r"(bar) : "memory");
}
__device__ __forceinline__ bool mbar_try(uint32_t bar, uint32_t parity) {
    uint32_t ok;
    asm volatile("{\n.reg .pred p;\nmbarrier.try_wait.parity.shared::cta.b64 p, [%1], %2;\nselp.u32 %0, 1, 0, p;\n}\n"
                 : "=r"(ok) : "r"(bar), "r"(parity) : "memory");
    return ok;
}
__device__ __forceinline__ bool mbar_test(uint32_t bar, uint32_t parity) {
    uint32_t ok;
    asm volatile("{\n.reg .pred p;\nmbarrier.test_wait.parity.shared::cta.b64 p, [%1], %2;\nselp.u32 %0, 1, 0, p;\n}\n"
                 : "=r"(ok) : "r"(bar), "r"(parity) : "memory");
    return ok;
}
__device__ __forceinline__ void mbar_wait(uint32_t bar, uint32_t parity) {
#pragma unroll 1
    for (int n = 0; n < SPIN_LIMIT; n++)
        if (mbar_try(bar, parity)) break;
}
__device__ __forceinline__ bool elect() {
    uint32_t p;
    asm volatile("{\n.reg .pred p;\nelect.sync _|p, 0xffffffff;\nselp.u32 %0, 1, 0, p;\n}\n" : "=r"(p));
    return p;
}
__device__ __forceinline__ void nb_sync(int id, int n) { asm volatile("bar.sync %0, %1;" ::"r"(id), "r"(n) : "memory"); }
__device__ __forceinline__ void nb_arrive(int id, int n) { asm volatile("bar.arrive %0, %1;" ::"r"(id), "r"(n) : "memory"); }
__device__ __forceinline__ void warp_arrive(uint32_t bar) {
    __syncwarp();
    if (elect()) mbar_arrive(bar);
}
__device__ __forceinline__ uint32_t band(uint32_t x, uint32_t m) {
    uint32_t r;
    asm volatile("and.b32 %0, %1, %2;" : "=r"(r) : "r"(x), "r"(m));
    return r;
}
__device__ __forceinline__ uint32_t dup(uint32_t x, uint32_t zero) {
    uint32_t r;
    asm volatile("xor.b32 %0, %1, %2;" : "=r"(r) : "r"(x), "r"(zero));
    return r;
}

__device__ __forceinline__ void tma_ld2(uint32_t dst, const CUtensorMap* m, int c0, int c1, uint32_t bar) {
    asm volatile("cp.async.bulk.tensor.2d.shared::cluster.global.mbarrier::complete_tx::bytes [%0], [%1, {%3, %4}], [%2];"
                 ::"r"(dst), "l"(m), "r"(bar), "r"(c0), "r"(c1) : "memory");
}
__device__ __forceinline__ void tma_ld4(uint32_t dst, const CUtensorMap* m, int c0, int c1, int c2, int c3, uint32_t bar) {
    asm volatile("cp.async.bulk.tensor.4d.shared::cluster.global.mbarrier::complete_tx::bytes [%0], [%1, {%3, %4, %5, %6}], [%2];"
                 ::"r"(dst), "l"(m), "r"(bar), "r"(c0), "r"(c1), "r"(c2), "r"(c3) : "memory");
}
__device__ __forceinline__ void bulk_ld(uint32_t dst, const void* src, uint32_t bytes, uint32_t bar) {
    asm volatile("cp.async.bulk.shared::cluster.global.mbarrier::complete_tx::bytes [%0], [%1], %2, [%3];"
                 ::"r"(dst), "l"(src), "r"(bytes), "r"(bar) : "memory");
}
__device__ __forceinline__ void tma_st2(const CUtensorMap* m, int c0, int c1, uint32_t src) {
    asm volatile("cp.async.bulk.tensor.2d.global.shared::cta.bulk_group [%0, {%1, %2}], [%3];"
                 ::"l"(m), "r"(c0), "r"(c1), "r"(src) : "memory");
}
__device__ __forceinline__ void bulk_commit() { asm volatile("cp.async.bulk.commit_group;" ::: "memory"); }
__device__ __forceinline__ void bulk_wait_read() { asm volatile("cp.async.bulk.wait_group.read 0;" ::: "memory"); }
__device__ __forceinline__ void fence_async_smem() { asm volatile("fence.proxy.async.shared::cta;" ::: "memory"); }
__device__ __forceinline__ void fence_async_global() { asm volatile("fence.proxy.async.global;" ::: "memory"); }

__device__ __forceinline__ void signal(Scratch* sc, int idx) {
    asm volatile("fence.proxy.async;\nred.relaxed.gpu.global.add.u32 [%0], 1;" ::"l"(&sc->cnt[idx * 32]) : "memory");
}
__device__ __forceinline__ unsigned peek(const unsigned* p) {
    unsigned v;
    asm volatile("ld.relaxed.gpu.global.u32 %0, [%1];" : "=r"(v) : "l"(p) : "memory");
    return v;
}
__device__ __forceinline__ void await(Scratch* sc, int idx, unsigned target) {
    const unsigned* p = &sc->cnt[idx * 32];
#pragma unroll 1
    for (int n = 0; n < SPIN_LIMIT; n++)
        if ((int)(peek(p) - target) >= 0) break;
    asm volatile("fence.acquire.gpu;" ::: "memory");
}
__device__ __forceinline__ void wait_dep(int k) {
    mbar_wait(base + BAR_DEP + k * 8, 0);
    fence_async_global();
}

#define WG_REGS                                                                                                     \
    "{%0,%1,%2,%3,%4,%5,%6,%7,%8,%9,%10,%11,%12,%13,%14,%15,%16,%17,%18,%19,%20,%21,%22,%23,%24,%25,%26,%27,"       \
    "%28,%29,%30,%31,%32,%33,%34,%35,%36,%37,%38,%39,%40,%41,%42,%43,%44,%45,%46,%47,%48,%49,%50,%51,%52,%53,%54,%55}"
#define WG_OPS(C)                                                                                                   \
    C(d[0]), C(d[1]), C(d[2]), C(d[3]), C(d[4]), C(d[5]), C(d[6]), C(d[7]), C(d[8]), C(d[9]), C(d[10]), C(d[11]),   \
    C(d[12]), C(d[13]), C(d[14]), C(d[15]), C(d[16]), C(d[17]), C(d[18]), C(d[19]), C(d[20]), C(d[21]), C(d[22]),   \
    C(d[23]), C(d[24]), C(d[25]), C(d[26]), C(d[27]), C(d[28]), C(d[29]), C(d[30]), C(d[31]), C(d[32]), C(d[33]),   \
    C(d[34]), C(d[35]), C(d[36]), C(d[37]), C(d[38]), C(d[39]), C(d[40]), C(d[41]), C(d[42]), C(d[43]), C(d[44]),   \
    C(d[45]), C(d[46]), C(d[47]), C(d[48]), C(d[49]), C(d[50]), C(d[51]), C(d[52]), C(d[53]), C(d[54]), C(d[55])

template <int TA, int TB, int SB, bool INIT, uint32_t AH, uint32_t BH>
__device__ __forceinline__ void wgmma112(float (&d)[56], uint32_t alo, uint32_t blo) {
    if (INIT) {
        asm volatile("{\n.reg .pred p;\n.reg .b64 da, db;\nsetp.ne.b32 p, 0, 0;\nmov.b64 da, {%56, %61};\nmov.b64 db, {%57, %62};\n"
                     "wgmma.mma_async.sync.aligned.m64n112k16.f32.bf16.bf16 " WG_REGS ", da, db, p, 1, %59, %60, %58;\n}\n"
                     : WG_OPS("=f") : "r"(alo), "r"(blo), "n"(TB), "n"(SB), "n"(TA), "n"(AH), "n"(BH));
    } else {
        asm volatile("{\n.reg .pred p;\n.reg .b64 da, db;\nsetp.ne.b32 p, 1, 0;\nmov.b64 da, {%56, %61};\nmov.b64 db, {%57, %62};\n"
                     "wgmma.mma_async.sync.aligned.m64n112k16.f32.bf16.bf16 " WG_REGS ", da, db, p, 1, %59, %60, %58;\n}\n"
                     : WG_OPS("+f") : "r"(alo), "r"(blo), "n"(TB), "n"(SB), "n"(TA), "n"(AH), "n"(BH));
    }
}
__device__ __forceinline__ void acc_fence(float (&d)[56]) {
#pragma unroll
    for (int i = 0; i < 56; i++) asm volatile("" : "+f"(d[i])::"memory");
}

__device__ __forceinline__ uint32_t pack2(float lo, float hi) {
    uint32_t r;
    asm volatile("cvt.rn.bf16x2.f32 %0, %1, %2;" : "=r"(r) : "f"(hi), "f"(lo));
    return r;
}
__device__ __forceinline__ uint32_t movm(uint32_t a) {
    uint32_t r;
    asm volatile("movmatrix.sync.aligned.m8n8.trans.b16 %0, %1;" : "=r"(r) : "r"(a));
    return r;
}
__device__ __forceinline__ void stsm4(uint32_t addr, uint32_t a, uint32_t b, uint32_t c, uint32_t d) {
    asm volatile("stmatrix.sync.aligned.m8n8.x4.shared.b16 [%0], {%1,%2,%3,%4};" ::"r"(addr), "r"(a), "r"(b), "r"(c), "r"(d) : "memory");
}
__device__ __forceinline__ void sts1(uint32_t addr, uint32_t a) { asm volatile("st.shared.b32 [%0], %1;" ::"r"(addr), "r"(a) : "memory"); }
__device__ __forceinline__ uint32_t lds1(uint32_t addr) {
    uint32_t a;
    asm volatile("ld.shared.b32 %0, [%1];" : "=r"(a) : "r"(addr) : "memory");
    return a;
}
__device__ __forceinline__ void stg1(uint8_t* p, uint32_t a) { asm volatile("st.global.b32 [%0], %1;" ::"l"(p), "r"(a) : "memory"); }
__device__ __forceinline__ void st_part(uint8_t* p, const uint32_t* v, uint32_t parity) {
    asm volatile("{\n.reg .b64 x, y;\nmov.b64 x, {%1, %2};\nmov.b64 y, {%3, %4};\nst.relaxed.gpu.global.v2.b64 [%0], {x, y};\n}\n"
                 ::"l"(p), "r"((v[0] & ~1u) | parity), "r"(v[1]), "r"((v[2] & ~1u) | parity), "r"(v[3]) : "memory");
}
__device__ __forceinline__ void mma16816(float (&d)[4], const uint32_t (&a)[4], uint32_t b0, uint32_t b1) {
    asm volatile("mma.sync.aligned.m16n8k16.row.col.f32.bf16.bf16.f32 {%0,%1,%2,%3}, {%4,%5,%6,%7}, {%8,%9}, {%0,%1,%2,%3};"
                 : "+f"(d[0]), "+f"(d[1]), "+f"(d[2]), "+f"(d[3]) : "r"(a[0]), "r"(a[1]), "r"(a[2]), "r"(a[3]), "r"(b0), "r"(b1));
}
__device__ __forceinline__ uint32_t add2(uint32_t a, uint32_t b) {
    uint32_t r;
    asm("add.rn.bf16x2 %0, %1, %2;" : "=r"(r) : "r"(a), "r"(b));
    return r;
}
__device__ __forceinline__ uint32_t max2(uint32_t a, uint32_t b) {
    uint32_t r;
    asm("max.bf16x2 %0, %1, %2;" : "=r"(r) : "r"(a), "r"(b));
    return r;
}
__device__ __forceinline__ void ld_tagged(const uint8_t* p, uint32_t& a, uint32_t& ta, uint32_t& b, uint32_t& tb) {
    asm volatile("{\n.reg .b64 x, y;\nld.relaxed.gpu.global.v2.b64 {x, y}, [%4];\nmov.b64 {%0, %1}, x;\nmov.b64 {%2, %3}, y;\n}\n"
                 : "=r"(a), "=r"(ta), "=r"(b), "=r"(tb) : "l"(p) : "memory");
}
__device__ __forceinline__ float bf_lo(uint32_t v) { return __uint_as_float(v << 16); }
__device__ __forceinline__ float bf_hi(uint32_t v) { return __uint_as_float(v & 0xFFFF0000u); }
__device__ __forceinline__ float rcp(float x) { float r; asm("rcp.approx.ftz.f32 %0, %1;" : "=f"(r) : "f"(x)); return r; }
__device__ __forceinline__ float ex2(float x) { float r; asm volatile("ex2.approx.ftz.f32 %0, %1;" : "=f"(r) : "f"(x)); return r; }

__device__ __forceinline__ uint32_t full_bar(int stage) { return base + BAR_FULL + (stage & 7) * 8; }
__device__ __forceinline__ void wait_released(int j) { mbar_wait(base + BAR_EMPTY + (j & 7) * 8, (j >> 3) & 1); }

template <int V>
struct Int { static constexpr int value = V; };

__host__ __device__ constexpr int bslot_e(int i) { return (i < 2 || i >= 14) ? (i + 5) % 7 : (i + 1) % 5; }
__host__ __device__ constexpr int bslot_l(int i) { return i % 6; }

template <uint32_t OFF>
struct Feed {
    int stage;
    uint32_t dst;
    __device__ __forceinline__ void seek(int i, int slot) { stage = i; dst = base + OFF + slot * SLOT; }
    template <int N>
    __device__ __forceinline__ uint32_t acquire() { wait_released(stage - N); return full_bar(stage); }
    template <int N>
    __device__ __forceinline__ void next() {
        stage++;
        dst += SLOT;
        if (dst == base + OFF + N * SLOT) dst = base + OFF;
    }
};
__device__ __forceinline__ int skip_own(int n, int mt) { return n == mt ? 15 : n; }

struct Desc { uint32_t lo, hi; };
__host__ __device__ constexpr Desc desc_const(uint32_t lbo, uint32_t sbo, uint32_t mode) { return {(lbo >> 4) << 16, (sbo >> 4) | (mode << 30)}; }
constexpr Desc D_K128 = desc_const(16, 1024, 1);
constexpr Desc D_N128 = desc_const(8192, 1024, 1);
constexpr Desc D_BLOB = desc_const(128, 256, 0);
constexpr Desc D_OT = desc_const(2048, 128, 0);

enum Kind { XW, XWN, QK, BIG, OUT };

struct Ring {
    int stage;
    uint32_t a, b;
    uint32_t wg;
    uint32_t zero;
    __device__ __forceinline__ void seek(int i, int bslot) {
        stage = i;
        a = (base + (i % NA) * SLOT) >> 4;
        b = (base + BRING + bslot * SLOT) >> 4;
    }
    __device__ __forceinline__ void wait() { mbar_wait(full_bar(stage), (stage >> 3) & 1); }
    __device__ __forceinline__ void take_turn() { nb_sync(1 + wg, 256); }
    __device__ __forceinline__ void pin() {
        uint32_t n = 0;
#pragma unroll 1
        do {
            asm volatile("pmevent 7;" ::: "memory");
        } while (n++ < zero);
    }
    template <Kind K, int NBS, bool INIT, int SB = 1, bool TAIL = false>
    __device__ __forceinline__ void run(float (&d)[56], float (&e)[56], bool first = true, bool last = true, bool more = true) {
        if (first) take_turn();
        asm volatile("wgmma.fence.sync.aligned;" ::: "memory");
        if (K == QK) {
            const uint32_t da = D_K128.lo + (base >> 4) + (stage >> 1) * (SLOT >> 4) + (stage & 1) * 4 + wg * 512, db = D_N128.lo + b;
            wgmma112<0, 1, 1, INIT, D_K128.hi, D_N128.hi>(d, da, db);
            wgmma112<0, 1, 1, INIT, D_K128.hi, D_N128.hi>(e, da, db + 256);
            wgmma112<0, 1, 1, false, D_K128.hi, D_N128.hi>(d, da + 2, db + 128);
            wgmma112<0, 1, 1, false, D_K128.hi, D_N128.hi>(e, da + 2, db + 384);
        } else {
            constexpr int TA = K == OUT, TB = K != XW;
            constexpr uint32_t sa = K == OUT ? 256 : 2, sb = K == XW ? 2 : K == BIG ? 224 : 128;
            constexpr Desc A = K == OUT ? D_OT : D_K128, B = K == XW ? D_K128 : K == BIG ? D_BLOB : D_N128;
            const uint32_t da = A.lo + a + wg * (K == OUT ? 64 : 512), db = B.lo + b;
            wgmma112<TA, TB, SB, INIT, A.hi, B.hi>(d, da, db);
            wgmma112<TA, TB, SB, false, A.hi, B.hi>(d, da + sa, db + sb);
            wgmma112<TA, TB, SB, false, A.hi, B.hi>(d, da + 2 * sa, db + 2 * sb);
            wgmma112<TA, TB, SB, false, A.hi, B.hi>(d, da + 3 * sa, db + 3 * sb);
        }
        asm volatile("wgmma.commit_group.sync.aligned;" ::: "memory");
        if (last) nb_arrive(2 - wg, 256);
        if (!TAIL) asm volatile("wgmma.wait_group.sync.aligned 1;" ::: "memory");
        if (!TAIL && stage > 0 && elect()) mbar_arrive(base + BAR_EMPTY + ((stage - 1) & 7) * 8);
        stage++;
        a += SLOT >> 4;
        if (a == (base + NA * SLOT) >> 4) a = base >> 4;
        b += SLOT >> 4;
        if (b == (base + BRING + NBS * SLOT) >> 4) b = (base + BRING) >> 4;
        if (more) wait();
    }
    template <Kind K, int NBS, bool INIT, int SB = 1, bool TAIL = false>
    __device__ __forceinline__ void run(float (&d)[56], bool first = true, bool last = true, bool more = true) {
        run<K, NBS, INIT, SB, TAIL>(d, d, first, last, more);
    }
};

__device__ __forceinline__ void pack_all(const float (&d)[56], uint32_t (&p)[28]) {
#pragma unroll
    for (int i = 0; i < 28; i++) p[i] = pack2(d[2 * i], d[2 * i + 1]);
}
template <int I0, int I1>
__device__ __forceinline__ void store_frags(uint8_t* dst, const uint32_t (&p)[28]) {
#pragma unroll
    for (int i = I0; i < I1; i++) stg1(dst + i * 128, p[i]);
}
template <int I0, int I1>
__device__ __forceinline__ void stage_frags(uint32_t lane_addr, const uint32_t (&p)[28]) {
#pragma unroll
    for (int i = I0; i < I1; i += 4) stsm4(lane_addr + i * 128, p[i], p[i + 1], p[i + 2], p[i + 3]);
}
template <class F>
__device__ __forceinline__ void store_out(F frag, int lane, uint32_t slab, const CUtensorMap* m, int c0, int c1) {
    const bool swap = lane & 16;
    const uint32_t addr = slab + (lane & 7) * 224 + ((lane >> 3) ^ ((lane >> 2) & 1)) * 16;
#pragma unroll
    for (int h = 0; h < 2; h++) {
#pragma unroll
        for (int c = 0; c < 14; c += 4) {
            const uint32_t t0 = frag(2 * c + h), t1 = frag(2 * c + 2 + h);
            if (c < 12) {
                const uint32_t t2 = frag(2 * c + 4 + h), t3 = frag(2 * c + 6 + h);
                stsm4(addr + h * 1792 + c * 16, swap ? t1 : t0, swap ? t0 : t1, swap ? t3 : t2, swap ? t2 : t3);
            } else {
                asm volatile("stmatrix.sync.aligned.m8n8.x2.shared.b16 [%0], {%1,%2};" ::"r"(addr + h * 1792 + c * 16), "r"(swap ? t1 : t0), "r"(swap ? t0 : t1) : "memory");
            }
        }
        fence_async_smem();
        __syncwarp();
        if (elect()) tma_st2(m, c0, c1 + 8 * h, slab + h * 1792);
    }
    if (elect()) {
        bulk_commit();
        bulk_wait_read();
    }
}
__host__ __device__ constexpr int tile_of(int t) { return 7 * (t >> 2) + 3 * ((t >> 1) & 1) + 2 * (t & 1); }

struct Role {
    bool H;
    int L, mt, ns, id;
    int kind, a0, a1, b3;
};
template <bool BY_SM>
__device__ __forceinline__ Role decode_role() {
    uint32_t sm;
    if (BY_SM) asm volatile("mov.u32 %0, %%smid;" : "=r"(sm));
    else asm volatile("mov.u32 %0, %%ctaid.x;" : "=r"(sm));
    const int tpc = sm >> 1, q2 = ((tpc - 32) * 37) >> 8;
    const int gpc = tpc < 32 ? tpc & 7 : tpc < 60 ? tpc - 31 - 7 * q2 : 0;
    const int pos = tpc < 32 ? tpc >> 3 : tpc < 60 ? q2 + 4 : tpc - 56;
    Role r;
    r.H = sm >= 128;
    r.L = gpc & 1;
    r.mt = (gpc >> 1) * 4 + (pos >> 1);
    r.ns = (pos & 1) * 2 + (sm & 1);
    r.id = r.H ? sm : gpc * 16 + pos * 2 + (sm & 1);
    r.kind = r.H ? 2 : r.L;
    r.a0 = r.L ? (r.mt >> 3) * 448 : 0;
    r.a1 = r.L ? (r.mt & 7) * 128 : r.H ? 120 : r.mt * 64;
    r.b3 = r.H ? 4 + r.ns : r.L ? r.ns : 0;
    return r;
}

__device__ __forceinline__ void first_fill(const Maps& maps, const Role& r, int i) {
    const bool E = r.kind == 0;
    const CUtensorMap* ma = &maps.m[r.kind];
    const uint32_t bar = full_bar(i);
    const int k = (i * 64) >> r.L;
    const bool has_a = !(i & r.L), has_b = i < 7 - r.L;
    const uint32_t dst = base + BRING + (E ? (0x2104365u >> (4 * i)) & 7 : i) * SLOT;
    mbar_expect(bar, (has_a ? SLOT : 0) + (has_b ? (E ? BLOB : SLOT) : 0));
    if (has_a) tma_ld4(base + (i >> r.L) * SLOT, ma, r.a0 + k, r.a1, 0, 0, bar);
    if (has_b) {
        tma_ld4(dst, ma + 3, E ? k : 0, E ? r.ns * 112 : k, 0, r.b3, bar);
        if (!E) tma_ld4(dst + 8192, ma + 3, 64, k, 0, r.b3, bar);
        mbar_arrive(bar);
    }
}
static_assert(bslot_e(0) == 5 && bslot_e(1) == 6 && bslot_e(2) == 3 && bslot_e(3) == 4 && bslot_e(4) == 0 && bslot_e(6) == 2, "");

template <bool BY_SM>
__global__ void __launch_bounds__(384, 1) fused_kernel(Scratch* sc, const __grid_constant__ Maps maps) {
    const unsigned t_open = clk32();
    const int warp = __shfl_sync(0xffffffffu, threadIdx.x >> 5, 0);
    if (warp == 8) {
        if (elect()) {
#pragma unroll
            for (int i = 0; i < LEAD; i++) mbar_init(base + BAR_FULL + i * 8, 2);
            asm volatile("fence.mbarrier_init.release.cluster;" ::: "memory");
            const Role r = decode_role<BY_SM>();
#pragma unroll 1
            for (int i = 0; i < LEAD; i++) first_fill(maps, r, i);
        }
    }
    if (warp == 9) {
        if (elect()) {
#pragma unroll
            for (int i = 0; i < 8; i++) mbar_init(base + BAR_EMPTY + i * 8, 8);
            asm volatile("fence.mbarrier_init.release.cluster;" ::: "memory");
        }
    } else if (warp == 10) {
        if (elect()) {
#pragma unroll
            for (int i = 0; i < 5; i++) mbar_init(base + BAR_RDY + i * 8, i < 2 ? 4 : 8);
#pragma unroll
            for (int i = 0; i < 2; i++) mbar_init(base + BAR_HALO + i * 8, 9);
            asm volatile("fence.mbarrier_init.release.cluster;" ::: "memory");
        }
    } else if (warp == 11) {
        if (elect()) {
#pragma unroll
            for (int i = LEAD; i < 8; i++) mbar_init(base + BAR_FULL + i * 8, 2);
#pragma unroll
            for (int i = 0; i < 3; i++) mbar_init(base + BAR_DEP + i * 8, 1);
#pragma unroll
            for (int i = 0; i < 2; i++) mbar_init(base + BAR_PART + i * 8, 1);
            asm volatile("fence.mbarrier_init.release.cluster;" ::: "memory");
        }
    }
    __syncthreads();

    const Role role = decode_role<BY_SM>();
    int lane = threadIdx.x & 31;
    asm volatile("" : "+r"(lane));
    const bool roleH = role.H;
    const int roleL = role.L, mt = role.mt, ns = role.ns, bid = role.id;
    const int par = mt >> 3, blk = mt & 7, col = ns * 112;

    if (__builtin_expect(warp >= 8, 1)) {
        asm volatile("setmaxnreg.dec.sync.aligned.u32 56;");
#define PROF_FEED_A
#define PROF_FEED_B
        if (__builtin_expect(warp == 8, 1)) {
            if (elect()) {
                PROF(129);
#pragma unroll 1
                for (int i = LEAD; i < 7; i++) {
                    while (clk32() - t_open < i * PACE) {}
                    first_fill(maps, role, i);
                }
                PROF(134);
                Feed<0> f;
                const int row = mt * 128;
                auto c_run = [&](const CUtensorMap* m, int off, int n0, int n1) {
#pragma unroll 1
                    for (int n = n0; n < n1; n++) {
                        const uint32_t bar = f.acquire<NA>();
                        mbar_expect(bar, SLOT);
                        tma_ld2(f.dst, m, (off + skip_own(n, mt)) * 64, row, bar);
                        PROF_FEED_A;
                        f.next<NA>();
                    }
                };
                if (roleH) {
                } else if (!roleL) {
                    f.seek(14, 0);
                    mbar_wait(base + BAR_RDY, 0);
#pragma unroll 1
                    for (int i = 0; i < 4; i++) {
                        const uint32_t bar = f.acquire<NA>();
                        mbar_expect(bar, SLOT);
                        tma_ld2(f.dst, &maps.m[M_CR + (i >> 1)], ((i & 1) * 16 + mt) * 64, row, bar);
                        mbar_arrive(bar);
                        PROF_FEED_A;
                        f.next<NA>();
                    }
                    c_run(&maps.m[M_CR], 0, 0, 15);
                    c_run(&maps.m[M_CI], 0, 0, NBE);
                    wait_dep(2);
#pragma unroll 1
                    for (int i = 0; i < 7; i++) {
                        const uint32_t bar = f.acquire<NA>();
                        mbar_expect(bar, SLOT);
                        bulk_ld(f.dst, sc->o + (size_t)(mt * 7 + i) * SLOT, SLOT, bar);
                        PROF_FEED_A;
                        f.next<NA>();
                    }
                } else {
#pragma unroll 1
                    for (int i = 4; i < 7; i++) {
                        wait_released(2 * i - 8);
                        mbar_expect(full_bar(2 * i), SLOT);
                        tma_ld4(base + i * SLOT, &maps.m[M_XA], par * 448 + i * 64, blk * 128, 0, 0, full_bar(2 * i));
                    }
                    wait_released(HALO_K_AT);
                    mbar_arrive(base + BAR_DEP + 16);
                    f.seek(21, 0);
                    c_run(&maps.m[M_CR], 16, 0, 15);
                    c_run(&maps.m[M_CI], 16, 0, 15);
                    c_run(&maps.m[M_CI], 0, NBE, 15);
                }
            }
        } else if (warp == 11) {
            if (elect()) {
                Feed<BRING> f;
                auto blob_run = [&](auto nbs, int quarter, int n0, int n1) {
                    constexpr int N = decltype(nbs)::value;
                    const uint8_t* src = sc->ab + (size_t)(quarter * 64 + ns) * BLOB;
#pragma unroll 1
                    for (int n = n0; n < n1; n++) {
                        const uint32_t bar = f.template acquire<N>();
                        mbar_expect(bar, BLOB);
                        bulk_ld(f.dst, src + skip_own(n, mt) * (4 * BLOB), BLOB, bar);
                        PROF_FEED_B;
                        f.template next<N>();
                    }
                };
                auto w_run = [&](auto nbs, const CUtensorMap* m, int slice, bool no_a) {
                    constexpr int N = decltype(nbs)::value;
#pragma unroll 1
                    for (int i = 0; i < 7; i++) {
                        const uint32_t bar = f.template acquire<N>();
                        mbar_expect(bar, SLOT);
                        tma_ld4(f.dst, m, 0, i * 64, 0, slice, bar);
                        tma_ld4(f.dst + 8192, m, 64, i * 64, 0, slice, bar);
                        if (no_a) mbar_arrive(bar);
                        PROF_FEED_B;
                        f.template next<N>();
                    }
                };
                if (roleH) {
                    f.seek(7, 0);
                    w_run(Int<7>(), &maps.m[M_WV], 8 + ns, true);
                } else if (!roleL) {
                    f.seek(7, bslot_e(7));
#pragma unroll 1
                    for (int i = 0; i < 7; i++) {
                        const uint32_t bar = f.acquire<5>();
                        mbar_expect(bar, BLOB);
                        tma_ld2(f.dst, &maps.m[M_WI], i * 64, col, bar);
                        mbar_arrive(bar);
                        PROF_FEED_B;
                        f.next<5>();
                    }
                    f.seek(18, bslot_e(18));
                    wait_dep(0);
                    blob_run(Int<7>(), 0, 0, 15);
                    wait_dep(1);
                    blob_run(Int<7>(), 2, 0, NBE);
                    w_run(Int<7>(), &maps.m[M_WO], ns, false);
                } else {
                    f.seek(6, 0);
#pragma unroll 1
                    for (int i = 6; i < 14; i++) {
                        const uint32_t bar = f.acquire<6>();
                        mbar_expect(bar, SLOT);
                        tma_ld4(f.dst, &maps.m[M_WQK], 0, i * 32, 0, ns, bar);
                        tma_ld4(f.dst + 8192, &maps.m[M_WQK], 64, i * 32, 0, ns, bar);
                        if (i & 1) mbar_arrive(bar);
                        PROF_FEED_B;
                        f.next<6>();
                    }
                    w_run(Int<6>(), &maps.m[M_WV], 8 + ns, true);
                    wait_dep(0);
                    blob_run(Int<6>(), 1, 0, 15);
                    wait_dep(1);
                    blob_run(Int<6>(), 3, 0, 15);
                    blob_run(Int<6>(), 2, NBE, 15);
                }
            }
        } else if (roleH) {
            if (elect()) {
                wait_released(warp == 9 ? 0 : 7);
#pragma unroll 1
                for (int i = 0; i < 7; i++) {
                    if (warp == 9) {
                        asm volatile("cp.async.bulk.prefetch.tensor.2d.L2.global [%0, {%1, %2}];" ::"l"(&maps.m[M_WI]), "r"(i * 64), "r"(col) : "memory");
                    } else {
                        asm volatile("cp.async.bulk.prefetch.tensor.4d.L2.global [%0, {%1, %2, 0, %3}];" ::"l"(&maps.m[M_WO]), "r"(0), "r"(i * 64), "r"(ns) : "memory");
                        asm volatile("cp.async.bulk.prefetch.tensor.4d.L2.global [%0, {%1, %2, 0, %3}];" ::"l"(&maps.m[M_WO]), "r"(64), "r"(i * 64), "r"(ns) : "memory");
                    }
                }
            }
        } else if (warp == 10) {
            if (elect()) {
                unsigned* epoch_ptr = &sc->epoch[(bid * 4 + 2) * 8];
                const unsigned ep = *epoch_ptr + 1;
                sts1(base + TAG, ep);
                asm volatile("prefetch.tensormap [%0];" ::"l"(&maps.m[M_OUTA + roleL]) : "memory");
                await(sc, CNT_A + roleL * 4 + ns, ep * 16);
                mbar_arrive(base + BAR_DEP);
                PROF(150);
                await(sc, CNT_B + ns, ep * 16);
                mbar_arrive(base + BAR_DEP + 8);
                PROF(151);
                if (!roleL) {
                    await(sc, CNT_O + mt, ep * 4);
                    mbar_arrive(base + BAR_DEP + 16);
                } else {
                    await(sc, CNT_P + mt * 4 + ns, ep * 2 - 1);
                    mbar_arrive(base + BAR_PART);
                    PROF(153);
                    await(sc, CNT_P + mt * 4 + ns, ep * 2);
                    mbar_arrive(base + BAR_PART + 8);
                }
                PROF(152);
                *epoch_ptr = ep;
            }
        } else if (!roleL) {
            if (elect()) {
                mbar_wait(base + BAR_RDY, 0);
                PROF(130);
                signal(sc, CNT_A + ns);
                PROF(131);
                mbar_wait(base + BAR_RDY + 8, 0);
                signal(sc, CNT_A + 4 + ns);
                PROF(135);
                mbar_wait(base + BAR_RDY + 32, 0);
                PROF(132);
                signal(sc, CNT_B + ns);
                PROF(133);
            }
        } else {
            unsigned* epoch_ptr = &sc->epoch[(bid * 4 + 1) * 8];
            const unsigned tag = *epoch_ptr + 1;
#pragma unroll 1
            for (int kv = 0; kv < 2; kv++) {
                uint32_t v[16];
#pragma unroll
                for (int i = 0; i < 16; i++) v[i] = 0;
                if (kv) mbar_wait(base + BAR_HALO, 0), wait_released(HALO_V_AT);
                else mbar_wait(base + BAR_DEP + 16, 0);
                if (blk > 0) {
                    const uint8_t* src = sc->halo + (size_t)(((mt - 1) * 4 + ns) * 2 + kv) * 2048 + lane * 16;
#pragma unroll 1
                    for (int n = 0; n < SPIN_LIMIT; n++) {
                        uint32_t stale = 0;
#pragma unroll
                        for (int i = 0; i < 4; i++) ld_tagged(src + i * 512, v[4 * i], v[4 * i + 1], v[4 * i + 2], v[4 * i + 3]);
#pragma unroll
                        for (int i = 0; i < 16; i += 2) stale |= v[i] ^ tag;
                        if (__all_sync(0xffffffffu, !(stale & 1))) break;
                    }
#pragma unroll
                    for (int c = 0; c < 14; c += 2) v[c] = (v[c] & ~1u) | ((v[15] >> c) & 1);
                }
#pragma unroll
                for (int i = 0; i < 14; i++) sts1(base + HALO + kv * (8 * HSLOT) + i * 128 + lane * 4, v[i]);
                warp_arrive(base + BAR_HALO + kv * 8);
                if (lane == 0) PROF(142 + kv);
            }
            if (elect()) {
                mbar_wait(base + BAR_RDY + 16, 0);
                PROF(130);
                signal(sc, CNT_O + mt);
                PROF(131);
                *epoch_ptr = tag;
            }
        }
    } else {
        asm volatile("setmaxnreg.inc.sync.aligned.u32 224;");
        Ring r;
        r.wg = warp >> 2;
        r.zero = blockIdx.y;
        const int wg = warp >> 2;
        if (wg) nb_arrive(1, 256);
        r.stage = 0;
        r.wait();
        uint8_t* part = sc->part + (size_t)(ns * 16 + mt) * (2 * BLOB) + warp * 512 + lane * 16;
        uint32_t p[28];

        if (roleH) {
            unsigned* epoch_ptr = &sc->epoch[bid * 4 * 8];
            const unsigned tag = *epoch_ptr + 1;
            uint8_t* hout = sc->halo + (size_t)((warp * 8 + ns) * 2) * 2048 + lane * 16;
            auto send = [&](int kv) {
#pragma unroll
                for (int h = 0; h < 2; h++) {
                    uint32_t v[16];
                    v[14] = v[15] = 0;
#pragma unroll
                    for (int c = 0; c < 14; c++) v[c] = p[2 * c + h];
#pragma unroll
                    for (int c = 0; c < 14; c += 2) v[15] |= (v[c] & 1) << c;
#pragma unroll
                    for (int i = 0; i < 4; i++) st_part(hout + (h * 8 + kv) * 2048 + i * 512, v + 4 * i, tag & 1);
                }
            };
            float x0[56], x1[56];
            r.seek(0, 0);
            r.run<XWN, 7, true>(x0);
#pragma unroll 1
            for (int i = 1; i < 7; i++) r.run<XWN, 7, false>(x0);
            r.run<XWN, 7, true>(x1);
            acc_fence(x0);
            pack_all(x0, p);
            send(0);
#pragma unroll 1
            for (int i = 1; i < 7; i++) r.run<XWN, 7, false>(x1, true, true, i < 6);
            asm volatile("wgmma.wait_group.sync.aligned 0;" ::: "memory");
            acc_fence(x1);
            pack_all(x1, p);
#pragma unroll
            for (int i = 0; i < 28; i++) p[i] = movm(p[i]);
            send(1);
            if (threadIdx.x == 0) *epoch_ptr = tag;
        } else if (!roleL) {
            uint8_t* blob = sc->ab + (size_t)((wg * 16 + mt) * 4 + ns) * BLOB + (warp & 3) * WSLOT + lane * 4;
            const uint32_t own = base + BRING + wg * SLOT + (warp & 3) * WSLOT + lane * 16;
            float x0[56], x1[56];
            r.seek(0, bslot_e(0));
            r.run<XW, 7, true>(x0);
            r.run<XW, 7, false>(x0);
            r.seek(2, bslot_e(2));
#pragma unroll 1
            for (int i = 2; i < 7; i++) r.run<XW, 5, false>(x0);

            r.seek(7, bslot_e(7));
            r.run<XW, 5, true, -1>(x1);
            acc_fence(x0);
            pack_all(x0, p);
#pragma unroll
            for (int i = 0; i < 2; i++) {
                if (wg == i) store_frags<0, 14>(blob, p);
                else stage_frags<0, 4>(own + 5 * SLOT, p);
                r.run<XW, 5, false, -1>(x1);
                if (wg == i) {
                    store_frags<14, 28>(blob, p);
                    warp_arrive(base + BAR_RDY + i * 8);
                } else {
                    stage_frags<4, 8>(own + 5 * SLOT, p);
                }
                r.run<XW, 5, false, -1>(x1);
            }
            stage_frags<8, 20>(own + 5 * SLOT, p);
            r.run<XW, 5, false, -1>(x1);
            stage_frags<20, 28>(own + 5 * SLOT, p);
            warp_arrive(base + BAR_RDY + 16);
            r.run<XW, 5, false, -1>(x1);

            mbar_wait(base + BAR_RDY + 16, 0);
            fence_async_smem();
            r.seek(14, bslot_e(14));
            r.run<BIG, 7, true>(x0);
            acc_fence(x1);
            pack_all(x1, p);
            wait_released(10);
            stage_frags<0, 28>(own, p);
            warp_arrive(base + BAR_RDY + 24);
            r.run<BIG, 7, false>(x0);
            mbar_wait(base + BAR_RDY + 24, 0);
            fence_async_smem();
            blob += (size_t)128 * BLOB;
#pragma unroll
            for (int i = 0; i < 28; i++) {
                if (i % B_SLICE == 0) r.run<BIG, 7, false>(x0);
                stg1(blob + i * 128, p[i]);
            }
            warp_arrive(base + BAR_RDY + 32);
#pragma unroll 1
            for (int i = 17 + 27 / B_SLICE; i < POUT; i++) r.run<BIG, 7, false>(x0);

            const uint32_t tag = lds1(base + TAG);
            r.seek(POUT, bslot_e(POUT));
            r.run<OUT, 7, true>(x1);
            acc_fence(x0);
            pack_all(x0, p);
#pragma unroll
            for (int k = 0; k < 3; k++) {
                if (k < 2 && wg == k) {
                    if ((warp & 3) == 0 && elect())
                        asm volatile("red.relaxed.gpu.global.add.u32 [%0], 1;" ::"l"(&sc->cnt[(CNT_P + mt * 4 + ns) * 32]) : "memory");
#pragma unroll
                    for (int i = 0; i < 4; i++) st_part(part + i * 4096, p + 4 * i, tag & 1);
                }
                if (k > 0 && wg == k - 1) {
#pragma unroll
                    for (int i = 4; i < 7; i++) st_part(part + i * 4096, p + 4 * i, tag & 1);
                }
                if (k < 2) r.run<OUT, 7, false>(x1);
            }
#pragma unroll
            for (int i = 3; i < 7; i++) r.run<OUT, 7, false, 1, true>(x1, i <= 7 - TURN, i < 7 - TURN || i == 6, i < 6);

            wait_released(ELAST - 6);
            asm volatile("wgmma.wait_group.sync.aligned 0;" ::: "memory");
            acc_fence(x1);
            const uint32_t slab = base + (wg ? BRING + bslot_e(ELAST - 6) * SLOT : ((ELAST - 6) % NA) * SLOT) + (warp & 3) * WSLOT;
            store_out([&](int i) { return pack2(x1[2 * i], x1[2 * i + 1]); }, lane, slab, &maps.m[M_OUTA], par * 896 + col, blk * 128 + warp * 16);
        } else {
            const int g = lane >> 2, tig = lane & 3;
            const uint32_t hin = base + HALO + warp * HSLOT + lane * 4;
            const uint32_t hpub = warp < 7 ? hin + HSLOT : base + HSPARE + lane * 4;
            auto publish = [&](const uint32_t (&h)[14], int c0, int c1) {
#pragma unroll
                for (int c = 0; c < 14; c++)
                    if (c >= c0 && c < c1) sts1(hpub + c * 128, h[c]);
            };
            float y0[56], y1[56], y2[56];
            r.seek(0, 0);
            r.run<QK, 6, true>(y0, y1);
#pragma unroll 1
            for (int i = 1; i < 14; i++) r.run<QK, 6, false>(y0, y1);

            uint32_t m1[8][4], m0[8][4], lo[14], hi[14], q[2][8][2];
            auto pack_q = [&](int b) {
                uint32_t v[14];
#pragma unroll
                for (int c = 0; c < 14; c++) v[c] = pack2(y0[4 * c + 2 * b], y0[4 * c + 2 * b + 1]);
#pragma unroll
                for (int t = 0; t < 8; t++) {
                    const int c = tile_of(t);
                    q[b][t][0] = (t & 3) == 2 ? (tig >= 2 ? v[c] : 0u) : v[c];
                    q[b][t][1] = (t & 3) == 1 ? (tig < 2 ? v[c + 1] : 0u) : v[c + 1];
                }
            };
            auto fetch = [&](uint32_t src, int hp, int i0) {
#pragma unroll
                for (int t = 4 * hp; t < 4 * hp + 4; t++) {
                    m0[t][i0] = (t & 3) == 2 ? dup(m0[t - 1][3], r.zero) : lds1(src + tile_of(t) * 128);
                    m0[t][3] = lds1(src + tile_of(t) * 128 + 128);
                }
            };
            r.seek(14, bslot_l(14));
            r.run<XWN, 6, true>(y2);
            acc_fence(y0);
            acc_fence(y1);
#pragma unroll
            for (int c = 0; c < 14; c++) hi[c] = pack2(y1[4 * c + 2], y1[4 * c + 3]);
            publish(hi, 0, 7);
            PIN;
            r.run<XWN, 6, false>(y2);
            publish(hi, 7, 14);
            warp_arrive(base + BAR_HALO);
#pragma unroll
            for (int c = 0; c < 14; c++) lo[c] = pack2(y1[4 * c], y1[4 * c + 1]);
#pragma unroll
            for (int t = 0; t < 8; t++) {
                const int c = tile_of(t);
                const bool shared = (t & 3) == 2;
                m1[t][0] = shared ? dup(lo[c], r.zero) : lo[c];
                m1[t][1] = shared ? dup(hi[c], r.zero) : hi[c];
                m1[t][2] = lo[c + 1];
                m1[t][3] = hi[c + 1];
                m0[t][0] = dup(m1[t][0], r.zero);
                m0[t][2] = dup(lo[c + 1], 2 * r.zero);
            }
            PIN;
            r.run<XWN, 6, false>(y2);
            mbar_wait(base + BAR_HALO, 0);
            fetch(hin, 0, 1);
            pack_q(1);
            PIN;
            r.run<XWN, 6, false>(y2);
            fetch(hin, 1, 1);
            pack_q(0);
            r.pin();
            r.take_turn();
            float s[8][4];
#pragma unroll
            for (int step = 0; step < 2; step++) {
#pragma unroll
                for (int i = 0; i < 8; i++) {
                    const int b = 1 - (i >> 2), h = i & 3, t = 2 * h + step;
                    float (&d)[4] = s[2 * h + b];
                    if (step == 0) d[0] = d[1] = d[2] = d[3] = 0.f;
                    mma16816(d, b ? m1[t] : m0[t], q[b][t][0], q[b][t][1]);
                }
            }
            r.pin();
            r.run<XWN, 6, false>(y2, false);

            uint32_t pr[8], mx[4], mx1[4];
            {
                const bool cur0 = g <= 2 * tig, cur1 = g <= 2 * tig + 1;
#pragma unroll
                for (int i = 0; i < 8; i++) {
                    const int c = (i & 1) ? 2 : 0;
                    pr[i] = movm(pack2(cur0 ? s[i][c] : s[i][2 - c], cur1 ? s[i][c + 1] : s[i][3 - c]));
                }
            }
            PIN;
            r.run<XWN, 6, false>(y2);
            const uint32_t curmask = (2 * tig <= g ? 0x0000FFFFu : 0u) | (2 * tig + 1 <= g ? 0xFFFF0000u : 0u);
            {
                const uint32_t keep = (blk == 0 && warp == 0) ? curmask : 0xFFFFFFFFu;
#pragma unroll
                for (int i = 0; i < 4; i++) {
                    pr[2 * i] = (pr[2 * i] & keep) | (0xCF9ECF9Eu & ~keep);
                    mx[i] = max2(__byte_perm(pr[2 * i], pr[2 * i + 1], 0x5410), __byte_perm(pr[2 * i], pr[2 * i + 1], 0x7632));
                    mx1[i] = __shfl_xor_sync(0xffffffffu, mx[i], 1);
                }
            }
            PIN;
            r.run<XWN, 6, false>(y2);
#pragma unroll
            for (int i = 0; i < 4; i++) {
                mx[i] = max2(mx[i], mx1[i]);
                mx1[i] = __shfl_xor_sync(0xffffffffu, mx[i], 2);
            }

            PIN;
            r.seek(21, bslot_l(21));
            r.run<BIG, 6, true>(y0);
            acc_fence(y2);
#pragma unroll
            for (int c = 0; c < 10; c++) hi[c] = movm(pack2(y2[4 * c + 2], y2[4 * c + 3]));
            constexpr float SCL = 0.18898223650461362f * 1.4426950408889634f;
            float e0[8], e1[8], sm[8], sm1[8];
#pragma unroll
            for (int i = 0; i < 8; i++) {
                const uint32_t m2 = max2(mx[i >> 1], mx1[i >> 1]);
                sm[i] = ((i & 1) ? bf_hi(m2) : bf_lo(m2)) * -SCL;
            }
            PIN;
            r.run<BIG, 6, false>(y0);
#pragma unroll
            for (int c = 10; c < 14; c++) hi[c] = movm(pack2(y2[4 * c + 2], y2[4 * c + 3]));
#pragma unroll
            for (int c = 0; c < 4; c++) lo[c] = movm(pack2(y2[4 * c], y2[4 * c + 1]));
#pragma unroll
            for (int i = 0; i < 8; i++) e0[i] = ex2(fmaf(bf_lo(pr[i]), SCL, sm[i]));
            PIN;
            r.run<BIG, 6, false>(y0);
            publish(hi, 0, 10);
#pragma unroll
            for (int i = 0; i < 8; i++) e1[i] = ex2(fmaf(bf_hi(pr[i]), SCL, sm[i]));
            PIN;
            r.run<BIG, 6, false>(y0);
            publish(hi, 10, 14);
            warp_arrive(base + BAR_HALO + 8);
#pragma unroll
            for (int i = 0; i < 8; i++) {
                sm[i] = e0[i] + e1[i];
                sm1[i] = __shfl_xor_sync(0xffffffffu, sm[i], 1);
            }
            PIN;
            r.run<BIG, 6, false>(y0);
#pragma unroll
            for (int c = 4; c < 14; c++) lo[c] = movm(pack2(y2[4 * c], y2[4 * c + 1]));
            PIN;
            r.run<BIG, 6, false>(y0);
#pragma unroll
            for (int i = 0; i < 8; i++) {
                sm[i] += sm1[i];
                sm1[i] = __shfl_xor_sync(0xffffffffu, sm[i], 2);
            }
#pragma unroll
            for (int t = 0; t < 8; t++) {
                const int c = tile_of(t);
                const bool shared = (t & 3) == 2;
                m1[t][0] = shared ? dup(lo[c], r.zero) : lo[c];
                m1[t][1] = lo[c + 1];
                m1[t][2] = shared ? dup(hi[c], r.zero) : hi[c];
                m1[t][3] = hi[c + 1];
                m0[t][0] = dup(m1[t][0], r.zero);
                m0[t][1] = dup(lo[c + 1], 2 * r.zero);
            }
            PIN;
            r.run<BIG, 6, false>(y0);
            mbar_wait(base + BAR_HALO + 8, 0);
            const uint32_t vin = warp ? hin : hin + 8 * HSLOT;
            fetch(vin, 0, 2);
#pragma unroll
            for (int i = 0; i < 8; i++) {
                const float inv = rcp(sm[i] + sm1[i]);
                pr[i] = pack2(e0[i] * inv, e1[i] * inv);
            }
            PIN;
            r.run<BIG, 6, false>(y0);
            fetch(vin, 1, 2);
            uint32_t pb[8][2];
#pragma unroll
            for (int t = 0; t < 8; t++) {
                pb[t][t & 1] = band(pr[t], curmask);
                pb[t][1 - (t & 1)] = band(pr[t], ~curmask);
            }
            r.pin();
            r.take_turn();
            float o[2][8][4];
#pragma unroll
            for (int i = 0; i < 16; i++) {
                const int b = 1 - (i >> 3), t = i & 7;
                float (&d)[4] = o[b][t];
                d[0] = d[1] = d[2] = d[3] = 0.f;
                mma16816(d, b ? m1[t] : m0[t], pb[(t & 6) + b][0], pb[(t & 6) + b][1]);
            }
            r.pin();
            r.run<BIG, 6, false>(y0, false);
            uint8_t* odst = sc->o + (size_t)mt * 7 * SLOT + ns * (14 * 2048) + warp * 256 + lane * 4;
#pragma unroll
            for (int hp = 0; hp < 2; hp++) {
#pragma unroll
                for (int b = 0; b < 2; b++) {
                    const float (&u)[8][4] = o[b];
                    const int t = 4 * hp;
                    uint32_t* w = p + 14 * hp + b;
                    w[0] = pack2(u[t][0], u[t][1]);
                    w[2] = pack2(u[t][2], u[t][3]);
                    w[4] = pack2(u[t + 1][0], u[t + 1][1]);
                    w[6] = pack2(g < 4 ? u[t + 1][2] : u[t + 2][0], g < 4 ? u[t + 1][3] : u[t + 2][1]);
                    w[8] = pack2(u[t + 2][2], u[t + 2][3]);
                    w[10] = pack2(u[t + 3][0], u[t + 3][1]);
                    w[12] = pack2(u[t + 3][2], u[t + 3][3]);
                }
            }
#pragma unroll
            for (int i = 0; i < 28; i++) {
                if (i && i % O_SLICE == 0) r.run<BIG, 6, false>(y0);
                stg1(odst + (i >> 1) * 2048 + (i & 1) * 128, p[i]);
            }
            warp_arrive(base + BAR_RDY + 16);

#pragma unroll 1
            for (int i = 30 + 27 / O_SLICE; i <= LLAST + 1 - TURN; i++) r.run<BIG, 6, false>(y0, true, i <= LLAST - TURN);
            const uint32_t tag = lds1(base + TAG);
            if (mbar_test(base + BAR_PART + wg * 8, 0)) {
#pragma unroll
                for (int i = 0; i < 7; i++) ld_tagged(part + i * 4096, p[4 * i], p[4 * i + 1], p[4 * i + 2], p[4 * i + 3]);
            } else {
                p[0] = ~tag;
            }
            r.seek(LLAST + 2 - TURN, bslot_l(LLAST + 2 - TURN));
#pragma unroll
            for (int i = 1; i < TURN; i++) r.run<BIG, 6, false, 1, true>(y0, false, i == TURN - 1, i < TURN - 1);
#pragma unroll 1
            for (int n = 0; n < SPIN_LIMIT; n++) {
                uint32_t stale = 0;
#pragma unroll
                for (int i = 0; i < 28; i += 2) stale |= p[i] ^ tag;
                if (__all_sync(0xffffffffu, !(stale & 1))) break;
                mbar_wait(base + BAR_PART + wg * 8, 0);
#pragma unroll
                for (int i = 0; i < 7; i++) ld_tagged(part + i * 4096, p[4 * i], p[4 * i + 1], p[4 * i + 2], p[4 * i + 3]);
            }
            wait_released(LLAST - 6);
            asm volatile("wgmma.wait_group.sync.aligned 0;" ::: "memory");
            acc_fence(y0);
            const uint32_t slab = base + (wg ? HALO : ((LLAST - 6) % NA) * SLOT) + (warp & 3) * WSLOT;
            store_out([&](int i) { return add2(pack2(y0[2 * i], y0[2 * i + 1]), p[i]); }, lane, slab, &maps.m[M_OUTB], 448 + col, mt * 128 + warp * 16);
        }
    }
}

typedef CUresult (*EncodeFn)(CUtensorMap*, CUtensorMapDataType, cuuint32_t, void*, const cuuint64_t*, const cuuint64_t*,
                             const cuuint32_t*, const cuuint32_t*, CUtensorMapInterleave, CUtensorMapSwizzle,
                             CUtensorMapL2promotion, CUtensorMapFloatOOBfill);

struct Dim { uint64_t size, stride; uint32_t box; };
void encode(EncodeFn fn, CUtensorMap* m, const void* ptr, CUtensorMapSwizzle sw, Dim d0, Dim d1, Dim d2 = {0, 0, 0}, Dim d3 = {0, 0, 0}) {
    const cuuint64_t dims[4] = {d0.size, d1.size, d2.size, d3.size};
    const cuuint64_t strides[3] = {d1.stride, d2.stride, d3.stride};
    const cuuint32_t box[4] = {d0.box, d1.box, d2.box, d3.box};
    const cuuint32_t es[4] = {1, 1, 1, 1};
    fn(m, CU_TENSOR_MAP_DATA_TYPE_BFLOAT16, d3.size ? 4 : d2.size ? 3 : 2, const_cast<void*>(ptr), dims, strides, box, es,
       CU_TENSOR_MAP_INTERLEAVE_NONE, sw, CU_TENSOR_MAP_L2_PROMOTION_L2_128B, CU_TENSOR_MAP_FLOAT_OOB_FILL_NONE);
}

}

extern "C" void kernel_launch(void* const* d_in, const int* in_sizes, int n_in, void* d_out, int out_size) {
    (void)in_sizes; (void)n_in; (void)out_size;
    void* fnp = nullptr;
    cudaDriverEntryPointQueryResult st;
    cudaGetDriverEntryPoint("cuTensorMapEncodeTiled", &fnp, cudaEnableDefault, &st);
    EncodeFn fn = (EncodeFn)fnp;
    void* scratch = nullptr;
    cudaGetSymbolAddress(&scratch, g_scratch);
    int dev = 0, sms = 0;
    cudaGetDevice(&dev);
    cudaDeviceGetAttribute(&sms, cudaDevAttrMultiProcessorCount, dev);
    auto kernel = sms == 132 ? fused_kernel<true> : fused_kernel<false>;
    cudaFuncSetAttribute(kernel, cudaFuncAttributeMaxDynamicSharedMemorySize, SMEM_BYTES);

    const CUtensorMapSwizzle S128 = CU_TENSOR_MAP_SWIZZLE_128B, S0 = CU_TENSOR_MAP_SWIZZLE_NONE;
    const Dim one = {1, 16, 1};
    Maps maps;
    encode(fn, &maps.m[M_XA], d_in[0], S128, {896, 2, 64}, {1024, 1792, 128}, one, one);
    encode(fn, &maps.m[M_WQK], d_in[1], S128, {112, 2, 64}, {448, 2688, 32}, {3, 896, 2}, {4, 224, 1});
    encode(fn, &maps.m[M_WV], d_in[1], S128, {112, 2, 64}, {448, 2688, 64}, one, {12, 224, 1});
    encode(fn, &maps.m[M_XH], d_in[0], S128, {448, 2, 64}, {128, 1792, 8}, {8, 128 * 1792, 8}, {2, 896, 2});
    encode(fn, &maps.m[M_WO], d_in[2], S128, {112, 2, 64}, {448, 896, 64}, one, {4, 224, 1});
    encode(fn, &maps.m[M_XB], d_in[3], S128, {448, 2, 64}, {1024, 896, 64}, {2, 896 * 1024, 2}, one);
    encode(fn, &maps.m[M_CR], d_in[4], S128, {2048, 2, 64}, {2048, 4096, 128});
    encode(fn, &maps.m[M_CI], d_in[5], S128, {2048, 2, 64}, {2048, 4096, 128});
    encode(fn, &maps.m[M_WR], d_in[6], S128, {448, 2, 64}, {448, 896, 112}, one, one);
    encode(fn, &maps.m[M_WI], d_in[7], S128, {448, 2, 64}, {448, 896, 112});
    encode(fn, &maps.m[M_OUTA], d_out, S0, {1792, 2, 112}, {1024, 3584, 8});
    encode(fn, &maps.m[M_OUTB], d_out, S0, {896, 2, 112}, {2048, 1792, 8});

    kernel<<<132, 384, SMEM_BYTES>>>((Scratch*)scratch, maps);
}
```

```cpp
#include <cuda.h>
#include <cuda_bf16.h>
#include <cuda_runtime.h>
#include <stdint.h>

namespace {

constexpr uint32_t SLOT = 16384;
constexpr int NA = 7;
constexpr uint32_t BRING = NA * SLOT;
constexpr uint32_t HALO = BRING + 6 * SLOT;
constexpr uint32_t HSLOT = 1792;
constexpr uint32_t WSLOT = 3584;
constexpr uint32_t BLOB = 14336;
constexpr uint32_t BARS = 14 * SLOT;
constexpr uint32_t BAR_FULL = BARS;
constexpr uint32_t BAR_EMPTY = BARS + 64;
constexpr uint32_t BAR_RDY = BARS + 128;
constexpr uint32_t BAR_DEP = BARS + 168;
constexpr uint32_t BAR_HALO = BARS + 192;
constexpr uint32_t BAR_PART = BARS + 208;
constexpr uint32_t TAG = BARS + 224;
constexpr uint32_t HSPARE = BARS + 256 + 1024;
constexpr uint32_t SMEM_BYTES = HSPARE + HSLOT;
constexpr uint32_t base = 1024;
constexpr int SPIN_LIMIT = 1 << 16;

#define E_EXTRA 0
#define HALO_K_AT 10
#define HALO_V_AT 19
#define O_SLICE 4
#define B_SLICE 4
#define LEAD 3
#define TURN 4
#define PIN r.pin()
#define PACE 450
#define E_END 1
#define L_END 1
#define HINT_TRIES 6
#define GPC_MAP 0x64752310u

constexpr int NBE = 13 + E_EXTRA;
constexpr int POUT = 33 + NBE;
constexpr int ELAST = POUT + 6;
constexpr int LLAST = 52 - E_EXTRA;

enum { M_XB, M_XA, M_XH, M_WR, M_WQK, M_WV, M_WO, M_WI, M_CR, M_CI, M_OUTA, M_OUTB, M_COUNT };
struct __align__(64) Maps { CUtensorMap m[M_COUNT]; };

constexpr int CNT_A = 0;
constexpr int CNT_B = 8;
constexpr int CNT_O = 16;
constexpr int CNT_P = 32;
constexpr int CNT_COUNT = 96;

struct Scratch {
    uint8_t ab[64 * 4 * BLOB];
    uint8_t o[16 * 7 * SLOT];
    uint8_t part[64 * 2 * BLOB];
    uint8_t halo[64 * 2 * 2048];
    unsigned cnt[CNT_COUNT * 32];
    unsigned epoch[132 * 4 * 8];
};
__device__ __align__(1024) Scratch g_scratch;

__device__ __forceinline__ unsigned clk32() { unsigned c; asm volatile("mov.u32 %0, %%clock;" : "=r"(c)); return c; }

#define PROF(idx)

__device__ __forceinline__ void mbar_init(uint32_t bar, uint32_t cnt) {
    asm volatile("mbarrier.init.shared::cta.b64 [%0], %1;" ::"r"(bar), "r"(cnt) : "memory");
}
__device__ __forceinline__ void mbar_expect(uint32_t bar, uint32_t bytes) {
    asm volatile("mbarrier.arrive.expect_tx.shared::cta.b64 _, [%0], %1;" ::"r"(bar), "r"(bytes) : "memory");
}
__device__ __forceinline__ void mbar_arrive(uint32_t bar) {
    asm volatile("mbarrier.arrive.shared::cta.b64 _, [%0];" ::"r"(bar) : "memory");
}
__device__ __forceinline__ bool mbar_try(uint32_t bar, uint32_t parity) {
    uint32_t ok;
    asm volatile("{\n.reg .pred p;\nmbarrier.try_wait.parity.shared::cta.b64 p, [%1], %2;\nselp.u32 %0, 1, 0, p;\n}\n"
                 : "=r"(ok) : "r"(bar), "r"(parity) : "memory");
    return ok;
}
__device__ __forceinline__ bool mbar_test(uint32_t bar, uint32_t parity) {
    uint32_t ok;
    asm volatile("{\n.reg .pred p;\nmbarrier.test_wait.parity.shared::cta.b64 p, [%1], %2;\nselp.u32 %0, 1, 0, p;\n}\n"
                 : "=r"(ok) : "r"(bar), "r"(parity) : "memory");
    return ok;
}
__device__ __forceinline__ void mbar_wait(uint32_t bar, uint32_t parity) {
#pragma unroll 1
    for (int n = 0; n < SPIN_LIMIT; n++)
        if (mbar_try(bar, parity)) break;
}
__device__ __forceinline__ bool elect() {
    uint32_t p;
    asm volatile("{\n.reg .pred p;\nelect.sync _|p, 0xffffffff;\nselp.u32 %0, 1, 0, p;\n}\n" : "=r"(p));
    return p;
}
__device__ __forceinline__ void nb_sync(int id, int n) { asm volatile("bar.sync %0, %1;" ::"r"(id), "r"(n) : "memory"); }
__device__ __forceinline__ void nb_arrive(int id, int n) { asm volatile("bar.arrive %0, %1;" ::"r"(id), "r"(n) : "memory"); }
__device__ __forceinline__ void warp_arrive(uint32_t bar) {
    __syncwarp();
    if (elect()) mbar_arrive(bar);
}
__device__ __forceinline__ uint32_t band(uint32_t x, uint32_t m) {
    uint32_t r;
    asm volatile("and.b32 %0, %1, %2;" : "=r"(r) : "r"(x), "r"(m));
    return r;
}
__device__ __forceinline__ uint32_t dup(uint32_t x, uint32_t zero) {
    uint32_t r;
    asm volatile("xor.b32 %0, %1, %2;" : "=r"(r) : "r"(x), "r"(zero));
    return r;
}

__device__ __forceinline__ void tma_ld2(uint32_t dst, const CUtensorMap* m, int c0, int c1, uint32_t bar) {
    asm volatile("cp.async.bulk.tensor.2d.shared::cluster.global.mbarrier::complete_tx::bytes [%0], [%1, {%3, %4}], [%2];"
                 ::"r"(dst), "l"(m), "r"(bar), "r"(c0), "r"(c1) : "memory");
}
__device__ __forceinline__ void tma_ld4(uint32_t dst, const CUtensorMap* m, int c0, int c1, int c2, int c3, uint32_t bar) {
    asm volatile("cp.async.bulk.tensor.4d.shared::cluster.global.mbarrier::complete_tx::bytes [%0], [%1, {%3, %4, %5, %6}], [%2];"
                 ::"r"(dst), "l"(m), "r"(bar), "r"(c0), "r"(c1), "r"(c2), "r"(c3) : "memory");
}
__device__ __forceinline__ void bulk_ld(uint32_t dst, const void* src, uint32_t bytes, uint32_t bar) {
    asm volatile("cp.async.bulk.shared::cluster.global.mbarrier::complete_tx::bytes [%0], [%1], %2, [%3];"
                 ::"r"(dst), "l"(src), "r"(bytes), "r"(bar) : "memory");
}
__device__ __forceinline__ void tma_st2(const CUtensorMap* m, int c0, int c1, uint32_t src) {
    asm volatile("cp.async.bulk.tensor.2d.global.shared::cta.bulk_group [%0, {%1, %2}], [%3];"
                 ::"l"(m), "r"(c0), "r"(c1), "r"(src) : "memory");
}
__device__ __forceinline__ void bulk_commit() { asm volatile("cp.async.bulk.commit_group;" ::: "memory"); }
__device__ __forceinline__ void bulk_wait_read() { asm volatile("cp.async.bulk.wait_group.read 0;" ::: "memory"); }
__device__ __forceinline__ void fence_async_smem() { asm volatile("fence.proxy.async.shared::cta;" ::: "memory"); }
__device__ __forceinline__ void fence_async_global() { asm volatile("fence.proxy.async.global;" ::: "memory"); }

__device__ __forceinline__ void signal(Scratch* sc, int idx) {
    asm volatile("fence.proxy.async;\nred.relaxed.gpu.global.add.u32 [%0], 1;" ::"l"(&sc->cnt[idx * 32]) : "memory");
}
__device__ __forceinline__ unsigned peek(const unsigned* p) {
    unsigned v;
    asm volatile("ld.relaxed.gpu.global.u32 %0, [%1];" : "=r"(v) : "l"(p) : "memory");
    return v;
}
__device__ __forceinline__ void await(Scratch* sc, int idx, unsigned target) {
    const unsigned* p = &sc->cnt[idx * 32];
#pragma unroll 1
    for (int n = 0; n < SPIN_LIMIT; n++)
        if ((int)(peek(p) - target) >= 0) break;
    asm volatile("fence.acquire.gpu;" ::: "memory");
}
__device__ __forceinline__ void wait_dep(int k) {
    mbar_wait(base + BAR_DEP + k * 8, 0);
    fence_async_global();
}

#define WG_REGS                                                                                                     \
    "{%0,%1,%2,%3,%4,%5,%6,%7,%8,%9,%10,%11,%12,%13,%14,%15,%16,%17,%18,%19,%20,%21,%22,%23,%24,%25,%26,%27,"       \
    "%28,%29,%30,%31,%32,%33,%34,%35,%36,%37,%38,%39,%40,%41,%42,%43,%44,%45,%46,%47,%48,%49,%50,%51,%52,%53,%54,%55}"
#define WG_OPS(C)                                                                                                   \
    C(d[0]), C(d[1]), C(d[2]), C(d[3]), C(d[4]), C(d[5]), C(d[6]), C(d[7]), C(d[8]), C(d[9]), C(d[10]), C(d[11]),   \
    C(d[12]), C(d[13]), C(d[14]), C(d[15]), C(d[16]), C(d[17]), C(d[18]), C(d[19]), C(d[20]), C(d[21]), C(d[22]),   \
    C(d[23]), C(d[24]), C(d[25]), C(d[26]), C(d[27]), C(d[28]), C(d[29]), C(d[30]), C(d[31]), C(d[32]), C(d[33]),   \
    C(d[34]), C(d[35]), C(d[36]), C(d[37]), C(d[38]), C(d[39]), C(d[40]), C(d[41]), C(d[42]), C(d[43]), C(d[44]),   \
    C(d[45]), C(d[46]), C(d[47]), C(d[48]), C(d[49]), C(d[50]), C(d[51]), C(d[52]), C(d[53]), C(d[54]), C(d[55])

template <int TA, int TB, int SB, bool INIT, uint32_t AH, uint32_t BH>
__device__ __forceinline__ void wgmma112(float (&d)[56], uint32_t alo, uint32_t blo) {
    if (INIT) {
        asm volatile("{\n.reg .pred p;\n.reg .b64 da, db;\nsetp.ne.b32 p, 0, 0;\nmov.b64 da, {%56, %61};\nmov.b64 db, {%57, %62};\n"
                     "wgmma.mma_async.sync.aligned.m64n112k16.f32.bf16.bf16 " WG_REGS ", da, db, p, 1, %59, %60, %58;\n}\n"
                     : WG_OPS("=f") : "r"(alo), "r"(blo), "n"(TB), "n"(SB), "n"(TA), "n"(AH), "n"(BH));
    } else {
        asm volatile("{\n.reg .pred p;\n.reg .b64 da, db;\nsetp.ne.b32 p, 1, 0;\nmov.b64 da, {%56, %61};\nmov.b64 db, {%57, %62};\n"
                     "wgmma.mma_async.sync.aligned.m64n112k16.f32.bf16.bf16 " WG_REGS ", da, db, p, 1, %59, %60, %58;\n}\n"
                     : WG_OPS("+f") : "r"(alo), "r"(blo), "n"(TB), "n"(SB), "n"(TA), "n"(AH), "n"(BH));
    }
}
__device__ __forceinline__ void acc_fence(float (&d)[56]) {
#pragma unroll
    for (int i = 0; i < 56; i++) asm volatile("" : "+f"(d[i])::"memory");
}

__device__ __forceinline__ uint32_t pack2(float lo, float hi) {
    uint32_t r;
    asm volatile("cvt.rn.bf16x2.f32 %0, %1, %2;" : "=r"(r) : "f"(hi), "f"(lo));
    return r;
}
__device__ __forceinline__ uint32_t movm(uint32_t a) {
    uint32_t r;
    asm volatile("movmatrix.sync.aligned.m8n8.trans.b16 %0, %1;" : "=r"(r) : "r"(a));
    return r;
}
__device__ __forceinline__ void stsm4(uint32_t addr, uint32_t a, uint32_t b, uint32_t c, uint32_t d) {
    asm volatile("stmatrix.sync.aligned.m8n8.x4.shared.b16 [%0], {%1,%2,%3,%4};" ::"r"(addr), "r"(a), "r"(b), "r"(c), "r"(d) : "memory");
}
__device__ __forceinline__ void sts1(uint32_t addr, uint32_t a) { asm volatile("st.shared.b32 [%0], %1;" ::"r"(addr), "r"(a) : "memory"); }
__device__ __forceinline__ uint32_t lds1(uint32_t addr) {
    uint32_t a;
    asm volatile("ld.shared.b32 %0, [%1];" : "=r"(a) : "r"(addr) : "memory");
    return a;
}
__device__ __forceinline__ void stg1(uint8_t* p, uint32_t a) { asm volatile("st.global.b32 [%0], %1;" ::"l"(p), "r"(a) : "memory"); }
__device__ __forceinline__ void st_part(uint8_t* p, const uint32_t* v, uint32_t parity) {
    asm volatile("{\n.reg .b64 x, y;\nmov.b64 x, {%1, %2};\nmov.b64 y, {%3, %4};\nst.relaxed.gpu.global.v2.b64 [%0], {x, y};\n}\n"
                 ::"l"(p), "r"((v[0] & ~1u) | parity), "r"(v[1]), "r"((v[2] & ~1u) | parity), "r"(v[3]) : "memory");
}
__device__ __forceinline__ void mma16816(float (&d)[4], const uint32_t (&a)[4], uint32_t b0, uint32_t b1) {
    asm volatile("mma.sync.aligned.m16n8k16.row.col.f32.bf16.bf16.f32 {%0,%1,%2,%3}, {%4,%5,%6,%7}, {%8,%9}, {%0,%1,%2,%3};"
                 : "+f"(d[0]), "+f"(d[1]), "+f"(d[2]), "+f"(d[3]) : "r"(a[0]), "r"(a[1]), "r"(a[2]), "r"(a[3]), "r"(b0), "r"(b1));
}
__device__ __forceinline__ uint32_t add2(uint32_t a, uint32_t b) {
    uint32_t r;
    asm("add.rn.bf16x2 %0, %1, %2;" : "=r"(r) : "r"(a), "r"(b));
    return r;
}
__device__ __forceinline__ uint32_t max2(uint32_t a, uint32_t b) {
    uint32_t r;
    asm("max.bf16x2 %0, %1, %2;" : "=r"(r) : "r"(a), "r"(b));
    return r;
}
__device__ __forceinline__ void ld_tagged(const uint8_t* p, uint32_t& a, uint32_t& ta, uint32_t& b, uint32_t& tb) {
    asm volatile("{\n.reg .b64 x, y;\nld.relaxed.gpu.global.v2.b64 {x, y}, [%4];\nmov.b64 {%0, %1}, x;\nmov.b64 {%2, %3}, y;\n}\n"
                 : "=r"(a), "=r"(ta), "=r"(b), "=r"(tb) : "l"(p) : "memory");
}
__device__ __forceinline__ float bf_lo(uint32_t v) { return __uint_as_float(v << 16); }
__device__ __forceinline__ float bf_hi(uint32_t v) { return __uint_as_float(v & 0xFFFF0000u); }
__device__ __forceinline__ float rcp(float x) { float r; asm("rcp.approx.ftz.f32 %0, %1;" : "=f"(r) : "f"(x)); return r; }
__device__ __forceinline__ float ex2(float x) { float r; asm volatile("ex2.approx.ftz.f32 %0, %1;" : "=f"(r) : "f"(x)); return r; }

__device__ __forceinline__ uint32_t full_bar(int stage) { return base + BAR_FULL + (stage & 7) * 8; }
__device__ __forceinline__ void wait_released(int j) { mbar_wait(base + BAR_EMPTY + (j & 7) * 8, (j >> 3) & 1); }

template <int V>
struct Int { static constexpr int value = V; };

__host__ __device__ constexpr int bslot_e(int i) { return (i < 2 || i >= 14) ? (i + 5) % 7 : (i + 1) % 5; }
__host__ __device__ constexpr int bslot_l(int i) { return i % 6; }

template <uint32_t OFF>
struct Feed {
    int stage;
    uint32_t dst;
    __device__ __forceinline__ void seek(int i, int slot) { stage = i; dst = base + OFF + slot * SLOT; }
    template <int N>
    __device__ __forceinline__ uint32_t acquire() { wait_released(stage - N); return full_bar(stage); }
    template <int N>
    __device__ __forceinline__ void next() {
        stage++;
        dst += SLOT;
        if (dst == base + OFF + N * SLOT) dst = base + OFF;
    }
};
__device__ __forceinline__ int skip_own(int n, int mt) { return n == mt ? 15 : n; }

struct Desc { uint32_t lo, hi; };
__host__ __device__ constexpr Desc desc_const(uint32_t lbo, uint32_t sbo, uint32_t mode) { return {(lbo >> 4) << 16, (sbo >> 4) | (mode << 30)}; }
constexpr Desc D_K128 = desc_const(16, 1024, 1);
constexpr Desc D_N128 = desc_const(8192, 1024, 1);
constexpr Desc D_BLOB = desc_const(128, 256, 0);
constexpr Desc D_OT = desc_const(2048, 128, 0);

enum Kind { XW, XWN, QK, BIG, OUT };

struct Ring {
    int stage;
    uint32_t a, b;
    uint32_t wg;
    uint32_t zero;
    __device__ __forceinline__ void seek(int i, int bslot) {
        stage = i;
        a = (base + (i % NA) * SLOT) >> 4;
        b = (base + BRING + bslot * SLOT) >> 4;
    }
    __device__ __forceinline__ void wait() { mbar_wait(full_bar(stage), (stage >> 3) & 1); }
    __device__ __forceinline__ void take_turn() { nb_sync(1 + wg, 256); }
    __device__ __forceinline__ void pin() {
        uint32_t n = 0;
#pragma unroll 1
        do {
            asm volatile("pmevent 7;" ::: "memory");
        } while (n++ < zero);
    }
    template <Kind K, int NBS, bool INIT, int SB = 1, bool TAIL = false>
    __device__ __forceinline__ void run(float (&d)[56], float (&e)[56], bool first = true, bool last = true, bool more = true) {
        if (first) take_turn();
        asm volatile("wgmma.fence.sync.aligned;" ::: "memory");
        if (K == QK) {
            const uint32_t da = D_K128.lo + (base >> 4) + (stage >> 1) * (SLOT >> 4) + (stage & 1) * 4 + wg * 512, db = D_N128.lo + b;
            wgmma112<0, 1, 1, INIT, D_K128.hi, D_N128.hi>(d, da, db);
            wgmma112<0, 1, 1, INIT, D_K128.hi, D_N128.hi>(e, da, db + 256);
            wgmma112<0, 1, 1, false, D_K128.hi, D_N128.hi>(d, da + 2, db + 128);
            wgmma112<0, 1, 1, false, D_K128.hi, D_N128.hi>(e, da + 2, db + 384);
        } else {
            constexpr int TA = K == OUT, TB = K != XW;
            constexpr uint32_t sa = K == OUT ? 256 : 2, sb = K == XW ? 2 : K == BIG ? 224 : 128;
            constexpr Desc A = K == OUT ? D_OT : D_K128, B = K == XW ? D_K128 : K == BIG ? D_BLOB : D_N128;
            const uint32_t da = A.lo + a + wg * (K == OUT ? 64 : 512), db = B.lo + b;
            wgmma112<TA, TB, SB, INIT, A.hi, B.hi>(d, da, db);
            wgmma112<TA, TB, SB, false, A.hi, B.hi>(d, da + sa, db + sb);
            wgmma112<TA, TB, SB, false, A.hi, B.hi>(d, da + 2 * sa, db + 2 * sb);
            wgmma112<TA, TB, SB, false, A.hi, B.hi>(d, da + 3 * sa, db + 3 * sb);
        }
        asm volatile("wgmma.commit_group.sync.aligned;" ::: "memory");
        if (last) nb_arrive(2 - wg, 256);
        if (!TAIL) asm volatile("wgmma.wait_group.sync.aligned 1;" ::: "memory");
        if (!TAIL && stage > 0 && elect()) mbar_arrive(base + BAR_EMPTY + ((stage - 1) & 7) * 8);
        stage++;
        a += SLOT >> 4;
        if (a == (base + NA * SLOT) >> 4) a = base >> 4;
        b += SLOT >> 4;
        if (b == (base + BRING + NBS * SLOT) >> 4) b = (base + BRING) >> 4;
        if (more) wait();
    }
    template <Kind K, int NBS, bool INIT, int SB = 1, bool TAIL = false>
    __device__ __forceinline__ void run(float (&d)[56], bool first = true, bool last = true, bool more = true) {
        run<K, NBS, INIT, SB, TAIL>(d, d, first, last, more);
    }
};

__device__ __forceinline__ void pack_all(const float (&d)[56], uint32_t (&p)[28]) {
#pragma unroll
    for (int i = 0; i < 28; i++) p[i] = pack2(d[2 * i], d[2 * i + 1]);
}
template <int I0, int I1>
__device__ __forceinline__ void store_frags(uint8_t* dst, const uint32_t (&p)[28]) {
#pragma unroll
    for (int i = I0; i < I1; i++) stg1(dst + i * 128, p[i]);
}
template <int I0, int I1>
__device__ __forceinline__ void stage_frags(uint32_t lane_addr, const uint32_t (&p)[28]) {
#pragma unroll
    for (int i = I0; i < I1; i += 4) stsm4(lane_addr + i * 128, p[i], p[i + 1], p[i + 2], p[i + 3]);
}
template <class F>
__device__ __forceinline__ void store_out(F frag, int lane, uint32_t slab, const CUtensorMap* m, int c0, int c1) {
    const bool swap = lane & 16;
    const uint32_t addr = slab + (lane & 7) * 224 + ((lane >> 3) ^ ((lane >> 2) & 1)) * 16;
#pragma unroll
    for (int h = 0; h < 2; h++) {
#pragma unroll
        for (int c = 0; c < 14; c += 4) {
            const uint32_t t0 = frag(2 * c + h), t1 = frag(2 * c + 2 + h);
            if (c < 12) {
                const uint32_t t2 = frag(2 * c + 4 + h), t3 = frag(2 * c + 6 + h);
                stsm4(addr + h * 1792 + c * 16, swap ? t1 : t0, swap ? t0 : t1, swap ? t3 : t2, swap ? t2 : t3);
            } else {
                asm volatile("stmatrix.sync.aligned.m8n8.x2.shared.b16 [%0], {%1,%2};" ::"r"(addr + h * 1792 + c * 16), "r"(swap ? t1 : t0), "r"(swap ? t0 : t1) : "memory");
            }
        }
        fence_async_smem();
        __syncwarp();
        if (elect()) tma_st2(m, c0, c1 + 8 * h, slab + h * 1792);
    }
    if (elect()) {
        bulk_commit();
        bulk_wait_read();
    }
}
__host__ __device__ constexpr int tile_of(int t) { return 7 * (t >> 2) + 3 * ((t >> 1) & 1) + 2 * (t & 1); }

struct Role {
    bool H;
    int L, mt, ns, id;
    int kind, a0, a1, b3;
};
template <bool BY_SM>
__device__ __forceinline__ Role decode_role() {
    uint32_t sm;
    if (BY_SM) asm volatile("mov.u32 %0, %%smid;" : "=r"(sm));
    else asm volatile("mov.u32 %0, %%ctaid.x;" : "=r"(sm));
    const int tpc = sm >> 1, q2 = ((tpc - 32) * 37) >> 8;
    const int gpc = tpc < 32 ? tpc & 7 : tpc < 60 ? tpc - 31 - 7 * q2 : 0;
    const int pos = tpc < 32 ? tpc >> 3 : tpc < 60 ? q2 + 4 : tpc - 56;
    Role r;
    r.H = sm >= 128;
    const int grp = (GPC_MAP >> (4 * gpc)) & 7;
    r.L = grp & 1;
    r.mt = (grp >> 1) * 4 + (pos >> 1);
    r.ns = (pos & 1) * 2 + (sm & 1);
    r.id = r.H ? sm : grp * 16 + pos * 2 + (sm & 1);
    r.kind = r.H ? 2 : r.L;
    r.a0 = r.L ? (r.mt >> 3) * 448 : 0;
    r.a1 = r.L ? (r.mt & 7) * 128 : r.H ? 120 : r.mt * 64;
    r.b3 = r.H ? 4 + r.ns : r.L ? r.ns : 0;
    return r;
}

__device__ __forceinline__ void first_fill(const Maps& maps, const Role& r, int i) {
    const bool E = r.kind == 0;
    const CUtensorMap* ma = &maps.m[r.kind];
    const uint32_t bar = full_bar(i);
    const int k = (i * 64) >> r.L;
    const bool has_a = !(i & r.L), has_b = i < 7 - r.L;
    const uint32_t dst = base + BRING + (E ? (0x2104365u >> (4 * i)) & 7 : i) * SLOT;
    mbar_expect(bar, (has_a ? SLOT : 0) + (has_b ? (E ? BLOB : SLOT) : 0));
    if (has_a) tma_ld4(base + (i >> r.L) * SLOT, ma, r.a0 + k, r.a1, 0, 0, bar);
    if (has_b) {
        tma_ld4(dst, ma + 3, E ? k : 0, E ? r.ns * 112 : k, 0, r.b3, bar);
        if (!E) tma_ld4(dst + 8192, ma + 3, 64, k, 0, r.b3, bar);
        mbar_arrive(bar);
    }
}
static_assert(bslot_e(0) == 5 && bslot_e(1) == 6 && bslot_e(2) == 3 && bslot_e(3) == 4 && bslot_e(4) == 0 && bslot_e(6) == 2, "");

template <bool BY_SM>
__global__ void __launch_bounds__(384, 1) fused_kernel(Scratch* sc, const __grid_constant__ Maps maps) {
    const unsigned t_open = clk32();
    const int warp = __shfl_sync(0xffffffffu, threadIdx.x >> 5, 0);
    if (warp == 8) {
        if (elect()) {
#pragma unroll
            for (int i = 0; i < LEAD; i++) mbar_init(base + BAR_FULL + i * 8, 2);
            asm volatile("fence.mbarrier_init.release.cluster;" ::: "memory");
            const Role r = decode_role<BY_SM>();
#pragma unroll 1
            for (int i = 0; i < LEAD; i++) {
                first_fill(maps, r, i);
            }
        }
    }
    if (warp == 9) {
        if (elect()) {
#pragma unroll
            for (int i = 0; i < 8; i++) mbar_init(base + BAR_EMPTY + i * 8, 8);
            asm volatile("fence.mbarrier_init.release.cluster;" ::: "memory");
        }
    } else if (warp == 10) {
        if (elect()) {
#pragma unroll
            for (int i = 0; i < 5; i++) mbar_init(base + BAR_RDY + i * 8, i < 2 ? 4 : 8);
#pragma unroll
            for (int i = 0; i < 2; i++) mbar_init(base + BAR_HALO + i * 8, 9);
            asm volatile("fence.mbarrier_init.release.cluster;" ::: "memory");
        }
    } else if (warp == 11) {
        if (elect()) {
#pragma unroll
            for (int i = LEAD; i < 8; i++) mbar_init(base + BAR_FULL + i * 8, 2);
#pragma unroll
            for (int i = 0; i < 3; i++) mbar_init(base + BAR_DEP + i * 8, 1);
#pragma unroll
            for (int i = 0; i < 2; i++) mbar_init(base + BAR_PART + i * 8, 1);
            asm volatile("fence.mbarrier_init.release.cluster;" ::: "memory");
        }
    }
    __syncthreads();

    const Role role = decode_role<BY_SM>();
    int lane = threadIdx.x & 31;
    asm volatile("" : "+r"(lane));
    const bool roleH = role.H;
    const int roleL = role.L, mt = role.mt, ns = role.ns, bid = role.id;
    const int par = mt >> 3, blk = mt & 7, col = ns * 112;

    if (__builtin_expect(warp >= 8, 1)) {
        asm volatile("setmaxnreg.dec.sync.aligned.u32 56;");
#define PROF_FEED_A
#define PROF_FEED_B
        if (__builtin_expect(warp == 8, 1)) {
            if (elect()) {
                PROF(129);
#pragma unroll 1
                for (int i = LEAD; i < 7; i++) {
                    while (clk32() - t_open < i * PACE) {}
                    first_fill(maps, role, i);
                }
                PROF(134);
                Feed<0> f;
                const int row = mt * 128;
                auto c_run = [&](const CUtensorMap* m, int off, int n0, int n1) {
#pragma unroll 1
                    for (int n = n0; n < n1; n++) {
                        const uint32_t bar = f.acquire<NA>();
                        mbar_expect(bar, SLOT);
                        tma_ld2(f.dst, m, (off + skip_own(n, mt)) * 64, row, bar);
                        PROF_FEED_A;
                        f.next<NA>();
                    }
                };
                if (roleH) {
                } else if (!roleL) {
                    f.seek(14, 0);
                    mbar_wait(base + BAR_RDY, 0);
#pragma unroll 1
                    for (int i = 0; i < 4; i++) {
                        const uint32_t bar = f.acquire<NA>();
                        mbar_expect(bar, SLOT);
                        tma_ld2(f.dst, &maps.m[M_CR + (i >> 1)], ((i & 1) * 16 + mt) * 64, row, bar);
                        mbar_arrive(bar);
                        PROF_FEED_A;
                        f.next<NA>();
                    }
                    c_run(&maps.m[M_CR], 0, 0, 15);
                    c_run(&maps.m[M_CI], 0, 0, NBE);
                    wait_dep(2);
#pragma unroll 1
                    for (int i = 0; i < 7; i++) {
                        const uint32_t bar = f.acquire<NA>();
                        mbar_expect(bar, SLOT);
                        bulk_ld(f.dst, sc->o + (size_t)(mt * 7 + i) * SLOT, SLOT, bar);
                        PROF_FEED_A;
                        f.next<NA>();
                    }
                } else {
#pragma unroll 1
                    for (int i = 4; i < 7; i++) {
                        wait_released(2 * i - 8);
                        mbar_expect(full_bar(2 * i), SLOT);
                        tma_ld4(base + i * SLOT, &maps.m[M_XA], par * 448 + i * 64, blk * 128, 0, 0, full_bar(2 * i));
                    }
                    wait_released(HALO_K_AT);
                    mbar_arrive(base + BAR_DEP + 16);
                    f.seek(21, 0);
                    c_run(&maps.m[M_CR], 16, 0, 15);
                    c_run(&maps.m[M_CI], 16, 0, 15);
                    c_run(&maps.m[M_CI], 0, NBE, 15);
                }
            }
        } else if (warp == 11) {
            if (elect()) {
                Feed<BRING> f;
                auto blob_run = [&](auto nbs, int quarter, int n0, int n1) {
                    constexpr int N = decltype(nbs)::value;
                    const uint8_t* src = sc->ab + (size_t)(quarter * 64 + ns) * BLOB;
#pragma unroll 1
                    for (int n = n0; n < n1; n++) {
                        const uint32_t bar = f.template acquire<N>();
                        mbar_expect(bar, BLOB);
                        bulk_ld(f.dst, src + skip_own(n, mt) * (4 * BLOB), BLOB, bar);
                        PROF_FEED_B;
                        f.template next<N>();
                    }
                };
                auto w_run = [&](auto nbs, const CUtensorMap* m, int slice, bool no_a) {
                    constexpr int N = decltype(nbs)::value;
#pragma unroll 1
                    for (int i = 0; i < 7; i++) {
                        const uint32_t bar = f.template acquire<N>();
                        mbar_expect(bar, SLOT);
                        tma_ld4(f.dst, m, 0, i * 64, 0, slice, bar);
                        tma_ld4(f.dst + 8192, m, 64, i * 64, 0, slice, bar);
                        if (no_a) mbar_arrive(bar);
                        PROF_FEED_B;
                        f.template next<N>();
                    }
                };
                if (roleH) {
                    f.seek(7, 0);
                    w_run(Int<7>(), &maps.m[M_WV], 8 + ns, true);
                } else if (!roleL) {
                    f.seek(7, bslot_e(7));
#pragma unroll 1
                    for (int i = 0; i < 7; i++) {
                        const uint32_t bar = f.acquire<5>();
                        mbar_expect(bar, BLOB);
                        tma_ld2(f.dst, &maps.m[M_WI], i * 64, col, bar);
                        mbar_arrive(bar);
                        PROF_FEED_B;
                        f.next<5>();
                    }
                    f.seek(18, bslot_e(18));
                    wait_dep(0);
                    blob_run(Int<7>(), 0, 0, 15);
                    wait_dep(1);
                    blob_run(Int<7>(), 2, 0, NBE);
                    w_run(Int<7>(), &maps.m[M_WO], ns, false);
                } else {
                    f.seek(6, 0);
#pragma unroll 1
                    for (int i = 6; i < 14; i++) {
                        const uint32_t bar = f.acquire<6>();
                        mbar_expect(bar, SLOT);
                        tma_ld4(f.dst, &maps.m[M_WQK], 0, i * 32, 0, ns, bar);
                        tma_ld4(f.dst + 8192, &maps.m[M_WQK], 64, i * 32, 0, ns, bar);
                        if (i & 1) mbar_arrive(bar);
                        PROF_FEED_B;
                        f.next<6>();
                    }
                    w_run(Int<6>(), &maps.m[M_WV], 8 + ns, true);
                    wait_dep(0);
                    blob_run(Int<6>(), 1, 0, 15);
                    wait_dep(1);
                    blob_run(Int<6>(), 3, 0, 15);
                    blob_run(Int<6>(), 2, NBE, 15);
                }
            }
        } else if (roleH) {
            if (elect()) {
                wait_released(warp == 9 ? 0 : 7);
#pragma unroll 1
                for (int i = 0; i < 7; i++) {
                    if (warp == 9) {
                        asm volatile("cp.async.bulk.prefetch.tensor.2d.L2.global [%0, {%1, %2}];" ::"l"(&maps.m[M_WI]), "r"(i * 64), "r"(col) : "memory");
                    } else {
                        asm volatile("cp.async.bulk.prefetch.tensor.4d.L2.global [%0, {%1, %2, 0, %3}];" ::"l"(&maps.m[M_WO]), "r"(0), "r"(i * 64), "r"(ns) : "memory");
                        asm volatile("cp.async.bulk.prefetch.tensor.4d.L2.global [%0, {%1, %2, 0, %3}];" ::"l"(&maps.m[M_WO]), "r"(64), "r"(i * 64), "r"(ns) : "memory");
                    }
                }
            }
        } else if (warp == 10) {
            if (elect()) {
                unsigned* epoch_ptr = &sc->epoch[(bid * 4 + 2) * 8];
                const unsigned ep = *epoch_ptr + 1;
                sts1(base + TAG, ep);
                asm volatile("prefetch.tensormap [%0];" ::"l"(&maps.m[M_OUTA + roleL]) : "memory");
                await(sc, CNT_A + roleL * 4 + ns, ep * 16);
                mbar_arrive(base + BAR_DEP);
                PROF(150);
                await(sc, CNT_B + ns, ep * 16);
                mbar_arrive(base + BAR_DEP + 8);
                PROF(151);
                if (!roleL) {
                    await(sc, CNT_O + mt, ep * 4);
                    mbar_arrive(base + BAR_DEP + 16);
                } else {
                    await(sc, CNT_P + mt * 4 + ns, ep * 2 - 1);
                    mbar_arrive(base + BAR_PART);
                    PROF(153);
                    await(sc, CNT_P + mt * 4 + ns, ep * 2);
                    mbar_arrive(base + BAR_PART + 8);
                }
                PROF(152);
                *epoch_ptr = ep;
            }
        } else if (!roleL) {
            if (elect()) {
                mbar_wait(base + BAR_RDY, 0);
                PROF(130);
                signal(sc, CNT_A + ns);
                PROF(131);
                mbar_wait(base + BAR_RDY + 8, 0);
                signal(sc, CNT_A + 4 + ns);
                PROF(135);
                mbar_wait(base + BAR_RDY + 32, 0);
                PROF(132);
                signal(sc, CNT_B + ns);
                PROF(133);
            }
        } else {
            unsigned* epoch_ptr = &sc->epoch[(bid * 4 + 1) * 8];
            const unsigned tag = *epoch_ptr + 1;
#pragma unroll 1
            for (int kv = 0; kv < 2; kv++) {
                uint32_t v[16];
#pragma unroll
                for (int i = 0; i < 16; i++) v[i] = 0;
                if (kv) mbar_wait(base + BAR_HALO, 0), wait_released(HALO_V_AT);
                else mbar_wait(base + BAR_DEP + 16, 0);
                if (blk > 0) {
                    const uint8_t* src = sc->halo + (size_t)(((mt - 1) * 4 + ns) * 2 + kv) * 2048 + lane * 16;
#pragma unroll 1
                    for (int n = 0; n < SPIN_LIMIT; n++) {
                        uint32_t stale = 0;
#pragma unroll
                        for (int i = 0; i < 4; i++) ld_tagged(src + i * 512, v[4 * i], v[4 * i + 1], v[4 * i + 2], v[4 * i + 3]);
#pragma unroll
                        for (int i = 0; i < 16; i += 2) stale |= v[i] ^ tag;
                        if (__all_sync(0xffffffffu, !(stale & 1))) break;
                    }
#pragma unroll
                    for (int c = 0; c < 14; c += 2) v[c] = (v[c] & ~1u) | ((v[15] >> c) & 1);
                }
#pragma unroll
                for (int i = 0; i < 14; i++) sts1(base + HALO + kv * (8 * HSLOT) + i * 128 + lane * 4, v[i]);
                warp_arrive(base + BAR_HALO + kv * 8);
                if (lane == 0) PROF(142 + kv);
            }
            if (elect()) {
                mbar_wait(base + BAR_RDY + 16, 0);
                PROF(130);
                signal(sc, CNT_O + mt);
                PROF(131);
                *epoch_ptr = tag;
            }
        }
    } else {
        asm volatile("setmaxnreg.inc.sync.aligned.u32 224;");
        Ring r;
        r.wg = warp >> 2;
        r.zero = blockIdx.y;
        const int wg = warp >> 2;
        if (wg) nb_arrive(1, 256);
        r.stage = 0;
        r.wait();
        uint8_t* part = sc->part + (size_t)(ns * 16 + mt) * (2 * BLOB) + warp * 512 + lane * 16;
        uint32_t p[28];

        if (roleH) {
            unsigned* epoch_ptr = &sc->epoch[bid * 4 * 8];
            const unsigned tag = *epoch_ptr + 1;
            uint8_t* hout = sc->halo + (size_t)((warp * 8 + ns) * 2) * 2048 + lane * 16;
            auto send = [&](int kv) {
#pragma unroll
                for (int h = 0; h < 2; h++) {
                    uint32_t v[16];
                    v[14] = v[15] = 0;
#pragma unroll
                    for (int c = 0; c < 14; c++) v[c] = p[2 * c + h];
#pragma unroll
                    for (int c = 0; c < 14; c += 2) v[15] |= (v[c] & 1) << c;
#pragma unroll
                    for (int i = 0; i < 4; i++) st_part(hout + (h * 8 + kv) * 2048 + i * 512, v + 4 * i, tag & 1);
                }
            };
            float x0[56], x1[56];
            r.seek(0, 0);
            r.run<XWN, 7, true>(x0);
#pragma unroll 1
            for (int i = 1; i < 7; i++) r.run<XWN, 7, false>(x0);
            r.run<XWN, 7, true>(x1);
            acc_fence(x0);
            pack_all(x0, p);
            send(0);
#pragma unroll 1
            for (int i = 1; i < 7; i++) r.run<XWN, 7, false>(x1, true, true, i < 6);
            asm volatile("wgmma.wait_group.sync.aligned 0;" ::: "memory");
            acc_fence(x1);
            pack_all(x1, p);
#pragma unroll
            for (int i = 0; i < 28; i++) p[i] = movm(p[i]);
            send(1);
            if (threadIdx.x == 0) *epoch_ptr = tag;
        } else if (!roleL) {
            uint8_t* blob = sc->ab + (size_t)((wg * 16 + mt) * 4 + ns) * BLOB + (warp & 3) * WSLOT + lane * 4;
            const uint32_t own = base + BRING + wg * SLOT + (warp & 3) * WSLOT + lane * 16;
            float x0[56], x1[56];
            r.seek(0, bslot_e(0));
            r.run<XW, 7, true>(x0);
            r.run<XW, 7, false>(x0);
            r.seek(2, bslot_e(2));
#pragma unroll 1
            for (int i = 2; i < 7; i++) r.run<XW, 5, false>(x0);

            r.seek(7, bslot_e(7));
            r.run<XW, 5, true, -1>(x1);
            acc_fence(x0);
            pack_all(x0, p);
#pragma unroll
            for (int i = 0; i < 2; i++) {
                if (wg == i) store_frags<0, 14>(blob, p);
                else stage_frags<0, 4>(own + 5 * SLOT, p);
                r.run<XW, 5, false, -1>(x1);
                if (wg == i) {
                    store_frags<14, 28>(blob, p);
                    warp_arrive(base + BAR_RDY + i * 8);
                } else {
                    stage_frags<4, 8>(own + 5 * SLOT, p);
                }
                r.run<XW, 5, false, -1>(x1);
            }
            stage_frags<8, 20>(own + 5 * SLOT, p);
            r.run<XW, 5, false, -1>(x1);
            stage_frags<20, 28>(own + 5 * SLOT, p);
            warp_arrive(base + BAR_RDY + 16);
            r.run<XW, 5, false, -1>(x1);

            mbar_wait(base + BAR_RDY + 16, 0);
            fence_async_smem();
            r.seek(14, bslot_e(14));
            r.run<BIG, 7, true>(x0);
            acc_fence(x1);
            pack_all(x1, p);
            wait_released(10);
            stage_frags<0, 28>(own, p);
            warp_arrive(base + BAR_RDY + 24);
            r.run<BIG, 7, false>(x0);
            mbar_wait(base + BAR_RDY + 24, 0);
            fence_async_smem();
            blob += (size_t)128 * BLOB;
#pragma unroll
            for (int i = 0; i < 28; i++) {
                if (i % B_SLICE == 0) r.run<BIG, 7, false>(x0);
                stg1(blob + i * 128, p[i]);
            }
            warp_arrive(base + BAR_RDY + 32);
#pragma unroll 1
            for (int i = 17 + 27 / B_SLICE; i < POUT; i++) r.run<BIG, 7, false>(x0);

            const uint32_t tag = lds1(base + TAG);
            r.seek(POUT, bslot_e(POUT));
            r.run<OUT, 7, true>(x1);
            acc_fence(x0);
            pack_all(x0, p);
            auto send = [&]() {
#pragma unroll
                for (int i = 0; i < 7; i++) st_part(part + i * 4096, p + 4 * i, tag & 1);
            };
            auto hint = [&]() {
                if ((warp & 3) == 0 && elect())
                    asm volatile("red.relaxed.gpu.global.add.u32 [%0], 1;" ::"l"(&sc->cnt[(CNT_P + mt * 4 + ns) * 32]) : "memory");
            };
            if (!wg) hint();
            r.pin();
            r.run<OUT, 7, false>(x1, true, !wg);
            if (!wg) send();
            else hint();
            r.run<OUT, 7, false, 1, true>(x1, !wg, wg);
            if (wg) send();
#pragma unroll
            for (int i = 3; i < 7; i++) r.run<OUT, 7, false, 1, true>(x1, i == 3 && wg, i == 6, i < 6);

            wait_released(ELAST - 6);
            asm volatile("wgmma.wait_group.sync.aligned 0;" ::: "memory");
            acc_fence(x1);
            const uint32_t slab = base + (wg ? BRING + bslot_e(ELAST - 6) * SLOT : ((ELAST - 6) % NA) * SLOT) + (warp & 3) * WSLOT;
            store_out([&](int i) { return pack2(x1[2 * i], x1[2 * i + 1]); }, lane, slab, &maps.m[M_OUTA], par * 896 + col, blk * 128 + warp * 16);
        } else {
            const int g = lane >> 2, tig = lane & 3;
            const uint32_t hin = base + HALO + warp * HSLOT + lane * 4;
            const uint32_t hpub = warp < 7 ? hin + HSLOT : base + HSPARE + lane * 4;
            auto publish = [&](const uint32_t (&h)[14], int c0, int c1) {
#pragma unroll
                for (int c = 0; c < 14; c++)
                    if (c >= c0 && c < c1) sts1(hpub + c * 128, h[c]);
            };
            float y0[56], y1[56], y2[56];
            r.seek(0, 0);
            r.run<QK, 6, true>(y0, y1);
#pragma unroll 1
            for (int i = 1; i < 14; i++) r.run<QK, 6, false>(y0, y1);

            uint32_t m1[8][4], m0[8][4], lo[14], hi[14], q[2][8][2];
            auto pack_q = [&](int b) {
                uint32_t v[14];
#pragma unroll
                for (int c = 0; c < 14; c++) v[c] = pack2(y0[4 * c + 2 * b], y0[4 * c + 2 * b + 1]);
#pragma unroll
                for (int t = 0; t < 8; t++) {
                    const int c = tile_of(t);
                    q[b][t][0] = (t & 3) == 2 ? (tig >= 2 ? v[c] : 0u) : v[c];
                    q[b][t][1] = (t & 3) == 1 ? (tig < 2 ? v[c + 1] : 0u) : v[c + 1];
                }
            };
            auto fetch = [&](uint32_t src, int hp, int i0) {
#pragma unroll
                for (int t = 4 * hp; t < 4 * hp + 4; t++) {
                    m0[t][i0] = (t & 3) == 2 ? dup(m0[t - 1][3], r.zero) : lds1(src + tile_of(t) * 128);
                    m0[t][3] = lds1(src + tile_of(t) * 128 + 128);
                }
            };
            r.seek(14, bslot_l(14));
            r.run<XWN, 6, true>(y2);
            acc_fence(y0);
            acc_fence(y1);
#pragma unroll
            for (int c = 0; c < 14; c++) hi[c] = pack2(y1[4 * c + 2], y1[4 * c + 3]);
            publish(hi, 0, 7);
            PIN;
            r.run<XWN, 6, false>(y2);
            publish(hi, 7, 14);
            warp_arrive(base + BAR_HALO);
#pragma unroll
            for (int c = 0; c < 14; c++) lo[c] = pack2(y1[4 * c], y1[4 * c + 1]);
#pragma unroll
            for (int t = 0; t < 8; t++) {
                const int c = tile_of(t);
                const bool shared = (t & 3) == 2;
                m1[t][0] = shared ? dup(lo[c], r.zero) : lo[c];
                m1[t][1] = shared ? dup(hi[c], r.zero) : hi[c];
                m1[t][2] = lo[c + 1];
                m1[t][3] = hi[c + 1];
                m0[t][0] = dup(m1[t][0], r.zero);
                m0[t][2] = dup(lo[c + 1], 2 * r.zero);
            }
            PIN;
            r.run<XWN, 6, false>(y2);
            mbar_wait(base + BAR_HALO, 0);
            fetch(hin, 0, 1);
            pack_q(1);
            PIN;
            r.run<XWN, 6, false>(y2);
            fetch(hin, 1, 1);
            pack_q(0);
            r.pin();
            r.take_turn();
            float s[8][4];
#pragma unroll
            for (int step = 0; step < 2; step++) {
#pragma unroll
                for (int i = 0; i < 8; i++) {
                    const int b = 1 - (i >> 2), h = i & 3, t = 2 * h + step;
                    float (&d)[4] = s[2 * h + b];
                    if (step == 0) d[0] = d[1] = d[2] = d[3] = 0.f;
                    mma16816(d, b ? m1[t] : m0[t], q[b][t][0], q[b][t][1]);
                }
            }
            r.pin();
            r.run<XWN, 6, false>(y2, false);

            uint32_t pr[8], mx[4], mx1[4];
            {
                const bool cur0 = g <= 2 * tig, cur1 = g <= 2 * tig + 1;
#pragma unroll
                for (int i = 0; i < 8; i++) {
                    const int c = (i & 1) ? 2 : 0;
                    pr[i] = movm(pack2(cur0 ? s[i][c] : s[i][2 - c], cur1 ? s[i][c + 1] : s[i][3 - c]));
                }
            }
            PIN;
            r.run<XWN, 6, false>(y2);
            const uint32_t curmask = (2 * tig <= g ? 0x0000FFFFu : 0u) | (2 * tig + 1 <= g ? 0xFFFF0000u : 0u);
            {
                const uint32_t keep = (blk == 0 && warp == 0) ? curmask : 0xFFFFFFFFu;
#pragma unroll
                for (int i = 0; i < 4; i++) {
                    pr[2 * i] = (pr[2 * i] & keep) | (0xCF9ECF9Eu & ~keep);
                    mx[i] = max2(__byte_perm(pr[2 * i], pr[2 * i + 1], 0x5410), __byte_perm(pr[2 * i], pr[2 * i + 1], 0x7632));
                    mx1[i] = __shfl_xor_sync(0xffffffffu, mx[i], 1);
                }
            }
            PIN;
            r.run<XWN, 6, false>(y2);
#pragma unroll
            for (int i = 0; i < 4; i++) {
                mx[i] = max2(mx[i], mx1[i]);
                mx1[i] = __shfl_xor_sync(0xffffffffu, mx[i], 2);
            }

            PIN;
            r.seek(21, bslot_l(21));
            r.run<BIG, 6, true>(y0);
            acc_fence(y2);
#pragma unroll
            for (int c = 0; c < 10; c++) hi[c] = movm(pack2(y2[4 * c + 2], y2[4 * c + 3]));
            constexpr float SCL = 0.18898223650461362f * 1.4426950408889634f;
            float e0[8], e1[8], sm[8], sm1[8];
#pragma unroll
            for (int i = 0; i < 8; i++) {
                const uint32_t m2 = max2(mx[i >> 1], mx1[i >> 1]);
                sm[i] = ((i & 1) ? bf_hi(m2) : bf_lo(m2)) * -SCL;
            }
            PIN;
            r.run<BIG, 6, false>(y0);
#pragma unroll
            for (int c = 10; c < 14; c++) hi[c] = movm(pack2(y2[4 * c + 2], y2[4 * c + 3]));
#pragma unroll
            for (int c = 0; c < 4; c++) lo[c] = movm(pack2(y2[4 * c], y2[4 * c + 1]));
#pragma unroll
            for (int i = 0; i < 8; i++) e0[i] = ex2(fmaf(bf_lo(pr[i]), SCL, sm[i]));
            PIN;
            r.run<BIG, 6, false>(y0);
            publish(hi, 0, 10);
#pragma unroll
            for (int i = 0; i < 8; i++) e1[i] = ex2(fmaf(bf_hi(pr[i]), SCL, sm[i]));
            PIN;
            r.run<BIG, 6, false>(y0);
            publish(hi, 10, 14);
            warp_arrive(base + BAR_HALO + 8);
#pragma unroll
            for (int i = 0; i < 8; i++) {
                sm[i] = e0[i] + e1[i];
                sm1[i] = __shfl_xor_sync(0xffffffffu, sm[i], 1);
            }
            PIN;
            r.run<BIG, 6, false>(y0);
#pragma unroll
            for (int c = 4; c < 14; c++) lo[c] = movm(pack2(y2[4 * c], y2[4 * c + 1]));
            PIN;
            r.run<BIG, 6, false>(y0);
#pragma unroll
            for (int i = 0; i < 8; i++) {
                sm[i] += sm1[i];
                sm1[i] = __shfl_xor_sync(0xffffffffu, sm[i], 2);
            }
#pragma unroll
            for (int t = 0; t < 8; t++) {
                const int c = tile_of(t);
                const bool shared = (t & 3) == 2;
                m1[t][0] = shared ? dup(lo[c], r.zero) : lo[c];
                m1[t][1] = lo[c + 1];
                m1[t][2] = shared ? dup(hi[c], r.zero) : hi[c];
                m1[t][3] = hi[c + 1];
                m0[t][0] = dup(m1[t][0], r.zero);
                m0[t][1] = dup(lo[c + 1], 2 * r.zero);
            }
            PIN;
            r.run<BIG, 6, false>(y0);
            mbar_wait(base + BAR_HALO + 8, 0);
            const uint32_t vin = warp ? hin : hin + 8 * HSLOT;
            fetch(vin, 0, 2);
#pragma unroll
            for (int i = 0; i < 8; i++) {
                const float inv = rcp(sm[i] + sm1[i]);
                pr[i] = pack2(e0[i] * inv, e1[i] * inv);
            }
            PIN;
            r.run<BIG, 6, false>(y0);
            fetch(vin, 1, 2);
            uint32_t pb[8][2];
#pragma unroll
            for (int t = 0; t < 8; t++) {
                pb[t][t & 1] = band(pr[t], curmask);
                pb[t][1 - (t & 1)] = band(pr[t], ~curmask);
            }
            r.pin();
            r.take_turn();
            float o[2][8][4];
#pragma unroll
            for (int i = 0; i < 16; i++) {
                const int b = 1 - (i >> 3), t = i & 7;
                float (&d)[4] = o[b][t];
                d[0] = d[1] = d[2] = d[3] = 0.f;
                mma16816(d, b ? m1[t] : m0[t], pb[(t & 6) + b][0], pb[(t & 6) + b][1]);
            }
            r.pin();
            r.run<BIG, 6, false>(y0, false);
            uint8_t* odst = sc->o + (size_t)mt * 7 * SLOT + ns * (14 * 2048) + warp * 256 + lane * 4;
#pragma unroll
            for (int hp = 0; hp < 2; hp++) {
#pragma unroll
                for (int b = 0; b < 2; b++) {
                    const float (&u)[8][4] = o[b];
                    const int t = 4 * hp;
                    uint32_t* w = p + 14 * hp + b;
                    w[0] = pack2(u[t][0], u[t][1]);
                    w[2] = pack2(u[t][2], u[t][3]);
                    w[4] = pack2(u[t + 1][0], u[t + 1][1]);
                    w[6] = pack2(g < 4 ? u[t + 1][2] : u[t + 2][0], g < 4 ? u[t + 1][3] : u[t + 2][1]);
                    w[8] = pack2(u[t + 2][2], u[t + 2][3]);
                    w[10] = pack2(u[t + 3][0], u[t + 3][1]);
                    w[12] = pack2(u[t + 3][2], u[t + 3][3]);
                }
            }
#pragma unroll
            for (int i = 0; i < 28; i++) {
                if (i && i % O_SLICE == 0) r.run<BIG, 6, false>(y0);
                stg1(odst + (i >> 1) * 2048 + (i & 1) * 128, p[i]);
            }
            warp_arrive(base + BAR_RDY + 16);

#pragma unroll 1
            for (int i = 30 + 27 / O_SLICE; i <= LLAST - TURN; i++) r.run<BIG, 6, false>(y0);
            const uint32_t tag = lds1(base + TAG);
            bool sent = false;
            if (wg) {
#pragma unroll 1
                for (int n = 0; n < HINT_TRIES && !sent; n++) sent = mbar_test(base + BAR_PART + 8, 0);
            }
            if (sent) {
#pragma unroll
                for (int i = 0; i < 7; i++) ld_tagged(part + i * 4096, p[4 * i], p[4 * i + 1], p[4 * i + 2], p[4 * i + 3]);
            } else {
                p[0] = ~tag;
            }
            r.seek(LLAST + 1 - TURN, bslot_l(LLAST + 1 - TURN));
#pragma unroll
            for (int i = 0; i < TURN; i++) r.run<BIG, 6, false, 1, true>(y0, i == 0, i == TURN - 1, i < TURN - 1);
#pragma unroll 1
            for (int n = 0; n < SPIN_LIMIT; n++) {
                uint32_t stale = 0;
#pragma unroll
                for (int i = 0; i < 28; i += 2) stale |= p[i] ^ tag;
                if (__all_sync(0xffffffffu, !(stale & 1))) break;
                mbar_wait(base + BAR_PART + wg * 8, 0);
#pragma unroll
                for (int i = 0; i < 7; i++) ld_tagged(part + i * 4096, p[4 * i], p[4 * i + 1], p[4 * i + 2], p[4 * i + 3]);
            }
            wait_released(LLAST - 6);
            asm volatile("wgmma.wait_group.sync.aligned 0;" ::: "memory");
            acc_fence(y0);
            const uint32_t slab = base + (wg ? HALO : ((LLAST - 6) % NA) * SLOT) + (warp & 3) * WSLOT;
            store_out([&](int i) { return add2(pack2(y0[2 * i], y0[2 * i + 1]), p[i]); }, lane, slab, &maps.m[M_OUTB], 448 + col, mt * 128 + warp * 16);
        }
    }
}

typedef CUresult (*EncodeFn)(CUtensorMap*, CUtensorMapDataType, cuuint32_t, void*, const cuuint64_t*, const cuuint64_t*,
                             const cuuint32_t*, const cuuint32_t*, CUtensorMapInterleave, CUtensorMapSwizzle,
                             CUtensorMapL2promotion, CUtensorMapFloatOOBfill);

struct Dim { uint64_t size, stride; uint32_t box; };
void encode(EncodeFn fn, CUtensorMap* m, const void* ptr, CUtensorMapSwizzle sw, Dim d0, Dim d1, Dim d2 = {0, 0, 0}, Dim d3 = {0, 0, 0}) {
    const cuuint64_t dims[4] = {d0.size, d1.size, d2.size, d3.size};
    const cuuint64_t strides[3] = {d1.stride, d2.stride, d3.stride};
    const cuuint32_t box[4] = {d0.box, d1.box, d2.box, d3.box};
    const cuuint32_t es[4] = {1, 1, 1, 1};
    fn(m, CU_TENSOR_MAP_DATA_TYPE_BFLOAT16, d3.size ? 4 : d2.size ? 3 : 2, const_cast<void*>(ptr), dims, strides, box, es,
       CU_TENSOR_MAP_INTERLEAVE_NONE, sw, CU_TENSOR_MAP_L2_PROMOTION_L2_128B, CU_TENSOR_MAP_FLOAT_OOB_FILL_NONE);
}

}

extern "C" void kernel_launch(void* const* d_in, const int* in_sizes, int n_in, void* d_out, int out_size) {
    (void)in_sizes; (void)n_in; (void)out_size;
    void* fnp = nullptr;
    cudaDriverEntryPointQueryResult st;
    cudaGetDriverEntryPoint("cuTensorMapEncodeTiled", &fnp, cudaEnableDefault, &st);
    EncodeFn fn = (EncodeFn)fnp;
    void* scratch = nullptr;
    cudaGetSymbolAddress(&scratch, g_scratch);
    int dev = 0, sms = 0;
    cudaGetDevice(&dev);
    cudaDeviceGetAttribute(&sms, cudaDevAttrMultiProcessorCount, dev);
    auto kernel = sms == 132 ? fused_kernel<true> : fused_kernel<false>;
    cudaFuncSetAttribute(kernel, cudaFuncAttributeMaxDynamicSharedMemorySize, SMEM_BYTES);

    const CUtensorMapSwizzle S128 = CU_TENSOR_MAP_SWIZZLE_128B, S0 = CU_TENSOR_MAP_SWIZZLE_NONE;
    const Dim one = {1, 16, 1};
    Maps maps;
    encode(fn, &maps.m[M_XA], d_in[0], S128, {896, 2, 64}, {1024, 1792, 128}, one, one);
    encode(fn, &maps.m[M_WQK], d_in[1], S128, {112, 2, 64}, {448, 2688, 32}, {3, 896, 2}, {4, 224, 1});
    encode(fn, &maps.m[M_WV], d_in[1], S128, {112, 2, 64}, {448, 2688, 64}, one, {12, 224, 1});
    encode(fn, &maps.m[M_XH], d_in[0], S128, {448, 2, 64}, {128, 1792, 8}, {8, 128 * 1792, 8}, {2, 896, 2});
    encode(fn, &maps.m[M_WO], d_in[2], S128, {112, 2, 64}, {448, 896, 64}, one, {4, 224, 1});
    encode(fn, &maps.m[M_XB], d_in[3], S128, {448, 2, 64}, {1024, 896, 64}, {2, 896 * 1024, 2}, one);
    encode(fn, &maps.m[M_CR], d_in[4], S128, {2048, 2, 64}, {2048, 4096, 128});
    encode(fn, &maps.m[M_CI], d_in[5], S128, {2048, 2, 64}, {2048, 4096, 128});
    encode(fn, &maps.m[M_WR], d_in[6], S128, {448, 2, 64}, {448, 896, 112}, one, one);
    encode(fn, &maps.m[M_WI], d_in[7], S128, {448, 2, 64}, {448, 896, 112});
    encode(fn, &maps.m[M_OUTA], d_out, S0, {1792, 2, 112}, {1024, 3584, 8});
    encode(fn, &maps.m[M_OUTB], d_out, S0, {896, 2, 112}, {2048, 1792, 8});

    kernel<<<132, 384, SMEM_BYTES>>>((Scratch*)scratch, maps);
}
```

```cpp
#include <cuda.h>
#include <cuda_bf16.h>
#include <cuda_runtime.h>
#include <stdint.h>

namespace {

constexpr uint32_t SLOT = 16384;
constexpr int NA = 7;
constexpr uint32_t BRING = NA * SLOT;
constexpr uint32_t HALO = BRING + 6 * SLOT;
constexpr uint32_t HSLOT = 1792;
constexpr uint32_t WSLOT = 3584;
constexpr uint32_t BLOB = 14336;
constexpr uint32_t BARS = 14 * SLOT;
constexpr uint32_t BAR_FULL = BARS;
constexpr uint32_t BAR_EMPTY = BARS + 64;
constexpr uint32_t BAR_RDY = BARS + 128;
constexpr uint32_t BAR_DEP = BARS + 168;
constexpr uint32_t BAR_HALO = BARS + 192;
constexpr uint32_t BAR_PART = BARS + 208;
constexpr uint32_t TAG = BARS + 224;
constexpr uint32_t HSPARE = BARS + 256 + 1024;
constexpr uint32_t SMEM_BYTES = HSPARE + HSLOT;
constexpr uint32_t base = 1024;
constexpr int SPIN_LIMIT = 1 << 16;

#define E_EXTRA 0
#define HALO_K_AT 10
#define HALO_V_AT 19
#define O_SLICE 4
#define B_SLICE 4
#define LEAD 3
#define TURN 4
#define PIN r.pin()
#define PACE 450
#define O_FIRST 8
#define B_OWN 16
#define MMA_SYNC 1
#define GPC_MAP 0x64752310u

constexpr int NBE = 13 + E_EXTRA;
constexpr int POUT = 33 + NBE;
constexpr int ELAST = POUT + 6;
constexpr int LLAST = 52 - E_EXTRA;
static_assert(TURN <= 4, "the output is staged in the slots of the seventh-last stage");

enum { M_XB, M_XA, M_XH, M_WR, M_WQK, M_WV, M_WO, M_WI, M_CR, M_CI, M_OUTA, M_OUTB, M_COUNT };
struct __align__(64) Maps { CUtensorMap m[M_COUNT]; };

constexpr int CNT_A = 0;
constexpr int CNT_B = 8;
constexpr int CNT_O = 16;
constexpr int CNT_P = 32;
constexpr int CNT_COUNT = 96;

struct Scratch {
    uint8_t ab[64 * 4 * BLOB];
    uint8_t o[16 * 7 * SLOT];
    uint8_t part[64 * 2 * BLOB];
    uint8_t halo[64 * 2 * 2048];
    unsigned cnt[CNT_COUNT * 32];
    unsigned epoch[132 * 4 * 8];
};
__device__ __align__(1024) Scratch g_scratch;

__device__ __forceinline__ unsigned clk32() { unsigned c; asm volatile("mov.u32 %0, %%clock;" : "=r"(c)); return c; }

#define PROF(idx)

__device__ __forceinline__ void mbar_init(uint32_t bar, uint32_t cnt) {
    asm volatile("mbarrier.init.shared::cta.b64 [%0], %1;" ::"r"(bar), "r"(cnt) : "memory");
}
__device__ __forceinline__ void mbar_expect(uint32_t bar, uint32_t bytes) {
    asm volatile("mbarrier.arrive.expect_tx.shared::cta.b64 _, [%0], %1;" ::"r"(bar), "r"(bytes) : "memory");
}
__device__ __forceinline__ void mbar_arrive(uint32_t bar) {
    asm volatile("mbarrier.arrive.shared::cta.b64 _, [%0];" ::"r"(bar) : "memory");
}
__device__ __forceinline__ bool mbar_try(uint32_t bar, uint32_t parity) {
    uint32_t ok;
    asm volatile("{\n.reg .pred p;\nmbarrier.try_wait.parity.shared::cta.b64 p, [%1], %2;\nselp.u32 %0, 1, 0, p;\n}\n"
                 : "=r"(ok) : "r"(bar), "r"(parity) : "memory");
    return ok;
}
__device__ __forceinline__ bool mbar_test(uint32_t bar, uint32_t parity) {
    uint32_t ok;
    asm volatile("{\n.reg .pred p;\nmbarrier.test_wait.parity.shared::cta.b64 p, [%1], %2;\nselp.u32 %0, 1, 0, p;\n}\n"
                 : "=r"(ok) : "r"(bar), "r"(parity) : "memory");
    return ok;
}
__device__ __forceinline__ void mbar_wait(uint32_t bar, uint32_t parity) {
#pragma unroll 1
    for (int n = 0; n < SPIN_LIMIT; n++)
        if (mbar_try(bar, parity)) break;
}
__device__ __forceinline__ bool elect() {
    uint32_t p;
    asm volatile("{\n.reg .pred p;\nelect.sync _|p, 0xffffffff;\nselp.u32 %0, 1, 0, p;\n}\n" : "=r"(p));
    return p;
}
__device__ __forceinline__ void nb_sync(int id, int n) { asm volatile("bar.sync %0, %1;" ::"r"(id), "r"(n) : "memory"); }
__device__ __forceinline__ void nb_arrive(int id, int n) { asm volatile("bar.arrive %0, %1;" ::"r"(id), "r"(n) : "memory"); }
__device__ __forceinline__ void warp_arrive(uint32_t bar) {
    __syncwarp();
    if (elect()) mbar_arrive(bar);
}
__device__ __forceinline__ uint32_t band(uint32_t x, uint32_t m) {
    uint32_t r;
    asm volatile("and.b32 %0, %1, %2;" : "=r"(r) : "r"(x), "r"(m));
    return r;
}
__device__ __forceinline__ uint32_t dup(uint32_t x, uint32_t zero) {
    uint32_t r;
    asm volatile("xor.b32 %0, %1, %2;" : "=r"(r) : "r"(x), "r"(zero));
    return r;
}

__device__ __forceinline__ void tma_ld2(uint32_t dst, const CUtensorMap* m, int c0, int c1, uint32_t bar) {
    asm volatile("cp.async.bulk.tensor.2d.shared::cluster.global.mbarrier::complete_tx::bytes [%0], [%1, {%3, %4}], [%2];"
                 ::"r"(dst), "l"(m), "r"(bar), "r"(c0), "r"(c1) : "memory");
}
__device__ __forceinline__ void tma_ld4(uint32_t dst, const CUtensorMap* m, int c0, int c1, int c2, int c3, uint32_t bar) {
    asm volatile("cp.async.bulk.tensor.4d.shared::cluster.global.mbarrier::complete_tx::bytes [%0], [%1, {%3, %4, %5, %6}], [%2];"
                 ::"r"(dst), "l"(m), "r"(bar), "r"(c0), "r"(c1), "r"(c2), "r"(c3) : "memory");
}
__device__ __forceinline__ void bulk_ld(uint32_t dst, const void* src, uint32_t bytes, uint32_t bar) {
    asm volatile("cp.async.bulk.shared::cluster.global.mbarrier::complete_tx::bytes [%0], [%1], %2, [%3];"
                 ::"r"(dst), "l"(src), "r"(bytes), "r"(bar) : "memory");
}
__device__ __forceinline__ void tma_st2(const CUtensorMap* m, int c0, int c1, uint32_t src) {
    asm volatile("cp.async.bulk.tensor.2d.global.shared::cta.bulk_group [%0, {%1, %2}], [%3];"
                 ::"l"(m), "r"(c0), "r"(c1), "r"(src) : "memory");
}
__device__ __forceinline__ void bulk_commit() { asm volatile("cp.async.bulk.commit_group;" ::: "memory"); }
__device__ __forceinline__ void bulk_wait_read() { asm volatile("cp.async.bulk.wait_group.read 0;" ::: "memory"); }
__device__ __forceinline__ void fence_async_smem() { asm volatile("fence.proxy.async.shared::cta;" ::: "memory"); }
__device__ __forceinline__ void fence_async_global() { asm volatile("fence.proxy.async.global;" ::: "memory"); }

__device__ __forceinline__ void signal(Scratch* sc, int idx) {
    asm volatile("fence.proxy.async;\nred.relaxed.gpu.global.add.u32 [%0], 1;" ::"l"(&sc->cnt[idx * 32]) : "memory");
}
__device__ __forceinline__ unsigned peek(const unsigned* p) {
    unsigned v;
    asm volatile("ld.relaxed.gpu.global.u32 %0, [%1];" : "=r"(v) : "l"(p) : "memory");
    return v;
}
__device__ __forceinline__ void await(Scratch* sc, int idx, unsigned target) {
    const unsigned* p = &sc->cnt[idx * 32];
#pragma unroll 1
    for (int n = 0; n < SPIN_LIMIT; n++)
        if ((int)(peek(p) - target) >= 0) break;
    asm volatile("fence.acquire.gpu;" ::: "memory");
}
__device__ __forceinline__ void wait_dep(int k) {
    mbar_wait(base + BAR_DEP + k * 8, 0);
    fence_async_global();
}

#define WG_REGS                                                                                                     \
    "{%0,%1,%2,%3,%4,%5,%6,%7,%8,%9,%10,%11,%12,%13,%14,%15,%16,%17,%18,%19,%20,%21,%22,%23,%24,%25,%26,%27,"       \
    "%28,%29,%30,%31,%32,%33,%34,%35,%36,%37,%38,%39,%40,%41,%42,%43,%44,%45,%46,%47,%48,%49,%50,%51,%52,%53,%54,%55}"
#define WG_OPS(C)                                                                                                   \
    C(d[0]), C(d[1]), C(d[2]), C(d[3]), C(d[4]), C(d[5]), C(d[6]), C(d[7]), C(d[8]), C(d[9]), C(d[10]), C(d[11]),   \
    C(d[12]), C(d[13]), C(d[14]), C(d[15]), C(d[16]), C(d[17]), C(d[18]), C(d[19]), C(d[20]), C(d[21]), C(d[22]),   \
    C(d[23]), C(d[24]), C(d[25]), C(d[26]), C(d[27]), C(d[28]), C(d[29]), C(d[30]), C(d[31]), C(d[32]), C(d[33]),   \
    C(d[34]), C(d[35]), C(d[36]), C(d[37]), C(d[38]), C(d[39]), C(d[40]), C(d[41]), C(d[42]), C(d[43]), C(d[44]),   \
    C(d[45]), C(d[46]), C(d[47]), C(d[48]), C(d[49]), C(d[50]), C(d[51]), C(d[52]), C(d[53]), C(d[54]), C(d[55])

template <int TA, int TB, int SB, bool INIT, uint32_t AH, uint32_t BH>
__device__ __forceinline__ void wgmma112(float (&d)[56], uint32_t alo, uint32_t blo) {
    if (INIT) {
        asm volatile("{\n.reg .pred p;\n.reg .b64 da, db;\nsetp.ne.b32 p, 0, 0;\nmov.b64 da, {%56, %61};\nmov.b64 db, {%57, %62};\n"
                     "wgmma.mma_async.sync.aligned.m64n112k16.f32.bf16.bf16 " WG_REGS ", da, db, p, 1, %59, %60, %58;\n}\n"
                     : WG_OPS("=f") : "r"(alo), "r"(blo), "n"(TB), "n"(SB), "n"(TA), "n"(AH), "n"(BH));
    } else {
        asm volatile("{\n.reg .pred p;\n.reg .b64 da, db;\nsetp.ne.b32 p, 1, 0;\nmov.b64 da, {%56, %61};\nmov.b64 db, {%57, %62};\n"
                     "wgmma.mma_async.sync.aligned.m64n112k16.f32.bf16.bf16 " WG_REGS ", da, db, p, 1, %59, %60, %58;\n}\n"
                     : WG_OPS("+f") : "r"(alo), "r"(blo), "n"(TB), "n"(SB), "n"(TA), "n"(AH), "n"(BH));
    }
}
__device__ __forceinline__ void acc_fence(float (&d)[56]) {
#pragma unroll
    for (int i = 0; i < 56; i++) asm volatile("" : "+f"(d[i])::"memory");
}

__device__ __forceinline__ uint32_t pack2(float lo, float hi) {
    uint32_t r;
    asm volatile("cvt.rn.bf16x2.f32 %0, %1, %2;" : "=r"(r) : "f"(hi), "f"(lo));
    return r;
}
__device__ __forceinline__ uint32_t movm(uint32_t a) {
    uint32_t r;
    asm volatile("movmatrix.sync.aligned.m8n8.trans.b16 %0, %1;" : "=r"(r) : "r"(a));
    return r;
}
__device__ __forceinline__ void stsm4(uint32_t addr, uint32_t a, uint32_t b, uint32_t c, uint32_t d) {
    asm volatile("stmatrix.sync.aligned.m8n8.x4.shared.b16 [%0], {%1,%2,%3,%4};" ::"r"(addr), "r"(a), "r"(b), "r"(c), "r"(d) : "memory");
}
__device__ __forceinline__ void sts1(uint32_t addr, uint32_t a) { asm volatile("st.shared.b32 [%0], %1;" ::"r"(addr), "r"(a) : "memory"); }
__device__ __forceinline__ uint32_t lds1(uint32_t addr) {
    uint32_t a;
    asm volatile("ld.shared.b32 %0, [%1];" : "=r"(a) : "r"(addr) : "memory");
    return a;
}
__device__ __forceinline__ void stg1(uint8_t* p, uint32_t a) { asm volatile("st.global.b32 [%0], %1;" ::"l"(p), "r"(a) : "memory"); }
__device__ __forceinline__ void st_part(uint8_t* p, const uint32_t* v, uint32_t parity) {
    asm volatile("{\n.reg .b64 x, y;\nmov.b64 x, {%1, %2};\nmov.b64 y, {%3, %4};\nst.relaxed.gpu.global.v2.b64 [%0], {x, y};\n}\n"
                 ::"l"(p), "r"((v[0] & ~1u) | parity), "r"(v[1]), "r"((v[2] & ~1u) | parity), "r"(v[3]) : "memory");
}
__device__ __forceinline__ void mma16816(float (&d)[4], const uint32_t (&a)[4], uint32_t b0, uint32_t b1) {
    asm volatile("mma.sync.aligned.m16n8k16.row.col.f32.bf16.bf16.f32 {%0,%1,%2,%3}, {%4,%5,%6,%7}, {%8,%9}, {%0,%1,%2,%3};"
                 : "+f"(d[0]), "+f"(d[1]), "+f"(d[2]), "+f"(d[3]) : "r"(a[0]), "r"(a[1]), "r"(a[2]), "r"(a[3]), "r"(b0), "r"(b1));
}
__device__ __forceinline__ uint32_t add2(uint32_t a, uint32_t b) {
    uint32_t r;
    asm("add.rn.bf16x2 %0, %1, %2;" : "=r"(r) : "r"(a), "r"(b));
    return r;
}
__device__ __forceinline__ uint32_t max2(uint32_t a, uint32_t b) {
    uint32_t r;
    asm("max.bf16x2 %0, %1, %2;" : "=r"(r) : "r"(a), "r"(b));
    return r;
}
__device__ __forceinline__ void ld_tagged(const uint8_t* p, uint32_t& a, uint32_t& ta, uint32_t& b, uint32_t& tb) {
    asm volatile("{\n.reg .b64 x, y;\nld.relaxed.gpu.global.v2.b64 {x, y}, [%4];\nmov.b64 {%0, %1}, x;\nmov.b64 {%2, %3}, y;\n}\n"
                 : "=r"(a), "=r"(ta), "=r"(b), "=r"(tb) : "l"(p) : "memory");
}
__device__ __forceinline__ float bf_lo(uint32_t v) { return __uint_as_float(v << 16); }
__device__ __forceinline__ float bf_hi(uint32_t v) { return __uint_as_float(v & 0xFFFF0000u); }
__device__ __forceinline__ float rcp(float x) { float r; asm("rcp.approx.ftz.f32 %0, %1;" : "=f"(r) : "f"(x)); return r; }
__device__ __forceinline__ float ex2(float x) { float r; asm volatile("ex2.approx.ftz.f32 %0, %1;" : "=f"(r) : "f"(x)); return r; }

__device__ __forceinline__ uint32_t full_bar(int stage) { return base + BAR_FULL + (stage & 7) * 8; }
__device__ __forceinline__ void wait_released(int j) { mbar_wait(base + BAR_EMPTY + (j & 7) * 8, (j >> 3) & 1); }

template <int V>
struct Int { static constexpr int value = V; };

__host__ __device__ constexpr int bslot_e(int i) { return (i < 2 || i >= 14) ? (i + 5) % 7 : (i + 1) % 5; }
__host__ __device__ constexpr int bslot_l(int i) { return i % 6; }

template <uint32_t OFF>
struct Feed {
    int stage;
    uint32_t dst;
    __device__ __forceinline__ void seek(int i, int slot) { stage = i; dst = base + OFF + slot * SLOT; }
    template <int N>
    __device__ __forceinline__ uint32_t acquire() { wait_released(stage - N); return full_bar(stage); }
    template <int N>
    __device__ __forceinline__ void next() {
        stage++;
        dst += SLOT;
        if (dst == base + OFF + N * SLOT) dst = base + OFF;
    }
};
__device__ __forceinline__ int skip_own(int n, int mt) { return n == mt ? 15 : n; }

struct Desc { uint32_t lo, hi; };
__host__ __device__ constexpr Desc desc_const(uint32_t lbo, uint32_t sbo, uint32_t mode) { return {(lbo >> 4) << 16, (sbo >> 4) | (mode << 30)}; }
constexpr Desc D_K128 = desc_const(16, 1024, 1);
constexpr Desc D_N128 = desc_const(8192, 1024, 1);
constexpr Desc D_BLOB = desc_const(128, 256, 0);
constexpr Desc D_OT = desc_const(2048, 128, 0);

enum Kind { XW, XWN, QK, BIG, OUT };

struct Ring {
    int stage;
    uint32_t a, b;
    uint32_t wg;
    uint32_t zero;
    __device__ __forceinline__ void seek(int i, int bslot) {
        stage = i;
        a = (base + (i % NA) * SLOT) >> 4;
        b = (base + BRING + bslot * SLOT) >> 4;
    }
    __device__ __forceinline__ void wait() { mbar_wait(full_bar(stage), (stage >> 3) & 1); }
    __device__ __forceinline__ void take_turn() { nb_sync(1 + wg, 256); }
    __device__ __forceinline__ void pin() {
        uint32_t n = 0;
#pragma unroll 1
        do {
            asm volatile("pmevent 7;" ::: "memory");
        } while (n++ < zero);
    }
    __device__ __forceinline__ void mma_begin() {
        pin();
        take_turn();
        if (MMA_SYNC) pin();
    }
    __device__ __forceinline__ void mma_end() { pin(); }
    template <Kind K, int NBS, bool INIT, int SB = 1, bool TAIL = false>
    __device__ __forceinline__ void run(float (&d)[56], float (&e)[56], bool first = true, bool last = true, bool more = true) {
        if (first) take_turn();
        asm volatile("wgmma.fence.sync.aligned;" ::: "memory");
        if (K == QK) {
            const uint32_t da = D_K128.lo + (base >> 4) + (stage >> 1) * (SLOT >> 4) + (stage & 1) * 4 + wg * 512, db = D_N128.lo + b;
            wgmma112<0, 1, 1, INIT, D_K128.hi, D_N128.hi>(d, da, db);
            wgmma112<0, 1, 1, INIT, D_K128.hi, D_N128.hi>(e, da, db + 256);
            wgmma112<0, 1, 1, false, D_K128.hi, D_N128.hi>(d, da + 2, db + 128);
            wgmma112<0, 1, 1, false, D_K128.hi, D_N128.hi>(e, da + 2, db + 384);
        } else {
            constexpr int TA = K == OUT, TB = K != XW;
            constexpr uint32_t sa = K == OUT ? 256 : 2, sb = K == XW ? 2 : K == BIG ? 224 : 128;
            constexpr Desc A = K == OUT ? D_OT : D_K128, B = K == XW ? D_K128 : K == BIG ? D_BLOB : D_N128;
            const uint32_t da = A.lo + a + wg * (K == OUT ? 64 : 512), db = B.lo + b;
            wgmma112<TA, TB, SB, INIT, A.hi, B.hi>(d, da, db);
            wgmma112<TA, TB, SB, false, A.hi, B.hi>(d, da + sa, db + sb);
            wgmma112<TA, TB, SB, false, A.hi, B.hi>(d, da + 2 * sa, db + 2 * sb);
            wgmma112<TA, TB, SB, false, A.hi, B.hi>(d, da + 3 * sa, db + 3 * sb);
        }
        asm volatile("wgmma.commit_group.sync.aligned;" ::: "memory");
        if (!TAIL) asm volatile("wgmma.wait_group.sync.aligned 1;" ::: "memory");
        if (last) nb_arrive(2 - wg, 256);
        if (!TAIL && stage > 0 && wg && elect()) mbar_arrive(base + BAR_EMPTY + ((stage - 1) & 7) * 8);
        stage++;
        a += SLOT >> 4;
        if (a == (base + NA * SLOT) >> 4) a = base >> 4;
        b += SLOT >> 4;
        if (b == (base + BRING + NBS * SLOT) >> 4) b = (base + BRING) >> 4;
        if (more && !wg) wait();
    }
    template <Kind K, int NBS, bool INIT, int SB = 1, bool TAIL = false>
    __device__ __forceinline__ void run(float (&d)[56], bool first = true, bool last = true, bool more = true) {
        run<K, NBS, INIT, SB, TAIL>(d, d, first, last, more);
    }
};

__device__ __forceinline__ void pack_all(const float (&d)[56], uint32_t (&p)[28]) {
#pragma unroll
    for (int i = 0; i < 28; i++) p[i] = pack2(d[2 * i], d[2 * i + 1]);
}
template <int I0, int I1>
__device__ __forceinline__ void store_frags(uint8_t* dst, const uint32_t (&p)[28]) {
#pragma unroll
    for (int i = I0; i < I1; i++) stg1(dst + i * 128, p[i]);
}
template <int I0, int I1>
__device__ __forceinline__ void stage_frags(uint32_t lane_addr, const uint32_t (&p)[28]) {
#pragma unroll
    for (int i = I0; i < I1; i += 4) stsm4(lane_addr + i * 128, p[i], p[i + 1], p[i + 2], p[i + 3]);
}
template <class F>
__device__ __forceinline__ void store_out(F frag, int lane, uint32_t slab, const CUtensorMap* m, int c0, int c1) {
    const bool swap = lane & 16;
    const uint32_t addr = slab + (lane & 7) * 224 + ((lane >> 3) ^ ((lane >> 2) & 1)) * 16;
#pragma unroll
    for (int h = 0; h < 2; h++) {
#pragma unroll
        for (int c = 0; c < 14; c += 4) {
            const uint32_t t0 = frag(2 * c + h), t1 = frag(2 * c + 2 + h);
            if (c < 12) {
                const uint32_t t2 = frag(2 * c + 4 + h), t3 = frag(2 * c + 6 + h);
                stsm4(addr + h * 1792 + c * 16, swap ? t1 : t0, swap ? t0 : t1, swap ? t3 : t2, swap ? t2 : t3);
            } else {
                asm volatile("stmatrix.sync.aligned.m8n8.x2.shared.b16 [%0], {%1,%2};" ::"r"(addr + h * 1792 + c * 16), "r"(swap ? t1 : t0), "r"(swap ? t0 : t1) : "memory");
            }
        }
        fence_async_smem();
        __syncwarp();
        if (elect()) tma_st2(m, c0, c1 + 8 * h, slab + h * 1792);
    }
    if (elect()) {
        bulk_commit();
        bulk_wait_read();
    }
}
__host__ __device__ constexpr int tile_of(int t) { return 7 * (t >> 2) + 3 * ((t >> 1) & 1) + 2 * (t & 1); }

struct Role {
    bool H;
    int L, mt, ns, id;
    int kind, a0, a1, b3;
};
template <bool BY_SM>
__device__ __forceinline__ Role decode_role() {
    uint32_t sm;
    if (BY_SM) asm volatile("mov.u32 %0, %%smid;" : "=r"(sm));
    else asm volatile("mov.u32 %0, %%ctaid.x;" : "=r"(sm));
    const int tpc = sm >> 1, q2 = ((tpc - 32) * 37) >> 8;
    const int gpc = tpc < 32 ? tpc & 7 : tpc < 60 ? tpc - 31 - 7 * q2 : 0;
    const int pos = tpc < 32 ? tpc >> 3 : tpc < 60 ? q2 + 4 : tpc - 56;
    Role r;
    r.H = sm >= 128;
    const int grp = (GPC_MAP >> (4 * gpc)) & 7;
    r.L = grp & 1;
    r.mt = (grp >> 1) * 4 + (pos >> 1);
    r.ns = (pos & 1) * 2 + (sm & 1);
    r.id = r.H ? sm : grp * 16 + pos * 2 + (sm & 1);
    r.kind = r.H ? 2 : r.L;
    r.a0 = r.L ? (r.mt >> 3) * 448 : 0;
    r.a1 = r.L ? (r.mt & 7) * 128 : r.H ? 120 : r.mt * 64;
    r.b3 = r.H ? 4 + r.ns : r.L ? r.ns : 0;
    return r;
}

__device__ __forceinline__ void first_fill(const Maps& maps, const Role& r, int i) {
    const bool E = r.kind == 0;
    const CUtensorMap* ma = &maps.m[r.kind];
    const uint32_t bar = full_bar(i);
    const int k = (i * 64) >> r.L;
    const bool has_a = !(i & r.L), has_b = i < 7 - r.L;
    const uint32_t dst = base + BRING + (E ? (0x2104365u >> (4 * i)) & 7 : i) * SLOT;
    mbar_expect(bar, (has_a ? SLOT : 0) + (has_b ? (E ? BLOB : SLOT) : 0));
    if (has_a) tma_ld4(base + (i >> r.L) * SLOT, ma, r.a0 + k, r.a1, 0, 0, bar);
    if (has_b) {
        tma_ld4(dst, ma + 3, E ? k : 0, E ? r.ns * 112 : k, 0, r.b3, bar);
        if (!E) tma_ld4(dst + 8192, ma + 3, 64, k, 0, r.b3, bar);
        mbar_arrive(bar);
    }
}
static_assert(bslot_e(0) == 5 && bslot_e(1) == 6 && bslot_e(2) == 3 && bslot_e(3) == 4 && bslot_e(4) == 0 && bslot_e(6) == 2, "");

template <bool BY_SM>
__global__ void __launch_bounds__(384, 1) fused_kernel(Scratch* sc, const __grid_constant__ Maps maps) {
    const unsigned t_open = clk32();
    const int warp = __shfl_sync(0xffffffffu, threadIdx.x >> 5, 0);
    if (warp == 8) {
        if (elect()) {
#pragma unroll
            for (int i = 0; i < LEAD; i++) mbar_init(base + BAR_FULL + i * 8, 2);
            asm volatile("fence.mbarrier_init.release.cluster;" ::: "memory");
            const Role r = decode_role<BY_SM>();
#pragma unroll 1
            for (int i = 0; i < LEAD; i++) {
                first_fill(maps, r, i);
            }
        }
    }
    if (warp == 9) {
        if (elect()) {
#pragma unroll
            for (int i = 0; i < 8; i++) mbar_init(base + BAR_EMPTY + i * 8, 4);
            asm volatile("fence.mbarrier_init.release.cluster;" ::: "memory");
        }
    } else if (warp == 10) {
        if (elect()) {
#pragma unroll
            for (int i = 0; i < 3; i++) mbar_init(base + BAR_RDY + i * 8, i < 2 ? 4 : 8);
#pragma unroll
            for (int i = 0; i < 2; i++) mbar_init(base + BAR_HALO + i * 8, 1);
            asm volatile("fence.mbarrier_init.release.cluster;" ::: "memory");
        }
    } else if (warp == 11) {
        if (elect()) {
#pragma unroll
            for (int i = LEAD; i < 8; i++) mbar_init(base + BAR_FULL + i * 8, 2);
#pragma unroll
            for (int i = 0; i < 3; i++) mbar_init(base + BAR_DEP + i * 8, 1);
#pragma unroll
            for (int i = 0; i < 2; i++) mbar_init(base + BAR_PART + i * 8, 1);
            asm volatile("fence.mbarrier_init.release.cluster;" ::: "memory");
        }
    }
    __syncthreads();

    const Role role = decode_role<BY_SM>();
    int lane = threadIdx.x & 31;
    asm volatile("" : "+r"(lane));
    const bool roleH = role.H;
    const int roleL = role.L, mt = role.mt, ns = role.ns, bid = role.id;
    const int par = mt >> 3, blk = mt & 7, col = ns * 112;

    if (__builtin_expect(warp >= 8, 1)) {
        asm volatile("setmaxnreg.dec.sync.aligned.u32 56;");
#define PROF_FEED_A
#define PROF_FEED_B
        if (__builtin_expect(warp == 8, 1)) {
            if (elect()) {
                PROF(129);
#pragma unroll 1
                for (int i = LEAD; i < 7; i++) {
                    while (clk32() - t_open < i * PACE) {}
                    first_fill(maps, role, i);
                }
                PROF(134);
                Feed<0> f;
                const int row = mt * 128;
                auto c_run = [&](const CUtensorMap* m, int off, int n0, int n1) {
#pragma unroll 1
                    for (int n = n0; n < n1; n++) {
                        const uint32_t bar = f.acquire<NA>();
                        mbar_expect(bar, SLOT);
                        tma_ld2(f.dst, m, (off + skip_own(n, mt)) * 64, row, bar);
                        PROF_FEED_A;
                        f.next<NA>();
                    }
                };
                if (roleH) {
                } else if (!roleL) {
                    f.seek(14, 0);
                    mbar_wait(base + BAR_RDY, 0);
#pragma unroll 1
                    for (int i = 0; i < 4; i++) {
                        const uint32_t bar = f.acquire<NA>();
                        mbar_expect(bar, SLOT);
                        tma_ld2(f.dst, &maps.m[M_CR + (i >> 1)], ((i & 1) * 16 + mt) * 64, row, bar);
                        mbar_arrive(bar);
                        PROF_FEED_A;
                        f.next<NA>();
                    }
                    c_run(&maps.m[M_CR], 0, 0, 15);
                    c_run(&maps.m[M_CI], 0, 0, NBE);
                    wait_dep(2);
#pragma unroll 1
                    for (int i = 0; i < 7; i++) {
                        const uint32_t bar = f.acquire<NA>();
                        mbar_expect(bar, SLOT);
                        bulk_ld(f.dst, sc->o + (size_t)(mt * 7 + i) * SLOT, SLOT, bar);
                        PROF_FEED_A;
                        f.next<NA>();
                    }
                } else {
#pragma unroll 1
                    for (int i = 4; i < 7; i++) {
                        wait_released(2 * i - 8);
                        mbar_expect(full_bar(2 * i), SLOT);
                        tma_ld4(base + i * SLOT, &maps.m[M_XA], par * 448 + i * 64, blk * 128, 0, 0, full_bar(2 * i));
                    }
                    wait_released(HALO_K_AT);
                    mbar_arrive(base + BAR_DEP + 16);
                    f.seek(21, 0);
                    c_run(&maps.m[M_CR], 16, 0, 15);
                    c_run(&maps.m[M_CI], 16, 0, 15);
                    c_run(&maps.m[M_CI], 0, NBE, 15);
                }
            }
        } else if (warp == 11) {
            if (elect()) {
                Feed<BRING> f;
                auto blob_run = [&](auto nbs, int quarter, int n0, int n1) {
                    constexpr int N = decltype(nbs)::value;
                    const uint8_t* src = sc->ab + (size_t)(quarter * 64 + ns) * BLOB;
#pragma unroll 1
                    for (int n = n0; n < n1; n++) {
                        const uint32_t bar = f.template acquire<N>();
                        mbar_expect(bar, BLOB);
                        bulk_ld(f.dst, src + skip_own(n, mt) * (4 * BLOB), BLOB, bar);
                        PROF_FEED_B;
                        f.template next<N>();
                    }
                };
                auto w_run = [&](auto nbs, const CUtensorMap* m, int slice, bool no_a) {
                    constexpr int N = decltype(nbs)::value;
#pragma unroll 1
                    for (int i = 0; i < 7; i++) {
                        const uint32_t bar = f.template acquire<N>();
                        mbar_expect(bar, SLOT);
                        tma_ld4(f.dst, m, 0, i * 64, 0, slice, bar);
                        tma_ld4(f.dst + 8192, m, 64, i * 64, 0, slice, bar);
                        if (no_a) mbar_arrive(bar);
                        PROF_FEED_B;
                        f.template next<N>();
                    }
                };
                if (roleH) {
                    f.seek(7, 0);
                    w_run(Int<7>(), &maps.m[M_WV], 8 + ns, true);
                } else if (!roleL) {
                    f.seek(7, bslot_e(7));
#pragma unroll 1
                    for (int i = 0; i < 7; i++) {
                        const uint32_t bar = f.acquire<5>();
                        mbar_expect(bar, BLOB);
                        tma_ld2(f.dst, &maps.m[M_WI], i * 64, col, bar);
                        mbar_arrive(bar);
                        PROF_FEED_B;
                        f.next<5>();
                    }
                    f.seek(18, bslot_e(18));
                    wait_dep(0);
                    blob_run(Int<7>(), 0, 0, 15);
                    wait_dep(1);
                    blob_run(Int<7>(), 2, 0, NBE);
                    w_run(Int<7>(), &maps.m[M_WO], ns, false);
                } else {
                    f.seek(6, 0);
#pragma unroll 1
                    for (int i = 6; i < 14; i++) {
                        const uint32_t bar = f.acquire<6>();
                        mbar_expect(bar, SLOT);
                        tma_ld4(f.dst, &maps.m[M_WQK], 0, i * 32, 0, ns, bar);
                        tma_ld4(f.dst + 8192, &maps.m[M_WQK], 64, i * 32, 0, ns, bar);
                        if (i & 1) mbar_arrive(bar);
                        PROF_FEED_B;
                        f.next<6>();
                    }
                    w_run(Int<6>(), &maps.m[M_WV], 8 + ns, true);
                    wait_dep(0);
                    blob_run(Int<6>(), 1, 0, 15);
                    wait_dep(1);
                    blob_run(Int<6>(), 3, 0, 15);
                    blob_run(Int<6>(), 2, NBE, 15);
                }
            }
        } else if (roleH) {
            if (elect()) {
                wait_released(warp == 9 ? 0 : 7);
#pragma unroll 1
                for (int i = 0; i < 7; i++) {
                    if (warp == 9) {
                        asm volatile("cp.async.bulk.prefetch.tensor.2d.L2.global [%0, {%1, %2}];" ::"l"(&maps.m[M_WI]), "r"(i * 64), "r"(col) : "memory");
                    } else {
                        asm volatile("cp.async.bulk.prefetch.tensor.4d.L2.global [%0, {%1, %2, 0, %3}];" ::"l"(&maps.m[M_WO]), "r"(0), "r"(i * 64), "r"(ns) : "memory");
                        asm volatile("cp.async.bulk.prefetch.tensor.4d.L2.global [%0, {%1, %2, 0, %3}];" ::"l"(&maps.m[M_WO]), "r"(64), "r"(i * 64), "r"(ns) : "memory");
                    }
                }
            }
        } else if (warp == 10) {
            if (elect()) {
                unsigned* epoch_ptr = &sc->epoch[(bid * 4 + 2) * 8];
                const unsigned ep = *epoch_ptr + 1;
                sts1(base + TAG, ep);
                asm volatile("prefetch.tensormap [%0];" ::"l"(&maps.m[M_OUTA + roleL]) : "memory");
                await(sc, CNT_A + roleL * 4 + ns, ep * 16);
                mbar_arrive(base + BAR_DEP);
                PROF(150);
                await(sc, CNT_B + ns, ep * 16);
                mbar_arrive(base + BAR_DEP + 8);
                PROF(151);
                if (!roleL) {
                    await(sc, CNT_O + mt, ep * 4);
                    mbar_arrive(base + BAR_DEP + 16);
                } else {
                    await(sc, CNT_P + mt * 4 + ns, ep * 2 - 1);
                    mbar_arrive(base + BAR_PART);
                    PROF(153);
                    await(sc, CNT_P + mt * 4 + ns, ep * 2);
                    mbar_arrive(base + BAR_PART + 8);
                }
                PROF(152);
                *epoch_ptr = ep;
            }
        } else if (!roleL) {
            if (elect()) {
                mbar_wait(base + BAR_RDY, 0);
                PROF(130);
                signal(sc, CNT_A + ns);
                PROF(131);
                mbar_wait(base + BAR_RDY + 8, 0);
                signal(sc, CNT_A + 4 + ns);
                PROF(135);
                mbar_wait(base + BAR_RDY + 16, 0);
                PROF(132);
                signal(sc, CNT_B + ns);
                PROF(133);
            }
        } else {
            unsigned* epoch_ptr = &sc->epoch[(bid * 4 + 1) * 8];
            const unsigned tag = *epoch_ptr + 1;
#pragma unroll 1
            for (int kv = 0; kv < 2; kv++) {
                uint32_t v[16];
#pragma unroll
                for (int i = 0; i < 16; i++) v[i] = 0;
                if (kv) wait_released(HALO_V_AT - 4), wait_released(HALO_V_AT);
                else mbar_wait(base + BAR_DEP + 16, 0);
                if (blk > 0) {
                    const uint8_t* src = sc->halo + (size_t)(((mt - 1) * 4 + ns) * 2 + kv) * 2048 + lane * 16;
#pragma unroll 1
                    for (int n = 0; n < SPIN_LIMIT; n++) {
                        uint32_t stale = 0;
#pragma unroll
                        for (int i = 0; i < 4; i++) ld_tagged(src + i * 512, v[4 * i], v[4 * i + 1], v[4 * i + 2], v[4 * i + 3]);
#pragma unroll
                        for (int i = 0; i < 16; i += 2) stale |= v[i] ^ tag;
                        if (__all_sync(0xffffffffu, !(stale & 1))) break;
                    }
#pragma unroll
                    for (int c = 0; c < 14; c += 2) v[c] = (v[c] & ~1u) | ((v[15] >> c) & 1);
                }
#pragma unroll
                for (int i = 0; i < 14; i++) sts1(base + HALO + kv * (8 * HSLOT) + i * 128 + lane * 4, v[i]);
                warp_arrive(base + BAR_HALO + kv * 8);
                if (lane == 0) PROF(142 + kv);
            }
            if (elect()) {
                mbar_wait(base + BAR_RDY + 16, 0);
                PROF(130);
                signal(sc, CNT_O + mt);
                PROF(131);
                *epoch_ptr = tag;
            }
        }
    } else {
        asm volatile("setmaxnreg.inc.sync.aligned.u32 224;");
        Ring r;
        r.wg = warp >> 2;
        r.zero = blockIdx.y;
        const int wg = warp >> 2;
        if (wg) nb_arrive(1, 256);
        uint8_t* part = sc->part + (size_t)(ns * 16 + mt) * (2 * BLOB) + warp * 512 + lane * 16;
        uint32_t p[28];

        if (roleH) {
            unsigned* epoch_ptr = &sc->epoch[bid * 4 * 8];
            const unsigned tag = *epoch_ptr + 1;
            uint8_t* hout = sc->halo + (size_t)((warp * 8 + ns) * 2) * 2048 + lane * 16;
            auto send = [&](int kv) {
#pragma unroll
                for (int h = 0; h < 2; h++) {
                    uint32_t v[16];
                    v[14] = v[15] = 0;
#pragma unroll
                    for (int c = 0; c < 14; c++) v[c] = p[2 * c + h];
#pragma unroll
                    for (int c = 0; c < 14; c += 2) v[15] |= (v[c] & 1) << c;
#pragma unroll
                    for (int i = 0; i < 4; i++) st_part(hout + (h * 8 + kv) * 2048 + i * 512, v + 4 * i, tag & 1);
                }
            };
            float x0[56], x1[56];
            r.seek(0, 0);
            r.wait();
            r.run<XWN, 7, true>(x0);
#pragma unroll 1
            for (int i = 1; i < 7; i++) r.run<XWN, 7, false>(x0);
            r.run<XWN, 7, true>(x1);
            acc_fence(x0);
            pack_all(x0, p);
            send(0);
#pragma unroll 1
            for (int i = 1; i < 7; i++) r.run<XWN, 7, false>(x1, true, true, i < 6);
            asm volatile("wgmma.wait_group.sync.aligned 0;" ::: "memory");
            acc_fence(x1);
            pack_all(x1, p);
#pragma unroll
            for (int i = 0; i < 28; i++) p[i] = movm(p[i]);
            send(1);
            if (threadIdx.x == 0) *epoch_ptr = tag;
        } else if (!roleL) {
            uint8_t* blob = sc->ab + (size_t)((wg * 16 + mt) * 4 + ns) * BLOB + (warp & 3) * WSLOT + lane * 4;
            const uint32_t own = base + BRING + wg * SLOT + (warp & 3) * WSLOT + lane * 16;
            float x0[56], x1[56];
            r.seek(0, bslot_e(0));
            r.wait();
            r.run<XW, 7, true>(x0);
            r.run<XW, 7, false>(x0);
            r.seek(2, bslot_e(2));
#pragma unroll 1
            for (int i = 2; i < 7; i++) r.run<XW, 5, false>(x0);

            r.seek(7, bslot_e(7));
            r.run<XW, 5, true, -1>(x1);
            acc_fence(x0);
            pack_all(x0, p);
#pragma unroll
            for (int i = 0; i < 2; i++) {
                if (wg == i) store_frags<0, 14>(blob, p);
                else stage_frags<0, 8>(own + 5 * SLOT, p);
                r.run<XW, 5, false, -1>(x1);
                if (wg == i) {
                    store_frags<14, 28>(blob, p);
                    warp_arrive(base + BAR_RDY + i * 8);
                } else {
                    stage_frags<8, 16>(own + 5 * SLOT, p);
                }
                r.run<XW, 5, false, -1>(x1);
            }
            stage_frags<16, 28>(own + 5 * SLOT, p);
            r.run<XW, 5, false, -1>(x1);
            fence_async_smem();
            r.run<XW, 5, false, -1>(x1);

            r.seek(14, bslot_e(14));
            r.run<BIG, 7, true>(x0);
            acc_fence(x1);
            pack_all(x1, p);
            stage_frags<0, B_OWN>(own, p);
            r.run<BIG, 7, false>(x0);
            stage_frags<B_OWN, 28>(own, p);
            fence_async_smem();
            blob += (size_t)128 * BLOB;
#pragma unroll
            for (int i = 0; i < 28; i++) {
                if (i % B_SLICE == 0) r.run<BIG, 7, false>(x0);
                stg1(blob + i * 128, p[i]);
            }
            warp_arrive(base + BAR_RDY + 16);
#pragma unroll 1
            for (int i = 17 + 27 / B_SLICE; i < POUT; i++) r.run<BIG, 7, false>(x0);

            const uint32_t tag = lds1(base + TAG);
            r.seek(POUT, bslot_e(POUT));
            r.run<OUT, 7, true>(x1);
            acc_fence(x0);
            pack_all(x0, p);
#pragma unroll
            for (int k = 0; k < 3; k++) {
                if (k < 2 && wg == k) {
                    if ((warp & 3) == 0 && elect())
                        asm volatile("red.relaxed.gpu.global.add.u32 [%0], 1;" ::"l"(&sc->cnt[(CNT_P + mt * 4 + ns) * 32]) : "memory");
#pragma unroll
                    for (int i = 0; i < 4; i++) st_part(part + i * 4096, p + 4 * i, tag & 1);
                }
                if (k > 0 && wg == k - 1) {
#pragma unroll
                    for (int i = 4; i < 7; i++) st_part(part + i * 4096, p + 4 * i, tag & 1);
                }
                if (k < 2) r.run<OUT, 7, false>(x1);
            }
#pragma unroll
            for (int i = 3; i < 7; i++) r.run<OUT, 7, false, 1, true>(x1, i <= 7 - TURN, i < 7 - TURN || i == 6, i < 6);

            asm volatile("wgmma.wait_group.sync.aligned 0;" ::: "memory");
            acc_fence(x1);
            const uint32_t slab = base + (wg ? BRING + bslot_e(ELAST - 6) * SLOT : ((ELAST - 6) % NA) * SLOT) + (warp & 3) * WSLOT;
            store_out([&](int i) { return pack2(x1[2 * i], x1[2 * i + 1]); }, lane, slab, &maps.m[M_OUTA], par * 896 + col, blk * 128 + warp * 16);
        } else {
            const int g = lane >> 2, tig = lane & 3;
            const uint32_t hin = base + HALO + warp * HSLOT + lane * 4;
            const uint32_t hpub = warp < 7 ? hin + HSLOT : base + HSPARE + lane * 4;
            auto publish = [&](const uint32_t (&h)[14], int c0, int c1) {
#pragma unroll
                for (int c = 0; c < 14; c++)
                    if (c >= c0 && c < c1) sts1(hpub + c * 128, h[c]);
            };
            float y0[56], y1[56], y2[56];
            r.seek(0, 0);
            r.wait();
            r.run<QK, 6, true>(y0, y1);
#pragma unroll 1
            for (int i = 1; i < 14; i++) r.run<QK, 6, false>(y0, y1);

            uint32_t m1[8][4], m0[8][4], lo[14], hi[14], q[2][8][2];
            auto pack_q = [&](int b) {
                uint32_t v[14];
#pragma unroll
                for (int c = 0; c < 14; c++) v[c] = pack2(y0[4 * c + 2 * b], y0[4 * c + 2 * b + 1]);
#pragma unroll
                for (int t = 0; t < 8; t++) {
                    const int c = tile_of(t);
                    q[b][t][0] = (t & 3) == 2 ? (tig >= 2 ? v[c] : 0u) : v[c];
                    q[b][t][1] = (t & 3) == 1 ? (tig < 2 ? v[c + 1] : 0u) : v[c + 1];
                }
            };
            auto fetch = [&](uint32_t src, int hp, int i0) {
#pragma unroll
                for (int t = 4 * hp; t < 4 * hp + 4; t++) {
                    m0[t][i0] = (t & 3) == 2 ? dup(m0[t - 1][3], r.zero) : lds1(src + tile_of(t) * 128);
                    m0[t][3] = lds1(src + tile_of(t) * 128 + 128);
                }
            };
            r.seek(14, bslot_l(14));
            r.run<XWN, 6, true>(y2);
            acc_fence(y0);
            acc_fence(y1);
#pragma unroll
            for (int c = 0; c < 14; c++) hi[c] = pack2(y1[4 * c + 2], y1[4 * c + 3]);
            publish(hi, 0, 7);
            PIN;
            r.run<XWN, 6, false>(y2);
            publish(hi, 7, 14);
#pragma unroll
            for (int c = 0; c < 14; c++) lo[c] = pack2(y1[4 * c], y1[4 * c + 1]);
#pragma unroll
            for (int t = 0; t < 8; t++) {
                const int c = tile_of(t);
                const bool shared = (t & 3) == 2;
                m1[t][0] = shared ? dup(lo[c], r.zero) : lo[c];
                m1[t][1] = shared ? dup(hi[c], r.zero) : hi[c];
                m1[t][2] = lo[c + 1];
                m1[t][3] = hi[c + 1];
                m0[t][0] = dup(m1[t][0], r.zero);
                m0[t][2] = dup(lo[c + 1], 2 * r.zero);
            }
            PIN;
            r.run<XWN, 6, false>(y2);
            if (warp == 0) mbar_wait(base + BAR_HALO, 0);
            fetch(hin, 0, 1);
            pack_q(1);
            PIN;
            r.run<XWN, 6, false>(y2);
            fetch(hin, 1, 1);
            pack_q(0);
            r.mma_begin();
            float s[8][4];
#pragma unroll
            for (int step = 0; step < 2; step++) {
#pragma unroll
                for (int i = 0; i < 8; i++) {
                    const int b = 1 - (i >> 2), h = i & 3, t = 2 * h + step;
                    float (&d)[4] = s[2 * h + b];
                    if (step == 0) d[0] = d[1] = d[2] = d[3] = 0.f;
                    mma16816(d, b ? m1[t] : m0[t], q[b][t][0], q[b][t][1]);
                }
            }
            r.mma_end();
            r.run<XWN, 6, false>(y2, false);

            uint32_t pr[8], mx[4], mx1[4];
            {
                const bool cur0 = g <= 2 * tig, cur1 = g <= 2 * tig + 1;
#pragma unroll
                for (int i = 0; i < 8; i++) {
                    const int c = (i & 1) ? 2 : 0;
                    pr[i] = movm(pack2(cur0 ? s[i][c] : s[i][2 - c], cur1 ? s[i][c + 1] : s[i][3 - c]));
                }
            }
            PIN;
            r.run<XWN, 6, false>(y2);
            const uint32_t curmask = (2 * tig <= g ? 0x0000FFFFu : 0u) | (2 * tig + 1 <= g ? 0xFFFF0000u : 0u);
            {
                const uint32_t keep = (blk == 0 && warp == 0) ? curmask : 0xFFFFFFFFu;
#pragma unroll
                for (int i = 0; i < 4; i++) {
                    pr[2 * i] = (pr[2 * i] & keep) | (0xCF9ECF9Eu & ~keep);
                    mx[i] = max2(__byte_perm(pr[2 * i], pr[2 * i + 1], 0x5410), __byte_perm(pr[2 * i], pr[2 * i + 1], 0x7632));
                    mx1[i] = __shfl_xor_sync(0xffffffffu, mx[i], 1);
                }
            }
            PIN;
            r.run<XWN, 6, false>(y2);
#pragma unroll
            for (int i = 0; i < 4; i++) {
                mx[i] = max2(mx[i], mx1[i]);
                mx1[i] = __shfl_xor_sync(0xffffffffu, mx[i], 2);
            }

            PIN;
            r.seek(21, bslot_l(21));
            r.run<BIG, 6, true>(y0);
            acc_fence(y2);
#pragma unroll
            for (int c = 0; c < 10; c++) hi[c] = movm(pack2(y2[4 * c + 2], y2[4 * c + 3]));
            constexpr float SCL = 0.18898223650461362f * 1.4426950408889634f;
            float e0[8], e1[8], sm[8], sm1[8];
#pragma unroll
            for (int i = 0; i < 8; i++) {
                const uint32_t m2 = max2(mx[i >> 1], mx1[i >> 1]);
                sm[i] = ((i & 1) ? bf_hi(m2) : bf_lo(m2)) * -SCL;
            }
            PIN;
            r.run<BIG, 6, false>(y0);
#pragma unroll
            for (int c = 10; c < 14; c++) hi[c] = movm(pack2(y2[4 * c + 2], y2[4 * c + 3]));
#pragma unroll
            for (int c = 0; c < 4; c++) lo[c] = movm(pack2(y2[4 * c], y2[4 * c + 1]));
#pragma unroll
            for (int i = 0; i < 8; i++) e0[i] = ex2(fmaf(bf_lo(pr[i]), SCL, sm[i]));
            PIN;
            r.run<BIG, 6, false>(y0);
            publish(hi, 0, 10);
#pragma unroll
            for (int i = 0; i < 8; i++) e1[i] = ex2(fmaf(bf_hi(pr[i]), SCL, sm[i]));
            PIN;
            r.run<BIG, 6, false>(y0);
            publish(hi, 10, 14);
#pragma unroll
            for (int i = 0; i < 8; i++) {
                sm[i] = e0[i] + e1[i];
                sm1[i] = __shfl_xor_sync(0xffffffffu, sm[i], 1);
            }
            PIN;
            r.run<BIG, 6, false>(y0);
#pragma unroll
            for (int c = 4; c < 14; c++) lo[c] = movm(pack2(y2[4 * c], y2[4 * c + 1]));
            PIN;
            r.run<BIG, 6, false>(y0);
#pragma unroll
            for (int i = 0; i < 8; i++) {
                sm[i] += sm1[i];
                sm1[i] = __shfl_xor_sync(0xffffffffu, sm[i], 2);
            }
#pragma unroll
            for (int t = 0; t < 8; t++) {
                const int c = tile_of(t);
                const bool shared = (t & 3) == 2;
                m1[t][0] = shared ? dup(lo[c], r.zero) : lo[c];
                m1[t][1] = lo[c + 1];
                m1[t][2] = shared ? dup(hi[c], r.zero) : hi[c];
                m1[t][3] = hi[c + 1];
                m0[t][0] = dup(m1[t][0], r.zero);
                m0[t][1] = dup(lo[c + 1], 2 * r.zero);
            }
            PIN;
            r.run<BIG, 6, false>(y0);
            if (warp == 0) mbar_wait(base + BAR_HALO + 8, 0);
            const uint32_t vin = warp ? hin : hin + 8 * HSLOT;
            fetch(vin, 0, 2);
#pragma unroll
            for (int i = 0; i < 8; i++) {
                const float inv = rcp(sm[i] + sm1[i]);
                pr[i] = pack2(e0[i] * inv, e1[i] * inv);
            }
            PIN;
            r.run<BIG, 6, false>(y0);
            fetch(vin, 1, 2);
            uint32_t pb[8][2];
#pragma unroll
            for (int t = 0; t < 8; t++) {
                pb[t][t & 1] = band(pr[t], curmask);
                pb[t][1 - (t & 1)] = band(pr[t], ~curmask);
            }
            r.mma_begin();
            float o[2][8][4];
#pragma unroll
            for (int i = 0; i < 16; i++) {
                const int b = 1 - (i >> 3), t = i & 7;
                float (&d)[4] = o[b][t];
                d[0] = d[1] = d[2] = d[3] = 0.f;
                mma16816(d, b ? m1[t] : m0[t], pb[(t & 6) + b][0], pb[(t & 6) + b][1]);
            }
            r.mma_end();
            r.run<BIG, 6, false>(y0, false);
            uint8_t* odst = sc->o + (size_t)mt * 7 * SLOT + ns * (14 * 2048) + warp * 256 + lane * 4;
#pragma unroll
            for (int hp = 0; hp < 2; hp++) {
#pragma unroll
                for (int b = 0; b < 2; b++) {
                    const float (&u)[8][4] = o[b];
                    const int t = 4 * hp;
                    uint32_t* w = p + 14 * hp + b;
                    w[0] = pack2(u[t][0], u[t][1]);
                    w[2] = pack2(u[t][2], u[t][3]);
                    w[4] = pack2(u[t + 1][0], u[t + 1][1]);
                    w[6] = pack2(g < 4 ? u[t + 1][2] : u[t + 2][0], g < 4 ? u[t + 1][3] : u[t + 2][1]);
                    w[8] = pack2(u[t + 2][2], u[t + 2][3]);
                    w[10] = pack2(u[t + 3][0], u[t + 3][1]);
                    w[12] = pack2(u[t + 3][2], u[t + 3][3]);
                }
            }
#pragma unroll
            for (int i = 0; i < 28; i++) {
                if (i >= O_FIRST && (i - O_FIRST) % O_SLICE == 0) r.run<BIG, 6, false>(y0);
                stg1(odst + (i >> 1) * 2048 + (i & 1) * 128, p[i]);
            }
            warp_arrive(base + BAR_RDY + 16);

#pragma unroll 1
            for (int i = 31 + (27 - O_FIRST) / O_SLICE; i <= LLAST + 1 - TURN; i++) r.run<BIG, 6, false>(y0, true, i <= LLAST - TURN);
            const uint32_t tag = lds1(base + TAG);
            if (mbar_test(base + BAR_PART + wg * 8, 0)) {
#pragma unroll
                for (int i = 0; i < 7; i++) ld_tagged(part + i * 4096, p[4 * i], p[4 * i + 1], p[4 * i + 2], p[4 * i + 3]);
            } else {
                p[0] = ~tag;
            }
            r.seek(LLAST + 2 - TURN, bslot_l(LLAST + 2 - TURN));
#pragma unroll
            for (int i = 1; i < TURN; i++) r.run<BIG, 6, false, 1, true>(y0, false, i == TURN - 1, i < TURN - 1);
#pragma unroll 1
            for (int n = 0; n < SPIN_LIMIT; n++) {
                uint32_t stale = 0;
#pragma unroll
                for (int i = 0; i < 28; i += 2) stale |= p[i] ^ tag;
                if (__all_sync(0xffffffffu, !(stale & 1))) break;
                mbar_wait(base + BAR_PART + wg * 8, 0);
#pragma unroll
                for (int i = 0; i < 7; i++) ld_tagged(part + i * 4096, p[4 * i], p[4 * i + 1], p[4 * i + 2], p[4 * i + 3]);
            }
            asm volatile("wgmma.wait_group.sync.aligned 0;" ::: "memory");
            acc_fence(y0);
            const uint32_t slab = base + (wg ? HALO : ((LLAST - 6) % NA) * SLOT) + (warp & 3) * WSLOT;
            store_out([&](int i) { return add2(pack2(y0[2 * i], y0[2 * i + 1]), p[i]); }, lane, slab, &maps.m[M_OUTB], 448 + col, mt * 128 + warp * 16);
        }
    }
}

typedef CUresult (*EncodeFn)(CUtensorMap*, CUtensorMapDataType, cuuint32_t, void*, const cuuint64_t*, const cuuint64_t*,
                             const cuuint32_t*, const cuuint32_t*, CUtensorMapInterleave, CUtensorMapSwizzle,
                             CUtensorMapL2promotion, CUtensorMapFloatOOBfill);

struct Dim { uint64_t size, stride; uint32_t box; };
void encode(EncodeFn fn, CUtensorMap* m, const void* ptr, CUtensorMapSwizzle sw, Dim d0, Dim d1, Dim d2 = {0, 0, 0}, Dim d3 = {0, 0, 0}) {
    const cuuint64_t dims[4] = {d0.size, d1.size, d2.size, d3.size};
    const cuuint64_t strides[3] = {d1.stride, d2.stride, d3.stride};
    const cuuint32_t box[4] = {d0.box, d1.box, d2.box, d3.box};
    const cuuint32_t es[4] = {1, 1, 1, 1};
    fn(m, CU_TENSOR_MAP_DATA_TYPE_BFLOAT16, d3.size ? 4 : d2.size ? 3 : 2, const_cast<void*>(ptr), dims, strides, box, es,
       CU_TENSOR_MAP_INTERLEAVE_NONE, sw, CU_TENSOR_MAP_L2_PROMOTION_L2_128B, CU_TENSOR_MAP_FLOAT_OOB_FILL_NONE);
}

}

extern "C" void kernel_launch(void* const* d_in, const int* in_sizes, int n_in, void* d_out, int out_size) {
    (void)in_sizes; (void)n_in; (void)out_size;
    void* fnp = nullptr;
    cudaDriverEntryPointQueryResult st;
    cudaGetDriverEntryPoint("cuTensorMapEncodeTiled", &fnp, cudaEnableDefault, &st);
    EncodeFn fn = (EncodeFn)fnp;
    void* scratch = nullptr;
    cudaGetSymbolAddress(&scratch, g_scratch);
    int dev = 0, sms = 0;
    cudaGetDevice(&dev);
    cudaDeviceGetAttribute(&sms, cudaDevAttrMultiProcessorCount, dev);
    auto kernel = sms == 132 ? fused_kernel<true> : fused_kernel<false>;
    cudaFuncSetAttribute(kernel, cudaFuncAttributeMaxDynamicSharedMemorySize, SMEM_BYTES);

    const CUtensorMapSwizzle S128 = CU_TENSOR_MAP_SWIZZLE_128B, S0 = CU_TENSOR_MAP_SWIZZLE_NONE;
    const Dim one = {1, 16, 1};
    Maps maps;
    encode(fn, &maps.m[M_XA], d_in[0], S128, {896, 2, 64}, {1024, 1792, 128}, one, one);
    encode(fn, &maps.m[M_WQK], d_in[1], S128, {112, 2, 64}, {448, 2688, 32}, {3, 896, 2}, {4, 224, 1});
    encode(fn, &maps.m[M_WV], d_in[1], S128, {112, 2, 64}, {448, 2688, 64}, one, {12, 224, 1});
    encode(fn, &maps.m[M_XH], d_in[0], S128, {448, 2, 64}, {128, 1792, 8}, {8, 128 * 1792, 8}, {2, 896, 2});
    encode(fn, &maps.m[M_WO], d_in[2], S128, {112, 2, 64}, {448, 896, 64}, one, {4, 224, 1});
    encode(fn, &maps.m[M_XB], d_in[3], S128, {448, 2, 64}, {1024, 896, 64}, {2, 896 * 1024, 2}, one);
    encode(fn, &maps.m[M_CR], d_in[4], S128, {2048, 2, 64}, {2048, 4096, 128});
    encode(fn, &maps.m[M_CI], d_in[5], S128, {2048, 2, 64}, {2048, 4096, 128});
    encode(fn, &maps.m[M_WR], d_in[6], S128, {448, 2, 64}, {448, 896, 112}, one, one);
    encode(fn, &maps.m[M_WI], d_in[7], S128, {448, 2, 64}, {448, 896, 112});
    encode(fn, &maps.m[M_OUTA], d_out, S0, {1792, 2, 112}, {1024, 3584, 8});
    encode(fn, &maps.m[M_OUTB], d_out, S0, {896, 2, 112}, {2048, 1792, 8});

    kernel<<<132, 384, SMEM_BYTES>>>((Scratch*)scratch, maps);
}
```

```cpp
#include <cuda.h>
#include <cuda_bf16.h>
#include <cuda_runtime.h>
#include <stdint.h>

namespace {

constexpr uint32_t SLOT = 16384;
constexpr int NA = 7;
constexpr uint32_t BRING = NA * SLOT;
constexpr uint32_t HALO = BRING + 6 * SLOT;
constexpr uint32_t HSLOT = 1792;
constexpr uint32_t WSLOT = 3584;
constexpr uint32_t BLOB = 14336;
constexpr uint32_t BARS = 14 * SLOT;
constexpr uint32_t BAR_FULL = BARS;
constexpr uint32_t BAR_EMPTY = BARS + 64;
constexpr uint32_t BAR_RDY = BARS + 128;
constexpr uint32_t BAR_DEP = BARS + 168;
constexpr uint32_t BAR_HALO = BARS + 192;
constexpr uint32_t BAR_PART = BARS + 208;
constexpr uint32_t TAG = BARS + 224;
constexpr uint32_t HSPARE = BARS + 256 + 1024;
constexpr uint32_t SMEM_BYTES = HSPARE + HSLOT;
constexpr uint32_t base = 1024;
constexpr int SPIN_LIMIT = 1 << 16;

#define E_EXTRA 0
#define HALO_K_AT 10
#define HALO_V_AT 19
#define O_SLICE 4
#define B_SLICE 4
#define LEAD 3
#define TURN 4
#define PIN r.pin()
#define PACE 450
#define O_FIRST 8
#define B_OWN 28
#define MMA_SYNC 2
#define A_OWN 4
#define A_OWN2 20
#define SPLIT_DUTY 1
#define GPC_MAP 0x64752310u

constexpr int NBE = 13 + E_EXTRA;
constexpr int POUT = 33 + NBE;
constexpr int ELAST = POUT + 6;
constexpr int LLAST = 52 - E_EXTRA;
static_assert(TURN <= 4, "the output is staged in the slots of the seventh-last stage");

enum { M_XB, M_XA, M_XH, M_WR, M_WQK, M_WV, M_WO, M_WI, M_CR, M_CI, M_OUTA, M_OUTB, M_COUNT };
struct __align__(64) Maps { CUtensorMap m[M_COUNT]; };

constexpr int CNT_A = 0;
constexpr int CNT_B = 8;
constexpr int CNT_O = 16;
constexpr int CNT_P = 32;
constexpr int CNT_COUNT = 96;

struct Scratch {
    uint8_t ab[64 * 4 * BLOB];
    uint8_t o[16 * 7 * SLOT];
    uint8_t part[64 * 2 * BLOB];
    uint8_t halo[64 * 2 * 2048];
    unsigned cnt[CNT_COUNT * 32];
    unsigned epoch[132 * 4 * 8];
};
__device__ __align__(1024) Scratch g_scratch;

__device__ __forceinline__ unsigned clk32() { unsigned c; asm volatile("mov.u32 %0, %%clock;" : "=r"(c)); return c; }

#define PROF(idx)

__device__ __forceinline__ void mbar_init(uint32_t bar, uint32_t cnt) {
    asm volatile("mbarrier.init.shared::cta.b64 [%0], %1;" ::"r"(bar), "r"(cnt) : "memory");
}
__device__ __forceinline__ void mbar_expect(uint32_t bar, uint32_t bytes) {
    asm volatile("mbarrier.arrive.expect_tx.shared::cta.b64 _, [%0], %1;" ::"r"(bar), "r"(bytes) : "memory");
}
__device__ __forceinline__ void mbar_arrive(uint32_t bar) {
    asm volatile("mbarrier.arrive.shared::cta.b64 _, [%0];" ::"r"(bar) : "memory");
}
__device__ __forceinline__ bool mbar_try(uint32_t bar, uint32_t parity) {
    uint32_t ok;
    asm volatile("{\n.reg .pred p;\nmbarrier.try_wait.parity.shared::cta.b64 p, [%1], %2;\nselp.u32 %0, 1, 0, p;\n}\n"
                 : "=r"(ok) : "r"(bar), "r"(parity) : "memory");
    return ok;
}
__device__ __forceinline__ bool mbar_test(uint32_t bar, uint32_t parity) {
    uint32_t ok;
    asm volatile("{\n.reg .pred p;\nmbarrier.test_wait.parity.shared::cta.b64 p, [%1], %2;\nselp.u32 %0, 1, 0, p;\n}\n"
                 : "=r"(ok) : "r"(bar), "r"(parity) : "memory");
    return ok;
}
__device__ __forceinline__ void mbar_wait(uint32_t bar, uint32_t parity) {
#pragma unroll 1
    for (int n = 0; n < SPIN_LIMIT; n++)
        if (mbar_try(bar, parity)) break;
}
__device__ __forceinline__ bool elect() {
    uint32_t p;
    asm volatile("{\n.reg .pred p;\nelect.sync _|p, 0xffffffff;\nselp.u32 %0, 1, 0, p;\n}\n" : "=r"(p));
    return p;
}
__device__ __forceinline__ void nb_sync(int id, int n) { asm volatile("bar.sync %0, %1;" ::"r"(id), "r"(n) : "memory"); }
__device__ __forceinline__ void nb_arrive(int id, int n) { asm volatile("bar.arrive %0, %1;" ::"r"(id), "r"(n) : "memory"); }
__device__ __forceinline__ void warp_arrive(uint32_t bar) {
    __syncwarp();
    if (elect()) mbar_arrive(bar);
}
__device__ __forceinline__ uint32_t band(uint32_t x, uint32_t m) {
    uint32_t r;
    asm volatile("and.b32 %0, %1, %2;" : "=r"(r) : "r"(x), "r"(m));
    return r;
}
__device__ __forceinline__ uint32_t dup(uint32_t x, uint32_t zero) {
    uint32_t r;
    asm volatile("xor.b32 %0, %1, %2;" : "=r"(r) : "r"(x), "r"(zero));
    return r;
}

__device__ __forceinline__ void tma_ld2(uint32_t dst, const CUtensorMap* m, int c0, int c1, uint32_t bar) {
    asm volatile("cp.async.bulk.tensor.2d.shared::cluster.global.mbarrier::complete_tx::bytes [%0], [%1, {%3, %4}], [%2];"
                 ::"r"(dst), "l"(m), "r"(bar), "r"(c0), "r"(c1) : "memory");
}
__device__ __forceinline__ void tma_ld4(uint32_t dst, const CUtensorMap* m, int c0, int c1, int c2, int c3, uint32_t bar) {
    asm volatile("cp.async.bulk.tensor.4d.shared::cluster.global.mbarrier::complete_tx::bytes [%0], [%1, {%3, %4, %5, %6}], [%2];"
                 ::"r"(dst), "l"(m), "r"(bar), "r"(c0), "r"(c1), "r"(c2), "r"(c3) : "memory");
}
__device__ __forceinline__ void bulk_ld(uint32_t dst, const void* src, uint32_t bytes, uint32_t bar) {
    asm volatile("cp.async.bulk.shared::cluster.global.mbarrier::complete_tx::bytes [%0], [%1], %2, [%3];"
                 ::"r"(dst), "l"(src), "r"(bytes), "r"(bar) : "memory");
}
__device__ __forceinline__ void tma_st2(const CUtensorMap* m, int c0, int c1, uint32_t src) {
    asm volatile("cp.async.bulk.tensor.2d.global.shared::cta.bulk_group [%0, {%1, %2}], [%3];"
                 ::"l"(m), "r"(c0), "r"(c1), "r"(src) : "memory");
}
__device__ __forceinline__ void bulk_commit() { asm volatile("cp.async.bulk.commit_group;" ::: "memory"); }
__device__ __forceinline__ void bulk_wait_read() { asm volatile("cp.async.bulk.wait_group.read 0;" ::: "memory"); }
__device__ __forceinline__ void fence_async_smem() { asm volatile("fence.proxy.async.shared::cta;" ::: "memory"); }
__device__ __forceinline__ void fence_async_global() { asm volatile("fence.proxy.async.global;" ::: "memory"); }

__device__ __forceinline__ void signal(Scratch* sc, int idx) {
    asm volatile("fence.proxy.async;\nred.relaxed.gpu.global.add.u32 [%0], 1;" ::"l"(&sc->cnt[idx * 32]) : "memory");
}
__device__ __forceinline__ unsigned peek(const unsigned* p) {
    unsigned v;
    asm volatile("ld.relaxed.gpu.global.u32 %0, [%1];" : "=r"(v) : "l"(p) : "memory");
    return v;
}
__device__ __forceinline__ void await(Scratch* sc, int idx, unsigned target) {
    const unsigned* p = &sc->cnt[idx * 32];
#pragma unroll 1
    for (int n = 0; n < SPIN_LIMIT; n++)
        if ((int)(peek(p) - target) >= 0) break;
    asm volatile("fence.acquire.gpu;" ::: "memory");
}
__device__ __forceinline__ void wait_dep(int k) {
    mbar_wait(base + BAR_DEP + k * 8, 0);
    fence_async_global();
}

#define WG_REGS                                                                                                     \
    "{%0,%1,%2,%3,%4,%5,%6,%7,%8,%9,%10,%11,%12,%13,%14,%15,%16,%17,%18,%19,%20,%21,%22,%23,%24,%25,%26,%27,"       \
    "%28,%29,%30,%31,%32,%33,%34,%35,%36,%37,%38,%39,%40,%41,%42,%43,%44,%45,%46,%47,%48,%49,%50,%51,%52,%53,%54,%55}"
#define WG_OPS(C)                                                                                                   \
    C(d[0]), C(d[1]), C(d[2]), C(d[3]), C(d[4]), C(d[5]), C(d[6]), C(d[7]), C(d[8]), C(d[9]), C(d[10]), C(d[11]),   \
    C(d[12]), C(d[13]), C(d[14]), C(d[15]), C(d[16]), C(d[17]), C(d[18]), C(d[19]), C(d[20]), C(d[21]), C(d[22]),   \
    C(d[23]), C(d[24]), C(d[25]), C(d[26]), C(d[27]), C(d[28]), C(d[29]), C(d[30]), C(d[31]), C(d[32]), C(d[33]),   \
    C(d[34]), C(d[35]), C(d[36]), C(d[37]), C(d[38]), C(d[39]), C(d[40]), C(d[41]), C(d[42]), C(d[43]), C(d[44]),   \
    C(d[45]), C(d[46]), C(d[47]), C(d[48]), C(d[49]), C(d[50]), C(d[51]), C(d[52]), C(d[53]), C(d[54]), C(d[55])

template <int TA, int TB, int SB, bool INIT, uint32_t AH, uint32_t BH>
__device__ __forceinline__ void wgmma112(float (&d)[56], uint32_t alo, uint32_t blo) {
    if (INIT) {
        asm volatile("{\n.reg .pred p;\n.reg .b64 da, db;\nsetp.ne.b32 p, 0, 0;\nmov.b64 da, {%56, %61};\nmov.b64 db, {%57, %62};\n"
                     "wgmma.mma_async.sync.aligned.m64n112k16.f32.bf16.bf16 " WG_REGS ", da, db, p, 1, %59, %60, %58;\n}\n"
                     : WG_OPS("=f") : "r"(alo), "r"(blo), "n"(TB), "n"(SB), "n"(TA), "n"(AH), "n"(BH));
    } else {
        asm volatile("{\n.reg .pred p;\n.reg .b64 da, db;\nsetp.ne.b32 p, 1, 0;\nmov.b64 da, {%56, %61};\nmov.b64 db, {%57, %62};\n"
                     "wgmma.mma_async.sync.aligned.m64n112k16.f32.bf16.bf16 " WG_REGS ", da, db, p, 1, %59, %60, %58;\n}\n"
                     : WG_OPS("+f") : "r"(alo), "r"(blo), "n"(TB), "n"(SB), "n"(TA), "n"(AH), "n"(BH));
    }
}
__device__ __forceinline__ void acc_fence(float (&d)[56]) {
#pragma unroll
    for (int i = 0; i < 56; i++) asm volatile("" : "+f"(d[i])::"memory");
}

__device__ __forceinline__ uint32_t pack2(float lo, float hi) {
    uint32_t r;
    asm volatile("cvt.rn.bf16x2.f32 %0, %1, %2;" : "=r"(r) : "f"(hi), "f"(lo));
    return r;
}
__device__ __forceinline__ uint32_t movm(uint32_t a) {
    uint32_t r;
    asm volatile("movmatrix.sync.aligned.m8n8.trans.b16 %0, %1;" : "=r"(r) : "r"(a));
    return r;
}
__device__ __forceinline__ void stsm4(uint32_t addr, uint32_t a, uint32_t b, uint32_t c, uint32_t d) {
    asm volatile("stmatrix.sync.aligned.m8n8.x4.shared.b16 [%0], {%1,%2,%3,%4};" ::"r"(addr), "r"(a), "r"(b), "r"(c), "r"(d) : "memory");
}
__device__ __forceinline__ void sts1(uint32_t addr, uint32_t a) { asm volatile("st.shared.b32 [%0], %1;" ::"r"(addr), "r"(a) : "memory"); }
__device__ __forceinline__ uint32_t lds1(uint32_t addr) {
    uint32_t a;
    asm volatile("ld.shared.b32 %0, [%1];" : "=r"(a) : "r"(addr) : "memory");
    return a;
}
__device__ __forceinline__ void stg1(uint8_t* p, uint32_t a) { asm volatile("st.global.b32 [%0], %1;" ::"l"(p), "r"(a) : "memory"); }
__device__ __forceinline__ void st_part(uint8_t* p, const uint32_t* v, uint32_t parity) {
    asm volatile("{\n.reg .b64 x, y;\nmov.b64 x, {%1, %2};\nmov.b64 y, {%3, %4};\nst.relaxed.gpu.global.v2.b64 [%0], {x, y};\n}\n"
                 ::"l"(p), "r"((v[0] & ~1u) | parity), "r"(v[1]), "r"((v[2] & ~1u) | parity), "r"(v[3]) : "memory");
}
__device__ __forceinline__ void mma16816(float (&d)[4], const uint32_t (&a)[4], uint32_t b0, uint32_t b1) {
    asm volatile("mma.sync.aligned.m16n8k16.row.col.f32.bf16.bf16.f32 {%0,%1,%2,%3}, {%4,%5,%6,%7}, {%8,%9}, {%0,%1,%2,%3};"
                 : "+f"(d[0]), "+f"(d[1]), "+f"(d[2]), "+f"(d[3]) : "r"(a[0]), "r"(a[1]), "r"(a[2]), "r"(a[3]), "r"(b0), "r"(b1));
}
__device__ __forceinline__ uint32_t add2(uint32_t a, uint32_t b) {
    uint32_t r;
    asm("add.rn.bf16x2 %0, %1, %2;" : "=r"(r) : "r"(a), "r"(b));
    return r;
}
__device__ __forceinline__ uint32_t max2(uint32_t a, uint32_t b) {
    uint32_t r;
    asm("max.bf16x2 %0, %1, %2;" : "=r"(r) : "r"(a), "r"(b));
    return r;
}
__device__ __forceinline__ void ld_tagged(const uint8_t* p, uint32_t& a, uint32_t& ta, uint32_t& b, uint32_t& tb) {
    asm volatile("{\n.reg .b64 x, y;\nld.relaxed.gpu.global.v2.b64 {x, y}, [%4];\nmov.b64 {%0, %1}, x;\nmov.b64 {%2, %3}, y;\n}\n"
                 : "=r"(a), "=r"(ta), "=r"(b), "=r"(tb) : "l"(p) : "memory");
}
__device__ __forceinline__ float bf_lo(uint32_t v) { return __uint_as_float(v << 16); }
__device__ __forceinline__ float bf_hi(uint32_t v) { return __uint_as_float(v & 0xFFFF0000u); }
__device__ __forceinline__ float rcp(float x) { float r; asm("rcp.approx.ftz.f32 %0, %1;" : "=f"(r) : "f"(x)); return r; }
__device__ __forceinline__ float ex2(float x) { float r; asm volatile("ex2.approx.ftz.f32 %0, %1;" : "=f"(r) : "f"(x)); return r; }

__device__ __forceinline__ uint32_t full_bar(int stage) { return base + BAR_FULL + (stage & 7) * 8; }
__device__ __forceinline__ void wait_released(int j) { mbar_wait(base + BAR_EMPTY + (j & 7) * 8, (j >> 3) & 1); }

template <int V>
struct Int { static constexpr int value = V; };

__host__ __device__ constexpr int bslot_e(int i) { return (i < 2 || i >= 14) ? (i + 5) % 7 : (i + 1) % 5; }
__host__ __device__ constexpr int bslot_l(int i) { return i % 6; }

template <uint32_t OFF>
struct Feed {
    int stage;
    uint32_t dst;
    __device__ __forceinline__ void seek(int i, int slot) { stage = i; dst = base + OFF + slot * SLOT; }
    template <int N>
    __device__ __forceinline__ uint32_t acquire() { wait_released(stage - N); return full_bar(stage); }
    template <int N>
    __device__ __forceinline__ void next() {
        stage++;
        dst += SLOT;
        if (dst == base + OFF + N * SLOT) dst = base + OFF;
    }
};
__device__ __forceinline__ int skip_own(int n, int mt) { return n == mt ? 15 : n; }

struct Desc { uint32_t lo, hi; };
__host__ __device__ constexpr Desc desc_const(uint32_t lbo, uint32_t sbo, uint32_t mode) { return {(lbo >> 4) << 16, (sbo >> 4) | (mode << 30)}; }
constexpr Desc D_K128 = desc_const(16, 1024, 1);
constexpr Desc D_N128 = desc_const(8192, 1024, 1);
constexpr Desc D_BLOB = desc_const(128, 256, 0);
constexpr Desc D_OT = desc_const(2048, 128, 0);

enum Kind { XW, XWN, QK, BIG, OUT };

struct Ring {
    int stage;
    uint32_t a, b;
    uint32_t wg;
    uint32_t zero;
    bool releaser;
    __device__ __forceinline__ void seek(int i, int bslot) {
        stage = i;
        a = (base + (i % NA) * SLOT) >> 4;
        b = (base + BRING + bslot * SLOT) >> 4;
    }
    __device__ __forceinline__ void wait() { mbar_wait(full_bar(stage), (stage >> 3) & 1); }
    __device__ __forceinline__ void take_turn() { nb_sync(1 + wg, 256); }
    __device__ __forceinline__ void pin() {
        uint32_t n = 0;
#pragma unroll 1
        do {
            asm volatile("pmevent 7;" ::: "memory");
        } while (n++ < zero);
    }
    __device__ __forceinline__ void mma_begin() {
        pin();
        if (!wg) take_turn();
        pin();
    }
    __device__ __forceinline__ void mma_end() {
        pin();
        if (wg) nb_arrive(3, 256);
        nb_sync(3 - wg, 256);
    }
    template <Kind K, int NBS, bool INIT, int SB = 1, bool TAIL = false>
    __device__ __forceinline__ void run(float (&d)[56], float (&e)[56], bool first = true, bool last = true, bool more = true) {
        if (first) take_turn();
        asm volatile("wgmma.fence.sync.aligned;" ::: "memory");
        if (K == QK) {
            const uint32_t da = D_K128.lo + (base >> 4) + (stage >> 1) * (SLOT >> 4) + (stage & 1) * 4 + wg * 512, db = D_N128.lo + b;
            wgmma112<0, 1, 1, INIT, D_K128.hi, D_N128.hi>(d, da, db);
            wgmma112<0, 1, 1, INIT, D_K128.hi, D_N128.hi>(e, da, db + 256);
            wgmma112<0, 1, 1, false, D_K128.hi, D_N128.hi>(d, da + 2, db + 128);
            wgmma112<0, 1, 1, false, D_K128.hi, D_N128.hi>(e, da + 2, db + 384);
        } else {
            constexpr int TA = K == OUT, TB = K != XW;
            constexpr uint32_t sa = K == OUT ? 256 : 2, sb = K == XW ? 2 : K == BIG ? 224 : 128;
            constexpr Desc A = K == OUT ? D_OT : D_K128, B = K == XW ? D_K128 : K == BIG ? D_BLOB : D_N128;
            const uint32_t da = A.lo + a + wg * (K == OUT ? 64 : 512), db = B.lo + b;
            wgmma112<TA, TB, SB, INIT, A.hi, B.hi>(d, da, db);
            wgmma112<TA, TB, SB, false, A.hi, B.hi>(d, da + sa, db + sb);
            wgmma112<TA, TB, SB, false, A.hi, B.hi>(d, da + 2 * sa, db + 2 * sb);
            wgmma112<TA, TB, SB, false, A.hi, B.hi>(d, da + 3 * sa, db + 3 * sb);
        }
        asm volatile("wgmma.commit_group.sync.aligned;" ::: "memory");
        if (!TAIL) asm volatile("wgmma.wait_group.sync.aligned 1;" ::: "memory");
        if (last) nb_arrive(2 - wg, 256);
        if (!TAIL && stage > 0) {
            if (SPLIT_DUTY == 2) {
                if (releaser) mbar_arrive(base + BAR_EMPTY + ((stage - 1) & 7) * 8);
            } else if (wg && elect()) {
                mbar_arrive(base + BAR_EMPTY + ((stage - 1) & 7) * 8);
            }
        }
        stage++;
        a += SLOT >> 4;
        if (a == (base + NA * SLOT) >> 4) a = base >> 4;
        b += SLOT >> 4;
        if (b == (base + BRING + NBS * SLOT) >> 4) b = (base + BRING) >> 4;
        if (more && (SPLIT_DUTY == 2 || !wg)) wait();
    }
    template <Kind K, int NBS, bool INIT, int SB = 1, bool TAIL = false>
    __device__ __forceinline__ void run(float (&d)[56], bool first = true, bool last = true, bool more = true) {
        run<K, NBS, INIT, SB, TAIL>(d, d, first, last, more);
    }
};

__device__ __forceinline__ void pack_all(const float (&d)[56], uint32_t (&p)[28]) {
#pragma unroll
    for (int i = 0; i < 28; i++) p[i] = pack2(d[2 * i], d[2 * i + 1]);
}
template <int I0, int I1>
__device__ __forceinline__ void store_frags(uint8_t* dst, const uint32_t (&p)[28]) {
#pragma unroll
    for (int i = I0; i < I1; i++) stg1(dst + i * 128, p[i]);
}
template <int I0, int I1>
__device__ __forceinline__ void stage_frags(uint32_t lane_addr, const uint32_t (&p)[28]) {
#pragma unroll
    for (int i = I0; i < I1; i += 4) stsm4(lane_addr + i * 128, p[i], p[i + 1], p[i + 2], p[i + 3]);
}
template <class F>
__device__ __forceinline__ void store_out(F frag, int lane, uint32_t slab, const CUtensorMap* m, int c0, int c1) {
    const bool swap = lane & 16;
    const uint32_t addr = slab + (lane & 7) * 224 + ((lane >> 3) ^ ((lane >> 2) & 1)) * 16;
#pragma unroll
    for (int h = 0; h < 2; h++) {
#pragma unroll
        for (int c = 0; c < 14; c += 4) {
            const uint32_t t0 = frag(2 * c + h), t1 = frag(2 * c + 2 + h);
            if (c < 12) {
                const uint32_t t2 = frag(2 * c + 4 + h), t3 = frag(2 * c + 6 + h);
                stsm4(addr + h * 1792 + c * 16, swap ? t1 : t0, swap ? t0 : t1, swap ? t3 : t2, swap ? t2 : t3);
            } else {
                asm volatile("stmatrix.sync.aligned.m8n8.x2.shared.b16 [%0], {%1,%2};" ::"r"(addr + h * 1792 + c * 16), "r"(swap ? t1 : t0), "r"(swap ? t0 : t1) : "memory");
            }
        }
        fence_async_smem();
        __syncwarp();
        if (elect()) tma_st2(m, c0, c1 + 8 * h, slab + h * 1792);
    }
    if (elect()) {
        bulk_commit();
        bulk_wait_read();
    }
}
__host__ __device__ constexpr int tile_of(int t) { return 7 * (t >> 2) + 3 * ((t >> 1) & 1) + 2 * (t & 1); }

struct Role {
    bool H;
    int L, mt, ns, id;
    int kind, a0, a1, b3;
};
template <bool BY_SM>
__device__ __forceinline__ Role decode_role() {
    uint32_t sm;
    if (BY_SM) asm volatile("mov.u32 %0, %%smid;" : "=r"(sm));
    else asm volatile("mov.u32 %0, %%ctaid.x;" : "=r"(sm));
    const int tpc = sm >> 1, q2 = ((tpc - 32) * 37) >> 8;
    const int gpc = tpc < 32 ? tpc & 7 : tpc < 60 ? tpc - 31 - 7 * q2 : 0;
    const int pos = tpc < 32 ? tpc >> 3 : tpc < 60 ? q2 + 4 : tpc - 56;
    Role r;
    r.H = sm >= 128;
    const int grp = (GPC_MAP >> (4 * gpc)) & 7;
    r.L = grp & 1;
    r.mt = (grp >> 1) * 4 + (pos >> 1);
    r.ns = (pos & 1) * 2 + (sm & 1);
    r.id = r.H ? sm : grp * 16 + pos * 2 + (sm & 1);
    r.kind = r.H ? 2 : r.L;
    r.a0 = r.L ? (r.mt >> 3) * 448 : 0;
    r.a1 = r.L ? (r.mt & 7) * 128 : r.H ? 120 : r.mt * 64;
    r.b3 = r.H ? 4 + r.ns : r.L ? r.ns : 0;
    return r;
}

__device__ __forceinline__ void first_fill(const Maps& maps, const Role& r, int i) {
    const bool E = r.kind == 0;
    const CUtensorMap* ma = &maps.m[r.kind];
    const uint32_t bar = full_bar(i);
    const int k = (i * 64) >> r.L;
    const bool has_a = !(i & r.L), has_b = i < 7 - r.L;
    const uint32_t dst = base + BRING + (E ? (0x2104365u >> (4 * i)) & 7 : i) * SLOT;
    mbar_expect(bar, (has_a ? SLOT : 0) + (has_b ? (E ? BLOB : SLOT) : 0));
    if (has_a) tma_ld4(base + (i >> r.L) * SLOT, ma, r.a0 + k, r.a1, 0, 0, bar);
    if (has_b) {
        tma_ld4(dst, ma + 3, E ? k : 0, E ? r.ns * 112 : k, 0, r.b3, bar);
        if (!E) tma_ld4(dst + 8192, ma + 3, 64, k, 0, r.b3, bar);
        mbar_arrive(bar);
    }
}
static_assert(bslot_e(0) == 5 && bslot_e(1) == 6 && bslot_e(2) == 3 && bslot_e(3) == 4 && bslot_e(4) == 0 && bslot_e(6) == 2, "");

template <bool BY_SM>
__global__ void __launch_bounds__(384, 1) fused_kernel(Scratch* sc, const __grid_constant__ Maps maps) {
    const unsigned t_open = clk32();
    const int warp = __shfl_sync(0xffffffffu, threadIdx.x >> 5, 0);
    if (warp == 8) {
        if (elect()) {
#pragma unroll
            for (int i = 0; i < LEAD; i++) mbar_init(base + BAR_FULL + i * 8, 2);
            asm volatile("fence.mbarrier_init.release.cluster;" ::: "memory");
            const Role r = decode_role<BY_SM>();
#pragma unroll 1
            for (int i = 0; i < LEAD; i++) {
                first_fill(maps, r, i);
            }
        }
    }
    if (warp == 9) {
        if (elect()) {
#pragma unroll
            for (int i = 0; i < 8; i++) mbar_init(base + BAR_EMPTY + i * 8, 4);
            asm volatile("fence.mbarrier_init.release.cluster;" ::: "memory");
        }
    } else if (warp == 10) {
        if (elect()) {
#pragma unroll
            for (int i = 0; i < 3; i++) mbar_init(base + BAR_RDY + i * 8, i < 2 ? 4 : 8);
#pragma unroll
            for (int i = 0; i < 2; i++) mbar_init(base + BAR_HALO + i * 8, 1);
            asm volatile("fence.mbarrier_init.release.cluster;" ::: "memory");
        }
    } else if (warp == 11) {
        if (elect()) {
#pragma unroll
            for (int i = LEAD; i < 8; i++) mbar_init(base + BAR_FULL + i * 8, 2);
#pragma unroll
            for (int i = 0; i < 3; i++) mbar_init(base + BAR_DEP + i * 8, 1);
#pragma unroll
            for (int i = 0; i < 2; i++) mbar_init(base + BAR_PART + i * 8, 1);
            asm volatile("fence.mbarrier_init.release.cluster;" ::: "memory");
        }
    }
    __syncthreads();

    const Role role = decode_role<BY_SM>();
    int lane = threadIdx.x & 31;
    asm volatile("" : "+r"(lane));
    const bool roleH = role.H;
    const int roleL = role.L, mt = role.mt, ns = role.ns, bid = role.id;
    const int par = mt >> 3, blk = mt & 7, col = ns * 112;

    if (__builtin_expect(warp >= 8, 1)) {
        asm volatile("setmaxnreg.dec.sync.aligned.u32 56;");
#define PROF_FEED_A
#define PROF_FEED_B
        if (__builtin_expect(warp == 8, 1)) {
            if (elect()) {
                PROF(129);
#pragma unroll 1
                for (int i = LEAD; i < 7; i++) {
                    while (clk32() - t_open < i * PACE) {}
                    first_fill(maps, role, i);
                }
                PROF(134);
                Feed<0> f;
                const int row = mt * 128;
                auto c_run = [&](const CUtensorMap* m, int off, int n0, int n1) {
#pragma unroll 1
                    for (int n = n0; n < n1; n++) {
                        const uint32_t bar = f.acquire<NA>();
                        mbar_expect(bar, SLOT);
                        tma_ld2(f.dst, m, (off + skip_own(n, mt)) * 64, row, bar);
                        PROF_FEED_A;
                        f.next<NA>();
                    }
                };
                if (roleH) {
                } else if (!roleL) {
                    f.seek(14, 0);
                    mbar_wait(base + BAR_RDY, 0);
#pragma unroll 1
                    for (int i = 0; i < 4; i++) {
                        const uint32_t bar = f.acquire<NA>();
                        mbar_expect(bar, SLOT);
                        tma_ld2(f.dst, &maps.m[M_CR + (i >> 1)], ((i & 1) * 16 + mt) * 64, row, bar);
                        mbar_arrive(bar);
                        PROF_FEED_A;
                        f.next<NA>();
                    }
                    c_run(&maps.m[M_CR], 0, 0, 15);
                    c_run(&maps.m[M_CI], 0, 0, NBE);
                    wait_dep(2);
#pragma unroll 1
                    for (int i = 0; i < 7; i++) {
                        const uint32_t bar = f.acquire<NA>();
                        mbar_expect(bar, SLOT);
                        bulk_ld(f.dst, sc->o + (size_t)(mt * 7 + i) * SLOT, SLOT, bar);
                        PROF_FEED_A;
                        f.next<NA>();
                    }
                } else {
#pragma unroll 1
                    for (int i = 4; i < 7; i++) {
                        wait_released(2 * i - 8);
                        mbar_expect(full_bar(2 * i), SLOT);
                        tma_ld4(base + i * SLOT, &maps.m[M_XA], par * 448 + i * 64, blk * 128, 0, 0, full_bar(2 * i));
                    }
                    wait_released(HALO_K_AT);
                    mbar_arrive(base + BAR_DEP + 16);
                    f.seek(21, 0);
                    c_run(&maps.m[M_CR], 16, 0, 15);
                    c_run(&maps.m[M_CI], 16, 0, 15);
                    c_run(&maps.m[M_CI], 0, NBE, 15);
                }
            }
        } else if (warp == 11) {
            if (elect()) {
                Feed<BRING> f;
                auto blob_run = [&](auto nbs, int quarter, int n0, int n1) {
                    constexpr int N = decltype(nbs)::value;
                    const uint8_t* src = sc->ab + (size_t)(quarter * 64 + ns) * BLOB;
#pragma unroll 1
                    for (int n = n0; n < n1; n++) {
                        const uint32_t bar = f.template acquire<N>();
                        mbar_expect(bar, BLOB);
                        bulk_ld(f.dst, src + skip_own(n, mt) * (4 * BLOB), BLOB, bar);
                        PROF_FEED_B;
                        f.template next<N>();
                    }
                };
                auto w_run = [&](auto nbs, const CUtensorMap* m, int slice, bool no_a) {
                    constexpr int N = decltype(nbs)::value;
#pragma unroll 1
                    for (int i = 0; i < 7; i++) {
                        const uint32_t bar = f.template acquire<N>();
                        mbar_expect(bar, SLOT);
                        tma_ld4(f.dst, m, 0, i * 64, 0, slice, bar);
                        tma_ld4(f.dst + 8192, m, 64, i * 64, 0, slice, bar);
                        if (no_a) mbar_arrive(bar);
                        PROF_FEED_B;
                        f.template next<N>();
                    }
                };
                if (roleH) {
                    f.seek(7, 0);
                    w_run(Int<7>(), &maps.m[M_WV], 8 + ns, true);
                } else if (!roleL) {
                    f.seek(7, bslot_e(7));
#pragma unroll 1
                    for (int i = 0; i < 7; i++) {
                        const uint32_t bar = f.acquire<5>();
                        mbar_expect(bar, BLOB);
                        tma_ld2(f.dst, &maps.m[M_WI], i * 64, col, bar);
                        mbar_arrive(bar);
                        PROF_FEED_B;
                        f.next<5>();
                    }
                    f.seek(18, bslot_e(18));
                    wait_dep(0);
                    blob_run(Int<7>(), 0, 0, 15);
                    wait_dep(1);
                    blob_run(Int<7>(), 2, 0, NBE);
                    w_run(Int<7>(), &maps.m[M_WO], ns, false);
                } else {
                    f.seek(6, 0);
#pragma unroll 1
                    for (int i = 6; i < 14; i++) {
                        const uint32_t bar = f.acquire<6>();
                        mbar_expect(bar, SLOT);
                        tma_ld4(f.dst, &maps.m[M_WQK], 0, i * 32, 0, ns, bar);
                        tma_ld4(f.dst + 8192, &maps.m[M_WQK], 64, i * 32, 0, ns, bar);
                        if (i & 1) mbar_arrive(bar);
                        PROF_FEED_B;
                        f.next<6>();
                    }
                    w_run(Int<6>(), &maps.m[M_WV], 8 + ns, true);
                    wait_dep(0);
                    blob_run(Int<6>(), 1, 0, 15);
                    wait_dep(1);
                    blob_run(Int<6>(), 3, 0, 15);
                    blob_run(Int<6>(), 2, NBE, 15);
                }
            }
        } else if (roleH) {
            if (elect()) {
                wait_released(warp == 9 ? 0 : 7);
#pragma unroll 1
                for (int i = 0; i < 7; i++) {
                    if (warp == 9) {
                        asm volatile("cp.async.bulk.prefetch.tensor.2d.L2.global [%0, {%1, %2}];" ::"l"(&maps.m[M_WI]), "r"(i * 64), "r"(col) : "memory");
                    } else {
                        asm volatile("cp.async.bulk.prefetch.tensor.4d.L2.global [%0, {%1, %2, 0, %3}];" ::"l"(&maps.m[M_WO]), "r"(0), "r"(i * 64), "r"(ns) : "memory");
                        asm volatile("cp.async.bulk.prefetch.tensor.4d.L2.global [%0, {%1, %2, 0, %3}];" ::"l"(&maps.m[M_WO]), "r"(64), "r"(i * 64), "r"(ns) : "memory");
                    }
                }
            }
        } else if (warp == 10) {
            if (elect()) {
                unsigned* epoch_ptr = &sc->epoch[(bid * 4 + 2) * 8];
                const unsigned ep = *epoch_ptr + 1;
                sts1(base + TAG, ep);
                asm volatile("prefetch.tensormap [%0];" ::"l"(&maps.m[M_OUTA + roleL]) : "memory");
                await(sc, CNT_A + roleL * 4 + ns, ep * 16);
                mbar_arrive(base + BAR_DEP);
                PROF(150);
                await(sc, CNT_B + ns, ep * 16);
                mbar_arrive(base + BAR_DEP + 8);
                PROF(151);
                if (!roleL) {
                    await(sc, CNT_O + mt, ep * 4);
                    mbar_arrive(base + BAR_DEP + 16);
                } else {
                    await(sc, CNT_P + mt * 4 + ns, ep * 2 - 1);
                    mbar_arrive(base + BAR_PART);
                    PROF(153);
                    await(sc, CNT_P + mt * 4 + ns, ep * 2);
                    mbar_arrive(base + BAR_PART + 8);
                }
                PROF(152);
                *epoch_ptr = ep;
            }
        } else if (!roleL) {
            if (elect()) {
                mbar_wait(base + BAR_RDY, 0);
                PROF(130);
                signal(sc, CNT_A + ns);
                PROF(131);
                mbar_wait(base + BAR_RDY + 8, 0);
                signal(sc, CNT_A + 4 + ns);
                PROF(135);
                mbar_wait(base + BAR_RDY + 16, 0);
                PROF(132);
                signal(sc, CNT_B + ns);
                PROF(133);
            }
        } else {
            unsigned* epoch_ptr = &sc->epoch[(bid * 4 + 1) * 8];
            const unsigned tag = *epoch_ptr + 1;
#pragma unroll 1
            for (int kv = 0; kv < 2; kv++) {
                uint32_t v[16];
#pragma unroll
                for (int i = 0; i < 16; i++) v[i] = 0;
                if (kv) wait_released(HALO_V_AT - 4), wait_released(HALO_V_AT);
                else mbar_wait(base + BAR_DEP + 16, 0);
                if (blk > 0) {
                    const uint8_t* src = sc->halo + (size_t)(((mt - 1) * 4 + ns) * 2 + kv) * 2048 + lane * 16;
#pragma unroll 1
                    for (int n = 0; n < SPIN_LIMIT; n++) {
                        uint32_t stale = 0;
#pragma unroll
                        for (int i = 0; i < 4; i++) ld_tagged(src + i * 512, v[4 * i], v[4 * i + 1], v[4 * i + 2], v[4 * i + 3]);
#pragma unroll
                        for (int i = 0; i < 16; i += 2) stale |= v[i] ^ tag;
                        if (__all_sync(0xffffffffu, !(stale & 1))) break;
                    }
#pragma unroll
                    for (int c = 0; c < 14; c += 2) v[c] = (v[c] & ~1u) | ((v[15] >> c) & 1);
                }
#pragma unroll
                for (int i = 0; i < 14; i++) sts1(base + HALO + kv * (8 * HSLOT) + i * 128 + lane * 4, v[i]);
                warp_arrive(base + BAR_HALO + kv * 8);
                if (lane == 0) PROF(142 + kv);
            }
            if (elect()) {
                mbar_wait(base + BAR_RDY + 16, 0);
                PROF(130);
                signal(sc, CNT_O + mt);
                PROF(131);
                *epoch_ptr = tag;
            }
        }
    } else {
        asm volatile("setmaxnreg.inc.sync.aligned.u32 224;");
        Ring r;
        r.wg = warp >> 2;
        r.zero = blockIdx.y;
        r.releaser = lane + 1 == (warp >> 2);
        const int wg = warp >> 2;
        if (wg) nb_arrive(1, 256);
        uint8_t* part = sc->part + (size_t)(ns * 16 + mt) * (2 * BLOB) + warp * 512 + lane * 16;
        uint32_t p[28];

        if (roleH) {
            unsigned* epoch_ptr = &sc->epoch[bid * 4 * 8];
            const unsigned tag = *epoch_ptr + 1;
            uint8_t* hout = sc->halo + (size_t)((warp * 8 + ns) * 2) * 2048 + lane * 16;
            auto send = [&](int kv) {
#pragma unroll
                for (int h = 0; h < 2; h++) {
                    uint32_t v[16];
                    v[14] = v[15] = 0;
#pragma unroll
                    for (int c = 0; c < 14; c++) v[c] = p[2 * c + h];
#pragma unroll
                    for (int c = 0; c < 14; c += 2) v[15] |= (v[c] & 1) << c;
#pragma unroll
                    for (int i = 0; i < 4; i++) st_part(hout + (h * 8 + kv) * 2048 + i * 512, v + 4 * i, tag & 1);
                }
            };
            float x0[56], x1[56];
            r.seek(0, 0);
            r.wait();
            r.run<XWN, 7, true>(x0);
#pragma unroll 1
            for (int i = 1; i < 7; i++) r.run<XWN, 7, false>(x0);
            r.run<XWN, 7, true>(x1);
            acc_fence(x0);
            pack_all(x0, p);
            send(0);
#pragma unroll 1
            for (int i = 1; i < 7; i++) r.run<XWN, 7, false>(x1, true, true, i < 6);
            asm volatile("wgmma.wait_group.sync.aligned 0;" ::: "memory");
            acc_fence(x1);
            pack_all(x1, p);
#pragma unroll
            for (int i = 0; i < 28; i++) p[i] = movm(p[i]);
            send(1);
            if (threadIdx.x == 0) *epoch_ptr = tag;
        } else if (!roleL) {
            uint8_t* blob = sc->ab + (size_t)((wg * 16 + mt) * 4 + ns) * BLOB + (warp & 3) * WSLOT + lane * 4;
            const uint32_t own = base + BRING + wg * SLOT + (warp & 3) * WSLOT + lane * 16;
            float x0[56], x1[56];
            r.seek(0, bslot_e(0));
            r.wait();
            r.run<XW, 7, true>(x0);
            r.run<XW, 7, false>(x0);
            r.seek(2, bslot_e(2));
#pragma unroll 1
            for (int i = 2; i < 7; i++) r.run<XW, 5, false>(x0);

            r.seek(7, bslot_e(7));
            r.run<XW, 5, true, -1>(x1);
            acc_fence(x0);
            pack_all(x0, p);
#pragma unroll
            for (int i = 0; i < 2; i++) {
                if (wg == i) store_frags<0, 14>(blob, p);
                else stage_frags<0, A_OWN>(own + 5 * SLOT, p);
                r.run<XW, 5, false, -1>(x1);
                if (wg == i) {
                    store_frags<14, 28>(blob, p);
                    warp_arrive(base + BAR_RDY + i * 8);
                } else {
                    stage_frags<A_OWN, 2 * A_OWN>(own + 5 * SLOT, p);
                }
                r.run<XW, 5, false, -1>(x1);
            }
            stage_frags<2 * A_OWN, A_OWN2>(own + 5 * SLOT, p);
            r.run<XW, 5, false, -1>(x1);
            stage_frags<A_OWN2, 28>(own + 5 * SLOT, p);
            fence_async_smem();
            r.run<XW, 5, false, -1>(x1);

            r.seek(14, bslot_e(14));
            r.run<BIG, 7, true>(x0);
            acc_fence(x1);
            pack_all(x1, p);
            stage_frags<0, B_OWN>(own, p);
            r.run<BIG, 7, false>(x0);
            stage_frags<B_OWN, 28>(own, p);
            fence_async_smem();
            blob += (size_t)128 * BLOB;
#pragma unroll
            for (int i = 0; i < 28; i++) {
                if (i % B_SLICE == 0) r.run<BIG, 7, false>(x0);
                stg1(blob + i * 128, p[i]);
            }
            warp_arrive(base + BAR_RDY + 16);
#pragma unroll 1
            for (int i = 17 + 27 / B_SLICE; i < POUT; i++) r.run<BIG, 7, false>(x0);

            const uint32_t tag = lds1(base + TAG);
            r.seek(POUT, bslot_e(POUT));
            r.run<OUT, 7, true>(x1);
            acc_fence(x0);
            pack_all(x0, p);
#pragma unroll
            for (int k = 0; k < 3; k++) {
                if (k < 2 && wg == k) {
                    if ((warp & 3) == 0 && elect())
                        asm volatile("red.relaxed.gpu.global.add.u32 [%0], 1;" ::"l"(&sc->cnt[(CNT_P + mt * 4 + ns) * 32]) : "memory");
#pragma unroll
                    for (int i = 0; i < 4; i++) st_part(part + i * 4096, p + 4 * i, tag & 1);
                }
                if (k > 0 && wg == k - 1) {
#pragma unroll
                    for (int i = 4; i < 7; i++) st_part(part + i * 4096, p + 4 * i, tag & 1);
                }
                if (k < 2) r.run<OUT, 7, false>(x1);
            }
#pragma unroll
            for (int i = 3; i < 7; i++) r.run<OUT, 7, false, 1, true>(x1, i <= 7 - TURN, i < 7 - TURN || i == 6, i < 6);

            asm volatile("wgmma.wait_group.sync.aligned 0;" ::: "memory");
            acc_fence(x1);
            const uint32_t slab = base + (wg ? BRING + bslot_e(ELAST - 6) * SLOT : ((ELAST - 6) % NA) * SLOT) + (warp & 3) * WSLOT;
            store_out([&](int i) { return pack2(x1[2 * i], x1[2 * i + 1]); }, lane, slab, &maps.m[M_OUTA], par * 896 + col, blk * 128 + warp * 16);
        } else {
            const int g = lane >> 2, tig = lane & 3;
            const uint32_t hin = base + HALO + warp * HSLOT + lane * 4;
            const uint32_t hpub = warp < 7 ? hin + HSLOT : base + HSPARE + lane * 4;
            auto publish = [&](const uint32_t (&h)[14], int c0, int c1) {
#pragma unroll
                for (int c = 0; c < 14; c++)
                    if (c >= c0 && c < c1) sts1(hpub + c * 128, h[c]);
            };
            float y0[56], y1[56], y2[56];
            r.seek(0, 0);
            r.wait();
            r.run<QK, 6, true>(y0, y1);
#pragma unroll 1
            for (int i = 1; i < 14; i++) r.run<QK, 6, false>(y0, y1);

            uint32_t m1[8][4], m0[8][4], lo[14], hi[14], q[2][8][2];
            auto pack_q = [&](int b) {
                uint32_t v[14];
#pragma unroll
                for (int c = 0; c < 14; c++) v[c] = pack2(y0[4 * c + 2 * b], y0[4 * c + 2 * b + 1]);
#pragma unroll
                for (int t = 0; t < 8; t++) {
                    const int c = tile_of(t);
                    q[b][t][0] = (t & 3) == 2 ? (tig >= 2 ? v[c] : 0u) : v[c];
                    q[b][t][1] = (t & 3) == 1 ? (tig < 2 ? v[c + 1] : 0u) : v[c + 1];
                }
            };
            auto fetch = [&](uint32_t src, int hp, int i0) {
#pragma unroll
                for (int t = 4 * hp; t < 4 * hp + 4; t++) {
                    m0[t][i0] = (t & 3) == 2 ? dup(m0[t - 1][3], r.zero) : lds1(src + tile_of(t) * 128);
                    m0[t][3] = lds1(src + tile_of(t) * 128 + 128);
                }
            };
            r.seek(14, bslot_l(14));
            r.run<XWN, 6, true>(y2);
            acc_fence(y0);
            acc_fence(y1);
#pragma unroll
            for (int c = 0; c < 14; c++) hi[c] = pack2(y1[4 * c + 2], y1[4 * c + 3]);
            publish(hi, 0, 7);
            PIN;
            r.run<XWN, 6, false>(y2);
            publish(hi, 7, 14);
#pragma unroll
            for (int c = 0; c < 14; c++) lo[c] = pack2(y1[4 * c], y1[4 * c + 1]);
#pragma unroll
            for (int t = 0; t < 8; t++) {
                const int c = tile_of(t);
                const bool shared = (t & 3) == 2;
                m1[t][0] = shared ? dup(lo[c], r.zero) : lo[c];
                m1[t][1] = shared ? dup(hi[c], r.zero) : hi[c];
                m1[t][2] = lo[c + 1];
                m1[t][3] = hi[c + 1];
                m0[t][0] = dup(m1[t][0], r.zero);
                m0[t][2] = dup(lo[c + 1], 2 * r.zero);
            }
            PIN;
            r.run<XWN, 6, false>(y2);
            if (warp == 0) mbar_wait(base + BAR_HALO, 0);
            fetch(hin, 0, 1);
            pack_q(1);
            PIN;
            r.run<XWN, 6, false>(y2);
            fetch(hin, 1, 1);
            pack_q(0);
            r.mma_begin();
            float s[8][4];
#pragma unroll
            for (int step = 0; step < 2; step++) {
#pragma unroll
                for (int i = 0; i < 8; i++) {
                    const int b = 1 - (i >> 2), h = i & 3, t = 2 * h + step;
                    float (&d)[4] = s[2 * h + b];
                    if (step == 0) d[0] = d[1] = d[2] = d[3] = 0.f;
                    mma16816(d, b ? m1[t] : m0[t], q[b][t][0], q[b][t][1]);
                }
            }
            r.mma_end();
            r.run<XWN, 6, false>(y2, false);

            uint32_t pr[8], mx[4], mx1[4];
            {
                const bool cur0 = g <= 2 * tig, cur1 = g <= 2 * tig + 1;
#pragma unroll
                for (int i = 0; i < 8; i++) {
                    const int c = (i & 1) ? 2 : 0;
                    pr[i] = movm(pack2(cur0 ? s[i][c] : s[i][2 - c], cur1 ? s[i][c + 1] : s[i][3 - c]));
                }
            }
            PIN;
            r.run<XWN, 6, false>(y2);
            const uint32_t curmask = (2 * tig <= g ? 0x0000FFFFu : 0u) | (2 * tig + 1 <= g ? 0xFFFF0000u : 0u);
            {
                const uint32_t keep = (blk == 0 && warp == 0) ? curmask : 0xFFFFFFFFu;
#pragma unroll
                for (int i = 0; i < 4; i++) {
                    pr[2 * i] = (pr[2 * i] & keep) | (0xCF9ECF9Eu & ~keep);
                    mx[i] = max2(__byte_perm(pr[2 * i], pr[2 * i + 1], 0x5410), __byte_perm(pr[2 * i], pr[2 * i + 1], 0x7632));
                    mx1[i] = __shfl_xor_sync(0xffffffffu, mx[i], 1);
                }
            }
            PIN;
            r.run<XWN, 6, false>(y2);
#pragma unroll
            for (int i = 0; i < 4; i++) {
                mx[i] = max2(mx[i], mx1[i]);
                mx1[i] = __shfl_xor_sync(0xffffffffu, mx[i], 2);
            }

            PIN;
            r.seek(21, bslot_l(21));
            r.run<BIG, 6, true>(y0);
            acc_fence(y2);
#pragma unroll
            for (int c = 0; c < 10; c++) hi[c] = movm(pack2(y2[4 * c + 2], y2[4 * c + 3]));
            constexpr float SCL = 0.18898223650461362f * 1.4426950408889634f;
            float e0[8], e1[8], sm[8], sm1[8];
#pragma unroll
            for (int i = 0; i < 8; i++) {
                const uint32_t m2 = max2(mx[i >> 1], mx1[i >> 1]);
                sm[i] = ((i & 1) ? bf_hi(m2) : bf_lo(m2)) * -SCL;
            }
            PIN;
            r.run<BIG, 6, false>(y0);
#pragma unroll
            for (int c = 10; c < 14; c++) hi[c] = movm(pack2(y2[4 * c + 2], y2[4 * c + 3]));
#pragma unroll
            for (int c = 0; c < 4; c++) lo[c] = movm(pack2(y2[4 * c], y2[4 * c + 1]));
#pragma unroll
            for (int i = 0; i < 8; i++) e0[i] = ex2(fmaf(bf_lo(pr[i]), SCL, sm[i]));
            PIN;
            r.run<BIG, 6, false>(y0);
            publish(hi, 0, 10);
#pragma unroll
            for (int i = 0; i < 8; i++) e1[i] = ex2(fmaf(bf_hi(pr[i]), SCL, sm[i]));
            PIN;
            r.run<BIG, 6, false>(y0);
            publish(hi, 10, 14);
#pragma unroll
            for (int i = 0; i < 8; i++) {
                sm[i] = e0[i] + e1[i];
                sm1[i] = __shfl_xor_sync(0xffffffffu, sm[i], 1);
            }
            PIN;
            r.run<BIG, 6, false>(y0);
#pragma unroll
            for (int c = 4; c < 14; c++) lo[c] = movm(pack2(y2[4 * c], y2[4 * c + 1]));
            PIN;
            r.run<BIG, 6, false>(y0);
#pragma unroll
            for (int i = 0; i < 8; i++) {
                sm[i] += sm1[i];
                sm1[i] = __shfl_xor_sync(0xffffffffu, sm[i], 2);
            }
#pragma unroll
            for (int t = 0; t < 8; t++) {
                const int c = tile_of(t);
                const bool shared = (t & 3) == 2;
                m1[t][0] = shared ? dup(lo[c], r.zero) : lo[c];
                m1[t][1] = lo[c + 1];
                m1[t][2] = shared ? dup(hi[c], r.zero) : hi[c];
                m1[t][3] = hi[c + 1];
                m0[t][0] = dup(m1[t][0], r.zero);
                m0[t][1] = dup(lo[c + 1], 2 * r.zero);
            }
            PIN;
            r.run<BIG, 6, false>(y0);
            if (warp == 0) mbar_wait(base + BAR_HALO + 8, 0);
            const uint32_t vin = warp ? hin : hin + 8 * HSLOT;
            fetch(vin, 0, 2);
#pragma unroll
            for (int i = 0; i < 8; i++) {
                const float inv = rcp(sm[i] + sm1[i]);
                pr[i] = pack2(e0[i] * inv, e1[i] * inv);
            }
            PIN;
            r.run<BIG, 6, false>(y0);
            fetch(vin, 1, 2);
            uint32_t pb[8][2];
#pragma unroll
            for (int t = 0; t < 8; t++) {
                pb[t][t & 1] = band(pr[t], curmask);
                pb[t][1 - (t & 1)] = band(pr[t], ~curmask);
            }
            r.mma_begin();
            float o[2][8][4];
#pragma unroll
            for (int i = 0; i < 16; i++) {
                const int b = 1 - (i >> 3), t = i & 7;
                float (&d)[4] = o[b][t];
                d[0] = d[1] = d[2] = d[3] = 0.f;
                mma16816(d, b ? m1[t] : m0[t], pb[(t & 6) + b][0], pb[(t & 6) + b][1]);
            }
            r.mma_end();
            r.run<BIG, 6, false>(y0, false);
            uint8_t* odst = sc->o + (size_t)mt * 7 * SLOT + ns * (14 * 2048) + warp * 256 + lane * 4;
#pragma unroll
            for (int hp = 0; hp < 2; hp++) {
#pragma unroll
                for (int b = 0; b < 2; b++) {
                    const float (&u)[8][4] = o[b];
                    const int t = 4 * hp;
                    uint32_t* w = p + 14 * hp + b;
                    w[0] = pack2(u[t][0], u[t][1]);
                    w[2] = pack2(u[t][2], u[t][3]);
                    w[4] = pack2(u[t + 1][0], u[t + 1][1]);
                    w[6] = pack2(g < 4 ? u[t + 1][2] : u[t + 2][0], g < 4 ? u[t + 1][3] : u[t + 2][1]);
                    w[8] = pack2(u[t + 2][2], u[t + 2][3]);
                    w[10] = pack2(u[t + 3][0], u[t + 3][1]);
                    w[12] = pack2(u[t + 3][2], u[t + 3][3]);
                }
            }
#pragma unroll
            for (int i = 0; i < 28; i++) {
                if (i >= O_FIRST && (i - O_FIRST) % O_SLICE == 0) r.run<BIG, 6, false>(y0);
                stg1(odst + (i >> 1) * 2048 + (i & 1) * 128, p[i]);
            }
            warp_arrive(base + BAR_RDY + 16);

#pragma unroll 1
            for (int i = 31 + (27 - O_FIRST) / O_SLICE; i <= LLAST + 1 - TURN; i++) r.run<BIG, 6, false>(y0, true, i <= LLAST - TURN);
            const uint32_t tag = lds1(base + TAG);
            if (mbar_test(base + BAR_PART + wg * 8, 0)) {
#pragma unroll
                for (int i = 0; i < 7; i++) ld_tagged(part + i * 4096, p[4 * i], p[4 * i + 1], p[4 * i + 2], p[4 * i + 3]);
            } else {
                p[0] = ~tag;
            }
            r.seek(LLAST + 2 - TURN, bslot_l(LLAST + 2 - TURN));
#pragma unroll
            for (int i = 1; i < TURN; i++) r.run<BIG, 6, false, 1, true>(y0, false, i == TURN - 1, i < TURN - 1);
#pragma unroll 1
            for (int n = 0; n < SPIN_LIMIT; n++) {
                uint32_t stale = 0;
#pragma unroll
                for (int i = 0; i < 28; i += 2) stale |= p[i] ^ tag;
                if (__all_sync(0xffffffffu, !(stale & 1))) break;
                mbar_wait(base + BAR_PART + wg * 8, 0);
#pragma unroll
                for (int i = 0; i < 7; i++) ld_tagged(part + i * 4096, p[4 * i], p[4 * i + 1], p[4 * i + 2], p[4 * i + 3]);
            }
            asm volatile("wgmma.wait_group.sync.aligned 0;" ::: "memory");
            acc_fence(y0);
            const uint32_t slab = base + (wg ? HALO : ((LLAST - 6) % NA) * SLOT) + (warp & 3) * WSLOT;
            store_out([&](int i) { return add2(pack2(y0[2 * i], y0[2 * i + 1]), p[i]); }, lane, slab, &maps.m[M_OUTB], 448 + col, mt * 128 + warp * 16);
        }
    }
}

typedef CUresult (*EncodeFn)(CUtensorMap*, CUtensorMapDataType, cuuint32_t, void*, const cuuint64_t*, const cuuint64_t*,
                             const cuuint32_t*, const cuuint32_t*, CUtensorMapInterleave, CUtensorMapSwizzle,
                             CUtensorMapL2promotion, CUtensorMapFloatOOBfill);

struct Dim { uint64_t size, stride; uint32_t box; };
void encode(EncodeFn fn, CUtensorMap* m, const void* ptr, CUtensorMapSwizzle sw, Dim d0, Dim d1, Dim d2 = {0, 0, 0}, Dim d3 = {0, 0, 0}) {
    const cuuint64_t dims[4] = {d0.size, d1.size, d2.size, d3.size};
    const cuuint64_t strides[3] = {d1.stride, d2.stride, d3.stride};
    const cuuint32_t box[4] = {d0.box, d1.box, d2.box, d3.box};
    const cuuint32_t es[4] = {1, 1, 1, 1};
    fn(m, CU_TENSOR_MAP_DATA_TYPE_BFLOAT16, d3.size ? 4 : d2.size ? 3 : 2, const_cast<void*>(ptr), dims, strides, box, es,
       CU_TENSOR_MAP_INTERLEAVE_NONE, sw, CU_TENSOR_MAP_L2_PROMOTION_L2_128B, CU_TENSOR_MAP_FLOAT_OOB_FILL_NONE);
}

}

extern "C" void kernel_launch(void* const* d_in, const int* in_sizes, int n_in, void* d_out, int out_size) {
    (void)in_sizes; (void)n_in; (void)out_size;
    void* fnp = nullptr;
    cudaDriverEntryPointQueryResult st;
    cudaGetDriverEntryPoint("cuTensorMapEncodeTiled", &fnp, cudaEnableDefault, &st);
    EncodeFn fn = (EncodeFn)fnp;
    void* scratch = nullptr;
    cudaGetSymbolAddress(&scratch, g_scratch);
    int dev = 0, sms = 0;
    cudaGetDevice(&dev);
    cudaDeviceGetAttribute(&sms, cudaDevAttrMultiProcessorCount, dev);
    auto kernel = sms == 132 ? fused_kernel<true> : fused_kernel<false>;
    cudaFuncSetAttribute(kernel, cudaFuncAttributeMaxDynamicSharedMemorySize, SMEM_BYTES);

    const CUtensorMapSwizzle S128 = CU_TENSOR_MAP_SWIZZLE_128B, S0 = CU_TENSOR_MAP_SWIZZLE_NONE;
    const Dim one = {1, 16, 1};
    Maps maps;
    encode(fn, &maps.m[M_XA], d_in[0], S128, {896, 2, 64}, {1024, 1792, 128}, one, one);
    encode(fn, &maps.m[M_WQK], d_in[1], S128, {112, 2, 64}, {448, 2688, 32}, {3, 896, 2}, {4, 224, 1});
    encode(fn, &maps.m[M_WV], d_in[1], S128, {112, 2, 64}, {448, 2688, 64}, one, {12, 224, 1});
    encode(fn, &maps.m[M_XH], d_in[0], S128, {448, 2, 64}, {128, 1792, 8}, {8, 128 * 1792, 8}, {2, 896, 2});
    encode(fn, &maps.m[M_WO], d_in[2], S128, {112, 2, 64}, {448, 896, 64}, one, {4, 224, 1});
    encode(fn, &maps.m[M_XB], d_in[3], S128, {448, 2, 64}, {1024, 896, 64}, {2, 896 * 1024, 2}, one);
    encode(fn, &maps.m[M_CR], d_in[4], S128, {2048, 2, 64}, {2048, 4096, 128});
    encode(fn, &maps.m[M_CI], d_in[5], S128, {2048, 2, 64}, {2048, 4096, 128});
    encode(fn, &maps.m[M_WR], d_in[6], S128, {448, 2, 64}, {448, 896, 112}, one, one);
    encode(fn, &maps.m[M_WI], d_in[7], S128, {448, 2, 64}, {448, 896, 112});
    encode(fn, &maps.m[M_OUTA], d_out, S0, {1792, 2, 112}, {1024, 3584, 8});
    encode(fn, &maps.m[M_OUTB], d_out, S0, {896, 2, 112}, {2048, 1792, 8});

    kernel<<<132, 384, SMEM_BYTES>>>((Scratch*)scratch, maps);
}
```

```cpp
#include <cuda.h>
#include <cuda_bf16.h>
#include <cuda_runtime.h>
#include <stdint.h>

namespace {

constexpr uint32_t SLOT = 16384;
constexpr int NA = 7;
constexpr uint32_t BRING = NA * SLOT;
constexpr uint32_t HALO = BRING + 6 * SLOT;
constexpr uint32_t HSLOT = 1792;
constexpr uint32_t WSLOT = 3584;
constexpr uint32_t BLOB = 14336;
constexpr uint32_t BARS = 14 * SLOT;
constexpr uint32_t BAR_FULL = BARS;
constexpr uint32_t BAR_EMPTY = BARS + 64;
constexpr uint32_t BAR_RDY = BARS + 128;
constexpr uint32_t BAR_DEP = BARS + 168;
constexpr uint32_t BAR_HALO = BARS + 192;
constexpr uint32_t BAR_PART = BARS + 208;
constexpr uint32_t TAG = BARS + 224;
constexpr uint32_t HSPARE = BARS + 256 + 1024;
constexpr uint32_t SMEM_BYTES = HSPARE + HSLOT;
constexpr uint32_t base = 1024;
constexpr int SPIN_LIMIT = 1 << 16;

#define E_EXTRA 0
#define HALO_K_AT 10
#define HALO_V_AT 19
#define O_SLICE 4
#define B_SLICE 4
#define LEAD 3
#define TURN 4
#define PACE 450
#define O_FIRST 8
#define B_OWN 28
#define MMA_SYNC 2
#define A_OWN 4
#define A_OWN2 20
#define PACE0 500
#define GPC_MAP 0x64752310u

constexpr int NBE = 13 + E_EXTRA;
constexpr int POUT = 33 + NBE;
constexpr int ELAST = POUT + 6;
constexpr int LLAST = 52 - E_EXTRA;
static_assert(TURN <= 4, "the output is staged in the slots of the seventh-last stage");

enum { M_XB, M_XA, M_XH, M_WR, M_WQK, M_WV, M_WO, M_WI, M_CR, M_CI, M_OUTA, M_OUTB, M_COUNT };
struct __align__(64) Maps { CUtensorMap m[M_COUNT]; };

constexpr int CNT_A = 0;
constexpr int CNT_B = 8;
constexpr int CNT_O = 16;
constexpr int CNT_P = 32;
constexpr int CNT_COUNT = 96;

struct Scratch {
    uint8_t ab[64 * 4 * BLOB];
    uint8_t o[16 * 7 * SLOT];
    uint8_t part[64 * 2 * BLOB];
    uint8_t halo[64 * 2 * 2048];
    unsigned cnt[CNT_COUNT * 32];
    unsigned epoch[132 * 4 * 8];
};
__device__ __align__(1024) Scratch g_scratch;

__device__ __forceinline__ unsigned clk32() { unsigned c; asm volatile("mov.u32 %0, %%clock;" : "=r"(c)); return c; }

#define PROF(idx)

__device__ __forceinline__ void mbar_init(uint32_t bar, uint32_t cnt) {
    asm volatile("mbarrier.init.shared::cta.b64 [%0], %1;" ::"r"(bar), "r"(cnt) : "memory");
}
__device__ __forceinline__ void mbar_expect(uint32_t bar, uint32_t bytes) {
    asm volatile("mbarrier.arrive.expect_tx.shared::cta.b64 _, [%0], %1;" ::"r"(bar), "r"(bytes) : "memory");
}
__device__ __forceinline__ void mbar_arrive(uint32_t bar) {
    asm volatile("mbarrier.arrive.shared::cta.b64 _, [%0];" ::"r"(bar) : "memory");
}
__device__ __forceinline__ bool mbar_try(uint32_t bar, uint32_t parity) {
    uint32_t ok;
    asm volatile("{\n.reg .pred p;\nmbarrier.try_wait.parity.shared::cta.b64 p, [%1], %2;\nselp.u32 %0, 1, 0, p;\n}\n"
                 : "=r"(ok) : "r"(bar), "r"(parity) : "memory");
    return ok;
}
__device__ __forceinline__ bool mbar_test(uint32_t bar, uint32_t parity) {
    uint32_t ok;
    asm volatile("{\n.reg .pred p;\nmbarrier.test_wait.parity.shared::cta.b64 p, [%1], %2;\nselp.u32 %0, 1, 0, p;\n}\n"
                 : "=r"(ok) : "r"(bar), "r"(parity) : "memory");
    return ok;
}
__device__ __forceinline__ void mbar_wait(uint32_t bar, uint32_t parity) {
#pragma unroll 1
    for (int n = 0; n < SPIN_LIMIT; n++)
        if (mbar_try(bar, parity)) break;
}
__device__ __forceinline__ bool elect() {
    uint32_t p;
    asm volatile("{\n.reg .pred p;\nelect.sync _|p, 0xffffffff;\nselp.u32 %0, 1, 0, p;\n}\n" : "=r"(p));
    return p;
}
__device__ __forceinline__ void nb_sync(int id, int n) { asm volatile("bar.sync %0, %1;" ::"r"(id), "r"(n) : "memory"); }
__device__ __forceinline__ void nb_arrive(int id, int n) { asm volatile("bar.arrive %0, %1;" ::"r"(id), "r"(n) : "memory"); }
__device__ __forceinline__ void warp_arrive(uint32_t bar) {
    __syncwarp();
    if (elect()) mbar_arrive(bar);
}
__device__ __forceinline__ uint32_t band(uint32_t x, uint32_t m) {
    uint32_t r;
    asm volatile("and.b32 %0, %1, %2;" : "=r"(r) : "r"(x), "r"(m));
    return r;
}
__device__ __forceinline__ uint32_t dup(uint32_t x, uint32_t zero) {
    uint32_t r;
    asm volatile("xor.b32 %0, %1, %2;" : "=r"(r) : "r"(x), "r"(zero));
    return r;
}

__device__ __forceinline__ void tma_ld2(uint32_t dst, const CUtensorMap* m, int c0, int c1, uint32_t bar) {
    asm volatile("cp.async.bulk.tensor.2d.shared::cluster.global.mbarrier::complete_tx::bytes [%0], [%1, {%3, %4}], [%2];"
                 ::"r"(dst), "l"(m), "r"(bar), "r"(c0), "r"(c1) : "memory");
}
__device__ __forceinline__ void tma_ld4(uint32_t dst, const CUtensorMap* m, int c0, int c1, int c2, int c3, uint32_t bar) {
    asm volatile("cp.async.bulk.tensor.4d.shared::cluster.global.mbarrier::complete_tx::bytes [%0], [%1, {%3, %4, %5, %6}], [%2];"
                 ::"r"(dst), "l"(m), "r"(bar), "r"(c0), "r"(c1), "r"(c2), "r"(c3) : "memory");
}
__device__ __forceinline__ void tma_ld5(uint32_t dst, const CUtensorMap* m, int c0, int c3, int c4, uint32_t bar) {
    asm volatile("cp.async.bulk.tensor.5d.shared::cluster.global.mbarrier::complete_tx::bytes [%0], [%1, {%3, 0, 0, %4, %5}], [%2];"
                 ::"r"(dst), "l"(m), "r"(bar), "r"(c0), "r"(c3), "r"(c4) : "memory");
}
__device__ __forceinline__ void bulk_ld(uint32_t dst, const void* src, uint32_t bytes, uint32_t bar) {
    asm volatile("cp.async.bulk.shared::cluster.global.mbarrier::complete_tx::bytes [%0], [%1], %2, [%3];"
                 ::"r"(dst), "l"(src), "r"(bytes), "r"(bar) : "memory");
}
__device__ __forceinline__ void tma_st2(const CUtensorMap* m, int c0, int c1, uint32_t src) {
    asm volatile("cp.async.bulk.tensor.2d.global.shared::cta.bulk_group [%0, {%1, %2}], [%3];"
                 ::"l"(m), "r"(c0), "r"(c1), "r"(src) : "memory");
}
__device__ __forceinline__ void bulk_commit() { asm volatile("cp.async.bulk.commit_group;" ::: "memory"); }
__device__ __forceinline__ void bulk_wait_read() { asm volatile("cp.async.bulk.wait_group.read 0;" ::: "memory"); }
__device__ __forceinline__ void fence_async_smem() { asm volatile("fence.proxy.async.shared::cta;" ::: "memory"); }
__device__ __forceinline__ void fence_async_global() { asm volatile("fence.proxy.async.global;" ::: "memory"); }

__device__ __forceinline__ void signal(Scratch* sc, int idx) {
    asm volatile("fence.proxy.async;\nred.relaxed.gpu.global.add.u32 [%0], 1;" ::"l"(&sc->cnt[idx * 32]) : "memory");
}
__device__ __forceinline__ unsigned peek(const unsigned* p) {
    unsigned v;
    asm volatile("ld.relaxed.gpu.global.u32 %0, [%1];" : "=r"(v) : "l"(p) : "memory");
    return v;
}
__device__ __forceinline__ void await(Scratch* sc, int idx, unsigned target) {
    const unsigned* p = &sc->cnt[idx * 32];
#pragma unroll 1
    for (int n = 0; n < SPIN_LIMIT; n++)
        if ((int)(peek(p) - target) >= 0) break;
    asm volatile("fence.acquire.gpu;" ::: "memory");
}
__device__ __forceinline__ void wait_dep(int k) {
    mbar_wait(base + BAR_DEP + k * 8, 0);
    fence_async_global();
}

#define WG_REGS                                                                                                     \
    "{%0,%1,%2,%3,%4,%5,%6,%7,%8,%9,%10,%11,%12,%13,%14,%15,%16,%17,%18,%19,%20,%21,%22,%23,%24,%25,%26,%27,"       \
    "%28,%29,%30,%31,%32,%33,%34,%35,%36,%37,%38,%39,%40,%41,%42,%43,%44,%45,%46,%47,%48,%49,%50,%51,%52,%53,%54,%55}"
#define WG_OPS(C)                                                                                                   \
    C(d[0]), C(d[1]), C(d[2]), C(d[3]), C(d[4]), C(d[5]), C(d[6]), C(d[7]), C(d[8]), C(d[9]), C(d[10]), C(d[11]),   \
    C(d[12]), C(d[13]), C(d[14]), C(d[15]), C(d[16]), C(d[17]), C(d[18]), C(d[19]), C(d[20]), C(d[21]), C(d[22]),   \
    C(d[23]), C(d[24]), C(d[25]), C(d[26]), C(d[27]), C(d[28]), C(d[29]), C(d[30]), C(d[31]), C(d[32]), C(d[33]),   \
    C(d[34]), C(d[35]), C(d[36]), C(d[37]), C(d[38]), C(d[39]), C(d[40]), C(d[41]), C(d[42]), C(d[43]), C(d[44]),   \
    C(d[45]), C(d[46]), C(d[47]), C(d[48]), C(d[49]), C(d[50]), C(d[51]), C(d[52]), C(d[53]), C(d[54]), C(d[55])

template <int TA, int TB, int SB, bool INIT, uint32_t AH, uint32_t BH>
__device__ __forceinline__ void wgmma112(float (&d)[56], uint32_t alo, uint32_t blo) {
    if (INIT) {
        asm volatile("{\n.reg .pred p;\n.reg .b64 da, db;\nsetp.ne.b32 p, 0, 0;\nmov.b64 da, {%56, %61};\nmov.b64 db, {%57, %62};\n"
                     "wgmma.mma_async.sync.aligned.m64n112k16.f32.bf16.bf16 " WG_REGS ", da, db, p, 1, %59, %60, %58;\n}\n"
                     : WG_OPS("=f") : "r"(alo), "r"(blo), "n"(TB), "n"(SB), "n"(TA), "n"(AH), "n"(BH));
    } else {
        asm volatile("{\n.reg .pred p;\n.reg .b64 da, db;\nsetp.ne.b32 p, 1, 0;\nmov.b64 da, {%56, %61};\nmov.b64 db, {%57, %62};\n"
                     "wgmma.mma_async.sync.aligned.m64n112k16.f32.bf16.bf16 " WG_REGS ", da, db, p, 1, %59, %60, %58;\n}\n"
                     : WG_OPS("+f") : "r"(alo), "r"(blo), "n"(TB), "n"(SB), "n"(TA), "n"(AH), "n"(BH));
    }
}
__device__ __forceinline__ void acc_fence(float (&d)[56]) {
#pragma unroll
    for (int i = 0; i < 56; i++) asm volatile("" : "+f"(d[i])::"memory");
}

__device__ __forceinline__ uint32_t pack2(float lo, float hi) {
    uint32_t r;
    asm volatile("cvt.rn.bf16x2.f32 %0, %1, %2;" : "=r"(r) : "f"(hi), "f"(lo));
    return r;
}
__device__ __forceinline__ uint32_t movm(uint32_t a) {
    uint32_t r;
    asm volatile("movmatrix.sync.aligned.m8n8.trans.b16 %0, %1;" : "=r"(r) : "r"(a));
    return r;
}
__device__ __forceinline__ void stsm4(uint32_t addr, uint32_t a, uint32_t b, uint32_t c, uint32_t d) {
    asm volatile("stmatrix.sync.aligned.m8n8.x4.shared.b16 [%0], {%1,%2,%3,%4};" ::"r"(addr), "r"(a), "r"(b), "r"(c), "r"(d) : "memory");
}
__device__ __forceinline__ void sts1(uint32_t addr, uint32_t a) { asm volatile("st.shared.b32 [%0], %1;" ::"r"(addr), "r"(a) : "memory"); }
__device__ __forceinline__ uint32_t lds1(uint32_t addr) {
    uint32_t a;
    asm volatile("ld.shared.b32 %0, [%1];" : "=r"(a) : "r"(addr) : "memory");
    return a;
}
__device__ __forceinline__ void stg1(uint8_t* p, uint32_t a) { asm volatile("st.global.b32 [%0], %1;" ::"l"(p), "r"(a) : "memory"); }
__device__ __forceinline__ void st_part(uint8_t* p, const uint32_t* v, uint32_t parity) {
    asm volatile("{\n.reg .b64 x, y;\nmov.b64 x, {%1, %2};\nmov.b64 y, {%3, %4};\nst.relaxed.gpu.global.v2.b64 [%0], {x, y};\n}\n"
                 ::"l"(p), "r"((v[0] & ~1u) | parity), "r"(v[1]), "r"((v[2] & ~1u) | parity), "r"(v[3]) : "memory");
}
__device__ __forceinline__ void mma16816(float (&d)[4], const uint32_t (&a)[4], uint32_t b0, uint32_t b1) {
    asm volatile("mma.sync.aligned.m16n8k16.row.col.f32.bf16.bf16.f32 {%0,%1,%2,%3}, {%4,%5,%6,%7}, {%8,%9}, {%0,%1,%2,%3};"
                 : "+f"(d[0]), "+f"(d[1]), "+f"(d[2]), "+f"(d[3]) : "r"(a[0]), "r"(a[1]), "r"(a[2]), "r"(a[3]), "r"(b0), "r"(b1));
}
__device__ __forceinline__ uint32_t add2(uint32_t a, uint32_t b) {
    uint32_t r;
    asm("add.rn.bf16x2 %0, %1, %2;" : "=r"(r) : "r"(a), "r"(b));
    return r;
}
__device__ __forceinline__ uint32_t max2(uint32_t a, uint32_t b) {
    uint32_t r;
    asm("max.bf16x2 %0, %1, %2;" : "=r"(r) : "r"(a), "r"(b));
    return r;
}
__device__ __forceinline__ void ld_tagged(const uint8_t* p, uint32_t& a, uint32_t& ta, uint32_t& b, uint32_t& tb) {
    asm volatile("{\n.reg .b64 x, y;\nld.relaxed.gpu.global.v2.b64 {x, y}, [%4];\nmov.b64 {%0, %1}, x;\nmov.b64 {%2, %3}, y;\n}\n"
                 : "=r"(a), "=r"(ta), "=r"(b), "=r"(tb) : "l"(p) : "memory");
}
__device__ __forceinline__ float bf_lo(uint32_t v) { return __uint_as_float(v << 16); }
__device__ __forceinline__ float bf_hi(uint32_t v) { return __uint_as_float(v & 0xFFFF0000u); }
__device__ __forceinline__ float rcp(float x) { float r; asm("rcp.approx.ftz.f32 %0, %1;" : "=f"(r) : "f"(x)); return r; }
__device__ __forceinline__ float ex2(float x) { float r; asm volatile("ex2.approx.ftz.f32 %0, %1;" : "=f"(r) : "f"(x)); return r; }

__device__ __forceinline__ uint32_t full_bar(int stage) { return base + BAR_FULL + (stage & 7) * 8; }
__device__ __forceinline__ void wait_released(int j) { mbar_wait(base + BAR_EMPTY + (j & 7) * 8, (j >> 3) & 1); }

template <int V>
struct Int { static constexpr int value = V; };

__host__ __device__ constexpr int bslot_e(int i) { return (i < 2 || i >= 14) ? (i + 5) % 7 : (i + 1) % 5; }
__host__ __device__ constexpr int bslot_l(int i) { return (i + 5) % 6; }
__host__ __device__ constexpr int bslot_h(int i) { return (i + 5) % 7; }

template <uint32_t OFF>
struct Feed {
    int stage;
    uint32_t dst;
    __device__ __forceinline__ void seek(int i, int slot) { stage = i; dst = base + OFF + slot * SLOT; }
    template <int N>
    __device__ __forceinline__ uint32_t acquire() { wait_released(stage - N); return full_bar(stage); }
    template <int N>
    __device__ __forceinline__ void next() {
        stage++;
        dst += SLOT;
        if (dst == base + OFF + N * SLOT) dst = base + OFF;
    }
};
__device__ __forceinline__ int skip_own(int n, int mt) { return n == mt ? 15 : n; }

struct Desc { uint32_t lo, hi; };
__host__ __device__ constexpr Desc desc_const(uint32_t lbo, uint32_t sbo, uint32_t mode) { return {(lbo >> 4) << 16, (sbo >> 4) | (mode << 30)}; }
constexpr Desc D_K128 = desc_const(16, 1024, 1);
constexpr Desc D_N128 = desc_const(8192, 1024, 1);
constexpr Desc D_BLOB = desc_const(128, 256, 0);
constexpr Desc D_OT = desc_const(2048, 128, 0);

enum Kind { XW, XWN, QK, BIG, OUT };

struct Ring {
    int stage;
    uint32_t a, b;
    uint32_t wg;
    uint32_t zero;
    bool releaser;
    __device__ __forceinline__ void seek(int i, int bslot) {
        stage = i;
        a = (base + (i % NA) * SLOT) >> 4;
        b = (base + BRING + bslot * SLOT) >> 4;
    }
    __device__ __forceinline__ void wait() { mbar_wait(full_bar(stage), (stage >> 3) & 1); }
    __device__ __forceinline__ void take_turn() { nb_sync(1 + wg, 256); }
    __device__ __forceinline__ void pin() {
        uint32_t n = 0;
#pragma unroll 1
        do {
            asm volatile("pmevent 7;" ::: "memory");
        } while (n++ < zero);
    }
    __device__ __forceinline__ void mma_begin() {
        pin();
        if (!wg) take_turn();
        pin();
    }
    __device__ __forceinline__ void mma_end() {
        pin();
        if (wg) nb_arrive(3, 256);
        nb_sync(3 - wg, 256);
    }
    template <Kind K, int NBS, bool INIT, int SB = 1, bool TAIL = false>
    __device__ __forceinline__ void run(float (&d)[56], float (&e)[56], bool first = true, bool last = true, bool more = true) {
        if (first) take_turn();
        asm volatile("wgmma.fence.sync.aligned;" ::: "memory");
        if (K == QK) {
            const uint32_t da = D_K128.lo + (base >> 4) + (stage >> 1) * (SLOT >> 4) + (stage & 1) * 4 + wg * 512, db = D_N128.lo + b;
            wgmma112<0, 1, 1, INIT, D_K128.hi, D_N128.hi>(d, da, db);
            wgmma112<0, 1, 1, INIT, D_K128.hi, D_N128.hi>(e, da, db + 256);
            wgmma112<0, 1, 1, false, D_K128.hi, D_N128.hi>(d, da + 2, db + 128);
            wgmma112<0, 1, 1, false, D_K128.hi, D_N128.hi>(e, da + 2, db + 384);
        } else {
            constexpr int TA = K == OUT, TB = K != XW;
            constexpr uint32_t sa = K == OUT ? 256 : 2, sb = K == XW ? 2 : K == BIG ? 224 : 128;
            constexpr Desc A = K == OUT ? D_OT : D_K128, B = K == XW ? D_K128 : K == BIG ? D_BLOB : D_N128;
            const uint32_t da = A.lo + a + wg * (K == OUT ? 64 : 512), db = B.lo + b;
            wgmma112<TA, TB, SB, INIT, A.hi, B.hi>(d, da, db);
            wgmma112<TA, TB, SB, false, A.hi, B.hi>(d, da + sa, db + sb);
            wgmma112<TA, TB, SB, false, A.hi, B.hi>(d, da + 2 * sa, db + 2 * sb);
            wgmma112<TA, TB, SB, false, A.hi, B.hi>(d, da + 3 * sa, db + 3 * sb);
        }
        asm volatile("wgmma.commit_group.sync.aligned;" ::: "memory");
        if (!TAIL) asm volatile("wgmma.wait_group.sync.aligned 1;" ::: "memory");
        if (last) nb_arrive(2 - wg, 256);
        if (!TAIL && stage > 0) {
            if (releaser) mbar_arrive(base + BAR_EMPTY + ((stage - 1) & 7) * 8);
        }
        stage++;
        a += SLOT >> 4;
        if (a == (base + NA * SLOT) >> 4) a = base >> 4;
        b += SLOT >> 4;
        if (b == (base + BRING + NBS * SLOT) >> 4) b = (base + BRING) >> 4;
        if (more) wait();
    }
    template <Kind K, int NBS, bool INIT, int SB = 1, bool TAIL = false>
    __device__ __forceinline__ void run(float (&d)[56], bool first = true, bool last = true, bool more = true) {
        run<K, NBS, INIT, SB, TAIL>(d, d, first, last, more);
    }
};

__device__ __forceinline__ void pack_all(const float (&d)[56], uint32_t (&p)[28]) {
#pragma unroll
    for (int i = 0; i < 28; i++) p[i] = pack2(d[2 * i], d[2 * i + 1]);
}
template <int I0, int I1>
__device__ __forceinline__ void store_frags(uint8_t* dst, const uint32_t (&p)[28]) {
#pragma unroll
    for (int i = I0; i < I1; i++) stg1(dst + i * 128, p[i]);
}
template <int I0, int I1>
__device__ __forceinline__ void stage_frags(uint32_t lane_addr, const uint32_t (&p)[28]) {
#pragma unroll
    for (int i = I0; i < I1; i += 4) stsm4(lane_addr + i * 128, p[i], p[i + 1], p[i + 2], p[i + 3]);
}
template <class F>
__device__ __forceinline__ void store_out(F frag, int lane, uint32_t slab, const CUtensorMap* m, int c0, int c1) {
    const bool swap = lane & 16;
    const uint32_t addr = slab + (lane & 7) * 224 + ((lane >> 3) ^ ((lane >> 2) & 1)) * 16;
#pragma unroll
    for (int h = 0; h < 2; h++) {
#pragma unroll
        for (int c = 0; c < 14; c += 4) {
            const uint32_t t0 = frag(2 * c + h), t1 = frag(2 * c + 2 + h);
            if (c < 12) {
                const uint32_t t2 = frag(2 * c + 4 + h), t3 = frag(2 * c + 6 + h);
                stsm4(addr + h * 1792 + c * 16, swap ? t1 : t0, swap ? t0 : t1, swap ? t3 : t2, swap ? t2 : t3);
            } else {
                asm volatile("stmatrix.sync.aligned.m8n8.x2.shared.b16 [%0], {%1,%2};" ::"r"(addr + h * 1792 + c * 16), "r"(swap ? t1 : t0), "r"(swap ? t0 : t1) : "memory");
            }
        }
        fence_async_smem();
        __syncwarp();
        if (elect()) tma_st2(m, c0, c1 + 8 * h, slab + h * 1792);
    }
    if (elect()) {
        bulk_commit();
        bulk_wait_read();
    }
}
__host__ __device__ constexpr int tile_of(int t) { return 7 * (t >> 2) + 3 * ((t >> 1) & 1) + 2 * (t & 1); }

struct Role {
    int kind;
    int par, blk;
    int ns, id;
};
template <bool BY_SM>
__device__ __forceinline__ Role decode_role() {
    uint32_t sm;
    if (BY_SM) asm volatile("mov.u32 %0, %%smid;" : "=r"(sm));
    else asm volatile("mov.u32 %0, %%ctaid.x;" : "=r"(sm));
    const int tpc = sm >> 1, q2 = ((tpc - 32) * 37) >> 8;
    const int gpc = tpc < 32 ? tpc & 7 : tpc < 60 ? tpc - 31 - 7 * q2 : 0;
    const int pos = tpc < 32 ? tpc >> 3 : tpc < 60 ? q2 + 4 : tpc - 56;
    const int grp = GPC_MAP >> (4 * gpc);
    Role r;
    r.kind = (grp & 1) | ((sm >> 7) << 1);
    r.par = (pos >> 1) & 1;
    r.blk = (grp & 6) + (pos >> 2);
    r.ns = (pos & 1) * 2 + (sm & 1);
    r.id = sm >= 128 ? sm : (grp & 7) * 16 + pos * 2 + (sm & 1);
    return r;
}
static_assert((GPC_MAP & 15) == 0, "role H decodes as blk = 2, par = 0");

__device__ __forceinline__ void first_fill(const Maps& maps, const Role& r, int i) {
    const int L = r.kind & 1;
    const CUtensorMap* ma = &maps.m[r.kind];
    const uint32_t bar = full_bar(i);
    const int k = (i * 64) >> L;
    const bool has_a = !(i & L), has_b = i < 7 - L;
    const uint32_t slots = r.kind == 0 ? 0x2104365u : L ? 0x5432105u : 0x4321065u;
    const uint32_t dst = base + BRING + (i == 0 ? 5 : (slots >> (4 * i)) & 7) * SLOT;
    mbar_expect(bar, (has_a ? SLOT : 0) + (has_b ? SLOT : 0));
    if (has_a) tma_ld5(base + (i >> L) * SLOT, ma, k, r.par, r.blk, bar);
    if (has_b) {
        tma_ld4(dst, ma + 3, r.kind ? 0 : k, r.kind ? k : 0, 0, r.ns, bar);
        tma_ld4(dst + 8192, ma + 3, r.kind ? 64 : k, r.kind ? k : 64, 0, r.ns, bar);
        mbar_arrive(bar);
    }
}
static_assert(bslot_e(0) == 5 && bslot_e(1) == 6 && bslot_e(2) == 3 && bslot_e(3) == 4 && bslot_e(4) == 0 && bslot_e(6) == 2, "");

template <bool BY_SM>
__global__ void __launch_bounds__(384, 1) fused_kernel(Scratch* sc, const __grid_constant__ Maps maps) {
    const int warp = __shfl_sync(0xffffffffu, threadIdx.x >> 5, 0);
    unsigned t_open = 0;
    if (warp == 8) {
        if (elect()) {
            mbar_init(base + BAR_FULL, 2);
            const Role r = decode_role<BY_SM>();
            first_fill(maps, r, 0);
            t_open = clk32();
#pragma unroll 1
            for (int i = 1 + blockIdx.y; i < LEAD; i++) {
                mbar_init(full_bar(i), 2);
                first_fill(maps, r, i);
            }
            asm volatile("fence.mbarrier_init.release.cluster;" ::: "memory");
        }
    }
    if (warp == 9) {
        if (elect()) {
#pragma unroll
            for (int i = 0; i < 8; i++) mbar_init(base + BAR_EMPTY + i * 8, 4);
            asm volatile("fence.mbarrier_init.release.cluster;" ::: "memory");
        }
    } else if (warp == 10) {
        if (elect()) {
#pragma unroll
            for (int i = 0; i < 3; i++) mbar_init(base + BAR_RDY + i * 8, i < 2 ? 4 : 8);
#pragma unroll
            for (int i = 0; i < 2; i++) mbar_init(base + BAR_HALO + i * 8, 1);
            asm volatile("fence.mbarrier_init.release.cluster;" ::: "memory");
        }
    } else if (warp == 11) {
        if (elect()) {
#pragma unroll
            for (int i = LEAD; i < 8; i++) mbar_init(base + BAR_FULL + i * 8, 2);
#pragma unroll
            for (int i = 0; i < 3; i++) mbar_init(base + BAR_DEP + i * 8, 1);
#pragma unroll
            for (int i = 0; i < 2; i++) mbar_init(base + BAR_PART + i * 8, 1);
            asm volatile("fence.mbarrier_init.release.cluster;" ::: "memory");
        }
    }
    __syncthreads();

    const Role role = decode_role<BY_SM>();
    int lane = threadIdx.x & 31;
    asm volatile("" : "+r"(lane));
    const bool roleH = role.kind == 2;
    const int roleL = role.kind & 1, par = role.par, blk = role.blk, ns = role.ns, bid = role.id;
    const int mt = 2 * blk + par, col = ns * 112;

    if (__builtin_expect(warp >= 8, 1)) {
        asm volatile("setmaxnreg.dec.sync.aligned.u32 56;");
#define PROF_FEED_A
#define PROF_FEED_B
        if (__builtin_expect(warp == 8, 1)) {
            if (elect()) {
                PROF(129);
#pragma unroll 1
                for (int i = LEAD; i < 7; i++) {
                    while (clk32() - t_open < i * PACE - PACE0) {}
                    first_fill(maps, role, i);
                }
                PROF(134);
                Feed<0> f;
                const int row = mt * 128;
                auto c_run = [&](const CUtensorMap* m, int off, int n0, int n1) {
#pragma unroll 1
                    for (int n = n0; n < n1; n++) {
                        const uint32_t bar = f.acquire<NA>();
                        mbar_expect(bar, SLOT);
                        tma_ld2(f.dst, m, (off + skip_own(n, mt)) * 64, row, bar);
                        PROF_FEED_A;
                        f.next<NA>();
                    }
                };
                if (roleH) {
                } else if (!roleL) {
                    f.seek(14, 0);
#pragma unroll 1
                    for (int i = 0; i < 4; i++) {
                        const uint32_t bar = f.acquire<NA>();
                        mbar_expect(bar, SLOT);
                        tma_ld2(f.dst, &maps.m[M_CR + (i >> 1)], ((i & 1) * 16 + mt) * 64, row, bar);
                        mbar_arrive(bar);
                        PROF_FEED_A;
                        f.next<NA>();
                    }
                    c_run(&maps.m[M_CR], 0, 0, 15);
                    c_run(&maps.m[M_CI], 0, 0, NBE);
                    wait_dep(2);
#pragma unroll 1
                    for (int i = 0; i < 7; i++) {
                        const uint32_t bar = f.acquire<NA>();
                        mbar_expect(bar, SLOT);
                        bulk_ld(f.dst, sc->o + (size_t)(mt * 7 + i) * SLOT, SLOT, bar);
                        PROF_FEED_A;
                        f.next<NA>();
                    }
                } else {
#pragma unroll 1
                    for (int i = 4; i < 7; i++) {
                        wait_released(2 * i - 8);
                        mbar_expect(full_bar(2 * i), SLOT);
                        tma_ld5(base + i * SLOT, &maps.m[M_XA], i * 64, par, blk, full_bar(2 * i));
                    }
                    wait_released(HALO_K_AT);
                    mbar_arrive(base + BAR_DEP + 16);
                    f.seek(21, 0);
                    c_run(&maps.m[M_CR], 16, 0, 15);
                    c_run(&maps.m[M_CI], 16, 0, 15);
                    c_run(&maps.m[M_CI], 0, NBE, 15);
                }
            }
        } else if (warp == 11) {
            if (elect()) {
                Feed<BRING> f;
                auto blob_run = [&](auto nbs, int quarter, int n0, int n1) {
                    constexpr int N = decltype(nbs)::value;
                    const uint8_t* src = sc->ab + (size_t)(quarter * 64 + ns) * BLOB;
#pragma unroll 1
                    for (int n = n0; n < n1; n++) {
                        const uint32_t bar = f.template acquire<N>();
                        mbar_expect(bar, BLOB);
                        bulk_ld(f.dst, src + skip_own(n, mt) * (4 * BLOB), BLOB, bar);
                        PROF_FEED_B;
                        f.template next<N>();
                    }
                };
                auto w_run = [&](auto nbs, const CUtensorMap* m, int slice, bool no_a) {
                    constexpr int N = decltype(nbs)::value;
#pragma unroll 1
                    for (int i = 0; i < 7; i++) {
                        const uint32_t bar = f.template acquire<N>();
                        mbar_expect(bar, SLOT);
                        tma_ld4(f.dst, m, 0, i * 64, 0, slice, bar);
                        tma_ld4(f.dst + 8192, m, 64, i * 64, 0, slice, bar);
                        if (no_a) mbar_arrive(bar);
                        PROF_FEED_B;
                        f.template next<N>();
                    }
                };
                if (roleH) {
                    f.seek(7, bslot_h(7));
                    w_run(Int<7>(), &maps.m[M_WV], 4 + ns, true);
                } else if (!roleL) {
                    f.seek(7, bslot_e(7));
#pragma unroll 1
                    for (int i = 0; i < 7; i++) {
                        const uint32_t bar = f.acquire<5>();
                        mbar_expect(bar, BLOB);
                        tma_ld2(f.dst, &maps.m[M_WI], i * 64, col, bar);
                        mbar_arrive(bar);
                        PROF_FEED_B;
                        f.next<5>();
                    }
                    f.seek(18, bslot_e(18));
                    wait_dep(0);
                    blob_run(Int<7>(), 0, 0, 15);
                    wait_dep(1);
                    blob_run(Int<7>(), 2, 0, NBE);
                    w_run(Int<7>(), &maps.m[M_WO], ns, false);
                } else {
                    f.seek(6, bslot_l(6));
#pragma unroll 1
                    for (int i = 6; i < 14; i++) {
                        const uint32_t bar = f.acquire<6>();
                        mbar_expect(bar, SLOT);
                        tma_ld4(f.dst, &maps.m[M_WQK], 0, i * 32, 0, ns, bar);
                        tma_ld4(f.dst + 8192, &maps.m[M_WQK], 64, i * 32, 0, ns, bar);
                        if (i & 1) mbar_arrive(bar);
                        PROF_FEED_B;
                        f.next<6>();
                    }
                    w_run(Int<6>(), &maps.m[M_WV], 4 + ns, true);
                    wait_dep(0);
                    blob_run(Int<6>(), 1, 0, 15);
                    wait_dep(1);
                    blob_run(Int<6>(), 3, 0, 15);
                    blob_run(Int<6>(), 2, NBE, 15);
                }
            }
        } else if (roleH) {
            if (elect()) {
                wait_released(warp == 9 ? 0 : 7);
#pragma unroll 1
                for (int i = 0; i < 7; i++) {
                    if (warp == 9) {
                        asm volatile("cp.async.bulk.prefetch.tensor.2d.L2.global [%0, {%1, %2}];" ::"l"(&maps.m[M_WI]), "r"(i * 64), "r"(col) : "memory");
                    } else {
                        asm volatile("cp.async.bulk.prefetch.tensor.4d.L2.global [%0, {%1, %2, 0, %3}];" ::"l"(&maps.m[M_WO]), "r"(0), "r"(i * 64), "r"(ns) : "memory");
                        asm volatile("cp.async.bulk.prefetch.tensor.4d.L2.global [%0, {%1, %2, 0, %3}];" ::"l"(&maps.m[M_WO]), "r"(64), "r"(i * 64), "r"(ns) : "memory");
                    }
                }
            }
        } else if (warp == 10) {
            if (elect()) {
                unsigned* epoch_ptr = &sc->epoch[(bid * 4 + 2) * 8];
                const unsigned ep = *epoch_ptr + 1;
                sts1(base + TAG, ep);
                asm volatile("prefetch.tensormap [%0];" ::"l"(&maps.m[M_OUTA + roleL]) : "memory");
                await(sc, CNT_A + roleL * 4 + ns, ep * 16);
                mbar_arrive(base + BAR_DEP);
                PROF(150);
                await(sc, CNT_B + ns, ep * 16);
                mbar_arrive(base + BAR_DEP + 8);
                PROF(151);
                if (!roleL) {
                    await(sc, CNT_O + mt, ep * 4);
                    mbar_arrive(base + BAR_DEP + 16);
                } else {
                    await(sc, CNT_P + mt * 4 + ns, ep * 2 - 1);
                    mbar_arrive(base + BAR_PART);
                    PROF(153);
                    await(sc, CNT_P + mt * 4 + ns, ep * 2);
                    mbar_arrive(base + BAR_PART + 8);
                }
                PROF(152);
                *epoch_ptr = ep;
            }
        } else if (!roleL) {
            if (elect()) {
                mbar_wait(base + BAR_RDY, 0);
                PROF(130);
                signal(sc, CNT_A + ns);
                PROF(131);
                mbar_wait(base + BAR_RDY + 8, 0);
                signal(sc, CNT_A + 4 + ns);
                PROF(135);
                mbar_wait(base + BAR_RDY + 16, 0);
                PROF(132);
                signal(sc, CNT_B + ns);
                PROF(133);
            }
        } else {
            unsigned* epoch_ptr = &sc->epoch[(bid * 4 + 1) * 8];
            const unsigned tag = *epoch_ptr + 1;
#pragma unroll 1
            for (int kv = 0; kv < 2; kv++) {
                uint32_t v[16];
#pragma unroll
                for (int i = 0; i < 16; i++) v[i] = 0;
                if (kv) wait_released(HALO_V_AT - 4), wait_released(HALO_V_AT);
                else mbar_wait(base + BAR_DEP + 16, 0);
                if (blk > 0) {
                    const uint8_t* src = sc->halo + (size_t)(((par * 8 + blk - 1) * 4 + ns) * 2 + kv) * 2048 + lane * 16;
#pragma unroll 1
                    for (int n = 0; n < SPIN_LIMIT; n++) {
                        uint32_t stale = 0;
#pragma unroll
                        for (int i = 0; i < 4; i++) ld_tagged(src + i * 512, v[4 * i], v[4 * i + 1], v[4 * i + 2], v[4 * i + 3]);
#pragma unroll
                        for (int i = 0; i < 16; i += 2) stale |= v[i] ^ tag;
                        if (__all_sync(0xffffffffu, !(stale & 1))) break;
                    }
#pragma unroll
                    for (int c = 0; c < 14; c += 2) v[c] = (v[c] & ~1u) | ((v[15] >> c) & 1);
                }
#pragma unroll
                for (int i = 0; i < 14; i++) sts1(base + HALO + kv * (8 * HSLOT) + i * 128 + lane * 4, v[i]);
                warp_arrive(base + BAR_HALO + kv * 8);
                if (lane == 0) PROF(142 + kv);
            }
            if (elect()) {
                mbar_wait(base + BAR_RDY + 16, 0);
                PROF(130);
                signal(sc, CNT_O + mt);
                PROF(131);
                *epoch_ptr = tag;
            }
        }
    } else {
        asm volatile("setmaxnreg.inc.sync.aligned.u32 224;");
        Ring r;
        r.wg = warp >> 2;
        r.zero = blockIdx.y;
        r.releaser = lane + 1 == (warp >> 2);
        const int wg = warp >> 2;
        if (wg) nb_arrive(1, 256);
        uint8_t* part = sc->part + (size_t)(ns * 16 + mt) * (2 * BLOB) + warp * 512 + lane * 16;
        uint32_t p[28];

        if (roleH) {
            unsigned* epoch_ptr = &sc->epoch[bid * 4 * 8];
            const unsigned tag = *epoch_ptr + 1;
            uint8_t* hout = sc->halo + (size_t)((warp * 8 + ns) * 2) * 2048 + lane * 16;
            auto send = [&](int kv) {
#pragma unroll
                for (int h = 0; h < 2; h++) {
                    uint32_t v[16];
                    v[14] = v[15] = 0;
#pragma unroll
                    for (int c = 0; c < 14; c++) v[c] = p[2 * c + h];
#pragma unroll
                    for (int c = 0; c < 14; c += 2) v[15] |= (v[c] & 1) << c;
#pragma unroll
                    for (int i = 0; i < 4; i++) st_part(hout + (h * 8 + kv) * 2048 + i * 512, v + 4 * i, tag & 1);
                }
            };
            float x0[56], x1[56];
            r.seek(0, bslot_h(0));
            r.wait();
            r.run<XWN, 7, true>(x0);
#pragma unroll 1
            for (int i = 1; i < 7; i++) r.run<XWN, 7, false>(x0);
            r.run<XWN, 7, true>(x1);
            acc_fence(x0);
            pack_all(x0, p);
            send(0);
#pragma unroll 1
            for (int i = 1; i < 7; i++) r.run<XWN, 7, false>(x1, true, true, i < 6);
            asm volatile("wgmma.wait_group.sync.aligned 0;" ::: "memory");
            acc_fence(x1);
            pack_all(x1, p);
#pragma unroll
            for (int i = 0; i < 28; i++) p[i] = movm(p[i]);
            send(1);
            if (threadIdx.x == 0) *epoch_ptr = tag;
        } else if (!roleL) {
            uint8_t* blob = sc->ab + (size_t)((wg * 16 + mt) * 4 + ns) * BLOB + (warp & 3) * WSLOT + lane * 4;
            const uint32_t own = base + BRING + wg * SLOT + (warp & 3) * WSLOT + lane * 16;
            float x0[56], x1[56];
            r.seek(0, bslot_e(0));
            r.wait();
            r.run<XW, 7, true>(x0);
            r.run<XW, 7, false>(x0);
            r.seek(2, bslot_e(2));
#pragma unroll 1
            for (int i = 2; i < 7; i++) r.run<XW, 5, false>(x0);

            r.seek(7, bslot_e(7));
            r.run<XW, 5, true, -1>(x1);
            acc_fence(x0);
            pack_all(x0, p);
#pragma unroll
            for (int i = 0; i < 2; i++) {
                if (wg == i) store_frags<0, 14>(blob, p);
                else stage_frags<0, A_OWN>(own + 5 * SLOT, p);
                r.run<XW, 5, false, -1>(x1);
                if (wg == i) {
                    store_frags<14, 28>(blob, p);
                    warp_arrive(base + BAR_RDY + i * 8);
                } else {
                    stage_frags<A_OWN, 2 * A_OWN>(own + 5 * SLOT, p);
                }
                r.run<XW, 5, false, -1>(x1);
            }
            stage_frags<2 * A_OWN, A_OWN2>(own + 5 * SLOT, p);
            r.run<XW, 5, false, -1>(x1);
            stage_frags<A_OWN2, 28>(own + 5 * SLOT, p);
            fence_async_smem();
            r.run<XW, 5, false, -1>(x1);

            r.seek(14, bslot_e(14));
            r.run<BIG, 7, true>(x0);
            acc_fence(x1);
            pack_all(x1, p);
            stage_frags<0, B_OWN>(own, p);
            r.run<BIG, 7, false>(x0);
            stage_frags<B_OWN, 28>(own, p);
            fence_async_smem();
            blob += (size_t)128 * BLOB;
#pragma unroll
            for (int i = 0; i < 28; i++) {
                if (i % B_SLICE == 0) r.run<BIG, 7, false>(x0);
                stg1(blob + i * 128, p[i]);
            }
            warp_arrive(base + BAR_RDY + 16);
#pragma unroll 1
            for (int i = 17 + 27 / B_SLICE; i < POUT; i++) r.run<BIG, 7, false>(x0);

            const uint32_t tag = lds1(base + TAG);
            r.seek(POUT, bslot_e(POUT));
            r.run<OUT, 7, true>(x1);
            acc_fence(x0);
            pack_all(x0, p);
#pragma unroll
            for (int k = 0; k < 3; k++) {
                if (k < 2 && wg == k) {
                    if ((warp & 3) == 0 && elect())
                        asm volatile("red.relaxed.gpu.global.add.u32 [%0], 1;" ::"l"(&sc->cnt[(CNT_P + mt * 4 + ns) * 32]) : "memory");
#pragma unroll
                    for (int i = 0; i < 4; i++) st_part(part + i * 4096, p + 4 * i, tag & 1);
                }
                if (k > 0 && wg == k - 1) {
#pragma unroll
                    for (int i = 4; i < 7; i++) st_part(part + i * 4096, p + 4 * i, tag & 1);
                }
                if (k < 2) r.run<OUT, 7, false>(x1);
            }
#pragma unroll
            for (int i = 3; i < 7; i++) r.run<OUT, 7, false, 1, true>(x1, i <= 7 - TURN, i < 7 - TURN || i == 6, i < 6);

            asm volatile("wgmma.wait_group.sync.aligned 0;" ::: "memory");
            acc_fence(x1);
            const uint32_t slab = base + (wg ? BRING + bslot_e(ELAST - 6) * SLOT : ((ELAST - 6) % NA) * SLOT) + (warp & 3) * WSLOT;
            store_out([&](int i) { return pack2(x1[2 * i], x1[2 * i + 1]); }, lane, slab, &maps.m[M_OUTA], par * 896 + col, blk * 128 + warp * 16);
        } else {
            const int g = lane >> 2, tig = lane & 3;
            const uint32_t hin = base + HALO + warp * HSLOT + lane * 4;
            const uint32_t hpub = warp < 7 ? hin + HSLOT : base + HSPARE + lane * 4;
            auto publish = [&](const uint32_t (&h)[14], int c0, int c1) {
#pragma unroll
                for (int c = 0; c < 14; c++)
                    if (c >= c0 && c < c1) sts1(hpub + c * 128, h[c]);
            };
            float y0[56], y1[56], y2[56];
            r.seek(0, bslot_l(0));
            r.wait();
            r.run<QK, 6, true>(y0, y1);
#pragma unroll 1
            for (int i = 1; i < 14; i++) r.run<QK, 6, false>(y0, y1);

            uint32_t m1[8][4], m0[8][4], lo[14], hi[14], q[2][8][2];
            auto pack_q = [&](int b) {
                uint32_t v[14];
#pragma unroll
                for (int c = 0; c < 14; c++) v[c] = pack2(y0[4 * c + 2 * b], y0[4 * c + 2 * b + 1]);
#pragma unroll
                for (int t = 0; t < 8; t++) {
                    const int c = tile_of(t);
                    q[b][t][0] = (t & 3) == 2 ? (tig >= 2 ? v[c] : 0u) : v[c];
                    q[b][t][1] = (t & 3) == 1 ? (tig < 2 ? v[c + 1] : 0u) : v[c + 1];
                }
            };
            auto fetch = [&](uint32_t src, int hp, int i0) {
#pragma unroll
                for (int t = 4 * hp; t < 4 * hp + 4; t++) {
                    m0[t][i0] = (t & 3) == 2 ? dup(m0[t - 1][3], r.zero) : lds1(src + tile_of(t) * 128);
                    m0[t][3] = lds1(src + tile_of(t) * 128 + 128);
                }
            };
            r.seek(14, bslot_l(14));
            r.run<XWN, 6, true>(y2);
            acc_fence(y0);
            acc_fence(y1);
#pragma unroll
            for (int c = 0; c < 14; c++) hi[c] = pack2(y1[4 * c + 2], y1[4 * c + 3]);
            publish(hi, 0, 7);
            r.run<XWN, 6, false>(y2);
            publish(hi, 7, 14);
#pragma unroll
            for (int c = 0; c < 14; c++) lo[c] = pack2(y1[4 * c], y1[4 * c + 1]);
#pragma unroll
            for (int t = 0; t < 8; t++) {
                const int c = tile_of(t);
                const bool shared = (t & 3) == 2;
                m1[t][0] = shared ? dup(lo[c], r.zero) : lo[c];
                m1[t][1] = shared ? dup(hi[c], r.zero) : hi[c];
                m1[t][2] = lo[c + 1];
                m1[t][3] = hi[c + 1];
                m0[t][0] = dup(m1[t][0], r.zero);
                m0[t][2] = dup(lo[c + 1], 2 * r.zero);
            }
            r.run<XWN, 6, false>(y2);
            if (warp == 0) mbar_wait(base + BAR_HALO, 0);
            fetch(hin, 0, 1);
            pack_q(1);
            r.run<XWN, 6, false>(y2);
            fetch(hin, 1, 1);
            pack_q(0);
            r.mma_begin();
            float s[8][4];
#pragma unroll
            for (int step = 0; step < 2; step++) {
#pragma unroll
                for (int i = 0; i < 8; i++) {
                    const int b = 1 - (i >> 2), h = i & 3, t = 2 * h + step;
                    float (&d)[4] = s[2 * h + b];
                    if (step == 0) d[0] = d[1] = d[2] = d[3] = 0.f;
                    mma16816(d, b ? m1[t] : m0[t], q[b][t][0], q[b][t][1]);
                }
            }
            r.mma_end();
            r.run<XWN, 6, false>(y2, false);

            uint32_t pr[8], mx[4], mx1[4];
            {
                const bool cur0 = g <= 2 * tig, cur1 = g <= 2 * tig + 1;
#pragma unroll
                for (int i = 0; i < 8; i++) {
                    const int c = (i & 1) ? 2 : 0;
                    pr[i] = movm(pack2(cur0 ? s[i][c] : s[i][2 - c], cur1 ? s[i][c + 1] : s[i][3 - c]));
                }
            }
            r.run<XWN, 6, false>(y2);
            const uint32_t curmask = (2 * tig <= g ? 0x0000FFFFu : 0u) | (2 * tig + 1 <= g ? 0xFFFF0000u : 0u);
            {
                const uint32_t keep = (blk == 0 && warp == 0) ? curmask : 0xFFFFFFFFu;
#pragma unroll
                for (int i = 0; i < 4; i++) {
                    pr[2 * i] = (pr[2 * i] & keep) | (0xCF9ECF9Eu & ~keep);
                    mx[i] = max2(__byte_perm(pr[2 * i], pr[2 * i + 1], 0x5410), __byte_perm(pr[2 * i], pr[2 * i + 1], 0x7632));
                    mx1[i] = __shfl_xor_sync(0xffffffffu, mx[i], 1);
                }
            }
#pragma unroll
            for (int i = 0; i < 4; i++) {
                mx[i] = max2(mx[i], mx1[i]);
                mx1[i] = __shfl_xor_sync(0xffffffffu, mx[i], 2);
            }
            r.run<XWN, 6, false>(y2);
            constexpr float SCL = 0.18898223650461362f * 1.4426950408889634f;
            float e0[8], e1[8], sm[8], sm1[8];
#pragma unroll
            for (int i = 0; i < 8; i++) {
                const uint32_t m2 = max2(mx[i >> 1], mx1[i >> 1]);
                sm[i] = ((i & 1) ? bf_hi(m2) : bf_lo(m2)) * -SCL;
                e0[i] = ex2(fmaf(bf_lo(pr[i]), SCL, sm[i]));
            }

            r.seek(21, bslot_l(21));
            r.run<BIG, 6, true>(y0);
            acc_fence(y2);
#pragma unroll
            for (int c = 0; c < 7; c++) hi[c] = movm(pack2(y2[4 * c + 2], y2[4 * c + 3]));
#pragma unroll
            for (int i = 0; i < 8; i++) e1[i] = ex2(fmaf(bf_hi(pr[i]), SCL, sm[i]));
            r.run<BIG, 6, false>(y0);
            publish(hi, 0, 7);
#pragma unroll
            for (int c = 7; c < 14; c++) hi[c] = movm(pack2(y2[4 * c + 2], y2[4 * c + 3]));
            r.run<BIG, 6, false>(y0);
            publish(hi, 7, 14);
#pragma unroll
            for (int i = 0; i < 8; i++) {
                sm[i] = e0[i] + e1[i];
                sm1[i] = __shfl_xor_sync(0xffffffffu, sm[i], 1);
            }
            r.run<BIG, 6, false>(y0);
#pragma unroll
            for (int c = 0; c < 14; c++) lo[c] = movm(pack2(y2[4 * c], y2[4 * c + 1]));
            r.run<BIG, 6, false>(y0);
#pragma unroll
            for (int i = 0; i < 8; i++) {
                sm[i] += sm1[i];
                sm1[i] = __shfl_xor_sync(0xffffffffu, sm[i], 2);
            }
#pragma unroll
            for (int t = 0; t < 8; t++) {
                const int c = tile_of(t);
                const bool shared = (t & 3) == 2;
                m1[t][0] = shared ? dup(lo[c], r.zero) : lo[c];
                m1[t][1] = lo[c + 1];
                m1[t][2] = shared ? dup(hi[c], r.zero) : hi[c];
                m1[t][3] = hi[c + 1];
                m0[t][0] = dup(m1[t][0], r.zero);
                m0[t][1] = dup(lo[c + 1], 2 * r.zero);
            }
            r.run<BIG, 6, false>(y0);
            if (warp == 0) mbar_wait(base + BAR_HALO + 8, 0);
            const uint32_t vin = warp ? hin : hin + 8 * HSLOT;
            fetch(vin, 0, 2);
#pragma unroll
            for (int i = 0; i < 8; i++) {
                const float inv = rcp(sm[i] + sm1[i]);
                pr[i] = pack2(e0[i] * inv, e1[i] * inv);
            }
            r.run<BIG, 6, false>(y0);
            fetch(vin, 1, 2);
            uint32_t pb[8][2];
#pragma unroll
            for (int t = 0; t < 8; t++) {
                pb[t][t & 1] = band(pr[t], curmask);
                pb[t][1 - (t & 1)] = band(pr[t], ~curmask);
            }
            r.mma_begin();
            float o[2][8][4];
#pragma unroll
            for (int i = 0; i < 16; i++) {
                const int b = 1 - (i >> 3), t = i & 7;
                float (&d)[4] = o[b][t];
                d[0] = d[1] = d[2] = d[3] = 0.f;
                mma16816(d, b ? m1[t] : m0[t], pb[(t & 6) + b][0], pb[(t & 6) + b][1]);
            }
            r.mma_end();
            r.run<BIG, 6, false>(y0, false);
            uint8_t* odst = sc->o + (size_t)mt * 7 * SLOT + ns * (14 * 2048) + warp * 256 + lane * 4;
#pragma unroll
            for (int hp = 0; hp < 2; hp++) {
#pragma unroll
                for (int b = 0; b < 2; b++) {
                    const float (&u)[8][4] = o[b];
                    const int t = 4 * hp;
                    uint32_t* w = p + 14 * hp + b;
                    w[0] = pack2(u[t][0], u[t][1]);
                    w[2] = pack2(u[t][2], u[t][3]);
                    w[4] = pack2(u[t + 1][0], u[t + 1][1]);
                    w[6] = pack2(g < 4 ? u[t + 1][2] : u[t + 2][0], g < 4 ? u[t + 1][3] : u[t + 2][1]);
                    w[8] = pack2(u[t + 2][2], u[t + 2][3]);
                    w[10] = pack2(u[t + 3][0], u[t + 3][1]);
                    w[12] = pack2(u[t + 3][2], u[t + 3][3]);
                }
            }
#pragma unroll
            for (int i = 0; i < 28; i++) {
                if (i >= O_FIRST && (i - O_FIRST) % O_SLICE == 0) r.run<BIG, 6, false>(y0);
                stg1(odst + (i >> 1) * 2048 + (i & 1) * 128, p[i]);
            }
            warp_arrive(base + BAR_RDY + 16);

#pragma unroll 1
            for (int i = 30 + (27 - O_FIRST) / O_SLICE; i <= LLAST + 1 - TURN; i++) r.run<BIG, 6, false>(y0, true, i <= LLAST - TURN);
            const uint32_t tag = lds1(base + TAG);
            if (mbar_test(base + BAR_PART + wg * 8, 0)) {
#pragma unroll
                for (int i = 0; i < 7; i++) ld_tagged(part + i * 4096, p[4 * i], p[4 * i + 1], p[4 * i + 2], p[4 * i + 3]);
            } else {
                p[0] = ~tag;
            }
            r.seek(LLAST + 2 - TURN, bslot_l(LLAST + 2 - TURN));
#pragma unroll
            for (int i = 1; i < TURN; i++) r.run<BIG, 6, false, 1, true>(y0, false, i == TURN - 1, i < TURN - 1);
#pragma unroll 1
            for (int n = 0; n < SPIN_LIMIT; n++) {
                uint32_t stale = 0;
#pragma unroll
                for (int i = 0; i < 28; i += 2) stale |= p[i] ^ tag;
                if (__all_sync(0xffffffffu, !(stale & 1))) break;
                mbar_wait(base + BAR_PART + wg * 8, 0);
#pragma unroll
                for (int i = 0; i < 7; i++) ld_tagged(part + i * 4096, p[4 * i], p[4 * i + 1], p[4 * i + 2], p[4 * i + 3]);
            }
            asm volatile("wgmma.wait_group.sync.aligned 0;" ::: "memory");
            acc_fence(y0);
            const uint32_t slab = base + (wg ? HALO : ((LLAST - 6) % NA) * SLOT) + (warp & 3) * WSLOT;
            store_out([&](int i) { return add2(pack2(y0[2 * i], y0[2 * i + 1]), p[i]); }, lane, slab, &maps.m[M_OUTB], 448 + col, mt * 128 + warp * 16);
        }
    }
}

typedef CUresult (*EncodeFn)(CUtensorMap*, CUtensorMapDataType, cuuint32_t, void*, const cuuint64_t*, const cuuint64_t*,
                             const cuuint32_t*, const cuuint32_t*, CUtensorMapInterleave, CUtensorMapSwizzle,
                             CUtensorMapL2promotion, CUtensorMapFloatOOBfill);

struct Dim { uint64_t size, stride; uint32_t box; };
void encode(EncodeFn fn, CUtensorMap* m, const void* ptr, CUtensorMapSwizzle sw, Dim d0, Dim d1, Dim d2 = {0, 0, 0},
            Dim d3 = {0, 0, 0}, Dim d4 = {0, 0, 0}) {
    const cuuint64_t dims[5] = {d0.size, d1.size, d2.size, d3.size, d4.size};
    const cuuint64_t strides[4] = {d1.stride, d2.stride, d3.stride, d4.stride};
    const cuuint32_t box[5] = {d0.box, d1.box, d2.box, d3.box, d4.box};
    const cuuint32_t es[5] = {1, 1, 1, 1, 1};
    fn(m, CU_TENSOR_MAP_DATA_TYPE_BFLOAT16, d4.size ? 5 : d3.size ? 4 : 2, const_cast<void*>(ptr), dims, strides, box, es,
       CU_TENSOR_MAP_INTERLEAVE_NONE, sw, CU_TENSOR_MAP_L2_PROMOTION_L2_128B, CU_TENSOR_MAP_FLOAT_OOB_FILL_NONE);
}

}

extern "C" void kernel_launch(void* const* d_in, const int* in_sizes, int n_in, void* d_out, int out_size) {
    (void)in_sizes; (void)n_in; (void)out_size;
    void* fnp = nullptr;
    cudaDriverEntryPointQueryResult st;
    cudaGetDriverEntryPoint("cuTensorMapEncodeTiled", &fnp, cudaEnableDefault, &st);
    EncodeFn fn = (EncodeFn)fnp;
    void* scratch = nullptr;
    cudaGetSymbolAddress(&scratch, g_scratch);
    int dev = 0, sms = 0;
    cudaGetDevice(&dev);
    cudaDeviceGetAttribute(&sms, cudaDevAttrMultiProcessorCount, dev);
    auto kernel = sms == 132 ? fused_kernel<true> : fused_kernel<false>;
    cudaFuncSetAttribute(kernel, cudaFuncAttributeMaxDynamicSharedMemorySize, SMEM_BYTES);

    const CUtensorMapSwizzle S128 = CU_TENSOR_MAP_SWIZZLE_128B, S0 = CU_TENSOR_MAP_SWIZZLE_NONE;
    const Dim one = {1, 16, 1};
    Maps maps;
    encode(fn, &maps.m[M_XA], d_in[0], S128, {448, 2, 64}, {128, 1792, 128}, one, {2, 896, 1}, {8, 128 * 1792, 1});
    encode(fn, &maps.m[M_WQK], d_in[1], S128, {112, 2, 64}, {448, 2688, 32}, {3, 896, 2}, {4, 224, 1});
    encode(fn, &maps.m[M_WV], (const uint8_t*)d_in[1] + 896, S128, {112, 2, 64}, {448, 2688, 64}, one, {8, 224, 1});
    encode(fn, &maps.m[M_XH], d_in[0], S128, {448, 2, 64}, {8, 1792, 8}, {8, 128 * 1792, 8}, {2, 896, 2}, {3, 60 * 1792, 1});
    encode(fn, &maps.m[M_WO], d_in[2], S128, {112, 2, 64}, {448, 896, 64}, one, {4, 224, 1});
    encode(fn, &maps.m[M_XB], d_in[3], S128, {448, 2, 64}, {64, 896, 64}, {2, 896 * 1024, 2}, {2, 64 * 896, 1}, {8, 128 * 896, 1});
    encode(fn, &maps.m[M_CR], d_in[4], S128, {2048, 2, 64}, {2048, 4096, 128});
    encode(fn, &maps.m[M_CI], d_in[5], S128, {2048, 2, 64}, {2048, 4096, 128});
    encode(fn, &maps.m[M_WR], d_in[6], S128, {448, 2, 64}, {112, 896, 64}, one, {4, 112 * 896, 1});
    encode(fn, &maps.m[M_WI], d_in[7], S128, {448, 2, 64}, {448, 896, 112});
    encode(fn, &maps.m[M_OUTA], d_out, S0, {1792, 2, 112}, {1024, 3584, 8});
    encode(fn, &maps.m[M_OUTB], d_out, S0, {896, 2, 112}, {2048, 1792, 8});

    kernel<<<132, 384, SMEM_BYTES>>>((Scratch*)scratch, maps);
}
```

```cpp
#include <cuda.h>
#include <cuda_bf16.h>
#include <cuda_runtime.h>
#include <stdint.h>

namespace {

constexpr uint32_t SLOT = 16384;
constexpr int NA = 7;
constexpr uint32_t BRING = NA * SLOT;
constexpr uint32_t HALO = BRING + 6 * SLOT;
constexpr uint32_t HSLOT = 1792;
constexpr uint32_t WSLOT = 3584;
constexpr uint32_t BLOB = 14336;
constexpr uint32_t BARS = 14 * SLOT;
constexpr uint32_t BAR_FULL = BARS;
constexpr uint32_t BAR_EMPTY = BARS + 64;
constexpr uint32_t BAR_RDY = BARS + 128;
constexpr uint32_t BAR_DEP = BARS + 168;
constexpr uint32_t BAR_HALO = BARS + 192;
constexpr uint32_t BAR_PART = BARS + 208;
constexpr uint32_t TAG = BARS + 224;
constexpr uint32_t HSPARE = BARS + 256 + 1024;
constexpr uint32_t SMEM_BYTES = HSPARE + HSLOT;
constexpr uint32_t base = 1024;
constexpr int SPIN_LIMIT = 1 << 16;

#define E_EXTRA 0
#define HALO_K_AT 10
#define HALO_V_AT 19
#define O_SLICE 4
#define B_SLICE 4
#define TURN 4
#define PACE 400
#define O_FIRST 8
#define B_OWN 28
#define MMA_SYNC 2
#define A_OWN 4
#define A_OWN2 20
#define PACE0 200
#define GPC_MAP 0x64752310u

constexpr int NBE = 13 + E_EXTRA;
constexpr int POUT = 33 + NBE;
constexpr int ELAST = POUT + 6;
constexpr int LLAST = 52 - E_EXTRA;
static_assert(TURN <= 4, "the output is staged in the slots of the seventh-last stage");

enum { M_XB, M_XA, M_XH, M_WR, M_WQK, M_WV, M_WO, M_WI, M_CR, M_CI, M_OUTA, M_OUTB, M_COUNT };
struct __align__(64) Maps { CUtensorMap m[M_COUNT]; };

constexpr int CNT_A = 0;
constexpr int CNT_B = 8;
constexpr int CNT_O = 16;
constexpr int CNT_P = 32;
constexpr int CNT_COUNT = 96;

struct Scratch {
    uint8_t ab[64 * 4 * BLOB];
    uint8_t o[16 * 7 * SLOT];
    uint8_t part[64 * 2 * BLOB];
    uint8_t halo[64 * 2 * 2048];
    unsigned cnt[CNT_COUNT * 32];
    unsigned epoch[132 * 4 * 8];
};
__device__ __align__(1024) Scratch g_scratch;

__device__ __forceinline__ unsigned clk32() { unsigned c; asm volatile("mov.u32 %0, %%clock;" : "=r"(c)); return c; }

#define PROF(idx)

__device__ __forceinline__ void mbar_init(uint32_t bar, uint32_t cnt) {
    asm volatile("mbarrier.init.shared::cta.b64 [%0], %1;" ::"r"(bar), "r"(cnt) : "memory");
}
__device__ __forceinline__ void mbar_expect(uint32_t bar, uint32_t bytes) {
    asm volatile("mbarrier.arrive.expect_tx.shared::cta.b64 _, [%0], %1;" ::"r"(bar), "r"(bytes) : "memory");
}
__device__ __forceinline__ void mbar_arrive(uint32_t bar) {
    asm volatile("mbarrier.arrive.shared::cta.b64 _, [%0];" ::"r"(bar) : "memory");
}
__device__ __forceinline__ bool mbar_try(uint32_t bar, uint32_t parity) {
    uint32_t ok;
    asm volatile("{\n.reg .pred p;\nmbarrier.try_wait.parity.shared::cta.b64 p, [%1], %2;\nselp.u32 %0, 1, 0, p;\n}\n"
                 : "=r"(ok) : "r"(bar), "r"(parity) : "memory");
    return ok;
}
__device__ __forceinline__ bool mbar_test(uint32_t bar, uint32_t parity) {
    uint32_t ok;
    asm volatile("{\n.reg .pred p;\nmbarrier.test_wait.parity.shared::cta.b64 p, [%1], %2;\nselp.u32 %0, 1, 0, p;\n}\n"
                 : "=r"(ok) : "r"(bar), "r"(parity) : "memory");
    return ok;
}
__device__ __forceinline__ void mbar_wait(uint32_t bar, uint32_t parity) {
#pragma unroll 1
    for (int n = 0; n < SPIN_LIMIT; n++)
        if (mbar_try(bar, parity)) break;
}
__device__ __forceinline__ bool elect() {
    uint32_t p;
    asm volatile("{\n.reg .pred p;\nelect.sync _|p, 0xffffffff;\nselp.u32 %0, 1, 0, p;\n}\n" : "=r"(p));
    return p;
}
__device__ __forceinline__ void nb_sync(int id, int n) { asm volatile("bar.sync %0, %1;" ::"r"(id), "r"(n) : "memory"); }
__device__ __forceinline__ void nb_arrive(int id, int n) { asm volatile("bar.arrive %0, %1;" ::"r"(id), "r"(n) : "memory"); }
__device__ __forceinline__ void warp_arrive(uint32_t bar) {
    __syncwarp();
    if (elect()) mbar_arrive(bar);
}
__device__ __forceinline__ uint32_t band(uint32_t x, uint32_t m) {
    uint32_t r;
    asm volatile("and.b32 %0, %1, %2;" : "=r"(r) : "r"(x), "r"(m));
    return r;
}
__device__ __forceinline__ uint32_t dup(uint32_t x, uint32_t zero) {
    uint32_t r;
    asm volatile("xor.b32 %0, %1, %2;" : "=r"(r) : "r"(x), "r"(zero));
    return r;
}

__device__ __forceinline__ void tma_ld2(uint32_t dst, const CUtensorMap* m, int c0, int c1, uint32_t bar) {
    asm volatile("cp.async.bulk.tensor.2d.shared::cluster.global.mbarrier::complete_tx::bytes [%0], [%1, {%3, %4}], [%2];"
                 ::"r"(dst), "l"(m), "r"(bar), "r"(c0), "r"(c1) : "memory");
}
__device__ __forceinline__ void tma_ld4(uint32_t dst, const CUtensorMap* m, int c0, int c1, int c2, int c3, uint32_t bar) {
    asm volatile("cp.async.bulk.tensor.4d.shared::cluster.global.mbarrier::complete_tx::bytes [%0], [%1, {%3, %4, %5, %6}], [%2];"
                 ::"r"(dst), "l"(m), "r"(bar), "r"(c0), "r"(c1), "r"(c2), "r"(c3) : "memory");
}
__device__ __forceinline__ void tma_ld5(uint32_t dst, const CUtensorMap* m, int c0, int c3, int c4, uint32_t bar) {
    asm volatile("cp.async.bulk.tensor.5d.shared::cluster.global.mbarrier::complete_tx::bytes [%0], [%1, {%3, 0, 0, %4, %5}], [%2];"
                 ::"r"(dst), "l"(m), "r"(bar), "r"(c0), "r"(c3), "r"(c4) : "memory");
}
__device__ __forceinline__ void bulk_ld(uint32_t dst, const void* src, uint32_t bytes, uint32_t bar) {
    asm volatile("cp.async.bulk.shared::cluster.global.mbarrier::complete_tx::bytes [%0], [%1], %2, [%3];"
                 ::"r"(dst), "l"(src), "r"(bytes), "r"(bar) : "memory");
}
__device__ __forceinline__ void tma_st2(const CUtensorMap* m, int c0, int c1, uint32_t src) {
    asm volatile("cp.async.bulk.tensor.2d.global.shared::cta.bulk_group [%0, {%1, %2}], [%3];"
                 ::"l"(m), "r"(c0), "r"(c1), "r"(src) : "memory");
}
__device__ __forceinline__ void bulk_commit() { asm volatile("cp.async.bulk.commit_group;" ::: "memory"); }
__device__ __forceinline__ void bulk_wait_read() { asm volatile("cp.async.bulk.wait_group.read 0;" ::: "memory"); }
__device__ __forceinline__ void fence_async_smem() { asm volatile("fence.proxy.async.shared::cta;" ::: "memory"); }
__device__ __forceinline__ void fence_async_global() { asm volatile("fence.proxy.async.global;" ::: "memory"); }

__device__ __forceinline__ void signal(Scratch* sc, int idx) {
    asm volatile("fence.proxy.async;\nred.relaxed.gpu.global.add.u32 [%0], 1;" ::"l"(&sc->cnt[idx * 32]) : "memory");
}
__device__ __forceinline__ unsigned peek(const unsigned* p) {
    unsigned v;
    asm volatile("ld.relaxed.gpu.global.u32 %0, [%1];" : "=r"(v) : "l"(p) : "memory");
    return v;
}
__device__ __forceinline__ void await(Scratch* sc, int idx, unsigned target) {
    const unsigned* p = &sc->cnt[idx * 32];
#pragma unroll 1
    for (int n = 0; n < SPIN_LIMIT; n++)
        if ((int)(peek(p) - target) >= 0) break;
    asm volatile("fence.acquire.gpu;" ::: "memory");
}
__device__ __forceinline__ void wait_dep(int k) {
    mbar_wait(base + BAR_DEP + k * 8, 0);
    fence_async_global();
}

#define WG_REGS                                                                                                     \
    "{%0,%1,%2,%3,%4,%5,%6,%7,%8,%9,%10,%11,%12,%13,%14,%15,%16,%17,%18,%19,%20,%21,%22,%23,%24,%25,%26,%27,"       \
    "%28,%29,%30,%31,%32,%33,%34,%35,%36,%37,%38,%39,%40,%41,%42,%43,%44,%45,%46,%47,%48,%49,%50,%51,%52,%53,%54,%55}"
#define WG_OPS(C)                                                                                                   \
    C(d[0]), C(d[1]), C(d[2]), C(d[3]), C(d[4]), C(d[5]), C(d[6]), C(d[7]), C(d[8]), C(d[9]), C(d[10]), C(d[11]),   \
    C(d[12]), C(d[13]), C(d[14]), C(d[15]), C(d[16]), C(d[17]), C(d[18]), C(d[19]), C(d[20]), C(d[21]), C(d[22]),   \
    C(d[23]), C(d[24]), C(d[25]), C(d[26]), C(d[27]), C(d[28]), C(d[29]), C(d[30]), C(d[31]), C(d[32]), C(d[33]),   \
    C(d[34]), C(d[35]), C(d[36]), C(d[37]), C(d[38]), C(d[39]), C(d[40]), C(d[41]), C(d[42]), C(d[43]), C(d[44]),   \
    C(d[45]), C(d[46]), C(d[47]), C(d[48]), C(d[49]), C(d[50]), C(d[51]), C(d[52]), C(d[53]), C(d[54]), C(d[55])

template <int TA, int TB, int SB, bool INIT, uint32_t AH, uint32_t BH>
__device__ __forceinline__ void wgmma112(float (&d)[56], uint32_t alo, uint32_t blo) {
    if (INIT) {
        asm volatile("{\n.reg .pred p;\n.reg .b64 da, db;\nsetp.ne.b32 p, 0, 0;\nmov.b64 da, {%56, %61};\nmov.b64 db, {%57, %62};\n"
                     "wgmma.mma_async.sync.aligned.m64n112k16.f32.bf16.bf16 " WG_REGS ", da, db, p, 1, %59, %60, %58;\n}\n"
                     : WG_OPS("=f") : "r"(alo), "r"(blo), "n"(TB), "n"(SB), "n"(TA), "n"(AH), "n"(BH));
    } else {
        asm volatile("{\n.reg .pred p;\n.reg .b64 da, db;\nsetp.ne.b32 p, 1, 0;\nmov.b64 da, {%56, %61};\nmov.b64 db, {%57, %62};\n"
                     "wgmma.mma_async.sync.aligned.m64n112k16.f32.bf16.bf16 " WG_REGS ", da, db, p, 1, %59, %60, %58;\n}\n"
                     : WG_OPS("+f") : "r"(alo), "r"(blo), "n"(TB), "n"(SB), "n"(TA), "n"(AH), "n"(BH));
    }
}
__device__ __forceinline__ void acc_fence(float (&d)[56]) {
#pragma unroll
    for (int i = 0; i < 56; i++) asm volatile("" : "+f"(d[i])::"memory");
}

__device__ __forceinline__ uint32_t pack2(float lo, float hi) {
    uint32_t r;
    asm volatile("cvt.rn.bf16x2.f32 %0, %1, %2;" : "=r"(r) : "f"(hi), "f"(lo));
    return r;
}
__device__ __forceinline__ uint32_t movm(uint32_t a) {
    uint32_t r;
    asm volatile("movmatrix.sync.aligned.m8n8.trans.b16 %0, %1;" : "=r"(r) : "r"(a));
    return r;
}
__device__ __forceinline__ void stsm4(uint32_t addr, uint32_t a, uint32_t b, uint32_t c, uint32_t d) {
    asm volatile("stmatrix.sync.aligned.m8n8.x4.shared.b16 [%0], {%1,%2,%3,%4};" ::"r"(addr), "r"(a), "r"(b), "r"(c), "r"(d) : "memory");
}
__device__ __forceinline__ void sts1(uint32_t addr, uint32_t a) { asm volatile("st.shared.b32 [%0], %1;" ::"r"(addr), "r"(a) : "memory"); }
__device__ __forceinline__ uint32_t lds1(uint32_t addr) {
    uint32_t a;
    asm volatile("ld.shared.b32 %0, [%1];" : "=r"(a) : "r"(addr) : "memory");
    return a;
}
__device__ __forceinline__ void stg1(uint8_t* p, uint32_t a) { asm volatile("st.global.b32 [%0], %1;" ::"l"(p), "r"(a) : "memory"); }
__device__ __forceinline__ void st_part(uint8_t* p, const uint32_t* v, uint32_t parity) {
    asm volatile("{\n.reg .b64 x, y;\nmov.b64 x, {%1, %2};\nmov.b64 y, {%3, %4};\nst.relaxed.gpu.global.v2.b64 [%0], {x, y};\n}\n"
                 ::"l"(p), "r"((v[0] & ~1u) | parity), "r"(v[1]), "r"((v[2] & ~1u) | parity), "r"(v[3]) : "memory");
}
__device__ __forceinline__ void mma16816(float (&d)[4], const uint32_t (&a)[4], uint32_t b0, uint32_t b1) {
    asm volatile("mma.sync.aligned.m16n8k16.row.col.f32.bf16.bf16.f32 {%0,%1,%2,%3}, {%4,%5,%6,%7}, {%8,%9}, {%0,%1,%2,%3};"
                 : "+f"(d[0]), "+f"(d[1]), "+f"(d[2]), "+f"(d[3]) : "r"(a[0]), "r"(a[1]), "r"(a[2]), "r"(a[3]), "r"(b0), "r"(b1));
}
__device__ __forceinline__ uint32_t add2(uint32_t a, uint32_t b) {
    uint32_t r;
    asm("add.rn.bf16x2 %0, %1, %2;" : "=r"(r) : "r"(a), "r"(b));
    return r;
}
__device__ __forceinline__ uint32_t max2(uint32_t a, uint32_t b) {
    uint32_t r;
    asm("max.bf16x2 %0, %1, %2;" : "=r"(r) : "r"(a), "r"(b));
    return r;
}
__device__ __forceinline__ void ld_tagged(const uint8_t* p, uint32_t& a, uint32_t& ta, uint32_t& b, uint32_t& tb) {
    asm volatile("{\n.reg .b64 x, y;\nld.relaxed.gpu.global.v2.b64 {x, y}, [%4];\nmov.b64 {%0, %1}, x;\nmov.b64 {%2, %3}, y;\n}\n"
                 : "=r"(a), "=r"(ta), "=r"(b), "=r"(tb) : "l"(p) : "memory");
}
__device__ __forceinline__ float bf_lo(uint32_t v) { return __uint_as_float(v << 16); }
__device__ __forceinline__ float bf_hi(uint32_t v) { return __uint_as_float(v & 0xFFFF0000u); }
__device__ __forceinline__ float rcp(float x) { float r; asm("rcp.approx.ftz.f32 %0, %1;" : "=f"(r) : "f"(x)); return r; }
__device__ __forceinline__ float ex2(float x) { float r; asm volatile("ex2.approx.ftz.f32 %0, %1;" : "=f"(r) : "f"(x)); return r; }

__device__ __forceinline__ uint32_t full_bar(int stage) { return base + BAR_FULL + (stage & 7) * 8; }
__device__ __forceinline__ void wait_released(int j) { mbar_wait(base + BAR_EMPTY + (j & 7) * 8, (j >> 3) & 1); }

template <int V>
struct Int { static constexpr int value = V; };

__host__ __device__ constexpr int bslot_e(int i) { return (i < 2 || i >= 14) ? (i + 5) % 7 : (i + 1) % 5; }
__host__ __device__ constexpr int bslot_l(int i) { return (i + 5) % 6; }
__host__ __device__ constexpr int bslot_h(int i) { return (i + 5) % 7; }

template <uint32_t OFF>
struct Feed {
    int stage;
    uint32_t dst;
    __device__ __forceinline__ void seek(int i, int slot) { stage = i; dst = base + OFF + slot * SLOT; }
    template <int N>
    __device__ __forceinline__ uint32_t acquire() { wait_released(stage - N); return full_bar(stage); }
    template <int N>
    __device__ __forceinline__ void next() {
        stage++;
        dst += SLOT;
        if (dst == base + OFF + N * SLOT) dst = base + OFF;
    }
};
__device__ __forceinline__ int skip_own(int n, int mt) { return n == mt ? 15 : n; }

struct Desc { uint32_t lo, hi; };
__host__ __device__ constexpr Desc desc_const(uint32_t lbo, uint32_t sbo, uint32_t mode) { return {(lbo >> 4) << 16, (sbo >> 4) | (mode << 30)}; }
constexpr Desc D_K128 = desc_const(16, 1024, 1);
constexpr Desc D_N128 = desc_const(8192, 1024, 1);
constexpr Desc D_BLOB = desc_const(128, 256, 0);
constexpr Desc D_OT = desc_const(2048, 128, 0);

enum Kind { XW, XWN, QK, BIG, OUT };

struct Ring {
    int stage;
    uint32_t a, b;
    uint32_t wg;
    uint32_t zero;
    bool releaser;
    __device__ __forceinline__ void seek(int i, int bslot) {
        stage = i;
        a = (base + (i % NA) * SLOT) >> 4;
        b = (base + BRING + bslot * SLOT) >> 4;
    }
    __device__ __forceinline__ void wait() { mbar_wait(full_bar(stage), (stage >> 3) & 1); }
    __device__ __forceinline__ void take_turn() { nb_sync(1 + wg, 256); }
    __device__ __forceinline__ void pin() {
        uint32_t n = 0;
#pragma unroll 1
        do {
            asm volatile("pmevent 7;" ::: "memory");
        } while (n++ < zero);
    }
    __device__ __forceinline__ void mma_begin() {
        pin();
        if (!wg) take_turn();
        pin();
    }
    __device__ __forceinline__ void mma_end() {
        pin();
        if (wg) nb_arrive(3, 256);
        nb_sync(3 - wg, 256);
    }
    template <Kind K, int NBS, bool INIT, int SB = 1, bool TAIL = false>
    __device__ __forceinline__ void run(float (&d)[56], float (&e)[56], bool first = true, bool last = true, bool more = true) {
        if (first) take_turn();
        asm volatile("wgmma.fence.sync.aligned;" ::: "memory");
        if (K == QK) {
            const uint32_t da = D_K128.lo + (base >> 4) + (stage >> 1) * (SLOT >> 4) + (stage & 1) * 4 + wg * 512, db = D_N128.lo + b;
            wgmma112<0, 1, 1, INIT, D_K128.hi, D_N128.hi>(d, da, db);
            wgmma112<0, 1, 1, INIT, D_K128.hi, D_N128.hi>(e, da, db + 256);
            wgmma112<0, 1, 1, false, D_K128.hi, D_N128.hi>(d, da + 2, db + 128);
            wgmma112<0, 1, 1, false, D_K128.hi, D_N128.hi>(e, da + 2, db + 384);
        } else {
            constexpr int TA = K == OUT, TB = K != XW;
            constexpr uint32_t sa = K == OUT ? 256 : 2, sb = K == XW ? 2 : K == BIG ? 224 : 128;
            constexpr Desc A = K == OUT ? D_OT : D_K128, B = K == XW ? D_K128 : K == BIG ? D_BLOB : D_N128;
            const uint32_t da = A.lo + a + wg * (K == OUT ? 64 : 512), db = B.lo + b;
            wgmma112<TA, TB, SB, INIT, A.hi, B.hi>(d, da, db);
            wgmma112<TA, TB, SB, false, A.hi, B.hi>(d, da + sa, db + sb);
            wgmma112<TA, TB, SB, false, A.hi, B.hi>(d, da + 2 * sa, db + 2 * sb);
            wgmma112<TA, TB, SB, false, A.hi, B.hi>(d, da + 3 * sa, db + 3 * sb);
        }
        asm volatile("wgmma.commit_group.sync.aligned;" ::: "memory");
        if (!TAIL) asm volatile("wgmma.wait_group.sync.aligned 1;" ::: "memory");
        if (last) nb_arrive(2 - wg, 256);
        if (!TAIL && stage > 0) {
            if (releaser) mbar_arrive(base + BAR_EMPTY + ((stage - 1) & 7) * 8);
        }
        stage++;
        a += SLOT >> 4;
        if (a == (base + NA * SLOT) >> 4) a = base >> 4;
        b += SLOT >> 4;
        if (b == (base + BRING + NBS * SLOT) >> 4) b = (base + BRING) >> 4;
        if (more) wait();
    }
    template <Kind K, int NBS, bool INIT, int SB = 1, bool TAIL = false>
    __device__ __forceinline__ void run(float (&d)[56], bool first = true, bool last = true, bool more = true) {
        run<K, NBS, INIT, SB, TAIL>(d, d, first, last, more);
    }
};

__device__ __forceinline__ void pack_all(const float (&d)[56], uint32_t (&p)[28]) {
#pragma unroll
    for (int i = 0; i < 28; i++) p[i] = pack2(d[2 * i], d[2 * i + 1]);
}
template <int I0, int I1>
__device__ __forceinline__ void store_frags(uint8_t* dst, const uint32_t (&p)[28]) {
#pragma unroll
    for (int i = I0; i < I1; i++) stg1(dst + i * 128, p[i]);
}
template <int I0, int I1>
__device__ __forceinline__ void stage_frags(uint32_t lane_addr, const uint32_t (&p)[28]) {
#pragma unroll
    for (int i = I0; i < I1; i += 4) stsm4(lane_addr + i * 128, p[i], p[i + 1], p[i + 2], p[i + 3]);
}
template <class F>
__device__ __forceinline__ void store_out(F frag, int lane, uint32_t slab, const CUtensorMap* m, int c0, int c1) {
    const bool swap = lane & 16;
    const uint32_t addr = slab + (lane & 7) * 224 + ((lane >> 3) ^ ((lane >> 2) & 1)) * 16;
#pragma unroll
    for (int h = 0; h < 2; h++) {
#pragma unroll
        for (int c = 0; c < 14; c += 4) {
            const uint32_t t0 = frag(2 * c + h), t1 = frag(2 * c + 2 + h);
            if (c < 12) {
                const uint32_t t2 = frag(2 * c + 4 + h), t3 = frag(2 * c + 6 + h);
                stsm4(addr + h * 1792 + c * 16, swap ? t1 : t0, swap ? t0 : t1, swap ? t3 : t2, swap ? t2 : t3);
            } else {
                asm volatile("stmatrix.sync.aligned.m8n8.x2.shared.b16 [%0], {%1,%2};" ::"r"(addr + h * 1792 + c * 16), "r"(swap ? t1 : t0), "r"(swap ? t0 : t1) : "memory");
            }
        }
        fence_async_smem();
        __syncwarp();
        if (elect()) tma_st2(m, c0, c1 + 8 * h, slab + h * 1792);
    }
    if (elect()) {
        bulk_commit();
        bulk_wait_read();
    }
}
__host__ __device__ constexpr int tile_of(int t) { return 7 * (t >> 2) + 3 * ((t >> 1) & 1) + 2 * (t & 1); }

struct Role {
    int kind;
    int par, blk;
    int ns, id;
};
template <bool BY_SM>
__device__ __forceinline__ Role decode_role() {
    uint32_t sm;
    if (BY_SM) asm volatile("mov.u32 %0, %%smid;" : "=r"(sm));
    else asm volatile("mov.u32 %0, %%ctaid.x;" : "=r"(sm));
    const int tpc = sm >> 1, q2 = ((tpc - 32) * 37) >> 8;
    const int gpc = tpc < 32 ? tpc & 7 : tpc < 60 ? tpc - 31 - 7 * q2 : 0;
    const int pos = tpc < 32 ? tpc >> 3 : tpc < 60 ? q2 + 4 : tpc - 56;
    const int grp = GPC_MAP >> (4 * gpc);
    Role r;
    r.kind = (grp & 1) | ((sm >> 7) << 1);
    r.par = (pos >> 1) & 1;
    r.blk = (grp & 6) + (pos >> 2);
    r.ns = (pos & 1) * 2 + (sm & 1);
    r.id = sm >= 128 ? sm : (grp & 7) * 16 + pos * 2 + (sm & 1);
    return r;
}
static_assert((GPC_MAP & 15) == 0, "role H decodes as blk = 2, par = 0");

__device__ __forceinline__ void first_fill(const Maps& maps, const Role& r, int i) {
    const int L = r.kind & 1;
    const CUtensorMap* ma = &maps.m[r.kind];
    const uint32_t bar = full_bar(i);
    const int k = (i * 64) >> L;
    const bool has_a = !(i & L), has_b = i < 7 - L;
    const uint32_t slots = r.kind == 0 ? 0x2104365u : L ? 0x5432105u : 0x4321065u;
    const uint32_t dst = base + BRING + (i == 0 ? 5 : (slots >> (4 * i)) & 7) * SLOT;
    mbar_expect(bar, (has_a ? SLOT : 0) + (has_b ? SLOT : 0));
    if (has_a) tma_ld5(base + (i >> L) * SLOT, ma, k, r.par, r.blk, bar);
    if (has_b) {
        tma_ld4(dst, ma + 3, r.kind ? 0 : k, r.kind ? k : 0, 0, r.ns, bar);
        tma_ld4(dst + 8192, ma + 3, r.kind ? 64 : k, r.kind ? k : 64, 0, r.ns, bar);
        mbar_arrive(bar);
    }
}
static_assert(bslot_e(0) == 5 && bslot_e(1) == 6 && bslot_e(2) == 3 && bslot_e(3) == 4 && bslot_e(4) == 0 && bslot_e(6) == 2, "");

template <bool BY_SM>
__global__ void __launch_bounds__(384, 1) fused_kernel(Scratch* sc, const __grid_constant__ Maps maps) {
    const int warp = __shfl_sync(0xffffffffu, threadIdx.x >> 5, 0);
    if (warp < 8) {
        nb_sync(0, 384);
        const Role role = decode_role<BY_SM>();
        int lane = threadIdx.x & 31;
        asm volatile("" : "+r"(lane));
        const bool roleH = role.kind == 2;
        const int roleL = role.kind & 1, par = role.par, blk = role.blk, ns = role.ns, bid = role.id;
        const int mt = 2 * blk + par, col = ns * 112;
        asm volatile("setmaxnreg.inc.sync.aligned.u32 224;");
        Ring r;
        r.wg = warp >> 2;
        r.zero = blockIdx.y;
        r.releaser = lane + 1 == (warp >> 2);
        const int wg = warp >> 2;
        if (wg) nb_arrive(1, 256);
        uint8_t* part = sc->part + (size_t)(ns * 16 + mt) * (2 * BLOB) + warp * 512 + lane * 16;
        uint32_t p[28];

        if (roleH) {
            unsigned* epoch_ptr = &sc->epoch[bid * 4 * 8];
            const unsigned tag = *epoch_ptr + 1;
            uint8_t* hout = sc->halo + (size_t)((warp * 8 + ns) * 2) * 2048 + lane * 16;
            auto send = [&](int kv) {
#pragma unroll
                for (int h = 0; h < 2; h++) {
                    uint32_t v[16];
                    v[14] = v[15] = 0;
#pragma unroll
                    for (int c = 0; c < 14; c++) v[c] = p[2 * c + h];
#pragma unroll
                    for (int c = 0; c < 14; c += 2) v[15] |= (v[c] & 1) << c;
#pragma unroll
                    for (int i = 0; i < 4; i++) st_part(hout + (h * 8 + kv) * 2048 + i * 512, v + 4 * i, tag & 1);
                }
            };
            float x0[56], x1[56];
            r.seek(0, bslot_h(0));
            r.wait();
            r.run<XWN, 7, true>(x0);
#pragma unroll 1
            for (int i = 1; i < 7; i++) r.run<XWN, 7, false>(x0);
            r.run<XWN, 7, true>(x1);
            acc_fence(x0);
            pack_all(x0, p);
            send(0);
#pragma unroll 1
            for (int i = 1; i < 7; i++) r.run<XWN, 7, false>(x1, true, true, i < 6);
            asm volatile("wgmma.wait_group.sync.aligned 0;" ::: "memory");
            acc_fence(x1);
            pack_all(x1, p);
#pragma unroll
            for (int i = 0; i < 28; i++) p[i] = movm(p[i]);
            send(1);
            if (threadIdx.x == 0) *epoch_ptr = tag;
        } else if (!roleL) {
            uint8_t* blob = sc->ab + (size_t)((wg * 16 + mt) * 4 + ns) * BLOB + (warp & 3) * WSLOT + lane * 4;
            const uint32_t own = base + BRING + wg * SLOT + (warp & 3) * WSLOT + lane * 16;
            float x0[56], x1[56];
            r.seek(0, bslot_e(0));
            r.wait();
            r.run<XW, 7, true>(x0);
            r.run<XW, 7, false>(x0);
            r.seek(2, bslot_e(2));
#pragma unroll 1
            for (int i = 2; i < 7; i++) r.run<XW, 5, false>(x0);

            r.seek(7, bslot_e(7));
            r.run<XW, 5, true, -1>(x1);
            acc_fence(x0);
            pack_all(x0, p);
#pragma unroll
            for (int i = 0; i < 2; i++) {
                if (wg == i) store_frags<0, 14>(blob, p);
                else stage_frags<0, A_OWN>(own + 5 * SLOT, p);
                r.run<XW, 5, false, -1>(x1);
                if (wg == i) {
                    store_frags<14, 28>(blob, p);
                    warp_arrive(base + BAR_RDY + i * 8);
                } else {
                    stage_frags<A_OWN, 2 * A_OWN>(own + 5 * SLOT, p);
                }
                r.run<XW, 5, false, -1>(x1);
            }
            stage_frags<2 * A_OWN, A_OWN2>(own + 5 * SLOT, p);
            r.run<XW, 5, false, -1>(x1);
            stage_frags<A_OWN2, 28>(own + 5 * SLOT, p);
            fence_async_smem();
            r.run<XW, 5, false, -1>(x1);

            r.seek(14, bslot_e(14));
            r.run<BIG, 7, true>(x0);
            acc_fence(x1);
            pack_all(x1, p);
            stage_frags<0, B_OWN>(own, p);
            r.run<BIG, 7, false>(x0);
            stage_frags<B_OWN, 28>(own, p);
            fence_async_smem();
            blob += (size_t)128 * BLOB;
#pragma unroll
            for (int i = 0; i < 28; i++) {
                if (i % B_SLICE == 0) r.run<BIG, 7, false>(x0);
                stg1(blob + i * 128, p[i]);
            }
            warp_arrive(base + BAR_RDY + 16);
#pragma unroll 1
            for (int i = 17 + 27 / B_SLICE; i < POUT; i++) r.run<BIG, 7, false>(x0);

            const uint32_t tag = lds1(base + TAG);
            r.seek(POUT, bslot_e(POUT));
            r.run<OUT, 7, true>(x1);
            acc_fence(x0);
            pack_all(x0, p);
#pragma unroll
            for (int k = 0; k < 3; k++) {
                if (k < 2 && wg == k) {
                    if ((warp & 3) == 0 && elect())
                        asm volatile("red.relaxed.gpu.global.add.u32 [%0], 1;" ::"l"(&sc->cnt[(CNT_P + mt * 4 + ns) * 32]) : "memory");
#pragma unroll
                    for (int i = 0; i < 4; i++) st_part(part + i * 4096, p + 4 * i, tag & 1);
                }
                if (k > 0 && wg == k - 1) {
#pragma unroll
                    for (int i = 4; i < 7; i++) st_part(part + i * 4096, p + 4 * i, tag & 1);
                }
                if (k < 2) r.run<OUT, 7, false>(x1);
            }
#pragma unroll
            for (int i = 3; i < 7; i++) r.run<OUT, 7, false, 1, true>(x1, i <= 7 - TURN, i < 7 - TURN || i == 6, i < 6);

            asm volatile("wgmma.wait_group.sync.aligned 0;" ::: "memory");
            acc_fence(x1);
            const uint32_t slab = base + (wg ? BRING + bslot_e(ELAST - 6) * SLOT : ((ELAST - 6) % NA) * SLOT) + (warp & 3) * WSLOT;
            store_out([&](int i) { return pack2(x1[2 * i], x1[2 * i + 1]); }, lane, slab, &maps.m[M_OUTA], par * 896 + col, blk * 128 + warp * 16);
        } else {
            const int g = lane >> 2, tig = lane & 3;
            const uint32_t hin = base + HALO + warp * HSLOT + lane * 4;
            const uint32_t hpub = warp < 7 ? hin + HSLOT : base + HSPARE + lane * 4;
            auto publish = [&](const uint32_t (&h)[14], int c0, int c1) {
#pragma unroll
                for (int c = 0; c < 14; c++)
                    if (c >= c0 && c < c1) sts1(hpub + c * 128, h[c]);
            };
            float y0[56], y1[56], y2[56];
            r.seek(0, bslot_l(0));
            r.wait();
            r.run<QK, 6, true>(y0, y1);
#pragma unroll 1
            for (int i = 1; i < 14; i++) r.run<QK, 6, false>(y0, y1);

            uint32_t m1[8][4], m0[8][4], lo[14], hi[14], q[2][8][2];
            auto pack_q = [&](int b) {
                uint32_t v[14];
#pragma unroll
                for (int c = 0; c < 14; c++) v[c] = pack2(y0[4 * c + 2 * b], y0[4 * c + 2 * b + 1]);
#pragma unroll
                for (int t = 0; t < 8; t++) {
                    const int c = tile_of(t);
                    q[b][t][0] = (t & 3) == 2 ? (tig >= 2 ? v[c] : 0u) : v[c];
                    q[b][t][1] = (t & 3) == 1 ? (tig < 2 ? v[c + 1] : 0u) : v[c + 1];
                }
            };
            auto fetch = [&](uint32_t src, int hp, int i0) {
#pragma unroll
                for (int t = 4 * hp; t < 4 * hp + 4; t++) {
                    m0[t][i0] = (t & 3) == 2 ? dup(m0[t - 1][3], r.zero) : lds1(src + tile_of(t) * 128);
                    m0[t][3] = lds1(src + tile_of(t) * 128 + 128);
                }
            };
            r.seek(14, bslot_l(14));
            r.run<XWN, 6, true>(y2);
            acc_fence(y0);
            acc_fence(y1);
#pragma unroll
            for (int c = 0; c < 14; c++) hi[c] = pack2(y1[4 * c + 2], y1[4 * c + 3]);
            publish(hi, 0, 7);
            r.run<XWN, 6, false>(y2);
            publish(hi, 7, 14);
#pragma unroll
            for (int c = 0; c < 14; c++) lo[c] = pack2(y1[4 * c], y1[4 * c + 1]);
#pragma unroll
            for (int t = 0; t < 8; t++) {
                const int c = tile_of(t);
                const bool shared = (t & 3) == 2;
                m1[t][0] = shared ? dup(lo[c], r.zero) : lo[c];
                m1[t][1] = shared ? dup(hi[c], r.zero) : hi[c];
                m1[t][2] = lo[c + 1];
                m1[t][3] = hi[c + 1];
                m0[t][0] = dup(m1[t][0], r.zero);
                m0[t][2] = dup(lo[c + 1], 2 * r.zero);
            }
            r.run<XWN, 6, false>(y2);
            if (warp == 0) mbar_wait(base + BAR_HALO, 0);
            fetch(hin, 0, 1);
            pack_q(1);
            r.run<XWN, 6, false>(y2);
            fetch(hin, 1, 1);
            pack_q(0);
            r.mma_begin();
            float s[8][4];
#pragma unroll
            for (int step = 0; step < 2; step++) {
#pragma unroll
                for (int i = 0; i < 8; i++) {
                    const int b = 1 - (i >> 2), h = i & 3, t = 2 * h + step;
                    float (&d)[4] = s[2 * h + b];
                    if (step == 0) d[0] = d[1] = d[2] = d[3] = 0.f;
                    mma16816(d, b ? m1[t] : m0[t], q[b][t][0], q[b][t][1]);
                }
            }
            r.mma_end();
            r.run<XWN, 6, false>(y2, false);

            uint32_t pr[8], mx[4], mx1[4];
            {
                const bool cur0 = g <= 2 * tig, cur1 = g <= 2 * tig + 1;
#pragma unroll
                for (int i = 0; i < 8; i++) {
                    const int c = (i & 1) ? 2 : 0;
                    pr[i] = movm(pack2(cur0 ? s[i][c] : s[i][2 - c], cur1 ? s[i][c + 1] : s[i][3 - c]));
                }
            }
            r.run<XWN, 6, false>(y2);
            const uint32_t curmask = (2 * tig <= g ? 0x0000FFFFu : 0u) | (2 * tig + 1 <= g ? 0xFFFF0000u : 0u);
            {
                const uint32_t keep = (blk == 0 && warp == 0) ? curmask : 0xFFFFFFFFu;
#pragma unroll
                for (int i = 0; i < 4; i++) {
                    pr[2 * i] = (pr[2 * i] & keep) | (0xCF9ECF9Eu & ~keep);
                    mx[i] = max2(__byte_perm(pr[2 * i], pr[2 * i + 1], 0x5410), __byte_perm(pr[2 * i], pr[2 * i + 1], 0x7632));
                    mx1[i] = __shfl_xor_sync(0xffffffffu, mx[i], 1);
                }
            }
#pragma unroll
            for (int i = 0; i < 4; i++) {
                mx[i] = max2(mx[i], mx1[i]);
                mx1[i] = __shfl_xor_sync(0xffffffffu, mx[i], 2);
            }
            r.run<XWN, 6, false>(y2);
            constexpr float SCL = 0.18898223650461362f * 1.4426950408889634f;
            float e0[8], e1[8], sm[8], sm1[8];
#pragma unroll
            for (int i = 0; i < 8; i++) {
                const uint32_t m2 = max2(mx[i >> 1], mx1[i >> 1]);
                sm[i] = ((i & 1) ? bf_hi(m2) : bf_lo(m2)) * -SCL;
                e0[i] = ex2(fmaf(bf_lo(pr[i]), SCL, sm[i]));
            }

            r.seek(21, bslot_l(21));
            r.run<BIG, 6, true>(y0);
            acc_fence(y2);
#pragma unroll
            for (int c = 0; c < 7; c++) hi[c] = movm(pack2(y2[4 * c + 2], y2[4 * c + 3]));
#pragma unroll
            for (int i = 0; i < 8; i++) e1[i] = ex2(fmaf(bf_hi(pr[i]), SCL, sm[i]));
            r.run<BIG, 6, false>(y0);
            publish(hi, 0, 7);
#pragma unroll
            for (int c = 7; c < 14; c++) hi[c] = movm(pack2(y2[4 * c + 2], y2[4 * c + 3]));
            r.run<BIG, 6, false>(y0);
            publish(hi, 7, 14);
#pragma unroll
            for (int i = 0; i < 8; i++) {
                sm[i] = e0[i] + e1[i];
                sm1[i] = __shfl_xor_sync(0xffffffffu, sm[i], 1);
            }
            r.run<BIG, 6, false>(y0);
#pragma unroll
            for (int c = 0; c < 14; c++) lo[c] = movm(pack2(y2[4 * c], y2[4 * c + 1]));
            r.run<BIG, 6, false>(y0);
#pragma unroll
            for (int i = 0; i < 8; i++) {
                sm[i] += sm1[i];
                sm1[i] = __shfl_xor_sync(0xffffffffu, sm[i], 2);
            }
#pragma unroll
            for (int t = 0; t < 8; t++) {
                const int c = tile_of(t);
                const bool shared = (t & 3) == 2;
                m1[t][0] = shared ? dup(lo[c], r.zero) : lo[c];
                m1[t][1] = lo[c + 1];
                m1[t][2] = shared ? dup(hi[c], r.zero) : hi[c];
                m1[t][3] = hi[c + 1];
                m0[t][0] = dup(m1[t][0], r.zero);
                m0[t][1] = dup(lo[c + 1], 2 * r.zero);
            }
            r.run<BIG, 6, false>(y0);
            if (warp == 0) mbar_wait(base + BAR_HALO + 8, 0);
            const uint32_t vin = warp ? hin : hin + 8 * HSLOT;
            fetch(vin, 0, 2);
#pragma unroll
            for (int i = 0; i < 8; i++) {
                const float inv = rcp(sm[i] + sm1[i]);
                pr[i] = pack2(e0[i] * inv, e1[i] * inv);
            }
            r.run<BIG, 6, false>(y0);
            fetch(vin, 1, 2);
            uint32_t pb[8][2];
#pragma unroll
            for (int t = 0; t < 8; t++) {
                pb[t][t & 1] = band(pr[t], curmask);
                pb[t][1 - (t & 1)] = band(pr[t], ~curmask);
            }
            r.mma_begin();
            float o[2][8][4];
#pragma unroll
            for (int i = 0; i < 16; i++) {
                const int b = 1 - (i >> 3), t = i & 7;
                float (&d)[4] = o[b][t];
                d[0] = d[1] = d[2] = d[3] = 0.f;
                mma16816(d, b ? m1[t] : m0[t], pb[(t & 6) + b][0], pb[(t & 6) + b][1]);
            }
            r.mma_end();
            r.run<BIG, 6, false>(y0, false);
            uint8_t* odst = sc->o + (size_t)mt * 7 * SLOT + ns * (14 * 2048) + warp * 256 + lane * 4;
#pragma unroll
            for (int hp = 0; hp < 2; hp++) {
#pragma unroll
                for (int b = 0; b < 2; b++) {
                    const float (&u)[8][4] = o[b];
                    const int t = 4 * hp;
                    uint32_t* w = p + 14 * hp + b;
                    w[0] = pack2(u[t][0], u[t][1]);
                    w[2] = pack2(u[t][2], u[t][3]);
                    w[4] = pack2(u[t + 1][0], u[t + 1][1]);
                    w[6] = pack2(g < 4 ? u[t + 1][2] : u[t + 2][0], g < 4 ? u[t + 1][3] : u[t + 2][1]);
                    w[8] = pack2(u[t + 2][2], u[t + 2][3]);
                    w[10] = pack2(u[t + 3][0], u[t + 3][1]);
                    w[12] = pack2(u[t + 3][2], u[t + 3][3]);
                }
            }
#pragma unroll
            for (int i = 0; i < 28; i++) {
                if (i >= O_FIRST && (i - O_FIRST) % O_SLICE == 0) r.run<BIG, 6, false>(y0);
                stg1(odst + (i >> 1) * 2048 + (i & 1) * 128, p[i]);
            }
            warp_arrive(base + BAR_RDY + 16);

#pragma unroll 1
            for (int i = 30 + (27 - O_FIRST) / O_SLICE; i <= LLAST + 1 - TURN; i++) r.run<BIG, 6, false>(y0, true, i <= LLAST - TURN);
            const uint32_t tag = lds1(base + TAG);
            if (mbar_test(base + BAR_PART + wg * 8, 0)) {
#pragma unroll
                for (int i = 0; i < 7; i++) ld_tagged(part + i * 4096, p[4 * i], p[4 * i + 1], p[4 * i + 2], p[4 * i + 3]);
            } else {
                p[0] = ~tag;
            }
            r.seek(LLAST + 2 - TURN, bslot_l(LLAST + 2 - TURN));
#pragma unroll
            for (int i = 1; i < TURN; i++) r.run<BIG, 6, false, 1, true>(y0, false, i == TURN - 1, i < TURN - 1);
#pragma unroll 1
            for (int n = 0; n < SPIN_LIMIT; n++) {
                uint32_t stale = 0;
#pragma unroll
                for (int i = 0; i < 28; i += 2) stale |= p[i] ^ tag;
                if (__all_sync(0xffffffffu, !(stale & 1))) break;
                mbar_wait(base + BAR_PART + wg * 8, 0);
#pragma unroll
                for (int i = 0; i < 7; i++) ld_tagged(part + i * 4096, p[4 * i], p[4 * i + 1], p[4 * i + 2], p[4 * i + 3]);
            }
            asm volatile("wgmma.wait_group.sync.aligned 0;" ::: "memory");
            acc_fence(y0);
            const uint32_t slab = base + (wg ? HALO : ((LLAST - 6) % NA) * SLOT) + (warp & 3) * WSLOT;
            store_out([&](int i) { return add2(pack2(y0[2 * i], y0[2 * i + 1]), p[i]); }, lane, slab, &maps.m[M_OUTB], 448 + col, mt * 128 + warp * 16);
        }
    } else {
        const Role role = decode_role<BY_SM>();
        if (warp == 9) {
            if (elect()) {
#pragma unroll
                for (int i = 0; i < 8; i++) mbar_init(base + BAR_EMPTY + i * 8, 4);
                asm volatile("fence.mbarrier_init.release.cluster;" ::: "memory");
            }
        } else if (warp == 10) {
            if (elect()) {
#pragma unroll
                for (int i = 0; i < 3; i++) mbar_init(base + BAR_RDY + i * 8, i < 2 ? 4 : 8);
#pragma unroll
                for (int i = 0; i < 2; i++) mbar_init(base + BAR_HALO + i * 8, 1);
                asm volatile("fence.mbarrier_init.release.cluster;" ::: "memory");
            }
        } else if (warp == 11) {
            if (elect()) {
#pragma unroll
                for (int i = 1; i < 8; i++) mbar_init(base + BAR_FULL + i * 8, 2);
#pragma unroll
                for (int i = 0; i < 3; i++) mbar_init(base + BAR_DEP + i * 8, 1);
#pragma unroll
                for (int i = 0; i < 2; i++) mbar_init(base + BAR_PART + i * 8, 1);
                asm volatile("fence.mbarrier_init.release.cluster;" ::: "memory");
            }
        } else {
            if (elect()) {
                mbar_init(base + BAR_FULL, 2);
                asm volatile("fence.mbarrier_init.release.cluster;" ::: "memory");
                first_fill(maps, role, 0);
            }
        }
        const unsigned t_open = clk32();
        asm volatile("setmaxnreg.dec.sync.aligned.u32 56;");
        nb_sync(0, 384);
        int lane = threadIdx.x & 31;
        asm volatile("" : "+r"(lane));
        const bool roleH = role.kind == 2;
        const int roleL = role.kind & 1, par = role.par, blk = role.blk, ns = role.ns, bid = role.id;
        const int mt = 2 * blk + par, col = ns * 112;
#define PROF_FEED_A
#define PROF_FEED_B
        if (warp != 8) {
        if (warp == 11) {
            if (elect()) {
                Feed<BRING> f;
                auto blob_run = [&](auto nbs, int quarter, int n0, int n1) {
                    constexpr int N = decltype(nbs)::value;
                    const uint8_t* src = sc->ab + (size_t)(quarter * 64 + ns) * BLOB;
#pragma unroll 1
                    for (int n = n0; n < n1; n++) {
                        const uint32_t bar = f.template acquire<N>();
                        mbar_expect(bar, BLOB);
                        bulk_ld(f.dst, src + skip_own(n, mt) * (4 * BLOB), BLOB, bar);
                        PROF_FEED_B;
                        f.template next<N>();
                    }
                };
                auto w_run = [&](auto nbs, const CUtensorMap* m, int slice, bool no_a) {
                    constexpr int N = decltype(nbs)::value;
#pragma unroll 1
                    for (int i = 0; i < 7; i++) {
                        const uint32_t bar = f.template acquire<N>();
                        mbar_expect(bar, SLOT);
                        tma_ld4(f.dst, m, 0, i * 64, 0, slice, bar);
                        tma_ld4(f.dst + 8192, m, 64, i * 64, 0, slice, bar);
                        if (no_a) mbar_arrive(bar);
                        PROF_FEED_B;
                        f.template next<N>();
                    }
                };
                if (roleH) {
                    f.seek(7, bslot_h(7));
                    w_run(Int<7>(), &maps.m[M_WV], 4 + ns, true);
                } else if (!roleL) {
                    f.seek(7, bslot_e(7));
#pragma unroll 1
                    for (int i = 0; i < 7; i++) {
                        const uint32_t bar = f.acquire<5>();
                        mbar_expect(bar, BLOB);
                        tma_ld2(f.dst, &maps.m[M_WI], i * 64, col, bar);
                        mbar_arrive(bar);
                        PROF_FEED_B;
                        f.next<5>();
                    }
                    f.seek(18, bslot_e(18));
                    wait_dep(0);
                    blob_run(Int<7>(), 0, 0, 15);
                    wait_dep(1);
                    blob_run(Int<7>(), 2, 0, NBE);
                    w_run(Int<7>(), &maps.m[M_WO], ns, false);
                } else {
                    f.seek(6, bslot_l(6));
#pragma unroll 1
                    for (int i = 6; i < 14; i++) {
                        const uint32_t bar = f.acquire<6>();
                        mbar_expect(bar, SLOT);
                        tma_ld4(f.dst, &maps.m[M_WQK], 0, i * 32, 0, ns, bar);
                        tma_ld4(f.dst + 8192, &maps.m[M_WQK], 64, i * 32, 0, ns, bar);
                        if (i & 1) mbar_arrive(bar);
                        PROF_FEED_B;
                        f.next<6>();
                    }
                    w_run(Int<6>(), &maps.m[M_WV], 4 + ns, true);
                    wait_dep(0);
                    blob_run(Int<6>(), 1, 0, 15);
                    wait_dep(1);
                    blob_run(Int<6>(), 3, 0, 15);
                    blob_run(Int<6>(), 2, NBE, 15);
                }
            }
        } else if (roleH) {
            if (elect()) {
                wait_released(warp == 9 ? 0 : 7);
#pragma unroll 1
                for (int i = 0; i < 7; i++) {
                    if (warp == 9) {
                        asm volatile("cp.async.bulk.prefetch.tensor.2d.L2.global [%0, {%1, %2}];" ::"l"(&maps.m[M_WI]), "r"(i * 64), "r"(col) : "memory");
                    } else {
                        asm volatile("cp.async.bulk.prefetch.tensor.4d.L2.global [%0, {%1, %2, 0, %3}];" ::"l"(&maps.m[M_WO]), "r"(0), "r"(i * 64), "r"(ns) : "memory");
                        asm volatile("cp.async.bulk.prefetch.tensor.4d.L2.global [%0, {%1, %2, 0, %3}];" ::"l"(&maps.m[M_WO]), "r"(64), "r"(i * 64), "r"(ns) : "memory");
                    }
                }
            }
        } else if (warp == 10) {
            if (elect()) {
                unsigned* epoch_ptr = &sc->epoch[(bid * 4 + 2) * 8];
                const unsigned ep = *epoch_ptr + 1;
                sts1(base + TAG, ep);
                asm volatile("prefetch.tensormap [%0];" ::"l"(&maps.m[M_OUTA + roleL]) : "memory");
                await(sc, CNT_A + roleL * 4 + ns, ep * 16);
                mbar_arrive(base + BAR_DEP);
                PROF(150);
                await(sc, CNT_B + ns, ep * 16);
                mbar_arrive(base + BAR_DEP + 8);
                PROF(151);
                if (!roleL) {
                    await(sc, CNT_O + mt, ep * 4);
                    mbar_arrive(base + BAR_DEP + 16);
                } else {
                    await(sc, CNT_P + mt * 4 + ns, ep * 2 - 1);
                    mbar_arrive(base + BAR_PART);
                    PROF(153);
                    await(sc, CNT_P + mt * 4 + ns, ep * 2);
                    mbar_arrive(base + BAR_PART + 8);
                }
                PROF(152);
                *epoch_ptr = ep;
            }
        } else if (!roleL) {
            if (elect()) {
                mbar_wait(base + BAR_RDY, 0);
                PROF(130);
                signal(sc, CNT_A + ns);
                PROF(131);
                mbar_wait(base + BAR_RDY + 8, 0);
                signal(sc, CNT_A + 4 + ns);
                PROF(135);
                mbar_wait(base + BAR_RDY + 16, 0);
                PROF(132);
                signal(sc, CNT_B + ns);
                PROF(133);
            }
        } else {
            unsigned* epoch_ptr = &sc->epoch[(bid * 4 + 1) * 8];
            const unsigned tag = *epoch_ptr + 1;
#pragma unroll 1
            for (int kv = 0; kv < 2; kv++) {
                uint32_t v[16];
#pragma unroll
                for (int i = 0; i < 16; i++) v[i] = 0;
                if (kv) wait_released(HALO_V_AT - 4), wait_released(HALO_V_AT);
                else mbar_wait(base + BAR_DEP + 16, 0);
                if (blk > 0) {
                    const uint8_t* src = sc->halo + (size_t)(((par * 8 + blk - 1) * 4 + ns) * 2 + kv) * 2048 + lane * 16;
#pragma unroll 1
                    for (int n = 0; n < SPIN_LIMIT; n++) {
                        uint32_t stale = 0;
#pragma unroll
                        for (int i = 0; i < 4; i++) ld_tagged(src + i * 512, v[4 * i], v[4 * i + 1], v[4 * i + 2], v[4 * i + 3]);
#pragma unroll
                        for (int i = 0; i < 16; i += 2) stale |= v[i] ^ tag;
                        if (__all_sync(0xffffffffu, !(stale & 1))) break;
                    }
#pragma unroll
                    for (int c = 0; c < 14; c += 2) v[c] = (v[c] & ~1u) | ((v[15] >> c) & 1);
                }
#pragma unroll
                for (int i = 0; i < 14; i++) sts1(base + HALO + kv * (8 * HSLOT) + i * 128 + lane * 4, v[i]);
                warp_arrive(base + BAR_HALO + kv * 8);
                if (lane == 0) PROF(142 + kv);
            }
            if (elect()) {
                mbar_wait(base + BAR_RDY + 16, 0);
                PROF(130);
                signal(sc, CNT_O + mt);
                PROF(131);
                *epoch_ptr = tag;
            }
        }
        } else {
            if (elect()) {
                PROF(129);
#pragma unroll 1
                for (int i = 1; i < 7; i++) {
                    while ((int)(clk32() - t_open) < i * PACE - PACE0) {}
                    first_fill(maps, role, i);
                }
                PROF(134);
                Feed<0> f;
                const int row = mt * 128;
                auto c_run = [&](const CUtensorMap* m, int off, int n0, int n1) {
#pragma unroll 1
                    for (int n = n0; n < n1; n++) {
                        const uint32_t bar = f.acquire<NA>();
                        mbar_expect(bar, SLOT);
                        tma_ld2(f.dst, m, (off + skip_own(n, mt)) * 64, row, bar);
                        PROF_FEED_A;
                        f.next<NA>();
                    }
                };
                if (roleH) {
                } else if (!roleL) {
                    f.seek(14, 0);
#pragma unroll 1
                    for (int i = 0; i < 4; i++) {
                        const uint32_t bar = f.acquire<NA>();
                        mbar_expect(bar, SLOT);
                        tma_ld2(f.dst, &maps.m[M_CR + (i >> 1)], ((i & 1) * 16 + mt) * 64, row, bar);
                        mbar_arrive(bar);
                        PROF_FEED_A;
                        f.next<NA>();
                    }
                    c_run(&maps.m[M_CR], 0, 0, 15);
                    c_run(&maps.m[M_CI], 0, 0, NBE);
                    wait_dep(2);
#pragma unroll 1
                    for (int i = 0; i < 7; i++) {
                        const uint32_t bar = f.acquire<NA>();
                        mbar_expect(bar, SLOT);
                        bulk_ld(f.dst, sc->o + (size_t)(mt * 7 + i) * SLOT, SLOT, bar);
                        PROF_FEED_A;
                        f.next<NA>();
                    }
                } else {
#pragma unroll 1
                    for (int i = 4; i < 7; i++) {
                        wait_released(2 * i - 8);
                        mbar_expect(full_bar(2 * i), SLOT);
                        tma_ld5(base + i * SLOT, &maps.m[M_XA], i * 64, par, blk, full_bar(2 * i));
                    }
                    wait_released(HALO_K_AT);
                    mbar_arrive(base + BAR_DEP + 16);
                    f.seek(21, 0);
                    c_run(&maps.m[M_CR], 16, 0, 15);
                    c_run(&maps.m[M_CI], 16, 0, 15);
                    c_run(&maps.m[M_CI], 0, NBE, 15);
                }
            }
        }
    }
}

typedef CUresult (*EncodeFn)(CUtensorMap*, CUtensorMapDataType, cuuint32_t, void*, const cuuint64_t*, const cuuint64_t*,
                             const cuuint32_t*, const cuuint32_t*, CUtensorMapInterleave, CUtensorMapSwizzle,
                             CUtensorMapL2promotion, CUtensorMapFloatOOBfill);

struct Dim { uint64_t size, stride; uint32_t box; };
void encode(EncodeFn fn, CUtensorMap* m, const void* ptr, CUtensorMapSwizzle sw, Dim d0, Dim d1, Dim d2 = {0, 0, 0},
            Dim d3 = {0, 0, 0}, Dim d4 = {0, 0, 0}) {
    const cuuint64_t dims[5] = {d0.size, d1.size, d2.size, d3.size, d4.size};
    const cuuint64_t strides[4] = {d1.stride, d2.stride, d3.stride, d4.stride};
    const cuuint32_t box[5] = {d0.box, d1.box, d2.box, d3.box, d4.box};
    const cuuint32_t es[5] = {1, 1, 1, 1, 1};
    fn(m, CU_TENSOR_MAP_DATA_TYPE_BFLOAT16, d4.size ? 5 : d3.size ? 4 : 2, const_cast<void*>(ptr), dims, strides, box, es,
       CU_TENSOR_MAP_INTERLEAVE_NONE, sw, CU_TENSOR_MAP_L2_PROMOTION_L2_128B, CU_TENSOR_MAP_FLOAT_OOB_FILL_NONE);
}

}

extern "C" void kernel_launch(void* const* d_in, const int* in_sizes, int n_in, void* d_out, int out_size) {
    (void)in_sizes; (void)n_in; (void)out_size;
    void* fnp = nullptr;
    cudaDriverEntryPointQueryResult st;
    cudaGetDriverEntryPoint("cuTensorMapEncodeTiled", &fnp, cudaEnableDefault, &st);
    EncodeFn fn = (EncodeFn)fnp;
    void* scratch = nullptr;
    cudaGetSymbolAddress(&scratch, g_scratch);
    int dev = 0, sms = 0;
    cudaGetDevice(&dev);
    cudaDeviceGetAttribute(&sms, cudaDevAttrMultiProcessorCount, dev);
    auto kernel = sms == 132 ? fused_kernel<true> : fused_kernel<false>;
    cudaFuncSetAttribute(kernel, cudaFuncAttributeMaxDynamicSharedMemorySize, SMEM_BYTES);

    const CUtensorMapSwizzle S128 = CU_TENSOR_MAP_SWIZZLE_128B, S0 = CU_TENSOR_MAP_SWIZZLE_NONE;
    const Dim one = {1, 16, 1};
    Maps maps;
    encode(fn, &maps.m[M_XA], d_in[0], S128, {448, 2, 64}, {128, 1792, 128}, one, {2, 896, 1}, {8, 128 * 1792, 1});
    encode(fn, &maps.m[M_WQK], d_in[1], S128, {112, 2, 64}, {448, 2688, 32}, {3, 896, 2}, {4, 224, 1});
    encode(fn, &maps.m[M_WV], (const uint8_t*)d_in[1] + 896, S128, {112, 2, 64}, {448, 2688, 64}, one, {8, 224, 1});
    encode(fn, &maps.m[M_XH], d_in[0], S128, {448, 2, 64}, {8, 1792, 8}, {8, 128 * 1792, 8}, {2, 896, 2}, {3, 60 * 1792, 1});
    encode(fn, &maps.m[M_WO], d_in[2], S128, {112, 2, 64}, {448, 896, 64}, one, {4, 224, 1});
    encode(fn, &maps.m[M_XB], d_in[3], S128, {448, 2, 64}, {64, 896, 64}, {2, 896 * 1024, 2}, {2, 64 * 896, 1}, {8, 128 * 896, 1});
    encode(fn, &maps.m[M_CR], d_in[4], S128, {2048, 2, 64}, {2048, 4096, 128});
    encode(fn, &maps.m[M_CI], d_in[5], S128, {2048, 2, 64}, {2048, 4096, 128});
    encode(fn, &maps.m[M_WR], d_in[6], S128, {448, 2, 64}, {112, 896, 64}, one, {4, 112 * 896, 1});
    encode(fn, &maps.m[M_WI], d_in[7], S128, {448, 2, 64}, {448, 896, 112});
    encode(fn, &maps.m[M_OUTA], d_out, S0, {1792, 2, 112}, {1024, 3584, 8});
    encode(fn, &maps.m[M_OUTB], d_out, S0, {896, 2, 112}, {2048, 1792, 8});

    kernel<<<132, 384, SMEM_BYTES>>>((Scratch*)scratch, maps);
}
```

```cpp
#include <cuda.h>
#include <cuda_bf16.h>
#include <cuda_runtime.h>
#include <stdint.h>

namespace {

constexpr uint32_t SLOT = 16384;
constexpr int NA = 7;
constexpr uint32_t BRING = NA * SLOT;
constexpr uint32_t HALO = BRING + 6 * SLOT;
constexpr uint32_t HSLOT = 1792;
constexpr uint32_t WSLOT = 3584;
constexpr uint32_t BLOB = 14336;
constexpr uint32_t BARS = 14 * SLOT;
constexpr uint32_t BAR_FULL = BARS;
constexpr uint32_t BAR_EMPTY = BARS + 64;
constexpr uint32_t BAR_RDY = BARS + 128;
constexpr uint32_t BAR_DEP = BARS + 168;
constexpr uint32_t BAR_HALO = BARS + 192;
constexpr uint32_t BAR_PART = BARS + 208;
constexpr uint32_t TAG = BARS + 224;
constexpr uint32_t HSPARE = BARS + 256 + 1024;
constexpr uint32_t SMEM_BYTES = HSPARE + HSLOT;
constexpr uint32_t base = 1024;
constexpr int SPIN_LIMIT = 1 << 16;

#define E_EXTRA 0
#define HALO_K_AT 10
#define HALO_V_AT 19
#define O_SLICE 4
#define B_SLICE 4
#define LEAD 3
#define TURN 4
#define PACE 450
#define O_FIRST 8
#define B_OWN 28
#define MMA_SYNC 2
#define A_OWN 4
#define A_OWN2 20
#define GPC_MAP 0x64752310u

constexpr int NBE = 13 + E_EXTRA;
constexpr int POUT = 33 + NBE;
constexpr int ELAST = POUT + 6;
constexpr int LLAST = 52 - E_EXTRA;
static_assert(TURN <= 4, "the output is staged in the slots of the seventh-last stage");

enum { M_XB, M_XA, M_XH, M_WR, M_WQK, M_WV, M_WO, M_WI, M_CR, M_CI, M_OUTA, M_OUTB, M_COUNT };
struct __align__(64) Maps { CUtensorMap m[M_COUNT]; };

constexpr int CNT_A = 0;
constexpr int CNT_B = 8;
constexpr int CNT_O = 16;
constexpr int CNT_P = 32;
constexpr int CNT_COUNT = 96;

struct Scratch {
    uint8_t ab[64 * 4 * BLOB];
    uint8_t o[16 * 7 * SLOT];
    uint8_t part[64 * 2 * BLOB];
    uint8_t halo[64 * 2 * 2048];
    unsigned cnt[CNT_COUNT * 32];
    unsigned epoch[132 * 4 * 8];
};
__device__ __align__(1024) Scratch g_scratch;

__device__ __forceinline__ unsigned clk32() { unsigned c; asm volatile("mov.u32 %0, %%clock;" : "=r"(c)); return c; }

#define PROF(idx)

__device__ __forceinline__ void mbar_init(uint32_t bar, uint32_t cnt) {
    asm volatile("mbarrier.init.shared::cta.b64 [%0], %1;" ::"r"(bar), "r"(cnt) : "memory");
}
__device__ __forceinline__ void mbar_expect(uint32_t bar, uint32_t bytes) {
    asm volatile("mbarrier.arrive.expect_tx.shared::cta.b64 _, [%0], %1;" ::"r"(bar), "r"(bytes) : "memory");
}
__device__ __forceinline__ void mbar_arrive(uint32_t bar) {
    asm volatile("mbarrier.arrive.shared::cta.b64 _, [%0];" ::"r"(bar) : "memory");
}
__device__ __forceinline__ bool mbar_try(uint32_t bar, uint32_t parity) {
    uint32_t ok;
    asm volatile("{\n.reg .pred p;\nmbarrier.try_wait.parity.shared::cta.b64 p, [%1], %2;\nselp.u32 %0, 1, 0, p;\n}\n"
                 : "=r"(ok) : "r"(bar), "r"(parity) : "memory");
    return ok;
}
__device__ __forceinline__ bool mbar_test(uint32_t bar, uint32_t parity) {
    uint32_t ok;
    asm volatile("{\n.reg .pred p;\nmbarrier.test_wait.parity.shared::cta.b64 p, [%1], %2;\nselp.u32 %0, 1, 0, p;\n}\n"
                 : "=r"(ok) : "r"(bar), "r"(parity) : "memory");
    return ok;
}
__device__ __forceinline__ void mbar_wait(uint32_t bar, uint32_t parity) {
#pragma unroll 1
    for (int n = 0; n < SPIN_LIMIT; n++)
        if (mbar_try(bar, parity)) break;
}
__device__ __forceinline__ bool elect() {
    uint32_t p;
    asm volatile("{\n.reg .pred p;\nelect.sync _|p, 0xffffffff;\nselp.u32 %0, 1, 0, p;\n}\n" : "=r"(p));
    return p;
}
__device__ __forceinline__ void nb_sync(int id, int n) { asm volatile("bar.sync %0, %1;" ::"r"(id), "r"(n) : "memory"); }
__device__ __forceinline__ void nb_arrive(int id, int n) { asm volatile("bar.arrive %0, %1;" ::"r"(id), "r"(n) : "memory"); }
__device__ __forceinline__ void warp_arrive(uint32_t bar) {
    __syncwarp();
    if (elect()) mbar_arrive(bar);
}
__device__ __forceinline__ uint32_t band(uint32_t x, uint32_t m) {
    uint32_t r;
    asm volatile("and.b32 %0, %1, %2;" : "=r"(r) : "r"(x), "r"(m));
    return r;
}
__device__ __forceinline__ uint32_t dup(uint32_t x, uint32_t zero) {
    uint32_t r;
    asm volatile("xor.b32 %0, %1, %2;" : "=r"(r) : "r"(x), "r"(zero));
    return r;
}

__device__ __forceinline__ void tma_ld2(uint32_t dst, const CUtensorMap* m, int c0, int c1, uint32_t bar) {
    asm volatile("cp.async.bulk.tensor.2d.shared::cluster.global.mbarrier::complete_tx::bytes [%0], [%1, {%3, %4}], [%2];"
                 ::"r"(dst), "l"(m), "r"(bar), "r"(c0), "r"(c1) : "memory");
}
__device__ __forceinline__ void tma_ld4(uint32_t dst, const CUtensorMap* m, int c0, int c1, int c2, int c3, uint32_t bar) {
    asm volatile("cp.async.bulk.tensor.4d.shared::cluster.global.mbarrier::complete_tx::bytes [%0], [%1, {%3, %4, %5, %6}], [%2];"
                 ::"r"(dst), "l"(m), "r"(bar), "r"(c0), "r"(c1), "r"(c2), "r"(c3) : "memory");
}
__device__ __forceinline__ void bulk_ld(uint32_t dst, const void* src, uint32_t bytes, uint32_t bar) {
    asm volatile("cp.async.bulk.shared::cluster.global.mbarrier::complete_tx::bytes [%0], [%1], %2, [%3];"
                 ::"r"(dst), "l"(src), "r"(bytes), "r"(bar) : "memory");
}
__device__ __forceinline__ void tma_st2(const CUtensorMap* m, int c0, int c1, uint32_t src) {
    asm volatile("cp.async.bulk.tensor.2d.global.shared::cta.bulk_group [%0, {%1, %2}], [%3];"
                 ::"l"(m), "r"(c0), "r"(c1), "r"(src) : "memory");
}
__device__ __forceinline__ void bulk_commit() { asm volatile("cp.async.bulk.commit_group;" ::: "memory"); }
__device__ __forceinline__ void bulk_wait_read() { asm volatile("cp.async.bulk.wait_group.read 0;" ::: "memory"); }
__device__ __forceinline__ void fence_async_smem() { asm volatile("fence.proxy.async.shared::cta;" ::: "memory"); }
__device__ __forceinline__ void fence_async_global() { asm volatile("fence.proxy.async.global;" ::: "memory"); }

__device__ __forceinline__ void signal(Scratch* sc, int idx) {
    asm volatile("fence.proxy.async;\nred.relaxed.gpu.global.add.u32 [%0], 1;" ::"l"(&sc->cnt[idx * 32]) : "memory");
}
__device__ __forceinline__ unsigned peek(const unsigned* p) {
    unsigned v;
    asm volatile("ld.relaxed.gpu.global.u32 %0, [%1];" : "=r"(v) : "l"(p) : "memory");
    return v;
}
__device__ __forceinline__ void await(Scratch* sc, int idx, unsigned target) {
    const unsigned* p = &sc->cnt[idx * 32];
#pragma unroll 1
    for (int n = 0; n < SPIN_LIMIT; n++)
        if ((int)(peek(p) - target) >= 0) break;
    asm volatile("fence.acquire.gpu;" ::: "memory");
}
__device__ __forceinline__ void wait_dep(int k) {
    mbar_wait(base + BAR_DEP + k * 8, 0);
    fence_async_global();
}

#define WG_REGS                                                                                                     \
    "{%0,%1,%2,%3,%4,%5,%6,%7,%8,%9,%10,%11,%12,%13,%14,%15,%16,%17,%18,%19,%20,%21,%22,%23,%24,%25,%26,%27,"       \
    "%28,%29,%30,%31,%32,%33,%34,%35,%36,%37,%38,%39,%40,%41,%42,%43,%44,%45,%46,%47,%48,%49,%50,%51,%52,%53,%54,%55}"
#define WG_OPS(C)                                                                                                   \
    C(d[0]), C(d[1]), C(d[2]), C(d[3]), C(d[4]), C(d[5]), C(d[6]), C(d[7]), C(d[8]), C(d[9]), C(d[10]), C(d[11]),   \
    C(d[12]), C(d[13]), C(d[14]), C(d[15]), C(d[16]), C(d[17]), C(d[18]), C(d[19]), C(d[20]), C(d[21]), C(d[22]),   \
    C(d[23]), C(d[24]), C(d[25]), C(d[26]), C(d[27]), C(d[28]), C(d[29]), C(d[30]), C(d[31]), C(d[32]), C(d[33]),   \
    C(d[34]), C(d[35]), C(d[36]), C(d[37]), C(d[38]), C(d[39]), C(d[40]), C(d[41]), C(d[42]), C(d[43]), C(d[44]),   \
    C(d[45]), C(d[46]), C(d[47]), C(d[48]), C(d[49]), C(d[50]), C(d[51]), C(d[52]), C(d[53]), C(d[54]), C(d[55])

template <int TA, int TB, int SB, bool INIT, uint32_t AH, uint32_t BH>
__device__ __forceinline__ void wgmma112(float (&d)[56], uint32_t alo, uint32_t blo) {
    if (INIT) {
        asm volatile("{\n.reg .pred p;\n.reg .b64 da, db;\nsetp.ne.b32 p, 0, 0;\nmov.b64 da, {%56, %61};\nmov.b64 db, {%57, %62};\n"
                     "wgmma.mma_async.sync.aligned.m64n112k16.f32.bf16.bf16 " WG_REGS ", da, db, p, 1, %59, %60, %58;\n}\n"
                     : WG_OPS("=f") : "r"(alo), "r"(blo), "n"(TB), "n"(SB), "n"(TA), "n"(AH), "n"(BH));
    } else {
        asm volatile("{\n.reg .pred p;\n.reg .b64 da, db;\nsetp.ne.b32 p, 1, 0;\nmov.b64 da, {%56, %61};\nmov.b64 db, {%57, %62};\n"
                     "wgmma.mma_async.sync.aligned.m64n112k16.f32.bf16.bf16 " WG_REGS ", da, db, p, 1, %59, %60, %58;\n}\n"
                     : WG_OPS("+f") : "r"(alo), "r"(blo), "n"(TB), "n"(SB), "n"(TA), "n"(AH), "n"(BH));
    }
}
__device__ __forceinline__ void acc_fence(float (&d)[56]) {
#pragma unroll
    for (int i = 0; i < 56; i++) asm volatile("" : "+f"(d[i])::"memory");
}

__device__ __forceinline__ uint32_t pack2(float lo, float hi) {
    uint32_t r;
    asm volatile("cvt.rn.bf16x2.f32 %0, %1, %2;" : "=r"(r) : "f"(hi), "f"(lo));
    return r;
}
__device__ __forceinline__ uint32_t movm(uint32_t a) {
    uint32_t r;
    asm volatile("movmatrix.sync.aligned.m8n8.trans.b16 %0, %1;" : "=r"(r) : "r"(a));
    return r;
}
__device__ __forceinline__ void stsm4(uint32_t addr, uint32_t a, uint32_t b, uint32_t c, uint32_t d) {
    asm volatile("stmatrix.sync.aligned.m8n8.x4.shared.b16 [%0], {%1,%2,%3,%4};" ::"r"(addr), "r"(a), "r"(b), "r"(c), "r"(d) : "memory");
}
__device__ __forceinline__ void sts1(uint32_t addr, uint32_t a) { asm volatile("st.shared.b32 [%0], %1;" ::"r"(addr), "r"(a) : "memory"); }
__device__ __forceinline__ uint32_t lds1(uint32_t addr) {
    uint32_t a;
    asm volatile("ld.shared.b32 %0, [%1];" : "=r"(a) : "r"(addr) : "memory");
    return a;
}
__device__ __forceinline__ void stg1(uint8_t* p, uint32_t a) { asm volatile("st.global.b32 [%0], %1;" ::"l"(p), "r"(a) : "memory"); }
__device__ __forceinline__ void st_part(uint8_t* p, const uint32_t* v, uint32_t parity) {
    asm volatile("{\n.reg .b64 x, y;\nmov.b64 x, {%1, %2};\nmov.b64 y, {%3, %4};\nst.relaxed.gpu.global.v2.b64 [%0], {x, y};\n}\n"
                 ::"l"(p), "r"((v[0] & ~1u) | parity), "r"(v[1]), "r"((v[2] & ~1u) | parity), "r"(v[3]) : "memory");
}
__device__ __forceinline__ void mma16816(float (&d)[4], const uint32_t (&a)[4], uint32_t b0, uint32_t b1) {
    asm volatile("mma.sync.aligned.m16n8k16.row.col.f32.bf16.bf16.f32 {%0,%1,%2,%3}, {%4,%5,%6,%7}, {%8,%9}, {%0,%1,%2,%3};"
                 : "+f"(d[0]), "+f"(d[1]), "+f"(d[2]), "+f"(d[3]) : "r"(a[0]), "r"(a[1]), "r"(a[2]), "r"(a[3]), "r"(b0), "r"(b1));
}
__device__ __forceinline__ uint32_t add2(uint32_t a, uint32_t b) {
    uint32_t r;
    asm("add.rn.bf16x2 %0, %1, %2;" : "=r"(r) : "r"(a), "r"(b));
    return r;
}
__device__ __forceinline__ uint32_t max2(uint32_t a, uint32_t b) {
    uint32_t r;
    asm("max.bf16x2 %0, %1, %2;" : "=r"(r) : "r"(a), "r"(b));
    return r;
}
__device__ __forceinline__ void ld_tagged(const uint8_t* p, uint32_t& a, uint32_t& ta, uint32_t& b, uint32_t& tb) {
    asm volatile("{\n.reg .b64 x, y;\nld.relaxed.gpu.global.v2.b64 {x, y}, [%4];\nmov.b64 {%0, %1}, x;\nmov.b64 {%2, %3}, y;\n}\n"
                 : "=r"(a), "=r"(ta), "=r"(b), "=r"(tb) : "l"(p) : "memory");
}
__device__ __forceinline__ float bf_lo(uint32_t v) { return __uint_as_float(v << 16); }
__device__ __forceinline__ float bf_hi(uint32_t v) { return __uint_as_float(v & 0xFFFF0000u); }
__device__ __forceinline__ float rcp(float x) { float r; asm("rcp.approx.ftz.f32 %0, %1;" : "=f"(r) : "f"(x)); return r; }
__device__ __forceinline__ float ex2(float x) { float r; asm volatile("ex2.approx.ftz.f32 %0, %1;" : "=f"(r) : "f"(x)); return r; }

__device__ __forceinline__ uint32_t full_bar(int stage) { return base + BAR_FULL + (stage & 7) * 8; }
__device__ __forceinline__ void wait_released(int j) { mbar_wait(base + BAR_EMPTY + (j & 7) * 8, (j >> 3) & 1); }

template <int V>
struct Int { static constexpr int value = V; };

__host__ __device__ constexpr int bslot_e(int i) { return (i < 2 || i >= 14) ? (i + 5) % 7 : (i + 1) % 5; }
__host__ __device__ constexpr int bslot_l(int i) { return i % 6; }

template <uint32_t OFF>
struct Feed {
    int stage;
    uint32_t dst;
    __device__ __forceinline__ void seek(int i, int slot) { stage = i; dst = base + OFF + slot * SLOT; }
    template <int N>
    __device__ __forceinline__ uint32_t acquire() { wait_released(stage - N); return full_bar(stage); }
    template <int N>
    __device__ __forceinline__ void next() {
        stage++;
        dst += SLOT;
        if (dst == base + OFF + N * SLOT) dst = base + OFF;
    }
};
__device__ __forceinline__ int skip_own(int n, int mt) { return n == mt ? 15 : n; }

struct Desc { uint32_t lo, hi; };
__host__ __device__ constexpr Desc desc_const(uint32_t lbo, uint32_t sbo, uint32_t mode) { return {(lbo >> 4) << 16, (sbo >> 4) | (mode << 30)}; }
constexpr Desc D_K128 = desc_const(16, 1024, 1);
constexpr Desc D_N128 = desc_const(8192, 1024, 1);
constexpr Desc D_BLOB = desc_const(128, 256, 0);
constexpr Desc D_OT = desc_const(2048, 128, 0);

enum Kind { XW, XWN, QK, BIG, OUT };

struct Ring {
    int stage;
    uint32_t a, b;
    uint32_t wg;
    uint32_t zero;
    bool releaser;
    __device__ __forceinline__ void seek(int i, int bslot) {
        stage = i;
        a = (base + (i % NA) * SLOT) >> 4;
        b = (base + BRING + bslot * SLOT) >> 4;
    }
    __device__ __forceinline__ void wait() { mbar_wait(full_bar(stage), (stage >> 3) & 1); }
    __device__ __forceinline__ void take_turn() { nb_sync(1 + wg, 256); }
    __device__ __forceinline__ void pin() {
        uint32_t n = 0;
#pragma unroll 1
        do {
            asm volatile("pmevent 7;" ::: "memory");
        } while (n++ < zero);
    }
    __device__ __forceinline__ void mma_begin() {
        pin();
        if (!wg) take_turn();
        pin();
    }
    __device__ __forceinline__ void mma_end() {
        pin();
        if (wg) nb_arrive(3, 256);
        nb_sync(3 - wg, 256);
    }
    template <Kind K, int NBS, bool INIT, int SB = 1, bool TAIL = false>
    __device__ __forceinline__ void run(float (&d)[56], float (&e)[56], bool first = true, bool last = true, bool more = true) {
        if (first) take_turn();
        asm volatile("wgmma.fence.sync.aligned;" ::: "memory");
        if (K == QK) {
            const uint32_t da = D_K128.lo + (base >> 4) + (stage >> 1) * (SLOT >> 4) + (stage & 1) * 4 + wg * 512, db = D_N128.lo + b;
            wgmma112<0, 1, 1, INIT, D_K128.hi, D_N128.hi>(d, da, db);
            wgmma112<0, 1, 1, INIT, D_K128.hi, D_N128.hi>(e, da, db + 256);
            wgmma112<0, 1, 1, false, D_K128.hi, D_N128.hi>(d, da + 2, db + 128);
            wgmma112<0, 1, 1, false, D_K128.hi, D_N128.hi>(e, da + 2, db + 384);
        } else {
            constexpr int TA = K == OUT, TB = K != XW;
            constexpr uint32_t sa = K == OUT ? 256 : 2, sb = K == XW ? 2 : K == BIG ? 224 : 128;
            constexpr Desc A = K == OUT ? D_OT : D_K128, B = K == XW ? D_K128 : K == BIG ? D_BLOB : D_N128;
            const uint32_t da = A.lo + a + wg * (K == OUT ? 64 : 512), db = B.lo + b;
            wgmma112<TA, TB, SB, INIT, A.hi, B.hi>(d, da, db);
            wgmma112<TA, TB, SB, false, A.hi, B.hi>(d, da + sa, db + sb);
            wgmma112<TA, TB, SB, false, A.hi, B.hi>(d, da + 2 * sa, db + 2 * sb);
            wgmma112<TA, TB, SB, false, A.hi, B.hi>(d, da + 3 * sa, db + 3 * sb);
        }
        asm volatile("wgmma.commit_group.sync.aligned;" ::: "memory");
        if (!TAIL) asm volatile("wgmma.wait_group.sync.aligned 1;" ::: "memory");
        if (last) nb_arrive(2 - wg, 256);
        if (!TAIL && stage > 0) {
            if (releaser) mbar_arrive(base + BAR_EMPTY + ((stage - 1) & 7) * 8);
        }
        stage++;
        a += SLOT >> 4;
        if (a == (base + NA * SLOT) >> 4) a = base >> 4;
        b += SLOT >> 4;
        if (b == (base + BRING + NBS * SLOT) >> 4) b = (base + BRING) >> 4;
        if (more) wait();
    }
    template <Kind K, int NBS, bool INIT, int SB = 1, bool TAIL = false>
    __device__ __forceinline__ void run(float (&d)[56], bool first = true, bool last = true, bool more = true) {
        run<K, NBS, INIT, SB, TAIL>(d, d, first, last, more);
    }
};

__device__ __forceinline__ void pack_all(const float (&d)[56], uint32_t (&p)[28]) {
#pragma unroll
    for (int i = 0; i < 28; i++) p[i] = pack2(d[2 * i], d[2 * i + 1]);
}
template <int I0, int I1>
__device__ __forceinline__ void store_frags(uint8_t* dst, const uint32_t (&p)[28]) {
#pragma unroll
    for (int i = I0; i < I1; i++) stg1(dst + i * 128, p[i]);
}
template <int I0, int I1>
__device__ __forceinline__ void stage_frags(uint32_t lane_addr, const uint32_t (&p)[28]) {
#pragma unroll
    for (int i = I0; i < I1; i += 4) stsm4(lane_addr + i * 128, p[i], p[i + 1], p[i + 2], p[i + 3]);
}
template <class F>
__device__ __forceinline__ void store_out(F frag, int lane, uint32_t slab, const CUtensorMap* m, int c0, int c1) {
    const bool swap = lane & 16;
    const uint32_t addr = slab + (lane & 7) * 224 + ((lane >> 3) ^ ((lane >> 2) & 1)) * 16;
#pragma unroll
    for (int h = 0; h < 2; h++) {
#pragma unroll
        for (int c = 0; c < 14; c += 4) {
            const uint32_t t0 = frag(2 * c + h), t1 = frag(2 * c + 2 + h);
            if (c < 12) {
                const uint32_t t2 = frag(2 * c + 4 + h), t3 = frag(2 * c + 6 + h);
                stsm4(addr + h * 1792 + c * 16, swap ? t1 : t0, swap ? t0 : t1, swap ? t3 : t2, swap ? t2 : t3);
            } else {
                asm volatile("stmatrix.sync.aligned.m8n8.x2.shared.b16 [%0], {%1,%2};" ::"r"(addr + h * 1792 + c * 16), "r"(swap ? t1 : t0), "r"(swap ? t0 : t1) : "memory");
            }
        }
        fence_async_smem();
        __syncwarp();
        if (elect()) tma_st2(m, c0, c1 + 8 * h, slab + h * 1792);
    }
    if (elect()) {
        bulk_commit();
        bulk_wait_read();
    }
}
__host__ __device__ constexpr int tile_of(int t) { return 7 * (t >> 2) + 3 * ((t >> 1) & 1) + 2 * (t & 1); }

struct Role {
    bool H;
    int L, mt, ns, id;
    int kind, a0, a1, b3;
};
template <bool BY_SM>
__device__ __forceinline__ Role decode_role() {
    uint32_t sm;
    if (BY_SM) asm volatile("mov.u32 %0, %%smid;" : "=r"(sm));
    else asm volatile("mov.u32 %0, %%ctaid.x;" : "=r"(sm));
    const int tpc = sm >> 1, q2 = ((tpc - 32) * 37) >> 8;
    const int gpc = tpc < 32 ? tpc & 7 : tpc < 60 ? tpc - 31 - 7 * q2 : 0;
    const int pos = tpc < 32 ? tpc >> 3 : tpc < 60 ? q2 + 4 : tpc - 56;
    Role r;
    r.H = sm >= 128;
    const int grp = (GPC_MAP >> (4 * gpc)) & 7;
    r.L = grp & 1;
    r.mt = (grp >> 1) * 4 + (pos >> 1);
    r.ns = (pos & 1) * 2 + (sm & 1);
    r.id = r.H ? sm : grp * 16 + pos * 2 + (sm & 1);
    r.kind = r.H ? 2 : r.L;
    r.a0 = r.L ? (r.mt >> 3) * 448 : 0;
    r.a1 = r.L ? (r.mt & 7) * 128 : r.H ? 120 : r.mt * 64;
    r.b3 = r.H ? 4 + r.ns : r.L ? r.ns : 0;
    return r;
}

__device__ __forceinline__ void first_fill(const Maps& maps, const Role& r, int i) {
    const bool E = r.kind == 0;
    const CUtensorMap* ma = &maps.m[r.kind];
    const uint32_t bar = full_bar(i);
    const int k = (i * 64) >> r.L;
    const bool has_a = !(i & r.L), has_b = i < 7 - r.L;
    const uint32_t dst = base + BRING + (E ? (0x2104365u >> (4 * i)) & 7 : i) * SLOT;
    mbar_expect(bar, (has_a ? SLOT : 0) + (has_b ? (E ? BLOB : SLOT) : 0));
    if (has_a) tma_ld4(base + (i >> r.L) * SLOT, ma, r.a0 + k, r.a1, 0, 0, bar);
    if (has_b) {
        tma_ld4(dst, ma + 3, E ? k : 0, E ? r.ns * 112 : k, 0, r.b3, bar);
        if (!E) tma_ld4(dst + 8192, ma + 3, 64, k, 0, r.b3, bar);
        mbar_arrive(bar);
    }
}
static_assert(bslot_e(0) == 5 && bslot_e(1) == 6 && bslot_e(2) == 3 && bslot_e(3) == 4 && bslot_e(4) == 0 && bslot_e(6) == 2, "");

template <bool BY_SM>
__global__ void __launch_bounds__(384, 1) fused_kernel(Scratch* sc, const __grid_constant__ Maps maps) {
    const unsigned t_open = clk32();
    const int warp = __shfl_sync(0xffffffffu, threadIdx.x >> 5, 0);
    if (warp == 8) {
        if (elect()) {
#pragma unroll
            for (int i = 0; i < LEAD; i++) mbar_init(base + BAR_FULL + i * 8, 2);
            asm volatile("fence.mbarrier_init.release.cluster;" ::: "memory");
            const Role r = decode_role<BY_SM>();
#pragma unroll 1
            for (int i = 0; i < LEAD; i++) {
                first_fill(maps, r, i);
            }
        }
    }
    if (warp == 9) {
        if (elect()) {
#pragma unroll
            for (int i = 0; i < 8; i++) mbar_init(base + BAR_EMPTY + i * 8, 4);
            asm volatile("fence.mbarrier_init.release.cluster;" ::: "memory");
        }
    } else if (warp == 10) {
        if (elect()) {
#pragma unroll
            for (int i = 0; i < 3; i++) mbar_init(base + BAR_RDY + i * 8, i < 2 ? 4 : 8);
#pragma unroll
            for (int i = 0; i < 2; i++) mbar_init(base + BAR_HALO + i * 8, 1);
            asm volatile("fence.mbarrier_init.release.cluster;" ::: "memory");
        }
    } else if (warp == 11) {
        if (elect()) {
#pragma unroll
            for (int i = LEAD; i < 8; i++) mbar_init(base + BAR_FULL + i * 8, 2);
#pragma unroll
            for (int i = 0; i < 3; i++) mbar_init(base + BAR_DEP + i * 8, 1);
#pragma unroll
            for (int i = 0; i < 2; i++) mbar_init(base + BAR_PART + i * 8, 1);
            asm volatile("fence.mbarrier_init.release.cluster;" ::: "memory");
        }
    }
    __syncthreads();

    const Role role = decode_role<BY_SM>();
    int lane = threadIdx.x & 31;
    asm volatile("" : "+r"(lane));
    const bool roleH = role.H;
    const int roleL = role.L, mt = role.mt, ns = role.ns, bid = role.id;
    const int par = mt >> 3, blk = mt & 7, col = ns * 112;

    if (__builtin_expect(warp >= 8, 1)) {
        asm volatile("setmaxnreg.dec.sync.aligned.u32 56;");
#define PROF_FEED_A
#define PROF_FEED_B
        if (__builtin_expect(warp == 8, 1)) {
            if (elect()) {
                PROF(129);
#pragma unroll 1
                for (int i = LEAD; i < 7; i++) {
                    while (clk32() - t_open < i * PACE) {}
                    first_fill(maps, role, i);
                }
                PROF(134);
                Feed<0> f;
                const int row = mt * 128;
                auto c_run = [&](const CUtensorMap* m, int off, int n0, int n1) {
#pragma unroll 1
                    for (int n = n0; n < n1; n++) {
                        const uint32_t bar = f.acquire<NA>();
                        mbar_expect(bar, SLOT);
                        tma_ld2(f.dst, m, (off + skip_own(n, mt)) * 64, row, bar);
                        PROF_FEED_A;
                        f.next<NA>();
                    }
                };
                if (roleH) {
                } else if (!roleL) {
                    f.seek(14, 0);
#pragma unroll 1
                    for (int i = 0; i < 4; i++) {
                        const uint32_t bar = f.acquire<NA>();
                        mbar_expect(bar, SLOT);
                        tma_ld2(f.dst, &maps.m[M_CR + (i >> 1)], ((i & 1) * 16 + mt) * 64, row, bar);
                        mbar_arrive(bar);
                        PROF_FEED_A;
                        f.next<NA>();
                    }
                    c_run(&maps.m[M_CR], 0, 0, 15);
                    c_run(&maps.m[M_CI], 0, 0, NBE);
                    wait_dep(2);
#pragma unroll 1
                    for (int i = 0; i < 7; i++) {
                        const uint32_t bar = f.acquire<NA>();
                        mbar_expect(bar, SLOT);
                        bulk_ld(f.dst, sc->o + (size_t)(mt * 7 + i) * SLOT, SLOT, bar);
                        PROF_FEED_A;
                        f.next<NA>();
                    }
                } else {
#pragma unroll 1
                    for (int i = 4; i < 7; i++) {
                        wait_released(2 * i - 8);
                        mbar_expect(full_bar(2 * i), SLOT);
                        tma_ld4(base + i * SLOT, &maps.m[M_XA], par * 448 + i * 64, blk * 128, 0, 0, full_bar(2 * i));
                    }
                    wait_released(HALO_K_AT);
                    mbar_arrive(base + BAR_DEP + 16);
                    f.seek(21, 0);
                    c_run(&maps.m[M_CR], 16, 0, 15);
                    c_run(&maps.m[M_CI], 16, 0, 15);
                    c_run(&maps.m[M_CI], 0, NBE, 15);
                }
            }
        } else if (warp == 11) {
            if (elect()) {
                Feed<BRING> f;
                auto blob_run = [&](auto nbs, int quarter, int n0, int n1) {
                    constexpr int N = decltype(nbs)::value;
                    const uint8_t* src = sc->ab + (size_t)(quarter * 64 + ns) * BLOB;
#pragma unroll 1
                    for (int n = n0; n < n1; n++) {
                        const uint32_t bar = f.template acquire<N>();
                        mbar_expect(bar, BLOB);
                        bulk_ld(f.dst, src + skip_own(n, mt) * (4 * BLOB), BLOB, bar);
                        PROF_FEED_B;
                        f.template next<N>();
                    }
                };
                auto w_run = [&](auto nbs, const CUtensorMap* m, int slice, bool no_a) {
                    constexpr int N = decltype(nbs)::value;
#pragma unroll 1
                    for (int i = 0; i < 7; i++) {
                        const uint32_t bar = f.template acquire<N>();
                        mbar_expect(bar, SLOT);
                        tma_ld4(f.dst, m, 0, i * 64, 0, slice, bar);
                        tma_ld4(f.dst + 8192, m, 64, i * 64, 0, slice, bar);
                        if (no_a) mbar_arrive(bar);
                        PROF_FEED_B;
                        f.template next<N>();
                    }
                };
                if (roleH) {
                    f.seek(7, 0);
                    w_run(Int<7>(), &maps.m[M_WV], 8 + ns, true);
                } else if (!roleL) {
                    f.seek(7, bslot_e(7));
#pragma unroll 1
                    for (int i = 0; i < 7; i++) {
                        const uint32_t bar = f.acquire<5>();
                        mbar_expect(bar, BLOB);
                        tma_ld2(f.dst, &maps.m[M_WI], i * 64, col, bar);
                        mbar_arrive(bar);
                        PROF_FEED_B;
                        f.next<5>();
                    }
                    f.seek(18, bslot_e(18));
                    wait_dep(0);
                    blob_run(Int<7>(), 0, 0, 15);
                    wait_dep(1);
                    blob_run(Int<7>(), 2, 0, NBE);
                    w_run(Int<7>(), &maps.m[M_WO], ns, false);
                } else {
                    f.seek(6, 0);
#pragma unroll 1
                    for (int i = 6; i < 14; i++) {
                        const uint32_t bar = f.acquire<6>();
                        mbar_expect(bar, SLOT);
                        tma_ld4(f.dst, &maps.m[M_WQK], 0, i * 32, 0, ns, bar);
                        tma_ld4(f.dst + 8192, &maps.m[M_WQK], 64, i * 32, 0, ns, bar);
                        if (i & 1) mbar_arrive(bar);
                        PROF_FEED_B;
                        f.next<6>();
                    }
                    w_run(Int<6>(), &maps.m[M_WV], 8 + ns, true);
                    wait_dep(0);
                    blob_run(Int<6>(), 1, 0, 15);
                    wait_dep(1);
                    blob_run(Int<6>(), 3, 0, 15);
                    blob_run(Int<6>(), 2, NBE, 15);
                }
            }
        } else if (roleH) {
            if (elect()) {
                wait_released(warp == 9 ? 0 : 7);
#pragma unroll 1
                for (int i = 0; i < 7; i++) {
                    if (warp == 9) {
                        asm volatile("cp.async.bulk.prefetch.tensor.2d.L2.global [%0, {%1, %2}];" ::"l"(&maps.m[M_WI]), "r"(i * 64), "r"(col) : "memory");
                    } else {
                        asm volatile("cp.async.bulk.prefetch.tensor.4d.L2.global [%0, {%1, %2, 0, %3}];" ::"l"(&maps.m[M_WO]), "r"(0), "r"(i * 64), "r"(ns) : "memory");
                        asm volatile("cp.async.bulk.prefetch.tensor.4d.L2.global [%0, {%1, %2, 0, %3}];" ::"l"(&maps.m[M_WO]), "r"(64), "r"(i * 64), "r"(ns) : "memory");
                    }
                }
            }
        } else if (warp == 10) {
            if (elect()) {
                unsigned* epoch_ptr = &sc->epoch[(bid * 4 + 2) * 8];
                const unsigned ep = *epoch_ptr + 1;
                sts1(base + TAG, ep);
                asm volatile("prefetch.tensormap [%0];" ::"l"(&maps.m[M_OUTA + roleL]) : "memory");
                await(sc, CNT_A + roleL * 4 + ns, ep * 16);
                mbar_arrive(base + BAR_DEP);
                PROF(150);
                await(sc, CNT_B + ns, ep * 16);
                mbar_arrive(base + BAR_DEP + 8);
                PROF(151);
                if (!roleL) {
                    await(sc, CNT_O + mt, ep * 4);
                    mbar_arrive(base + BAR_DEP + 16);
                } else {
                    await(sc, CNT_P + mt * 4 + ns, ep * 2 - 1);
                    mbar_arrive(base + BAR_PART);
                    PROF(153);
                    await(sc, CNT_P + mt * 4 + ns, ep * 2);
                    mbar_arrive(base + BAR_PART + 8);
                }
                PROF(152);
                *epoch_ptr = ep;
            }
        } else if (!roleL) {
            if (elect()) {
                mbar_wait(base + BAR_RDY, 0);
                PROF(130);
                signal(sc, CNT_A + ns);
                PROF(131);
                mbar_wait(base + BAR_RDY + 8, 0);
                signal(sc, CNT_A + 4 + ns);
                PROF(135);
                mbar_wait(base + BAR_RDY + 16, 0);
                PROF(132);
                signal(sc, CNT_B + ns);
                PROF(133);
            }
        } else {
            unsigned* epoch_ptr = &sc->epoch[(bid * 4 + 1) * 8];
            const unsigned tag = *epoch_ptr + 1;
#pragma unroll 1
            for (int kv = 0; kv < 2; kv++) {
                uint32_t v[16];
#pragma unroll
                for (int i = 0; i < 16; i++) v[i] = 0;
                if (kv) wait_released(HALO_V_AT - 4), wait_released(HALO_V_AT);
                else mbar_wait(base + BAR_DEP + 16, 0);
                if (blk > 0) {
                    const uint8_t* src = sc->halo + (size_t)(((mt - 1) * 4 + ns) * 2 + kv) * 2048 + lane * 16;
#pragma unroll 1
                    for (int n = 0; n < SPIN_LIMIT; n++) {
                        uint32_t stale = 0;
#pragma unroll
                        for (int i = 0; i < 4; i++) ld_tagged(src + i * 512, v[4 * i], v[4 * i + 1], v[4 * i + 2], v[4 * i + 3]);
#pragma unroll
                        for (int i = 0; i < 16; i += 2) stale |= v[i] ^ tag;
                        if (__all_sync(0xffffffffu, !(stale & 1))) break;
                    }
#pragma unroll
                    for (int c = 0; c < 14; c += 2) v[c] = (v[c] & ~1u) | ((v[15] >> c) & 1);
                }
#pragma unroll
                for (int i = 0; i < 14; i++) sts1(base + HALO + kv * (8 * HSLOT) + i * 128 + lane * 4, v[i]);
                warp_arrive(base + BAR_HALO + kv * 8);
                if (lane == 0) PROF(142 + kv);
            }
            if (elect()) {
                mbar_wait(base + BAR_RDY + 16, 0);
                PROF(130);
                signal(sc, CNT_O + mt);
                PROF(131);
                *epoch_ptr = tag;
            }
        }
    } else {
        asm volatile("setmaxnreg.inc.sync.aligned.u32 224;");
        Ring r;
        r.wg = warp >> 2;
        r.zero = blockIdx.y;
        r.releaser = lane + 1 == (warp >> 2);
        const int wg = warp >> 2;
        if (wg) nb_arrive(1, 256);
        uint8_t* part = sc->part + (size_t)(ns * 16 + mt) * (2 * BLOB) + warp * 512 + lane * 16;
        uint32_t p[28];

        if (roleH) {
            unsigned* epoch_ptr = &sc->epoch[bid * 4 * 8];
            const unsigned tag = *epoch_ptr + 1;
            uint8_t* hout = sc->halo + (size_t)((warp * 8 + ns) * 2) * 2048 + lane * 16;
            auto send = [&](int kv) {
#pragma unroll
                for (int h = 0; h < 2; h++) {
                    uint32_t v[16];
                    v[14] = v[15] = 0;
#pragma unroll
                    for (int c = 0; c < 14; c++) v[c] = p[2 * c + h];
#pragma unroll
                    for (int c = 0; c < 14; c += 2) v[15] |= (v[c] & 1) << c;
#pragma unroll
                    for (int i = 0; i < 4; i++) st_part(hout + (h * 8 + kv) * 2048 + i * 512, v + 4 * i, tag & 1);
                }
            };
            float x0[56], x1[56];
            r.seek(0, 0);
            r.wait();
            r.run<XWN, 7, true>(x0);
#pragma unroll 1
            for (int i = 1; i < 7; i++) r.run<XWN, 7, false>(x0);
            r.run<XWN, 7, true>(x1);
            acc_fence(x0);
            pack_all(x0, p);
            send(0);
#pragma unroll 1
            for (int i = 1; i < 7; i++) r.run<XWN, 7, false>(x1, true, true, i < 6);
            asm volatile("wgmma.wait_group.sync.aligned 0;" ::: "memory");
            acc_fence(x1);
            pack_all(x1, p);
#pragma unroll
            for (int i = 0; i < 28; i++) p[i] = movm(p[i]);
            send(1);
            if (threadIdx.x == 0) *epoch_ptr = tag;
        } else if (!roleL) {
            uint8_t* blob = sc->ab + (size_t)((wg * 16 + mt) * 4 + ns) * BLOB + (warp & 3) * WSLOT + lane * 4;
            const uint32_t own = base + BRING + wg * SLOT + (warp & 3) * WSLOT + lane * 16;
            float x0[56], x1[56];
            r.seek(0, bslot_e(0));
            r.wait();
            r.run<XW, 7, true>(x0);
            r.run<XW, 7, false>(x0);
            r.seek(2, bslot_e(2));
#pragma unroll 1
            for (int i = 2; i < 7; i++) r.run<XW, 5, false>(x0);

            r.seek(7, bslot_e(7));
            r.run<XW, 5, true, -1>(x1);
            acc_fence(x0);
            pack_all(x0, p);
#pragma unroll
            for (int i = 0; i < 2; i++) {
                if (wg == i) store_frags<0, 14>(blob, p);
                else stage_frags<0, A_OWN>(own + 5 * SLOT, p);
                r.run<XW, 5, false, -1>(x1);
                if (wg == i) {
                    store_frags<14, 28>(blob, p);
                    warp_arrive(base + BAR_RDY + i * 8);
                } else {
                    stage_frags<A_OWN, 2 * A_OWN>(own + 5 * SLOT, p);
                }
                r.run<XW, 5, false, -1>(x1);
            }
            stage_frags<2 * A_OWN, A_OWN2>(own + 5 * SLOT, p);
            r.run<XW, 5, false, -1>(x1);
            stage_frags<A_OWN2, 28>(own + 5 * SLOT, p);
            fence_async_smem();
            r.run<XW, 5, false, -1>(x1);

            r.seek(14, bslot_e(14));
            r.run<BIG, 7, true>(x0);
            acc_fence(x1);
            pack_all(x1, p);
            stage_frags<0, B_OWN>(own, p);
            r.run<BIG, 7, false>(x0);
            stage_frags<B_OWN, 28>(own, p);
            fence_async_smem();
            blob += (size_t)128 * BLOB;
#pragma unroll
            for (int i = 0; i < 28; i++) {
                if (i % B_SLICE == 0) r.run<BIG, 7, false>(x0);
                stg1(blob + i * 128, p[i]);
            }
            warp_arrive(base + BAR_RDY + 16);
#pragma unroll 1
            for (int i = 17 + 27 / B_SLICE; i < POUT; i++) r.run<BIG, 7, false>(x0);

            const uint32_t tag = lds1(base + TAG);
            r.seek(POUT, bslot_e(POUT));
            r.run<OUT, 7, true>(x1);
            acc_fence(x0);
            pack_all(x0, p);
#pragma unroll
            for (int k = 0; k < 3; k++) {
                if (k < 2 && wg == k) {
                    if ((warp & 3) == 0 && elect())
                        asm volatile("red.relaxed.gpu.global.add.u32 [%0], 1;" ::"l"(&sc->cnt[(CNT_P + mt * 4 + ns) * 32]) : "memory");
#pragma unroll
                    for (int i = 0; i < 4; i++) st_part(part + i * 4096, p + 4 * i, tag & 1);
                }
                if (k > 0 && wg == k - 1) {
#pragma unroll
                    for (int i = 4; i < 7; i++) st_part(part + i * 4096, p + 4 * i, tag & 1);
                }
                if (k < 2) r.run<OUT, 7, false>(x1);
            }
#pragma unroll
            for (int i = 3; i < 7; i++) r.run<OUT, 7, false, 1, true>(x1, i <= 7 - TURN, i < 7 - TURN || i == 6, i < 6);

            asm volatile("wgmma.wait_group.sync.aligned 0;" ::: "memory");
            acc_fence(x1);
            const uint32_t slab = base + (wg ? BRING + bslot_e(ELAST - 6) * SLOT : ((ELAST - 6) % NA) * SLOT) + (warp & 3) * WSLOT;
            store_out([&](int i) { return pack2(x1[2 * i], x1[2 * i + 1]); }, lane, slab, &maps.m[M_OUTA], par * 896 + col, blk * 128 + warp * 16);
        } else {
            const int g = lane >> 2, tig = lane & 3;
            const uint32_t hin = base + HALO + warp * HSLOT + lane * 4;
            const uint32_t hpub = warp < 7 ? hin + HSLOT : base + HSPARE + lane * 4;
            auto publish = [&](const uint32_t (&h)[14], int c0, int c1) {
#pragma unroll
                for (int c = 0; c < 14; c++)
                    if (c >= c0 && c < c1) sts1(hpub + c * 128, h[c]);
            };
            float y0[56], y1[56], y2[56];
            r.seek(0, 0);
            r.wait();
            r.run<QK, 6, true>(y0, y1);
#pragma unroll 1
            for (int i = 1; i < 14; i++) r.run<QK, 6, false>(y0, y1);

            uint32_t m1[8][4], m0[8][4], lo[14], hi[14], q[2][8][2];
            auto pack_q = [&](int b) {
                uint32_t v[14];
#pragma unroll
                for (int c = 0; c < 14; c++) v[c] = pack2(y0[4 * c + 2 * b], y0[4 * c + 2 * b + 1]);
#pragma unroll
                for (int t = 0; t < 8; t++) {
                    const int c = tile_of(t);
                    q[b][t][0] = (t & 3) == 2 ? (tig >= 2 ? v[c] : 0u) : v[c];
                    q[b][t][1] = (t & 3) == 1 ? (tig < 2 ? v[c + 1] : 0u) : v[c + 1];
                }
            };
            auto fetch = [&](uint32_t src, int hp, int i0) {
#pragma unroll
                for (int t = 4 * hp; t < 4 * hp + 4; t++) {
                    m0[t][i0] = (t & 3) == 2 ? dup(m0[t - 1][3], r.zero) : lds1(src + tile_of(t) * 128);
                    m0[t][3] = lds1(src + tile_of(t) * 128 + 128);
                }
            };
            r.seek(14, bslot_l(14));
            r.run<XWN, 6, true>(y2);
            acc_fence(y0);
            acc_fence(y1);
#pragma unroll
            for (int c = 0; c < 14; c++) hi[c] = pack2(y1[4 * c + 2], y1[4 * c + 3]);
            publish(hi, 0, 7);
            r.run<XWN, 6, false>(y2);
            publish(hi, 7, 14);
#pragma unroll
            for (int c = 0; c < 14; c++) lo[c] = pack2(y1[4 * c], y1[4 * c + 1]);
#pragma unroll
            for (int t = 0; t < 8; t++) {
                const int c = tile_of(t);
                const bool shared = (t & 3) == 2;
                m1[t][0] = shared ? dup(lo[c], r.zero) : lo[c];
                m1[t][1] = shared ? dup(hi[c], r.zero) : hi[c];
                m1[t][2] = lo[c + 1];
                m1[t][3] = hi[c + 1];
                m0[t][0] = dup(m1[t][0], r.zero);
                m0[t][2] = dup(lo[c + 1], 2 * r.zero);
            }
            r.run<XWN, 6, false>(y2);
            if (warp == 0) mbar_wait(base + BAR_HALO, 0);
            fetch(hin, 0, 1);
            pack_q(1);
            r.run<XWN, 6, false>(y2);
            fetch(hin, 1, 1);
            pack_q(0);
            r.mma_begin();
            float s[8][4];
#pragma unroll
            for (int step = 0; step < 2; step++) {
#pragma unroll
                for (int i = 0; i < 8; i++) {
                    const int b = 1 - (i >> 2), h = i & 3, t = 2 * h + step;
                    float (&d)[4] = s[2 * h + b];
                    if (step == 0) d[0] = d[1] = d[2] = d[3] = 0.f;
                    mma16816(d, b ? m1[t] : m0[t], q[b][t][0], q[b][t][1]);
                }
            }
            r.mma_end();
            r.run<XWN, 6, false>(y2, false);

            uint32_t pr[8], mx[4], mx1[4];
            {
                const bool cur0 = g <= 2 * tig, cur1 = g <= 2 * tig + 1;
#pragma unroll
                for (int i = 0; i < 8; i++) {
                    const int c = (i & 1) ? 2 : 0;
                    pr[i] = movm(pack2(cur0 ? s[i][c] : s[i][2 - c], cur1 ? s[i][c + 1] : s[i][3 - c]));
                }
            }
            r.run<XWN, 6, false>(y2);
            const uint32_t curmask = (2 * tig <= g ? 0x0000FFFFu : 0u) | (2 * tig + 1 <= g ? 0xFFFF0000u : 0u);
            {
                const uint32_t keep = (blk == 0 && warp == 0) ? curmask : 0xFFFFFFFFu;
#pragma unroll
                for (int i = 0; i < 4; i++) {
                    pr[2 * i] = (pr[2 * i] & keep) | (0xCF9ECF9Eu & ~keep);
                    mx[i] = max2(__byte_perm(pr[2 * i], pr[2 * i + 1], 0x5410), __byte_perm(pr[2 * i], pr[2 * i + 1], 0x7632));
                    mx1[i] = __shfl_xor_sync(0xffffffffu, mx[i], 1);
                }
            }
#pragma unroll
            for (int i = 0; i < 4; i++) {
                mx[i] = max2(mx[i], mx1[i]);
                mx1[i] = __shfl_xor_sync(0xffffffffu, mx[i], 2);
            }
            r.run<XWN, 6, false>(y2);
            constexpr float SCL = 0.18898223650461362f * 1.4426950408889634f;
            float e0[8], e1[8], sm[8], sm1[8];
#pragma unroll
            for (int i = 0; i < 8; i++) {
                const uint32_t m2 = max2(mx[i >> 1], mx1[i >> 1]);
                sm[i] = ((i & 1) ? bf_hi(m2) : bf_lo(m2)) * -SCL;
                e0[i] = ex2(fmaf(bf_lo(pr[i]), SCL, sm[i]));
            }

            r.seek(21, bslot_l(21));
            r.run<BIG, 6, true>(y0);
            acc_fence(y2);
#pragma unroll
            for (int c = 0; c < 7; c++) hi[c] = movm(pack2(y2[4 * c + 2], y2[4 * c + 3]));
#pragma unroll
            for (int i = 0; i < 8; i++) e1[i] = ex2(fmaf(bf_hi(pr[i]), SCL, sm[i]));
            r.run<BIG, 6, false>(y0);
            publish(hi, 0, 7);
#pragma unroll
            for (int c = 7; c < 14; c++) hi[c] = movm(pack2(y2[4 * c + 2], y2[4 * c + 3]));
            r.run<BIG, 6, false>(y0);
            publish(hi, 7, 14);
#pragma unroll
            for (int i = 0; i < 8; i++) {
                sm[i] = e0[i] + e1[i];
                sm1[i] = __shfl_xor_sync(0xffffffffu, sm[i], 1);
            }
            r.run<BIG, 6, false>(y0);
#pragma unroll
            for (int c = 0; c < 14; c++) lo[c] = movm(pack2(y2[4 * c], y2[4 * c + 1]));
            r.run<BIG, 6, false>(y0);
#pragma unroll
            for (int i = 0; i < 8; i++) {
                sm[i] += sm1[i];
                sm1[i] = __shfl_xor_sync(0xffffffffu, sm[i], 2);
            }
#pragma unroll
            for (int t = 0; t < 8; t++) {
                const int c = tile_of(t);
                const bool shared = (t & 3) == 2;
                m1[t][0] = shared ? dup(lo[c], r.zero) : lo[c];
                m1[t][1] = lo[c + 1];
                m1[t][2] = shared ? dup(hi[c], r.zero) : hi[c];
                m1[t][3] = hi[c + 1];
                m0[t][0] = dup(m1[t][0], r.zero);
                m0[t][1] = dup(lo[c + 1], 2 * r.zero);
            }
            r.run<BIG, 6, false>(y0);
            if (warp == 0) mbar_wait(base + BAR_HALO + 8, 0);
            const uint32_t vin = warp ? hin : hin + 8 * HSLOT;
            fetch(vin, 0, 2);
#pragma unroll
            for (int i = 0; i < 8; i++) {
                const float inv = rcp(sm[i] + sm1[i]);
                pr[i] = pack2(e0[i] * inv, e1[i] * inv);
            }
            r.run<BIG, 6, false>(y0);
            fetch(vin, 1, 2);
            uint32_t pb[8][2];
#pragma unroll
            for (int t = 0; t < 8; t++) {
                pb[t][t & 1] = band(pr[t], curmask);
                pb[t][1 - (t & 1)] = band(pr[t], ~curmask);
            }
            r.mma_begin();
            float o[2][8][4];
#pragma unroll
            for (int i = 0; i < 16; i++) {
                const int b = 1 - (i >> 3), t = i & 7;
                float (&d)[4] = o[b][t];
                d[0] = d[1] = d[2] = d[3] = 0.f;
                mma16816(d, b ? m1[t] : m0[t], pb[(t & 6) + b][0], pb[(t & 6) + b][1]);
            }
            r.mma_end();
            r.run<BIG, 6, false>(y0, false);
            uint8_t* odst = sc->o + (size_t)mt * 7 * SLOT + ns * (14 * 2048) + warp * 256 + lane * 4;
#pragma unroll
            for (int hp = 0; hp < 2; hp++) {
#pragma unroll
                for (int b = 0; b < 2; b++) {
                    const float (&u)[8][4] = o[b];
                    const int t = 4 * hp;
                    uint32_t* w = p + 14 * hp + b;
                    w[0] = pack2(u[t][0], u[t][1]);
                    w[2] = pack2(u[t][2], u[t][3]);
                    w[4] = pack2(u[t + 1][0], u[t + 1][1]);
                    w[6] = pack2(g < 4 ? u[t + 1][2] : u[t + 2][0], g < 4 ? u[t + 1][3] : u[t + 2][1]);
                    w[8] = pack2(u[t + 2][2], u[t + 2][3]);
                    w[10] = pack2(u[t + 3][0], u[t + 3][1]);
                    w[12] = pack2(u[t + 3][2], u[t + 3][3]);
                }
            }
#pragma unroll
            for (int i = 0; i < 28; i++) {
                if (i >= O_FIRST && (i - O_FIRST) % O_SLICE == 0) r.run<BIG, 6, false>(y0);
                stg1(odst + (i >> 1) * 2048 + (i & 1) * 128, p[i]);
            }
            warp_arrive(base + BAR_RDY + 16);

#pragma unroll 1
            for (int i = 30 + (27 - O_FIRST) / O_SLICE; i <= LLAST + 1 - TURN; i++) r.run<BIG, 6, false>(y0, true, i <= LLAST - TURN);
            const uint32_t tag = lds1(base + TAG);
            if (mbar_test(base + BAR_PART + wg * 8, 0)) {
#pragma unroll
                for (int i = 0; i < 7; i++) ld_tagged(part + i * 4096, p[4 * i], p[4 * i + 1], p[4 * i + 2], p[4 * i + 3]);
            } else {
                p[0] = ~tag;
            }
            r.seek(LLAST + 2 - TURN, bslot_l(LLAST + 2 - TURN));
#pragma unroll
            for (int i = 1; i < TURN; i++) r.run<BIG, 6, false, 1, true>(y0, false, i == TURN - 1, i < TURN - 1);
#pragma unroll 1
            for (int n = 0; n < SPIN_LIMIT; n++) {
                uint32_t stale = 0;
#pragma unroll
                for (int i = 0; i < 28; i += 2) stale |= p[i] ^ tag;
                if (__all_sync(0xffffffffu, !(stale & 1))) break;
                mbar_wait(base + BAR_PART + wg * 8, 0);
#pragma unroll
                for (int i = 0; i < 7; i++) ld_tagged(part + i * 4096, p[4 * i], p[4 * i + 1], p[4 * i + 2], p[4 * i + 3]);
            }
            asm volatile("wgmma.wait_group.sync.aligned 0;" ::: "memory");
            acc_fence(y0);
            const uint32_t slab = base + (wg ? HALO : ((LLAST - 6) % NA) * SLOT) + (warp & 3) * WSLOT;
            store_out([&](int i) { return add2(pack2(y0[2 * i], y0[2 * i + 1]), p[i]); }, lane, slab, &maps.m[M_OUTB], 448 + col, mt * 128 + warp * 16);
        }
    }
}

typedef CUresult (*EncodeFn)(CUtensorMap*, CUtensorMapDataType, cuuint32_t, void*, const cuuint64_t*, const cuuint64_t*,
                             const cuuint32_t*, const cuuint32_t*, CUtensorMapInterleave, CUtensorMapSwizzle,
                             CUtensorMapL2promotion, CUtensorMapFloatOOBfill);

struct Dim { uint64_t size, stride; uint32_t box; };
void encode(EncodeFn fn, CUtensorMap* m, const void* ptr, CUtensorMapSwizzle sw, Dim d0, Dim d1, Dim d2 = {0, 0, 0}, Dim d3 = {0, 0, 0}) {
    const cuuint64_t dims[4] = {d0.size, d1.size, d2.size, d3.size};
    const cuuint64_t strides[3] = {d1.stride, d2.stride, d3.stride};
    const cuuint32_t box[4] = {d0.box, d1.box, d2.box, d3.box};
    const cuuint32_t es[4] = {1, 1, 1, 1};
    fn(m, CU_TENSOR_MAP_DATA_TYPE_BFLOAT16, d3.size ? 4 : d2.size ? 3 : 2, const_cast<void*>(ptr), dims, strides, box, es,
       CU_TENSOR_MAP_INTERLEAVE_NONE, sw, CU_TENSOR_MAP_L2_PROMOTION_L2_128B, CU_TENSOR_MAP_FLOAT_OOB_FILL_NONE);
}

}

extern "C" void kernel_launch(void* const* d_in, const int* in_sizes, int n_in, void* d_out, int out_size) {
    (void)in_sizes; (void)n_in; (void)out_size;
    void* fnp = nullptr;
    cudaDriverEntryPointQueryResult st;
    cudaGetDriverEntryPoint("cuTensorMapEncodeTiled", &fnp, cudaEnableDefault, &st);
    EncodeFn fn = (EncodeFn)fnp;
    void* scratch = nullptr;
    cudaGetSymbolAddress(&scratch, g_scratch);
    int dev = 0, sms = 0;
    cudaGetDevice(&dev);
    cudaDeviceGetAttribute(&sms, cudaDevAttrMultiProcessorCount, dev);
    auto kernel = sms == 132 ? fused_kernel<true> : fused_kernel<false>;
    cudaFuncSetAttribute(kernel, cudaFuncAttributeMaxDynamicSharedMemorySize, SMEM_BYTES);

    const CUtensorMapSwizzle S128 = CU_TENSOR_MAP_SWIZZLE_128B, S0 = CU_TENSOR_MAP_SWIZZLE_NONE;
    const Dim one = {1, 16, 1};
    Maps maps;
    encode(fn, &maps.m[M_XA], d_in[0], S128, {896, 2, 64}, {1024, 1792, 128}, one, one);
    encode(fn, &maps.m[M_WQK], d_in[1], S128, {112, 2, 64}, {448, 2688, 32}, {3, 896, 2}, {4, 224, 1});
    encode(fn, &maps.m[M_WV], d_in[1], S128, {112, 2, 64}, {448, 2688, 64}, one, {12, 224, 1});
    encode(fn, &maps.m[M_XH], d_in[0], S128, {448, 2, 64}, {128, 1792, 8}, {8, 128 * 1792, 8}, {2, 896, 2});
    encode(fn, &maps.m[M_WO], d_in[2], S128, {112, 2, 64}, {448, 896, 64}, one, {4, 224, 1});
    encode(fn, &maps.m[M_XB], d_in[3], S128, {448, 2, 64}, {1024, 896, 64}, {2, 896 * 1024, 2}, one);
    encode(fn, &maps.m[M_CR], d_in[4], S128, {2048, 2, 64}, {2048, 4096, 128});
    encode(fn, &maps.m[M_CI], d_in[5], S128, {2048, 2, 64}, {2048, 4096, 128});
    encode(fn, &maps.m[M_WR], d_in[6], S128, {448, 2, 64}, {448, 896, 112}, one, one);
    encode(fn, &maps.m[M_WI], d_in[7], S128, {448, 2, 64}, {448, 896, 112});
    encode(fn, &maps.m[M_OUTA], d_out, S0, {1792, 2, 112}, {1024, 3584, 8});
    encode(fn, &maps.m[M_OUTB], d_out, S0, {896, 2, 112}, {2048, 1792, 8});

    kernel<<<132, 384, SMEM_BYTES>>>((Scratch*)scratch, maps);
}
```

```cpp
#include <cuda.h>
#include <cuda_bf16.h>
#include <cuda_runtime.h>
#include <stdint.h>

namespace {

constexpr uint32_t SLOT = 16384;
constexpr int NA = 7;
constexpr uint32_t BRING = NA * SLOT;
constexpr uint32_t HALO = BRING + 6 * SLOT;
constexpr uint32_t HSLOT = 1792;
constexpr uint32_t WSLOT = 3584;
constexpr uint32_t BLOB = 14336;
constexpr uint32_t BARS = 14 * SLOT;
constexpr uint32_t BAR_FULL = BARS;
constexpr uint32_t BAR_EMPTY = BARS + 64;
constexpr uint32_t BAR_RDY = BARS + 128;
constexpr uint32_t BAR_DEP = BARS + 168;
constexpr uint32_t BAR_HALO = BARS + 192;
constexpr uint32_t BAR_PART = BARS + 208;
constexpr uint32_t TAG = BARS + 224;
constexpr uint32_t HSPARE = BARS + 256 + 1024;
constexpr uint32_t SMEM_BYTES = HSPARE + HSLOT;
constexpr uint32_t base = 1024;
constexpr int SPIN_LIMIT = 1 << 16;

#define E_EXTRA 0
#define HALO_K_AT 10
#define HALO_V_AT 19
#define O_SLICE 4
#define B_SLICE 4
#define LEAD 3
#define TURN 4
#define PACE 450
#define O_FIRST 8
#define LAZY 1
#define P_FIRST 2
#define MMA_SYNC 2
#define A_OWN 4
#define A_OWN2 20
#define E_STEPS 2
#define GPC_MAP 0x64752310u

constexpr int NBL = 13 + E_EXTRA;
constexpr int NBE = NBL + (E_STEPS > 0);
constexpr int POUT = 33 + NBE;
constexpr int ELAST = POUT + 6;
constexpr int LLAST = 52 - E_EXTRA;
static_assert(TURN <= 4, "the output is staged in the slots of the seventh-last stage");

enum { M_XB, M_XA, M_XH, M_WR, M_WQK, M_WV, M_WO, M_WI, M_CR, M_CI, M_OUTA, M_OUTB, M_COUNT };
struct __align__(64) Maps { CUtensorMap m[M_COUNT]; };

constexpr int CNT_A = 0;
constexpr int CNT_B = 8;
constexpr int CNT_O = 16;
constexpr int CNT_P = 32;
constexpr int CNT_COUNT = 96;

struct Scratch {
    uint8_t ab[64 * 4 * BLOB];
    uint8_t o[16 * 7 * SLOT];
    uint8_t part[64 * 2 * BLOB];
    uint8_t halo[64 * 2 * 2048];
    unsigned cnt[CNT_COUNT * 32];
    unsigned epoch[132 * 4 * 8];
};
__device__ __align__(1024) Scratch g_scratch;

__device__ __forceinline__ unsigned clk32() { unsigned c; asm volatile("mov.u32 %0, %%clock;" : "=r"(c)); return c; }

#define PROF(idx)

__device__ __forceinline__ void mbar_init(uint32_t bar, uint32_t cnt) {
    asm volatile("mbarrier.init.shared::cta.b64 [%0], %1;" ::"r"(bar), "r"(cnt) : "memory");
}
__device__ __forceinline__ void mbar_expect(uint32_t bar, uint32_t bytes) {
    asm volatile("mbarrier.arrive.expect_tx.shared::cta.b64 _, [%0], %1;" ::"r"(bar), "r"(bytes) : "memory");
}
__device__ __forceinline__ void mbar_arrive(uint32_t bar) {
    asm volatile("mbarrier.arrive.shared::cta.b64 _, [%0];" ::"r"(bar) : "memory");
}
__device__ __forceinline__ bool mbar_try(uint32_t bar, uint32_t parity) {
    uint32_t ok;
    asm volatile("{\n.reg .pred p;\nmbarrier.try_wait.parity.shared::cta.b64 p, [%1], %2;\nselp.u32 %0, 1, 0, p;\n}\n"
                 : "=r"(ok) : "r"(bar), "r"(parity) : "memory");
    return ok;
}
__device__ __forceinline__ bool mbar_test(uint32_t bar, uint32_t parity) {
    uint32_t ok;
    asm volatile("{\n.reg .pred p;\nmbarrier.test_wait.parity.shared::cta.b64 p, [%1], %2;\nselp.u32 %0, 1, 0, p;\n}\n"
                 : "=r"(ok) : "r"(bar), "r"(parity) : "memory");
    return ok;
}
__device__ __forceinline__ void mbar_wait(uint32_t bar, uint32_t parity) {
#pragma unroll 1
    for (int n = 0; n < SPIN_LIMIT; n++)
        if (mbar_try(bar, parity)) break;
}
__device__ __forceinline__ bool elect() {
    uint32_t p;
    asm volatile("{\n.reg .pred p;\nelect.sync _|p, 0xffffffff;\nselp.u32 %0, 1, 0, p;\n}\n" : "=r"(p));
    return p;
}
__device__ __forceinline__ void nb_sync(int id, int n) { asm volatile("bar.sync %0, %1;" ::"r"(id), "r"(n) : "memory"); }
__device__ __forceinline__ void nb_arrive(int id, int n) { asm volatile("bar.arrive %0, %1;" ::"r"(id), "r"(n) : "memory"); }
__device__ __forceinline__ void warp_arrive(uint32_t bar) {
    __syncwarp();
    if (elect()) mbar_arrive(bar);
}
__device__ __forceinline__ uint32_t band(uint32_t x, uint32_t m) {
    uint32_t r;
    asm volatile("and.b32 %0, %1, %2;" : "=r"(r) : "r"(x), "r"(m));
    return r;
}
__device__ __forceinline__ uint32_t dup(uint32_t x, uint32_t zero) {
    uint32_t r;
    asm volatile("xor.b32 %0, %1, %2;" : "=r"(r) : "r"(x), "r"(zero));
    return r;
}

__device__ __forceinline__ void tma_ld2(uint32_t dst, const CUtensorMap* m, int c0, int c1, uint32_t bar) {
    asm volatile("cp.async.bulk.tensor.2d.shared::cluster.global.mbarrier::complete_tx::bytes [%0], [%1, {%3, %4}], [%2];"
                 ::"r"(dst), "l"(m), "r"(bar), "r"(c0), "r"(c1) : "memory");
}
__device__ __forceinline__ void tma_ld4(uint32_t dst, const CUtensorMap* m, int c0, int c1, int c2, int c3, uint32_t bar) {
    asm volatile("cp.async.bulk.tensor.4d.shared::cluster.global.mbarrier::complete_tx::bytes [%0], [%1, {%3, %4, %5, %6}], [%2];"
                 ::"r"(dst), "l"(m), "r"(bar), "r"(c0), "r"(c1), "r"(c2), "r"(c3) : "memory");
}
__device__ __forceinline__ void bulk_ld(uint32_t dst, const void* src, uint32_t bytes, uint32_t bar) {
    asm volatile("cp.async.bulk.shared::cluster.global.mbarrier::complete_tx::bytes [%0], [%1], %2, [%3];"
                 ::"r"(dst), "l"(src), "r"(bytes), "r"(bar) : "memory");
}
__device__ __forceinline__ void tma_st2(const CUtensorMap* m, int c0, int c1, uint32_t src) {
    asm volatile("cp.async.bulk.tensor.2d.global.shared::cta.bulk_group [%0, {%1, %2}], [%3];"
                 ::"l"(m), "r"(c0), "r"(c1), "r"(src) : "memory");
}
__device__ __forceinline__ void bulk_commit() { asm volatile("cp.async.bulk.commit_group;" ::: "memory"); }
__device__ __forceinline__ void bulk_wait_read() { asm volatile("cp.async.bulk.wait_group.read 0;" ::: "memory"); }
__device__ __forceinline__ void fence_async_smem() { asm volatile("fence.proxy.async.shared::cta;" ::: "memory"); }
__device__ __forceinline__ void fence_async_global() { asm volatile("fence.proxy.async.global;" ::: "memory"); }

__device__ __forceinline__ void signal(Scratch* sc, int idx) {
    asm volatile("fence.proxy.async;\nred.relaxed.gpu.global.add.u32 [%0], 1;" ::"l"(&sc->cnt[idx * 32]) : "memory");
}
__device__ __forceinline__ unsigned peek(const unsigned* p) {
    unsigned v;
    asm volatile("ld.relaxed.gpu.global.u32 %0, [%1];" : "=r"(v) : "l"(p) : "memory");
    return v;
}
__device__ __forceinline__ void await(Scratch* sc, int idx, unsigned target) {
    const unsigned* p = &sc->cnt[idx * 32];
#pragma unroll 1
    for (int n = 0; n < SPIN_LIMIT; n++)
        if ((int)(peek(p) - target) >= 0) break;
    asm volatile("fence.acquire.gpu;" ::: "memory");
}
__device__ __forceinline__ void wait_dep(int k) {
    mbar_wait(base + BAR_DEP + k * 8, 0);
    fence_async_global();
}

#define WG_REGS                                                                                                     \
    "{%0,%1,%2,%3,%4,%5,%6,%7,%8,%9,%10,%11,%12,%13,%14,%15,%16,%17,%18,%19,%20,%21,%22,%23,%24,%25,%26,%27,"       \
    "%28,%29,%30,%31,%32,%33,%34,%35,%36,%37,%38,%39,%40,%41,%42,%43,%44,%45,%46,%47,%48,%49,%50,%51,%52,%53,%54,%55}"
#define WG_OPS(C)                                                                                                   \
    C(d[0]), C(d[1]), C(d[2]), C(d[3]), C(d[4]), C(d[5]), C(d[6]), C(d[7]), C(d[8]), C(d[9]), C(d[10]), C(d[11]),   \
    C(d[12]), C(d[13]), C(d[14]), C(d[15]), C(d[16]), C(d[17]), C(d[18]), C(d[19]), C(d[20]), C(d[21]), C(d[22]),   \
    C(d[23]), C(d[24]), C(d[25]), C(d[26]), C(d[27]), C(d[28]), C(d[29]), C(d[30]), C(d[31]), C(d[32]), C(d[33]),   \
    C(d[34]), C(d[35]), C(d[36]), C(d[37]), C(d[38]), C(d[39]), C(d[40]), C(d[41]), C(d[42]), C(d[43]), C(d[44]),   \
    C(d[45]), C(d[46]), C(d[47]), C(d[48]), C(d[49]), C(d[50]), C(d[51]), C(d[52]), C(d[53]), C(d[54]), C(d[55])

template <int TA, int TB, int SB, bool INIT, uint32_t AH, uint32_t BH>
__device__ __forceinline__ void wgmma112(float (&d)[56], uint32_t alo, uint32_t blo) {
    if (INIT) {
        asm volatile("{\n.reg .pred p;\n.reg .b64 da, db;\nsetp.ne.b32 p, 0, 0;\nmov.b64 da, {%56, %61};\nmov.b64 db, {%57, %62};\n"
                     "wgmma.mma_async.sync.aligned.m64n112k16.f32.bf16.bf16 " WG_REGS ", da, db, p, 1, %59, %60, %58;\n}\n"
                     : WG_OPS("=f") : "r"(alo), "r"(blo), "n"(TB), "n"(SB), "n"(TA), "n"(AH), "n"(BH));
    } else {
        asm volatile("{\n.reg .pred p;\n.reg .b64 da, db;\nsetp.ne.b32 p, 1, 0;\nmov.b64 da, {%56, %61};\nmov.b64 db, {%57, %62};\n"
                     "wgmma.mma_async.sync.aligned.m64n112k16.f32.bf16.bf16 " WG_REGS ", da, db, p, 1, %59, %60, %58;\n}\n"
                     : WG_OPS("+f") : "r"(alo), "r"(blo), "n"(TB), "n"(SB), "n"(TA), "n"(AH), "n"(BH));
    }
}
__device__ __forceinline__ void acc_fence(float (&d)[56]) {
#pragma unroll
    for (int i = 0; i < 56; i++) asm volatile("" : "+f"(d[i])::"memory");
}

__device__ __forceinline__ uint32_t pack2(float lo, float hi) {
    uint32_t r;
    asm volatile("cvt.rn.bf16x2.f32 %0, %1, %2;" : "=r"(r) : "f"(hi), "f"(lo));
    return r;
}
__device__ __forceinline__ uint32_t movm(uint32_t a) {
    uint32_t r;
    asm volatile("movmatrix.sync.aligned.m8n8.trans.b16 %0, %1;" : "=r"(r) : "r"(a));
    return r;
}
__device__ __forceinline__ void stsm4(uint32_t addr, uint32_t a, uint32_t b, uint32_t c, uint32_t d) {
    asm volatile("stmatrix.sync.aligned.m8n8.x4.shared.b16 [%0], {%1,%2,%3,%4};" ::"r"(addr), "r"(a), "r"(b), "r"(c), "r"(d) : "memory");
}
__device__ __forceinline__ void sts1(uint32_t addr, uint32_t a) { asm volatile("st.shared.b32 [%0], %1;" ::"r"(addr), "r"(a) : "memory"); }
__device__ __forceinline__ uint32_t lds1(uint32_t addr) {
    uint32_t a;
    asm volatile("ld.shared.b32 %0, [%1];" : "=r"(a) : "r"(addr) : "memory");
    return a;
}
__device__ __forceinline__ void stg1(uint8_t* p, uint32_t a) { asm volatile("st.global.b32 [%0], %1;" ::"l"(p), "r"(a) : "memory"); }
__device__ __forceinline__ void st_part(uint8_t* p, const uint32_t* v, uint32_t parity) {
    asm volatile("{\n.reg .b64 x, y;\nmov.b64 x, {%1, %2};\nmov.b64 y, {%3, %4};\nst.relaxed.gpu.global.v2.b64 [%0], {x, y};\n}\n"
                 ::"l"(p), "r"((v[0] & ~1u) | parity), "r"(v[1]), "r"((v[2] & ~1u) | parity), "r"(v[3]) : "memory");
}
__device__ __forceinline__ void mma16816(float (&d)[4], const uint32_t (&a)[4], uint32_t b0, uint32_t b1) {
    asm volatile("mma.sync.aligned.m16n8k16.row.col.f32.bf16.bf16.f32 {%0,%1,%2,%3}, {%4,%5,%6,%7}, {%8,%9}, {%0,%1,%2,%3};"
                 : "+f"(d[0]), "+f"(d[1]), "+f"(d[2]), "+f"(d[3]) : "r"(a[0]), "r"(a[1]), "r"(a[2]), "r"(a[3]), "r"(b0), "r"(b1));
}
__device__ __forceinline__ uint32_t add2(uint32_t a, uint32_t b) {
    uint32_t r;
    asm("add.rn.bf16x2 %0, %1, %2;" : "=r"(r) : "r"(a), "r"(b));
    return r;
}
__device__ __forceinline__ uint32_t max2(uint32_t a, uint32_t b) {
    uint32_t r;
    asm("max.bf16x2 %0, %1, %2;" : "=r"(r) : "r"(a), "r"(b));
    return r;
}
__device__ __forceinline__ void ld_tagged(const uint8_t* p, uint32_t& a, uint32_t& ta, uint32_t& b, uint32_t& tb) {
    asm volatile("{\n.reg .b64 x, y;\nld.relaxed.gpu.global.v2.b64 {x, y}, [%4];\nmov.b64 {%0, %1}, x;\nmov.b64 {%2, %3}, y;\n}\n"
                 : "=r"(a), "=r"(ta), "=r"(b), "=r"(tb) : "l"(p) : "memory");
}
__device__ __forceinline__ float bf_lo(uint32_t v) { return __uint_as_float(v << 16); }
__device__ __forceinline__ float bf_hi(uint32_t v) { return __uint_as_float(v & 0xFFFF0000u); }
__device__ __forceinline__ float rcp(float x) { float r; asm("rcp.approx.ftz.f32 %0, %1;" : "=f"(r) : "f"(x)); return r; }
__device__ __forceinline__ float ex2(float x) { float r; asm volatile("ex2.approx.ftz.f32 %0, %1;" : "=f"(r) : "f"(x)); return r; }

__device__ __forceinline__ uint32_t full_bar(int stage) { return base + BAR_FULL + (stage & 7) * 8; }
__device__ __forceinline__ void wait_released(int j) { mbar_wait(base + BAR_EMPTY + (j & 7) * 8, (j >> 3) & 1); }

template <int V>
struct Int { static constexpr int value = V; };

__host__ __device__ constexpr int bslot_e(int i) { return (i < 2 || i >= 14) ? (i + 5) % 7 : (i + 1) % 5; }
__host__ __device__ constexpr int bslot_l(int i) { return i % 6; }

template <uint32_t OFF>
struct Feed {
    int stage;
    uint32_t dst;
    __device__ __forceinline__ void seek(int i, int slot) { stage = i; dst = base + OFF + slot * SLOT; }
    template <int N>
    __device__ __forceinline__ uint32_t acquire() { wait_released(stage - N); return full_bar(stage); }
    template <int N>
    __device__ __forceinline__ void next() {
        stage++;
        dst += SLOT;
        if (dst == base + OFF + N * SLOT) dst = base + OFF;
    }
};
__device__ __forceinline__ int skip_own(int n, int mt) { return n == mt ? 15 : n; }

struct Desc { uint32_t lo, hi; };
__host__ __device__ constexpr Desc desc_const(uint32_t lbo, uint32_t sbo, uint32_t mode) { return {(lbo >> 4) << 16, (sbo >> 4) | (mode << 30)}; }
constexpr Desc D_K128 = desc_const(16, 1024, 1);
constexpr Desc D_N128 = desc_const(8192, 1024, 1);
constexpr Desc D_BLOB = desc_const(128, 256, 0);
constexpr Desc D_OT = desc_const(2048, 128, 0);

enum Kind { XW, XWN, QK, BIG, OUT };

struct Ring {
    int stage;
    uint32_t a, b;
    uint32_t wg;
    uint32_t zero;
    bool releaser;
    __device__ __forceinline__ void seek(int i, int bslot) {
        stage = i;
        a = (base + (i % NA) * SLOT) >> 4;
        b = (base + BRING + bslot * SLOT) >> 4;
    }
    __device__ __forceinline__ void wait() { mbar_wait(full_bar(stage), (stage >> 3) & 1); }
    __device__ __forceinline__ void take_turn() { nb_sync(1 + wg, 256); }
    __device__ __forceinline__ void pin() {
        uint32_t n = 0;
#pragma unroll 1
        do {
            asm volatile("pmevent 7;" ::: "memory");
        } while (n++ < zero);
    }
    __device__ __forceinline__ void mma_begin() {
        pin();
        if (!wg) take_turn();
        pin();
    }
    __device__ __forceinline__ void mma_end() {
        pin();
        if (wg) nb_arrive(3, 256);
        nb_sync(3 - wg, 256);
    }
    template <Kind K, int NBS, bool INIT, int SB = 1, bool TAIL = false, int S0 = 0, int S1 = 4>
    __device__ __forceinline__ void run(float (&d)[56], float (&e)[56], bool first = true, bool last = true, bool more = true) {
        if (first) take_turn();
        asm volatile("wgmma.fence.sync.aligned;" ::: "memory");
        if (K == QK) {
            const uint32_t da = D_K128.lo + (base >> 4) + (stage >> 1) * (SLOT >> 4) + (stage & 1) * 4 + wg * 512, db = D_N128.lo + b;
            wgmma112<0, 1, 1, INIT, D_K128.hi, D_N128.hi>(d, da, db);
            wgmma112<0, 1, 1, INIT, D_K128.hi, D_N128.hi>(e, da, db + 256);
            wgmma112<0, 1, 1, false, D_K128.hi, D_N128.hi>(d, da + 2, db + 128);
            wgmma112<0, 1, 1, false, D_K128.hi, D_N128.hi>(e, da + 2, db + 384);
        } else {
            constexpr int TA = K == OUT, TB = K != XW;
            constexpr uint32_t sa = K == OUT ? 256 : 2, sb = K == XW ? 2 : K == BIG ? 224 : 128;
            constexpr Desc A = K == OUT ? D_OT : D_K128, B = K == XW ? D_K128 : K == BIG ? D_BLOB : D_N128;
            const uint32_t da = A.lo + a + wg * (K == OUT ? 64 : 512), db = B.lo + b;
            if (S0 == 0) wgmma112<TA, TB, SB, INIT, A.hi, B.hi>(d, da, db);
#pragma unroll
            for (int q = S0 ? S0 : 1; q < S1; q++) wgmma112<TA, TB, SB, false, A.hi, B.hi>(d, da + q * sa, db + q * sb);
        }
        asm volatile("wgmma.commit_group.sync.aligned;" ::: "memory");
        if (!TAIL) asm volatile("wgmma.wait_group.sync.aligned 1;" ::: "memory");
        if (last) nb_arrive(2 - wg, 256);
        if (!TAIL && stage > 0) {
            if (releaser) mbar_arrive(base + BAR_EMPTY + ((stage - 1) & 7) * 8);
        }
        stage++;
        a += SLOT >> 4;
        if (a == (base + NA * SLOT) >> 4) a = base >> 4;
        b += SLOT >> 4;
        if (b == (base + BRING + NBS * SLOT) >> 4) b = (base + BRING) >> 4;
        if (more) wait();
    }
    template <Kind K, int NBS, bool INIT, int SB = 1, bool TAIL = false, int S0 = 0, int S1 = 4>
    __device__ __forceinline__ void run(float (&d)[56], bool first = true, bool last = true, bool more = true) {
        run<K, NBS, INIT, SB, TAIL, S0, S1>(d, d, first, last, more);
    }
};

template <int I0 = 0, int I1 = 28>
__device__ __forceinline__ void pack_all(const float (&d)[56], uint32_t (&p)[28]) {
#pragma unroll
    for (int i = I0; i < I1; i++) p[i] = pack2(d[2 * i], d[2 * i + 1]);
}
template <int I0, int I1>
__device__ __forceinline__ void store_frags(uint8_t* dst, const uint32_t (&p)[28]) {
#pragma unroll
    for (int i = I0; i < I1; i++) stg1(dst + i * 128, p[i]);
}
template <int I0, int I1>
__device__ __forceinline__ void stage_frags(uint32_t lane_addr, const uint32_t (&p)[28]) {
#pragma unroll
    for (int i = I0; i < I1; i += 4) stsm4(lane_addr + i * 128, p[i], p[i + 1], p[i + 2], p[i + 3]);
}
template <class F>
__device__ __forceinline__ void store_out(F frag, int lane, uint32_t slab, const CUtensorMap* m, int c0, int c1) {
    const bool swap = lane & 16;
    const uint32_t addr = slab + (lane & 7) * 224 + ((lane >> 3) ^ ((lane >> 2) & 1)) * 16;
#pragma unroll
    for (int h = 0; h < 2; h++) {
#pragma unroll
        for (int c = 0; c < 14; c += 4) {
            const uint32_t t0 = frag(2 * c + h), t1 = frag(2 * c + 2 + h);
            if (c < 12) {
                const uint32_t t2 = frag(2 * c + 4 + h), t3 = frag(2 * c + 6 + h);
                stsm4(addr + h * 1792 + c * 16, swap ? t1 : t0, swap ? t0 : t1, swap ? t3 : t2, swap ? t2 : t3);
            } else {
                asm volatile("stmatrix.sync.aligned.m8n8.x2.shared.b16 [%0], {%1,%2};" ::"r"(addr + h * 1792 + c * 16), "r"(swap ? t1 : t0), "r"(swap ? t0 : t1) : "memory");
            }
        }
        fence_async_smem();
        __syncwarp();
        if (elect()) tma_st2(m, c0, c1 + 8 * h, slab + h * 1792);
    }
    if (elect()) {
        bulk_commit();
        bulk_wait_read();
    }
}
__host__ __device__ constexpr int tile_of(int t) { return 7 * (t >> 2) + 3 * ((t >> 1) & 1) + 2 * (t & 1); }

struct Role {
    bool H;
    int L, mt, ns, id;
    int kind, a0, a1, b3;
};
template <bool BY_SM>
__device__ __forceinline__ Role decode_role() {
    uint32_t sm;
    if (BY_SM) asm volatile("mov.u32 %0, %%smid;" : "=r"(sm));
    else asm volatile("mov.u32 %0, %%ctaid.x;" : "=r"(sm));
    const int tpc = sm >> 1, q2 = ((tpc - 32) * 37) >> 8;
    const int gpc = tpc < 32 ? tpc & 7 : tpc < 60 ? tpc - 31 - 7 * q2 : 0;
    const int pos = tpc < 32 ? tpc >> 3 : tpc < 60 ? q2 + 4 : tpc - 56;
    Role r;
    r.H = sm >= 128;
    const int grp = (GPC_MAP >> (4 * gpc)) & 7;
    r.L = grp & 1;
    r.mt = (grp >> 1) * 4 + (pos >> 1);
    r.ns = (pos & 1) * 2 + (sm & 1);
    r.id = r.H ? sm : grp * 16 + pos * 2 + (sm & 1);
    r.kind = r.H ? 2 : r.L;
    r.a0 = r.L ? (r.mt >> 3) * 448 : 0;
    r.a1 = r.L ? (r.mt & 7) * 128 : r.H ? 120 : r.mt * 64;
    r.b3 = r.H ? 4 + r.ns : r.L ? r.ns : 0;
    return r;
}

__device__ __forceinline__ void first_fill(const Maps& maps, const Role& r, int i) {
    const bool E = r.kind == 0;
    const CUtensorMap* ma = &maps.m[r.kind];
    const uint32_t bar = full_bar(i);
    const int k = (i * 64) >> r.L;
    const bool has_a = !(i & r.L), has_b = i < 7 - r.L;
    const uint32_t dst = base + BRING + (E ? (0x2104365u >> (4 * i)) & 7 : i) * SLOT;
    mbar_expect(bar, (has_a ? SLOT : 0) + (has_b ? (E ? BLOB : SLOT) : 0));
    if (has_a) tma_ld4(base + (i >> r.L) * SLOT, ma, r.a0 + k, r.a1, 0, 0, bar);
    if (has_b) {
        tma_ld4(dst, ma + 3, E ? k : 0, E ? r.ns * 112 : k, 0, r.b3, bar);
        if (!E) tma_ld4(dst + 8192, ma + 3, 64, k, 0, r.b3, bar);
        mbar_arrive(bar);
    }
}
static_assert(bslot_e(0) == 5 && bslot_e(1) == 6 && bslot_e(2) == 3 && bslot_e(3) == 4 && bslot_e(4) == 0 && bslot_e(6) == 2, "");

template <bool BY_SM>
__global__ void __launch_bounds__(384, 1) fused_kernel(Scratch* sc, const __grid_constant__ Maps maps) {
    const unsigned t_open = clk32();
    const int warp = __shfl_sync(0xffffffffu, threadIdx.x >> 5, 0);
    if (warp == 8) {
        if (elect()) {
#pragma unroll
            for (int i = 0; i < LEAD; i++) mbar_init(base + BAR_FULL + i * 8, 2);
            asm volatile("fence.mbarrier_init.release.cluster;" ::: "memory");
            const Role r = decode_role<BY_SM>();
#pragma unroll 1
            for (int i = 0; i < LEAD; i++) {
                first_fill(maps, r, i);
            }
        }
    }
    if (warp == 9) {
        if (elect()) {
#pragma unroll
            for (int i = 0; i < 8; i++) mbar_init(base + BAR_EMPTY + i * 8, 4);
            asm volatile("fence.mbarrier_init.release.cluster;" ::: "memory");
        }
    } else if (warp == 10) {
        if (elect()) {
#pragma unroll
            for (int i = 0; i < 3; i++) mbar_init(base + BAR_RDY + i * 8, i < 2 ? 4 : 8);
#pragma unroll
            for (int i = 0; i < 2; i++) mbar_init(base + BAR_HALO + i * 8, 1);
            asm volatile("fence.mbarrier_init.release.cluster;" ::: "memory");
        }
    } else if (warp == 11) {
        if (elect()) {
#pragma unroll
            for (int i = LEAD; i < 8; i++) mbar_init(base + BAR_FULL + i * 8, 2);
#pragma unroll
            for (int i = 0; i < 3; i++) mbar_init(base + BAR_DEP + i * 8, 1);
#pragma unroll
            for (int i = 0; i < 2; i++) mbar_init(base + BAR_PART + i * 8, 1);
            asm volatile("fence.mbarrier_init.release.cluster;" ::: "memory");
        }
    }
    __syncthreads();

    const Role role = decode_role<BY_SM>();
    int lane = threadIdx.x & 31;
    asm volatile("" : "+r"(lane));
    const bool roleH = role.H;
    const int roleL = role.L, mt = role.mt, ns = role.ns, bid = role.id;
    const int par = mt >> 3, blk = mt & 7, col = ns * 112;

    if (__builtin_expect(warp >= 8, 1)) {
        asm volatile("setmaxnreg.dec.sync.aligned.u32 56;");
#define PROF_FEED_A
#define PROF_FEED_B
        if (__builtin_expect(warp == 8, 1)) {
            if (elect()) {
                PROF(129);
#pragma unroll 1
                for (int i = LEAD; i < 7; i++) {
                    while (clk32() - t_open < i * PACE) {}
                    first_fill(maps, role, i);
                }
                PROF(134);
                Feed<0> f;
                const int row = mt * 128;
                auto c_run = [&](const CUtensorMap* m, int off, int n0, int n1) {
#pragma unroll 1
                    for (int n = n0; n < n1; n++) {
                        const uint32_t bar = f.acquire<NA>();
                        mbar_expect(bar, SLOT);
                        tma_ld2(f.dst, m, (off + skip_own(n, mt)) * 64, row, bar);
                        PROF_FEED_A;
                        f.next<NA>();
                    }
                };
                if (roleH) {
                } else if (!roleL) {
                    f.seek(14, 0);
#pragma unroll 1
                    for (int i = 0; i < 4; i++) {
                        const uint32_t bar = f.acquire<NA>();
                        mbar_expect(bar, SLOT);
                        tma_ld2(f.dst, &maps.m[M_CR + (i >> 1)], ((i & 1) * 16 + mt) * 64, row, bar);
                        mbar_arrive(bar);
                        PROF_FEED_A;
                        f.next<NA>();
                    }
                    c_run(&maps.m[M_CR], 0, 0, 15);
                    c_run(&maps.m[M_CI], 0, 0, NBE);
                    wait_dep(2);
#pragma unroll 1
                    for (int i = 0; i < 7; i++) {
                        const uint32_t bar = f.acquire<NA>();
                        mbar_expect(bar, SLOT);
                        bulk_ld(f.dst, sc->o + (size_t)(mt * 7 + i) * SLOT, SLOT, bar);
                        PROF_FEED_A;
                        f.next<NA>();
                    }
                } else {
#pragma unroll 1
                    for (int i = 4; i < 7; i++) {
                        wait_released(2 * i - 8);
                        mbar_expect(full_bar(2 * i), SLOT);
                        tma_ld4(base + i * SLOT, &maps.m[M_XA], par * 448 + i * 64, blk * 128, 0, 0, full_bar(2 * i));
                    }
                    wait_released(HALO_K_AT);
                    mbar_arrive(base + BAR_DEP + 16);
                    f.seek(21, 0);
                    c_run(&maps.m[M_CR], 16, 0, 15);
                    c_run(&maps.m[M_CI], 16, 0, 15);
                    c_run(&maps.m[M_CI], 0, NBL, 15);
                }
            }
        } else if (warp == 11) {
            if (elect()) {
                Feed<BRING> f;
                auto blob_run = [&](auto nbs, int quarter, int n0, int n1) {
                    constexpr int N = decltype(nbs)::value;
                    const uint8_t* src = sc->ab + (size_t)(quarter * 64 + ns) * BLOB;
#pragma unroll 1
                    for (int n = n0; n < n1; n++) {
                        const uint32_t bar = f.template acquire<N>();
                        mbar_expect(bar, BLOB);
                        bulk_ld(f.dst, src + skip_own(n, mt) * (4 * BLOB), BLOB, bar);
                        PROF_FEED_B;
                        f.template next<N>();
                    }
                };
                auto w_run = [&](auto nbs, const CUtensorMap* m, int slice, bool no_a) {
                    constexpr int N = decltype(nbs)::value;
#pragma unroll 1
                    for (int i = 0; i < 7; i++) {
                        const uint32_t bar = f.template acquire<N>();
                        mbar_expect(bar, SLOT);
                        tma_ld4(f.dst, m, 0, i * 64, 0, slice, bar);
                        tma_ld4(f.dst + 8192, m, 64, i * 64, 0, slice, bar);
                        if (no_a) mbar_arrive(bar);
                        PROF_FEED_B;
                        f.template next<N>();
                    }
                };
                if (roleH) {
                    f.seek(7, 0);
                    w_run(Int<7>(), &maps.m[M_WV], 8 + ns, true);
                } else if (!roleL) {
                    f.seek(7, bslot_e(7));
#pragma unroll 1
                    for (int i = 0; i < 7; i++) {
                        const uint32_t bar = f.acquire<5>();
                        mbar_expect(bar, BLOB);
                        tma_ld2(f.dst, &maps.m[M_WI], i * 64, col, bar);
                        mbar_arrive(bar);
                        PROF_FEED_B;
                        f.next<5>();
                    }
                    f.seek(18, bslot_e(18));
                    wait_dep(0);
                    blob_run(Int<7>(), 0, 0, 15);
                    wait_dep(1);
                    blob_run(Int<7>(), 2, 0, NBE);
                    w_run(Int<7>(), &maps.m[M_WO], ns, false);
                } else {
                    f.seek(6, 0);
#pragma unroll 1
                    for (int i = 6; i < 14; i++) {
                        const uint32_t bar = f.acquire<6>();
                        mbar_expect(bar, SLOT);
                        tma_ld4(f.dst, &maps.m[M_WQK], 0, i * 32, 0, ns, bar);
                        tma_ld4(f.dst + 8192, &maps.m[M_WQK], 64, i * 32, 0, ns, bar);
                        if (i & 1) mbar_arrive(bar);
                        PROF_FEED_B;
                        f.next<6>();
                    }
                    w_run(Int<6>(), &maps.m[M_WV], 8 + ns, true);
                    wait_dep(0);
                    blob_run(Int<6>(), 1, 0, 15);
                    wait_dep(1);
                    blob_run(Int<6>(), 3, 0, 15);
                    blob_run(Int<6>(), 2, NBL, 15);
                }
            }
        } else if (roleH) {
            if (elect()) {
                wait_released(warp == 9 ? 0 : 7);
#pragma unroll 1
                for (int i = 0; i < 7; i++) {
                    if (warp == 9) {
                        asm volatile("cp.async.bulk.prefetch.tensor.2d.L2.global [%0, {%1, %2}];" ::"l"(&maps.m[M_WI]), "r"(i * 64), "r"(col) : "memory");
                    } else {
                        asm volatile("cp.async.bulk.prefetch.tensor.4d.L2.global [%0, {%1, %2, 0, %3}];" ::"l"(&maps.m[M_WO]), "r"(0), "r"(i * 64), "r"(ns) : "memory");
                        asm volatile("cp.async.bulk.prefetch.tensor.4d.L2.global [%0, {%1, %2, 0, %3}];" ::"l"(&maps.m[M_WO]), "r"(64), "r"(i * 64), "r"(ns) : "memory");
                    }
                }
            }
        } else if (warp == 10) {
            if (elect()) {
                unsigned* epoch_ptr = &sc->epoch[(bid * 4 + 2) * 8];
                const unsigned ep = *epoch_ptr + 1;
                sts1(base + TAG, ep);
                asm volatile("prefetch.tensormap [%0];" ::"l"(&maps.m[M_OUTA + roleL]) : "memory");
                await(sc, CNT_A + roleL * 4 + ns, ep * 16);
                mbar_arrive(base + BAR_DEP);
                PROF(150);
                await(sc, CNT_B + ns, ep * 16);
                mbar_arrive(base + BAR_DEP + 8);
                PROF(151);
                if (!roleL) {
                    await(sc, CNT_O + mt, ep * 4);
                    mbar_arrive(base + BAR_DEP + 16);
                } else {
                    await(sc, CNT_P + mt * 4 + ns, ep * 2 - 1);
                    mbar_arrive(base + BAR_PART);
                    PROF(153);
                    await(sc, CNT_P + mt * 4 + ns, ep * 2);
                    mbar_arrive(base + BAR_PART + 8);
                }
                PROF(152);
                *epoch_ptr = ep;
            }
        } else if (!roleL) {
            if (elect()) {
                mbar_wait(base + BAR_RDY, 0);
                PROF(130);
                signal(sc, CNT_A + ns);
                PROF(131);
                mbar_wait(base + BAR_RDY + 8, 0);
                signal(sc, CNT_A + 4 + ns);
                PROF(135);
                mbar_wait(base + BAR_RDY + 16, 0);
                PROF(132);
                signal(sc, CNT_B + ns);
                PROF(133);
            }
        } else {
            unsigned* epoch_ptr = &sc->epoch[(bid * 4 + 1) * 8];
            const unsigned tag = *epoch_ptr + 1;
#pragma unroll 1
            for (int kv = 0; kv < 2; kv++) {
                uint32_t v[16];
#pragma unroll
                for (int i = 0; i < 16; i++) v[i] = 0;
                if (kv) wait_released(HALO_V_AT - 4), wait_released(HALO_V_AT);
                else mbar_wait(base + BAR_DEP + 16, 0);
                if (blk > 0) {
                    const uint8_t* src = sc->halo + (size_t)(((mt - 1) * 4 + ns) * 2 + kv) * 2048 + lane * 16;
#pragma unroll 1
                    for (int n = 0; n < SPIN_LIMIT; n++) {
                        uint32_t stale = 0;
#pragma unroll
                        for (int i = 0; i < 4; i++) ld_tagged(src + i * 512, v[4 * i], v[4 * i + 1], v[4 * i + 2], v[4 * i + 3]);
#pragma unroll
                        for (int i = 0; i < 16; i += 2) stale |= v[i] ^ tag;
                        if (__all_sync(0xffffffffu, !(stale & 1))) break;
                    }
#pragma unroll
                    for (int c = 0; c < 14; c += 2) v[c] = (v[c] & ~1u) | ((v[15] >> c) & 1);
                }
#pragma unroll
                for (int i = 0; i < 14; i++) sts1(base + HALO + kv * (8 * HSLOT) + i * 128 + lane * 4, v[i]);
                warp_arrive(base + BAR_HALO + kv * 8);
                if (lane == 0) PROF(142 + kv);
            }
            if (elect()) {
                mbar_wait(base + BAR_RDY + 16, 0);
                PROF(130);
                signal(sc, CNT_O + mt);
                PROF(131);
                *epoch_ptr = tag;
            }
        }
    } else {
        asm volatile("setmaxnreg.inc.sync.aligned.u32 224;");
        Ring r;
        r.wg = warp >> 2;
        r.zero = blockIdx.y;
        r.releaser = lane + 1 == (warp >> 2);
        const int wg = warp >> 2;
        if (wg) nb_arrive(1, 256);
        uint8_t* part = sc->part + (size_t)(ns * 16 + mt) * (2 * BLOB) + warp * 512 + lane * 16;
        uint32_t p[28];

        if (roleH) {
            unsigned* epoch_ptr = &sc->epoch[bid * 4 * 8];
            const unsigned tag = *epoch_ptr + 1;
            uint8_t* hout = sc->halo + (size_t)((warp * 8 + ns) * 2) * 2048 + lane * 16;
            auto send = [&](int kv) {
#pragma unroll
                for (int h = 0; h < 2; h++) {
                    uint32_t v[16];
                    v[14] = v[15] = 0;
#pragma unroll
                    for (int c = 0; c < 14; c++) v[c] = p[2 * c + h];
#pragma unroll
                    for (int c = 0; c < 14; c += 2) v[15] |= (v[c] & 1) << c;
#pragma unroll
                    for (int i = 0; i < 4; i++) st_part(hout + (h * 8 + kv) * 2048 + i * 512, v + 4 * i, tag & 1);
                }
            };
            float x0[56], x1[56];
            r.seek(0, 0);
            r.wait();
            r.run<XWN, 7, true>(x0);
#pragma unroll 1
            for (int i = 1; i < 7; i++) r.run<XWN, 7, false>(x0);
            r.run<XWN, 7, true>(x1);
            acc_fence(x0);
            pack_all(x0, p);
            send(0);
#pragma unroll 1
            for (int i = 1; i < 7; i++) r.run<XWN, 7, false>(x1, true, i < 6 || !wg, i < 6);
            asm volatile("wgmma.wait_group.sync.aligned 0;" ::: "memory");
            acc_fence(x1);
            pack_all(x1, p);
#pragma unroll
            for (int i = 0; i < 28; i++) p[i] = movm(p[i]);
            send(1);
            if (threadIdx.x == 0) *epoch_ptr = tag;
        } else if (!roleL) {
            uint8_t* blob = sc->ab + (size_t)((wg * 16 + mt) * 4 + ns) * BLOB + (warp & 3) * WSLOT + lane * 4;
            const uint32_t own = base + BRING + wg * SLOT + (warp & 3) * WSLOT + lane * 16;
            float x0[56], x1[56];
            r.seek(0, bslot_e(0));
            r.wait();
            r.run<XW, 7, true>(x0);
            r.run<XW, 7, false>(x0);
            r.seek(2, bslot_e(2));
#pragma unroll 1
            for (int i = 2; i < 7; i++) r.run<XW, 5, false>(x0);

            r.seek(7, bslot_e(7));
            r.run<XW, 5, true, -1>(x1);
            acc_fence(x0);
            pack_all<0, LAZY ? 14 : 28>(x0, p);
#pragma unroll
            for (int i = 0; i < 2; i++) {
                if (wg == i) store_frags<0, 14>(blob, p);
                else stage_frags<0, A_OWN>(own + 5 * SLOT, p);
                r.run<XW, 5, false, -1>(x1);
                if (LAZY && i == 0) pack_all<14, 28>(x0, p);
                if (wg == i) {
                    store_frags<14, 28>(blob, p);
                    warp_arrive(base + BAR_RDY + i * 8);
                } else {
                    stage_frags<A_OWN, 2 * A_OWN>(own + 5 * SLOT, p);
                }
                r.run<XW, 5, false, -1>(x1);
            }
            stage_frags<2 * A_OWN, A_OWN2>(own + 5 * SLOT, p);
            r.run<XW, 5, false, -1>(x1);
            stage_frags<A_OWN2, 28>(own + 5 * SLOT, p);
            fence_async_smem();
            r.run<XW, 5, false, -1>(x1);

            r.seek(14, bslot_e(14));
            r.run<BIG, 7, true>(x0);
            acc_fence(x1);
            pack_all(x1, p);
            stage_frags<0, 28>(own, p);
            r.run<BIG, 7, false>(x0);
            fence_async_smem();
            blob += (size_t)128 * BLOB;
#pragma unroll
            for (int i = 0; i < 28; i++) {
                if (i % B_SLICE == 0) r.run<BIG, 7, false>(x0);
                stg1(blob + i * 128, p[i]);
            }
            warp_arrive(base + BAR_RDY + 16);
#pragma unroll 1
            for (int i = 17 + 27 / B_SLICE; i < 33 + NBL; i++) r.run<BIG, 7, false>(x0);
            if (E_STEPS) {
                r.seek(POUT - 1, bslot_e(POUT - 1));
                r.run<BIG, 7, false, 1, false, 0, E_STEPS>(x0);
            }

            const uint32_t tag = lds1(base + TAG);
            r.seek(POUT, bslot_e(POUT));
            r.run<OUT, 7, true>(x1);
            acc_fence(x0);
            pack_all(x0, p);
#pragma unroll
            for (int k = 0; k < 3; k++) {
                if (k < 2 && wg == k) {
                    if ((warp & 3) == 0 && elect())
                        asm volatile("red.relaxed.gpu.global.add.u32 [%0], 1;" ::"l"(&sc->cnt[(CNT_P + mt * 4 + ns) * 32]) : "memory");
#pragma unroll
                    for (int i = 0; i < P_FIRST; i++) st_part(part + i * 4096, p + 4 * i, tag & 1);
                }
                if (k > 0 && wg == k - 1) {
#pragma unroll
                    for (int i = P_FIRST; i < 7; i++) st_part(part + i * 4096, p + 4 * i, tag & 1);
                }
                if (k < 2) r.run<OUT, 7, false>(x1);
            }
#pragma unroll
            for (int i = 3; i < 7; i++) r.run<OUT, 7, false, 1, true>(x1, i <= 7 - TURN, i < 7 - TURN || (i == 6 && !wg), i < 6);

            asm volatile("wgmma.wait_group.sync.aligned 0;" ::: "memory");
            acc_fence(x1);
            const uint32_t slab = base + (wg ? BRING + bslot_e(ELAST - 6) * SLOT : ((ELAST - 6) % NA) * SLOT) + (warp & 3) * WSLOT;
            store_out([&](int i) { return pack2(x1[2 * i], x1[2 * i + 1]); }, lane, slab, &maps.m[M_OUTA], par * 896 + col, blk * 128 + warp * 16);
        } else {
            const int g = lane >> 2, tig = lane & 3;
            const uint32_t hin = base + HALO + warp * HSLOT + lane * 4;
            const uint32_t hpub = warp < 7 ? hin + HSLOT : base + HSPARE + lane * 4;
            auto publish = [&](const uint32_t (&h)[14], int c0, int c1) {
#pragma unroll
                for (int c = 0; c < 14; c++)
                    if (c >= c0 && c < c1) sts1(hpub + c * 128, h[c]);
            };
            float y0[56], y1[56], y2[56];
            r.seek(0, 0);
            r.wait();
            r.run<QK, 6, true>(y0, y1);
#pragma unroll 1
            for (int i = 1; i < 14; i++) r.run<QK, 6, false>(y0, y1);

            uint32_t m1[8][4], m0[8][4], lo[14], hi[14], q[2][8][2];
            auto pack_q = [&](int b) {
                uint32_t v[14];
#pragma unroll
                for (int c = 0; c < 14; c++) v[c] = pack2(y0[4 * c + 2 * b], y0[4 * c + 2 * b + 1]);
#pragma unroll
                for (int t = 0; t < 8; t++) {
                    const int c = tile_of(t);
                    q[b][t][0] = (t & 3) == 2 ? (tig >= 2 ? v[c] : 0u) : v[c];
                    q[b][t][1] = (t & 3) == 1 ? (tig < 2 ? v[c + 1] : 0u) : v[c + 1];
                }
            };
            auto fetch = [&](uint32_t src, int hp, int i0) {
#pragma unroll
                for (int t = 4 * hp; t < 4 * hp + 4; t++) {
                    m0[t][i0] = (t & 3) == 2 ? dup(m0[t - 1][3], r.zero) : lds1(src + tile_of(t) * 128);
                    m0[t][3] = lds1(src + tile_of(t) * 128 + 128);
                }
            };
            r.seek(14, bslot_l(14));
            r.run<XWN, 6, true>(y2);
            acc_fence(y0);
            acc_fence(y1);
#pragma unroll
            for (int c = 0; c < 14; c++) hi[c] = pack2(y1[4 * c + 2], y1[4 * c + 3]);
            publish(hi, 0, 7);
            r.run<XWN, 6, false>(y2);
            publish(hi, 7, 14);
#pragma unroll
            for (int c = 0; c < 14; c++) lo[c] = pack2(y1[4 * c], y1[4 * c + 1]);
#pragma unroll
            for (int t = 0; t < 8; t++) {
                const int c = tile_of(t);
                const bool shared = (t & 3) == 2;
                m1[t][0] = shared ? dup(lo[c], r.zero) : lo[c];
                m1[t][1] = shared ? dup(hi[c], r.zero) : hi[c];
                m1[t][2] = lo[c + 1];
                m1[t][3] = hi[c + 1];
                m0[t][0] = dup(m1[t][0], r.zero);
                m0[t][2] = dup(lo[c + 1], 2 * r.zero);
            }
            r.run<XWN, 6, false>(y2);
            if (warp == 0) mbar_wait(base + BAR_HALO, 0);
            fetch(hin, 0, 1);
            pack_q(1);
            r.run<XWN, 6, false>(y2);
            fetch(hin, 1, 1);
            pack_q(0);
            r.mma_begin();
            float s[8][4];
#pragma unroll
            for (int step = 0; step < 2; step++) {
#pragma unroll
                for (int i = 0; i < 8; i++) {
                    const int b = 1 - (i >> 2), h = i & 3, t = 2 * h + step;
                    float (&d)[4] = s[2 * h + b];
                    if (step == 0) d[0] = d[1] = d[2] = d[3] = 0.f;
                    mma16816(d, b ? m1[t] : m0[t], q[b][t][0], q[b][t][1]);
                }
            }
            r.mma_end();
            r.run<XWN, 6, false>(y2, false);

            uint32_t pr[8], mx[4], mx1[4];
            {
                const bool cur0 = g <= 2 * tig, cur1 = g <= 2 * tig + 1;
#pragma unroll
                for (int i = 0; i < 8; i++) {
                    const int c = (i & 1) ? 2 : 0;
                    pr[i] = movm(pack2(cur0 ? s[i][c] : s[i][2 - c], cur1 ? s[i][c + 1] : s[i][3 - c]));
                }
            }
            r.run<XWN, 6, false>(y2);
            const uint32_t curmask = (2 * tig <= g ? 0x0000FFFFu : 0u) | (2 * tig + 1 <= g ? 0xFFFF0000u : 0u);
            {
                const uint32_t keep = (blk == 0 && warp == 0) ? curmask : 0xFFFFFFFFu;
#pragma unroll
                for (int i = 0; i < 4; i++) {
                    pr[2 * i] = (pr[2 * i] & keep) | (0xCF9ECF9Eu & ~keep);
                    mx[i] = max2(__byte_perm(pr[2 * i], pr[2 * i + 1], 0x5410), __byte_perm(pr[2 * i], pr[2 * i + 1], 0x7632));
                    mx1[i] = __shfl_xor_sync(0xffffffffu, mx[i], 1);
                }
            }
#pragma unroll
            for (int i = 0; i < 4; i++) {
                mx[i] = max2(mx[i], mx1[i]);
                mx1[i] = __shfl_xor_sync(0xffffffffu, mx[i], 2);
            }
            r.run<XWN, 6, false>(y2);
            constexpr float SCL = 0.18898223650461362f * 1.4426950408889634f;
            float e0[8], e1[8], sm[8], sm1[8];
#pragma unroll
            for (int i = 0; i < 8; i++) {
                const uint32_t m2 = max2(mx[i >> 1], mx1[i >> 1]);
                sm[i] = ((i & 1) ? bf_hi(m2) : bf_lo(m2)) * -SCL;
                e0[i] = ex2(fmaf(bf_lo(pr[i]), SCL, sm[i]));
            }

            r.seek(21, bslot_l(21));
            r.run<BIG, 6, true>(y0);
            acc_fence(y2);
#pragma unroll
            for (int c = 0; c < 7; c++) hi[c] = movm(pack2(y2[4 * c + 2], y2[4 * c + 3]));
#pragma unroll
            for (int i = 0; i < 8; i++) e1[i] = ex2(fmaf(bf_hi(pr[i]), SCL, sm[i]));
            r.run<BIG, 6, false>(y0);
            publish(hi, 0, 7);
#pragma unroll
            for (int c = 7; c < 14; c++) hi[c] = movm(pack2(y2[4 * c + 2], y2[4 * c + 3]));
            r.run<BIG, 6, false>(y0);
            publish(hi, 7, 14);
#pragma unroll
            for (int i = 0; i < 8; i++) {
                sm[i] = e0[i] + e1[i];
                sm1[i] = __shfl_xor_sync(0xffffffffu, sm[i], 1);
            }
            r.run<BIG, 6, false>(y0);
#pragma unroll
            for (int c = 0; c < 14; c++) lo[c] = movm(pack2(y2[4 * c], y2[4 * c + 1]));
            r.run<BIG, 6, false>(y0);
#pragma unroll
            for (int i = 0; i < 8; i++) {
                sm[i] += sm1[i];
                sm1[i] = __shfl_xor_sync(0xffffffffu, sm[i], 2);
            }
#pragma unroll
            for (int t = 0; t < 8; t++) {
                const int c = tile_of(t);
                const bool shared = (t & 3) == 2;
                m1[t][0] = shared ? dup(lo[c], r.zero) : lo[c];
                m1[t][1] = lo[c + 1];
                m1[t][2] = shared ? dup(hi[c], r.zero) : hi[c];
                m1[t][3] = hi[c + 1];
                m0[t][0] = dup(m1[t][0], r.zero);
                m0[t][1] = dup(lo[c + 1], 2 * r.zero);
            }
            r.run<BIG, 6, false>(y0);
            if (warp == 0) mbar_wait(base + BAR_HALO + 8, 0);
            const uint32_t vin = warp ? hin : hin + 8 * HSLOT;
            fetch(vin, 0, 2);
#pragma unroll
            for (int i = 0; i < 8; i++) {
                const float inv = rcp(sm[i] + sm1[i]);
                pr[i] = pack2(e0[i] * inv, e1[i] * inv);
            }
            r.run<BIG, 6, false>(y0);
            fetch(vin, 1, 2);
            uint32_t pb[8][2];
#pragma unroll
            for (int t = 0; t < 8; t++) {
                pb[t][t & 1] = band(pr[t], curmask);
                pb[t][1 - (t & 1)] = band(pr[t], ~curmask);
            }
            r.mma_begin();
            float o[2][8][4];
#pragma unroll
            for (int i = 0; i < 16; i++) {
                const int b = 1 - (i >> 3), t = i & 7;
                float (&d)[4] = o[b][t];
                d[0] = d[1] = d[2] = d[3] = 0.f;
                mma16816(d, b ? m1[t] : m0[t], pb[(t & 6) + b][0], pb[(t & 6) + b][1]);
            }
            r.mma_end();
            r.run<BIG, 6, false>(y0, false);
            uint8_t* odst = sc->o + (size_t)mt * 7 * SLOT + ns * (14 * 2048) + warp * 256 + lane * 4;
#pragma unroll
            for (int hp = 0; hp < 2; hp++) {
#pragma unroll
                for (int b = 0; b < 2; b++) {
                    const float (&u)[8][4] = o[b];
                    const int t = 4 * hp;
                    uint32_t* w = p + 14 * hp + b;
                    w[0] = pack2(u[t][0], u[t][1]);
                    w[2] = pack2(u[t][2], u[t][3]);
                    w[4] = pack2(u[t + 1][0], u[t + 1][1]);
                    w[6] = pack2(g < 4 ? u[t + 1][2] : u[t + 2][0], g < 4 ? u[t + 1][3] : u[t + 2][1]);
                    w[8] = pack2(u[t + 2][2], u[t + 2][3]);
                    w[10] = pack2(u[t + 3][0], u[t + 3][1]);
                    w[12] = pack2(u[t + 3][2], u[t + 3][3]);
                }
            }
#pragma unroll
            for (int i = 0; i < 28; i++) {
                if (i >= O_FIRST && (i - O_FIRST) % O_SLICE == 0) r.run<BIG, 6, false>(y0);
                stg1(odst + (i >> 1) * 2048 + (i & 1) * 128, p[i]);
            }
            warp_arrive(base + BAR_RDY + 16);

#pragma unroll 1
            for (int i = 30 + (27 - O_FIRST) / O_SLICE; i <= LLAST + 1 - TURN; i++) r.run<BIG, 6, false>(y0, true, i <= LLAST - TURN);
            const uint32_t tag = lds1(base + TAG);
            if (mbar_test(base + BAR_PART + wg * 8, 0)) {
#pragma unroll
                for (int i = 0; i < 7; i++) ld_tagged(part + i * 4096, p[4 * i], p[4 * i + 1], p[4 * i + 2], p[4 * i + 3]);
            } else {
                p[0] = ~tag;
            }
            r.seek(LLAST + 2 - TURN, bslot_l(LLAST + 2 - TURN));
#pragma unroll
            for (int i = 1; i < TURN; i++) {
                if (LLAST + 1 - TURN + i == 51) r.run<BIG, 6, false, 1, true, E_STEPS>(y0, false, i == TURN - 1 && !wg, i < TURN - 1);
                else r.run<BIG, 6, false, 1, true>(y0, false, i == TURN - 1 && !wg, i < TURN - 1);
            }
#pragma unroll 1
            for (int n = 0; n < SPIN_LIMIT; n++) {
                uint32_t stale = 0;
#pragma unroll
                for (int i = 0; i < 28; i += 2) stale |= p[i] ^ tag;
                if (__all_sync(0xffffffffu, !(stale & 1))) break;
                mbar_wait(base + BAR_PART + wg * 8, 0);
#pragma unroll
                for (int i = 0; i < 7; i++) ld_tagged(part + i * 4096, p[4 * i], p[4 * i + 1], p[4 * i + 2], p[4 * i + 3]);
            }
            asm volatile("wgmma.wait_group.sync.aligned 0;" ::: "memory");
            acc_fence(y0);
            const uint32_t slab = base + (wg ? HALO : ((LLAST - 6) % NA) * SLOT) + (warp & 3) * WSLOT;
            store_out([&](int i) { return add2(pack2(y0[2 * i], y0[2 * i + 1]), p[i]); }, lane, slab, &maps.m[M_OUTB], 448 + col, mt * 128 + warp * 16);
        }
    }
}

typedef CUresult (*EncodeFn)(CUtensorMap*, CUtensorMapDataType, cuuint32_t, void*, const cuuint64_t*, const cuuint64_t*,
                             const cuuint32_t*, const cuuint32_t*, CUtensorMapInterleave, CUtensorMapSwizzle,
                             CUtensorMapL2promotion, CUtensorMapFloatOOBfill);

struct Dim { uint64_t size, stride; uint32_t box; };
void encode(EncodeFn fn, CUtensorMap* m, const void* ptr, CUtensorMapSwizzle sw, Dim d0, Dim d1, Dim d2 = {0, 0, 0}, Dim d3 = {0, 0, 0}) {
    const cuuint64_t dims[4] = {d0.size, d1.size, d2.size, d3.size};
    const cuuint64_t strides[3] = {d1.stride, d2.stride, d3.stride};
    const cuuint32_t box[4] = {d0.box, d1.box, d2.box, d3.box};
    const cuuint32_t es[4] = {1, 1, 1, 1};
    fn(m, CU_TENSOR_MAP_DATA_TYPE_BFLOAT16, d3.size ? 4 : d2.size ? 3 : 2, const_cast<void*>(ptr), dims, strides, box, es,
       CU_TENSOR_MAP_INTERLEAVE_NONE, sw, CU_TENSOR_MAP_L2_PROMOTION_L2_128B, CU_TENSOR_MAP_FLOAT_OOB_FILL_NONE);
}

}

extern "C" void kernel_launch(void* const* d_in, const int* in_sizes, int n_in, void* d_out, int out_size) {
    (void)in_sizes; (void)n_in; (void)out_size;
    void* fnp = nullptr;
    cudaDriverEntryPointQueryResult st;
    cudaGetDriverEntryPoint("cuTensorMapEncodeTiled", &fnp, cudaEnableDefault, &st);
    EncodeFn fn = (EncodeFn)fnp;
    void* scratch = nullptr;
    cudaGetSymbolAddress(&scratch, g_scratch);
    int dev = 0, sms = 0;
    cudaGetDevice(&dev);
    cudaDeviceGetAttribute(&sms, cudaDevAttrMultiProcessorCount, dev);
    auto kernel = sms == 132 ? fused_kernel<true> : fused_kernel<false>;
    cudaFuncSetAttribute(kernel, cudaFuncAttributeMaxDynamicSharedMemorySize, SMEM_BYTES);

    const CUtensorMapSwizzle S128 = CU_TENSOR_MAP_SWIZZLE_128B, S0 = CU_TENSOR_MAP_SWIZZLE_NONE;
    const Dim one = {1, 16, 1};
    Maps maps;
    encode(fn, &maps.m[M_XA], d_in[0], S128, {896, 2, 64}, {1024, 1792, 128}, one, one);
    encode(fn, &maps.m[M_WQK], d_in[1], S128, {112, 2, 64}, {448, 2688, 32}, {3, 896, 2}, {4, 224, 1});
    encode(fn, &maps.m[M_WV], d_in[1], S128, {112, 2, 64}, {448, 2688, 64}, one, {12, 224, 1});
    encode(fn, &maps.m[M_XH], d_in[0], S128, {448, 2, 64}, {128, 1792, 8}, {8, 128 * 1792, 8}, {2, 896, 2});
    encode(fn, &maps.m[M_WO], d_in[2], S128, {112, 2, 64}, {448, 896, 64}, one, {4, 224, 1});
    encode(fn, &maps.m[M_XB], d_in[3], S128, {448, 2, 64}, {1024, 896, 64}, {2, 896 * 1024, 2}, one);
    encode(fn, &maps.m[M_CR], d_in[4], S128, {2048, 2, 64}, {2048, 4096, 128});
    encode(fn, &maps.m[M_CI], d_in[5], S128, {2048, 2, 64}, {2048, 4096, 128});
    encode(fn, &maps.m[M_WR], d_in[6], S128, {448, 2, 64}, {448, 896, 112}, one, one);
    encode(fn, &maps.m[M_WI], d_in[7], S128, {448, 2, 64}, {448, 896, 112});
    encode(fn, &maps.m[M_OUTA], d_out, S0, {1792, 2, 112}, {1024, 3584, 8});
    encode(fn, &maps.m[M_OUTB], d_out, S0, {896, 2, 112}, {2048, 1792, 8});

    kernel<<<132, 384, SMEM_BYTES>>>((Scratch*)scratch, maps);
}
```

```cpp
#include <cuda.h>
#include <cuda_bf16.h>
#include <cuda_runtime.h>
#include <stdint.h>

namespace {

constexpr uint32_t SLOT = 16384;
constexpr int NA = 7;
constexpr uint32_t BRING = NA * SLOT;
constexpr uint32_t HALO = BRING + 6 * SLOT;
constexpr uint32_t HSLOT = 1792;
constexpr uint32_t WSLOT = 3584;
constexpr uint32_t BLOB = 14336;
constexpr uint32_t BARS = 14 * SLOT;
constexpr uint32_t BAR_FULL = BARS;
constexpr uint32_t BAR_EMPTY = BARS + 64;
constexpr uint32_t BAR_RDY = BARS + 128;
constexpr uint32_t BAR_DEP = BARS + 168;
constexpr uint32_t BAR_HALO = BARS + 192;
constexpr uint32_t BAR_PART = BARS + 208;
constexpr uint32_t TAG = BARS + 224;
constexpr uint32_t HSPARE = BARS + 256 + 1024;
constexpr uint32_t SMEM_BYTES = HSPARE + HSLOT;
constexpr uint32_t base = 1024;
constexpr int SPIN_LIMIT = 1 << 16;

#define E_EXTRA 0
#define HALO_K_AT 10
#define HALO_V_AT 19
#define O_SLICE 4
#define B_SLICE 4
#define LEAD 3
#define TURN 4
#define PACE 450
#define O_FIRST 8
#define LAZY 1
#define P_FIRST 2
#define MMA_SYNC 2
#define A_OWN 4
#define A_OWN2 20
#define E_STEPS 0
#define HINT_AT 2
#define GPC_MAP 0x64752310u

constexpr int NBL = 13 + E_EXTRA;
constexpr int NBE = NBL + (E_STEPS > 0);
constexpr int POUT = 33 + NBE;
constexpr int ELAST = POUT + 6;
constexpr int LLAST = 52 - E_EXTRA;
constexpr uint32_t LSLAB = ((LLAST - 6) % NA) * SLOT;
static_assert(TURN <= 4, "the output is staged in the slots of the seventh-last stage");

enum { M_XB, M_XA, M_XH, M_WR, M_WQK, M_WV, M_WO, M_WI, M_CR, M_CI, M_OUTA, M_OUTB, M_COUNT };
struct __align__(64) Maps { CUtensorMap m[M_COUNT]; };

constexpr int CNT_A = 0;
constexpr int CNT_B = 8;
constexpr int CNT_O = 16;
constexpr int CNT_P = 32;
constexpr int CNT_COUNT = 96;

struct Scratch {
    uint8_t ab[64 * 4 * BLOB];
    uint8_t o[16 * 7 * SLOT];
    uint8_t part[64 * 2 * BLOB];
    uint8_t halo[64 * 2 * 2048];
    unsigned cnt[CNT_COUNT * 32];
    unsigned epoch[132 * 4 * 8];
};
__device__ __align__(1024) Scratch g_scratch;

__device__ __forceinline__ unsigned clk32() { unsigned c; asm volatile("mov.u32 %0, %%clock;" : "=r"(c)); return c; }

#define PROF(idx)

__device__ __forceinline__ void mbar_init(uint32_t bar, uint32_t cnt) {
    asm volatile("mbarrier.init.shared::cta.b64 [%0], %1;" ::"r"(bar), "r"(cnt) : "memory");
}
__device__ __forceinline__ void mbar_expect(uint32_t bar, uint32_t bytes) {
    asm volatile("mbarrier.arrive.expect_tx.shared::cta.b64 _, [%0], %1;" ::"r"(bar), "r"(bytes) : "memory");
}
__device__ __forceinline__ void mbar_arrive(uint32_t bar) {
    asm volatile("mbarrier.arrive.shared::cta.b64 _, [%0];" ::"r"(bar) : "memory");
}
__device__ __forceinline__ bool mbar_try(uint32_t bar, uint32_t parity) {
    uint32_t ok;
    asm volatile("{\n.reg .pred p;\nmbarrier.try_wait.parity.shared::cta.b64 p, [%1], %2;\nselp.u32 %0, 1, 0, p;\n}\n"
                 : "=r"(ok) : "r"(bar), "r"(parity) : "memory");
    return ok;
}
__device__ __forceinline__ void mbar_wait(uint32_t bar, uint32_t parity) {
#pragma unroll 1
    for (int n = 0; n < SPIN_LIMIT; n++)
        if (mbar_try(bar, parity)) break;
}
__device__ __forceinline__ bool elect() {
    uint32_t p;
    asm volatile("{\n.reg .pred p;\nelect.sync _|p, 0xffffffff;\nselp.u32 %0, 1, 0, p;\n}\n" : "=r"(p));
    return p;
}
__device__ __forceinline__ void nb_sync(int id, int n) { asm volatile("bar.sync %0, %1;" ::"r"(id), "r"(n) : "memory"); }
__device__ __forceinline__ void nb_arrive(int id, int n) { asm volatile("bar.arrive %0, %1;" ::"r"(id), "r"(n) : "memory"); }
__device__ __forceinline__ void warp_arrive(uint32_t bar) {
    __syncwarp();
    if (elect()) mbar_arrive(bar);
}
__device__ __forceinline__ uint32_t band(uint32_t x, uint32_t m) {
    uint32_t r;
    asm volatile("and.b32 %0, %1, %2;" : "=r"(r) : "r"(x), "r"(m));
    return r;
}
__device__ __forceinline__ uint32_t dup(uint32_t x, uint32_t zero) {
    uint32_t r;
    asm volatile("xor.b32 %0, %1, %2;" : "=r"(r) : "r"(x), "r"(zero));
    return r;
}

__device__ __forceinline__ void tma_ld2(uint32_t dst, const CUtensorMap* m, int c0, int c1, uint32_t bar) {
    asm volatile("cp.async.bulk.tensor.2d.shared::cluster.global.mbarrier::complete_tx::bytes [%0], [%1, {%3, %4}], [%2];"
                 ::"r"(dst), "l"(m), "r"(bar), "r"(c0), "r"(c1) : "memory");
}
__device__ __forceinline__ void tma_ld4(uint32_t dst, const CUtensorMap* m, int c0, int c1, int c2, int c3, uint32_t bar) {
    asm volatile("cp.async.bulk.tensor.4d.shared::cluster.global.mbarrier::complete_tx::bytes [%0], [%1, {%3, %4, %5, %6}], [%2];"
                 ::"r"(dst), "l"(m), "r"(bar), "r"(c0), "r"(c1), "r"(c2), "r"(c3) : "memory");
}
__device__ __forceinline__ void bulk_ld(uint32_t dst, const void* src, uint32_t bytes, uint32_t bar) {
    asm volatile("cp.async.bulk.shared::cluster.global.mbarrier::complete_tx::bytes [%0], [%1], %2, [%3];"
                 ::"r"(dst), "l"(src), "r"(bytes), "r"(bar) : "memory");
}
__device__ __forceinline__ void tma_st2(const CUtensorMap* m, int c0, int c1, uint32_t src) {
    asm volatile("cp.async.bulk.tensor.2d.global.shared::cta.bulk_group [%0, {%1, %2}], [%3];"
                 ::"l"(m), "r"(c0), "r"(c1), "r"(src) : "memory");
}
__device__ __forceinline__ void bulk_commit() { asm volatile("cp.async.bulk.commit_group;" ::: "memory"); }
__device__ __forceinline__ void bulk_wait_read() { asm volatile("cp.async.bulk.wait_group.read 0;" ::: "memory"); }
__device__ __forceinline__ void fence_async_smem() { asm volatile("fence.proxy.async.shared::cta;" ::: "memory"); }
__device__ __forceinline__ void fence_async_global() { asm volatile("fence.proxy.async.global;" ::: "memory"); }

__device__ __forceinline__ void signal(Scratch* sc, int idx) {
    asm volatile("fence.proxy.async;\nred.relaxed.gpu.global.add.u32 [%0], 1;" ::"l"(&sc->cnt[idx * 32]) : "memory");
}
__device__ __forceinline__ unsigned peek(const unsigned* p) {
    unsigned v;
    asm volatile("ld.relaxed.gpu.global.u32 %0, [%1];" : "=r"(v) : "l"(p) : "memory");
    return v;
}
__device__ __forceinline__ void await(Scratch* sc, int idx, unsigned target) {
    const unsigned* p = &sc->cnt[idx * 32];
#pragma unroll 1
    for (int n = 0; n < SPIN_LIMIT; n++)
        if ((int)(peek(p) - target) >= 0) break;
    asm volatile("fence.acquire.gpu;" ::: "memory");
}
__device__ __forceinline__ void wait_dep(int k) {
    mbar_wait(base + BAR_DEP + k * 8, 0);
    fence_async_global();
}

#define WG_REGS                                                                                                     \
    "{%0,%1,%2,%3,%4,%5,%6,%7,%8,%9,%10,%11,%12,%13,%14,%15,%16,%17,%18,%19,%20,%21,%22,%23,%24,%25,%26,%27,"       \
    "%28,%29,%30,%31,%32,%33,%34,%35,%36,%37,%38,%39,%40,%41,%42,%43,%44,%45,%46,%47,%48,%49,%50,%51,%52,%53,%54,%55}"
#define WG_OPS(C)                                                                                                   \
    C(d[0]), C(d[1]), C(d[2]), C(d[3]), C(d[4]), C(d[5]), C(d[6]), C(d[7]), C(d[8]), C(d[9]), C(d[10]), C(d[11]),   \
    C(d[12]), C(d[13]), C(d[14]), C(d[15]), C(d[16]), C(d[17]), C(d[18]), C(d[19]), C(d[20]), C(d[21]), C(d[22]),   \
    C(d[23]), C(d[24]), C(d[25]), C(d[26]), C(d[27]), C(d[28]), C(d[29]), C(d[30]), C(d[31]), C(d[32]), C(d[33]),   \
    C(d[34]), C(d[35]), C(d[36]), C(d[37]), C(d[38]), C(d[39]), C(d[40]), C(d[41]), C(d[42]), C(d[43]), C(d[44]),   \
    C(d[45]), C(d[46]), C(d[47]), C(d[48]), C(d[49]), C(d[50]), C(d[51]), C(d[52]), C(d[53]), C(d[54]), C(d[55])

template <int TA, int TB, int SB, bool INIT, uint32_t AH, uint32_t BH>
__device__ __forceinline__ void wgmma112(float (&d)[56], uint32_t alo, uint32_t blo) {
    if (INIT) {
        asm volatile("{\n.reg .pred p;\n.reg .b64 da, db;\nsetp.ne.b32 p, 0, 0;\nmov.b64 da, {%56, %61};\nmov.b64 db, {%57, %62};\n"
                     "wgmma.mma_async.sync.aligned.m64n112k16.f32.bf16.bf16 " WG_REGS ", da, db, p, 1, %59, %60, %58;\n}\n"
                     : WG_OPS("=f") : "r"(alo), "r"(blo), "n"(TB), "n"(SB), "n"(TA), "n"(AH), "n"(BH));
    } else {
        asm volatile("{\n.reg .pred p;\n.reg .b64 da, db;\nsetp.ne.b32 p, 1, 0;\nmov.b64 da, {%56, %61};\nmov.b64 db, {%57, %62};\n"
                     "wgmma.mma_async.sync.aligned.m64n112k16.f32.bf16.bf16 " WG_REGS ", da, db, p, 1, %59, %60, %58;\n}\n"
                     : WG_OPS("+f") : "r"(alo), "r"(blo), "n"(TB), "n"(SB), "n"(TA), "n"(AH), "n"(BH));
    }
}
__device__ __forceinline__ void acc_fence(float (&d)[56]) {
#pragma unroll
    for (int i = 0; i < 56; i++) asm volatile("" : "+f"(d[i])::"memory");
}

__device__ __forceinline__ uint32_t pack2(float lo, float hi) {
    uint32_t r;
    asm volatile("cvt.rn.bf16x2.f32 %0, %1, %2;" : "=r"(r) : "f"(hi), "f"(lo));
    return r;
}
__device__ __forceinline__ uint32_t movm(uint32_t a) {
    uint32_t r;
    asm volatile("movmatrix.sync.aligned.m8n8.trans.b16 %0, %1;" : "=r"(r) : "r"(a));
    return r;
}
__device__ __forceinline__ void stsm4(uint32_t addr, uint32_t a, uint32_t b, uint32_t c, uint32_t d) {
    asm volatile("stmatrix.sync.aligned.m8n8.x4.shared.b16 [%0], {%1,%2,%3,%4};" ::"r"(addr), "r"(a), "r"(b), "r"(c), "r"(d) : "memory");
}
__device__ __forceinline__ void sts1(uint32_t addr, uint32_t a) { asm volatile("st.shared.b32 [%0], %1;" ::"r"(addr), "r"(a) : "memory"); }
__device__ __forceinline__ uint32_t lds1(uint32_t addr) {
    uint32_t a;
    asm volatile("ld.shared.b32 %0, [%1];" : "=r"(a) : "r"(addr) : "memory");
    return a;
}
__device__ __forceinline__ void lds4(uint32_t addr, uint32_t* v) {
    asm volatile("ld.shared.v4.b32 {%0,%1,%2,%3}, [%4];" : "=r"(v[0]), "=r"(v[1]), "=r"(v[2]), "=r"(v[3]) : "r"(addr) : "memory");
}
__device__ __forceinline__ void stg1(uint8_t* p, uint32_t a) { asm volatile("st.global.b32 [%0], %1;" ::"l"(p), "r"(a) : "memory"); }
__device__ __forceinline__ void st_part(uint8_t* p, const uint32_t* v, uint32_t parity) {
    asm volatile("{\n.reg .b64 x, y;\nmov.b64 x, {%1, %2};\nmov.b64 y, {%3, %4};\nst.relaxed.gpu.global.v2.b64 [%0], {x, y};\n}\n"
                 ::"l"(p), "r"((v[0] & ~1u) | parity), "r"(v[1]), "r"((v[2] & ~1u) | parity), "r"(v[3]) : "memory");
}
__device__ __forceinline__ void mma16816(float (&d)[4], const uint32_t (&a)[4], uint32_t b0, uint32_t b1) {
    asm volatile("mma.sync.aligned.m16n8k16.row.col.f32.bf16.bf16.f32 {%0,%1,%2,%3}, {%4,%5,%6,%7}, {%8,%9}, {%0,%1,%2,%3};"
                 : "+f"(d[0]), "+f"(d[1]), "+f"(d[2]), "+f"(d[3]) : "r"(a[0]), "r"(a[1]), "r"(a[2]), "r"(a[3]), "r"(b0), "r"(b1));
}
__device__ __forceinline__ uint32_t add2(uint32_t a, uint32_t b) {
    uint32_t r;
    asm("add.rn.bf16x2 %0, %1, %2;" : "=r"(r) : "r"(a), "r"(b));
    return r;
}
__device__ __forceinline__ uint32_t max2(uint32_t a, uint32_t b) {
    uint32_t r;
    asm("max.bf16x2 %0, %1, %2;" : "=r"(r) : "r"(a), "r"(b));
    return r;
}
__device__ __forceinline__ void ld_tagged(const uint8_t* p, uint32_t& a, uint32_t& ta, uint32_t& b, uint32_t& tb) {
    asm volatile("{\n.reg .b64 x, y;\nld.relaxed.gpu.global.v2.b64 {x, y}, [%4];\nmov.b64 {%0, %1}, x;\nmov.b64 {%2, %3}, y;\n}\n"
                 : "=r"(a), "=r"(ta), "=r"(b), "=r"(tb) : "l"(p) : "memory");
}
__device__ __forceinline__ float bf_lo(uint32_t v) { return __uint_as_float(v << 16); }
__device__ __forceinline__ float bf_hi(uint32_t v) { return __uint_as_float(v & 0xFFFF0000u); }
__device__ __forceinline__ float rcp(float x) { float r; asm("rcp.approx.ftz.f32 %0, %1;" : "=f"(r) : "f"(x)); return r; }
__device__ __forceinline__ float ex2(float x) { float r; asm volatile("ex2.approx.ftz.f32 %0, %1;" : "=f"(r) : "f"(x)); return r; }

__device__ __forceinline__ uint32_t full_bar(int stage) { return base + BAR_FULL + (stage & 7) * 8; }
__device__ __forceinline__ void wait_released(int j) { mbar_wait(base + BAR_EMPTY + (j & 7) * 8, (j >> 3) & 1); }

template <int V>
struct Int { static constexpr int value = V; };

__host__ __device__ constexpr int bslot_e(int i) { return (i < 2 || i >= 14) ? (i + 5) % 7 : (i + 1) % 5; }
__host__ __device__ constexpr int bslot_l(int i) { return i % 6; }

template <uint32_t OFF>
struct Feed {
    int stage;
    uint32_t dst;
    __device__ __forceinline__ void seek(int i, int slot) { stage = i; dst = base + OFF + slot * SLOT; }
    template <int N>
    __device__ __forceinline__ uint32_t acquire() { wait_released(stage - N); return full_bar(stage); }
    template <int N>
    __device__ __forceinline__ void next() {
        stage++;
        dst += SLOT;
        if (dst == base + OFF + N * SLOT) dst = base + OFF;
    }
};
__device__ __forceinline__ int skip_own(int n, int mt) { return n == mt ? 15 : n; }

struct Desc { uint32_t lo, hi; };
__host__ __device__ constexpr Desc desc_const(uint32_t lbo, uint32_t sbo, uint32_t mode) { return {(lbo >> 4) << 16, (sbo >> 4) | (mode << 30)}; }
constexpr Desc D_K128 = desc_const(16, 1024, 1);
constexpr Desc D_N128 = desc_const(8192, 1024, 1);
constexpr Desc D_BLOB = desc_const(128, 256, 0);
constexpr Desc D_OT = desc_const(2048, 128, 0);

enum Kind { XW, XWN, QK, BIG, OUT };

struct Ring {
    int stage;
    uint32_t a, b;
    uint32_t wg;
    uint32_t zero;
    bool releaser;
    __device__ __forceinline__ void seek(int i, int bslot) {
        stage = i;
        a = (base + (i % NA) * SLOT) >> 4;
        b = (base + BRING + bslot * SLOT) >> 4;
    }
    __device__ __forceinline__ void wait() { mbar_wait(full_bar(stage), (stage >> 3) & 1); }
    __device__ __forceinline__ void take_turn() { nb_sync(1 + wg, 256); }
    __device__ __forceinline__ void pin() {
        uint32_t n = 0;
#pragma unroll 1
        do {
            asm volatile("pmevent 7;" ::: "memory");
        } while (n++ < zero);
    }
    __device__ __forceinline__ void mma_begin() {
        pin();
        if (!wg) take_turn();
        pin();
    }
    __device__ __forceinline__ void mma_end() {
        pin();
        if (wg) nb_arrive(3, 256);
        nb_sync(3 - wg, 256);
    }
    template <Kind K, int NBS, bool INIT, int SB = 1, bool TAIL = false, int S0 = 0, int S1 = 4>
    __device__ __forceinline__ void run(float (&d)[56], float (&e)[56], bool first = true, bool last = true, bool more = true) {
        if (first) take_turn();
        asm volatile("wgmma.fence.sync.aligned;" ::: "memory");
        if (K == QK) {
            const uint32_t da = D_K128.lo + (base >> 4) + (stage >> 1) * (SLOT >> 4) + (stage & 1) * 4 + wg * 512, db = D_N128.lo + b;
            wgmma112<0, 1, 1, INIT, D_K128.hi, D_N128.hi>(d, da, db);
            wgmma112<0, 1, 1, INIT, D_K128.hi, D_N128.hi>(e, da, db + 256);
            wgmma112<0, 1, 1, false, D_K128.hi, D_N128.hi>(d, da + 2, db + 128);
            wgmma112<0, 1, 1, false, D_K128.hi, D_N128.hi>(e, da + 2, db + 384);
        } else {
            constexpr int TA = K == OUT, TB = K != XW;
            constexpr uint32_t sa = K == OUT ? 256 : 2, sb = K == XW ? 2 : K == BIG ? 224 : 128;
            constexpr Desc A = K == OUT ? D_OT : D_K128, B = K == XW ? D_K128 : K == BIG ? D_BLOB : D_N128;
            const uint32_t da = A.lo + a + wg * (K == OUT ? 64 : 512), db = B.lo + b;
            if (S0 == 0) wgmma112<TA, TB, SB, INIT, A.hi, B.hi>(d, da, db);
#pragma unroll
            for (int q = S0 ? S0 : 1; q < S1; q++) wgmma112<TA, TB, SB, false, A.hi, B.hi>(d, da + q * sa, db + q * sb);
        }
        asm volatile("wgmma.commit_group.sync.aligned;" ::: "memory");
        if (!TAIL) asm volatile("wgmma.wait_group.sync.aligned 1;" ::: "memory");
        if (last) nb_arrive(2 - wg, 256);
        if (!TAIL && stage > 0) {
            if (releaser) mbar_arrive(base + BAR_EMPTY + ((stage - 1) & 7) * 8);
        }
        stage++;
        a += SLOT >> 4;
        if (a == (base + NA * SLOT) >> 4) a = base >> 4;
        b += SLOT >> 4;
        if (b == (base + BRING + NBS * SLOT) >> 4) b = (base + BRING) >> 4;
        if (more) wait();
    }
    template <Kind K, int NBS, bool INIT, int SB = 1, bool TAIL = false, int S0 = 0, int S1 = 4>
    __device__ __forceinline__ void run(float (&d)[56], bool first = true, bool last = true, bool more = true) {
        run<K, NBS, INIT, SB, TAIL, S0, S1>(d, d, first, last, more);
    }
};

template <int I0 = 0, int I1 = 28>
__device__ __forceinline__ void pack_all(const float (&d)[56], uint32_t (&p)[28]) {
#pragma unroll
    for (int i = I0; i < I1; i++) p[i] = pack2(d[2 * i], d[2 * i + 1]);
}
template <int I0, int I1>
__device__ __forceinline__ void store_frags(uint8_t* dst, const uint32_t (&p)[28]) {
#pragma unroll
    for (int i = I0; i < I1; i++) stg1(dst + i * 128, p[i]);
}
template <int I0, int I1>
__device__ __forceinline__ void stage_frags(uint32_t lane_addr, const uint32_t (&p)[28]) {
#pragma unroll
    for (int i = I0; i < I1; i += 4) stsm4(lane_addr + i * 128, p[i], p[i + 1], p[i + 2], p[i + 3]);
}
template <class F>
__device__ __forceinline__ void store_out(F frag, int lane, uint32_t slab, const CUtensorMap* m, int c0, int c1) {
    const bool swap = lane & 16;
    const uint32_t addr = slab + (lane & 7) * 224 + ((lane >> 3) ^ ((lane >> 2) & 1)) * 16;
#pragma unroll
    for (int h = 0; h < 2; h++) {
#pragma unroll
        for (int c = 0; c < 14; c += 4) {
            const uint32_t t0 = frag(2 * c + h), t1 = frag(2 * c + 2 + h);
            if (c < 12) {
                const uint32_t t2 = frag(2 * c + 4 + h), t3 = frag(2 * c + 6 + h);
                stsm4(addr + h * 1792 + c * 16, swap ? t1 : t0, swap ? t0 : t1, swap ? t3 : t2, swap ? t2 : t3);
            } else {
                asm volatile("stmatrix.sync.aligned.m8n8.x2.shared.b16 [%0], {%1,%2};" ::"r"(addr + h * 1792 + c * 16), "r"(swap ? t1 : t0), "r"(swap ? t0 : t1) : "memory");
            }
        }
        fence_async_smem();
        __syncwarp();
        if (elect()) tma_st2(m, c0, c1 + 8 * h, slab + h * 1792);
    }
    if (elect()) {
        bulk_commit();
        bulk_wait_read();
    }
}
__host__ __device__ constexpr int tile_of(int t) { return 7 * (t >> 2) + 3 * ((t >> 1) & 1) + 2 * (t & 1); }

struct Role {
    bool H;
    int L, mt, ns, id;
    int kind, a0, a1, b3;
};
template <bool BY_SM>
__device__ __forceinline__ Role decode_role() {
    uint32_t sm;
    if (BY_SM) asm volatile("mov.u32 %0, %%smid;" : "=r"(sm));
    else asm volatile("mov.u32 %0, %%ctaid.x;" : "=r"(sm));
    const int tpc = sm >> 1, q2 = ((tpc - 32) * 37) >> 8;
    const int gpc = tpc < 32 ? tpc & 7 : tpc < 60 ? tpc - 31 - 7 * q2 : 0;
    const int pos = tpc < 32 ? tpc >> 3 : tpc < 60 ? q2 + 4 : tpc - 56;
    Role r;
    r.H = sm >= 128;
    const int grp = (GPC_MAP >> (4 * gpc)) & 7;
    r.L = grp & 1;
    r.mt = (grp >> 1) * 4 + (pos >> 1);
    r.ns = (pos & 1) * 2 + (sm & 1);
    r.id = r.H ? sm : grp * 16 + pos * 2 + (sm & 1);
    r.kind = r.H ? 2 : r.L;
    r.a0 = r.L ? (r.mt >> 3) * 448 : 0;
    r.a1 = r.L ? (r.mt & 7) * 128 : r.H ? 120 : r.mt * 64;
    r.b3 = r.H ? 4 + r.ns : r.L ? r.ns : 0;
    return r;
}

__device__ __forceinline__ void first_fill(const Maps& maps, const Role& r, int i) {
    const bool E = r.kind == 0;
    const CUtensorMap* ma = &maps.m[r.kind];
    const uint32_t bar = full_bar(i);
    const int k = (i * 64) >> r.L;
    const bool has_a = !(i & r.L), has_b = i < 7 - r.L;
    const uint32_t dst = base + BRING + (E ? (0x2104365u >> (4 * i)) & 7 : i) * SLOT;
    mbar_expect(bar, (has_a ? SLOT : 0) + (has_b ? (E ? BLOB : SLOT) : 0));
    if (has_a) tma_ld4(base + (i >> r.L) * SLOT, ma, r.a0 + k, r.a1, 0, 0, bar);
    if (has_b) {
        tma_ld4(dst, ma + 3, E ? k : 0, E ? r.ns * 112 : k, 0, r.b3, bar);
        if (!E) tma_ld4(dst + 8192, ma + 3, 64, k, 0, r.b3, bar);
        mbar_arrive(bar);
    }
}
static_assert(bslot_e(0) == 5 && bslot_e(1) == 6 && bslot_e(2) == 3 && bslot_e(3) == 4 && bslot_e(4) == 0 && bslot_e(6) == 2, "");

template <bool BY_SM>
__global__ void __launch_bounds__(384, 1) fused_kernel(Scratch* sc, const __grid_constant__ Maps maps) {
    const unsigned t_open = clk32();
    const int warp = __shfl_sync(0xffffffffu, threadIdx.x >> 5, 0);
    if (warp == 8) {
        if (elect()) {
#pragma unroll
            for (int i = 0; i < LEAD; i++) mbar_init(base + BAR_FULL + i * 8, 2);
            asm volatile("fence.mbarrier_init.release.cluster;" ::: "memory");
            const Role r = decode_role<BY_SM>();
#pragma unroll 1
            for (int i = 0; i < LEAD; i++) {
                first_fill(maps, r, i);
            }
        }
    }
    if (warp == 9) {
        if (elect()) {
#pragma unroll
            for (int i = 0; i < 8; i++) mbar_init(base + BAR_EMPTY + i * 8, 4);
            asm volatile("fence.mbarrier_init.release.cluster;" ::: "memory");
        }
    } else if (warp == 10) {
        if (elect()) {
#pragma unroll
            for (int i = 0; i < 3; i++) mbar_init(base + BAR_RDY + i * 8, i < 2 ? 4 : 8);
#pragma unroll
            for (int i = 0; i < 2; i++) mbar_init(base + BAR_HALO + i * 8, 1);
            asm volatile("fence.mbarrier_init.release.cluster;" ::: "memory");
        }
    } else if (warp == 11) {
        if (elect()) {
#pragma unroll
            for (int i = LEAD; i < 8; i++) mbar_init(base + BAR_FULL + i * 8, 2);
#pragma unroll
            for (int i = 0; i < 3; i++) mbar_init(base + BAR_DEP + i * 8, 1);
#pragma unroll
            for (int i = 0; i < 2; i++) mbar_init(base + BAR_PART + i * 8, 1);
            asm volatile("fence.mbarrier_init.release.cluster;" ::: "memory");
        }
    }
    __syncthreads();

    const Role role = decode_role<BY_SM>();
    int lane = threadIdx.x & 31;
    asm volatile("" : "+r"(lane));
    const bool roleH = role.H;
    const int roleL = role.L, mt = role.mt, ns = role.ns, bid = role.id;
    const int par = mt >> 3, blk = mt & 7, col = ns * 112;

    if (__builtin_expect(warp >= 8, 1)) {
        asm volatile("setmaxnreg.dec.sync.aligned.u32 56;");
#define PROF_FEED_A
#define PROF_FEED_B
        if (__builtin_expect(warp == 8, 1)) {
            if (elect()) {
                PROF(129);
#pragma unroll 1
                for (int i = LEAD; i < 7; i++) {
                    while (clk32() - t_open < i * PACE) {}
                    first_fill(maps, role, i);
                }
                PROF(134);
                Feed<0> f;
                const int row = mt * 128;
                auto c_run = [&](const CUtensorMap* m, int off, int n0, int n1) {
#pragma unroll 1
                    for (int n = n0; n < n1; n++) {
                        const uint32_t bar = f.acquire<NA>();
                        mbar_expect(bar, SLOT);
                        tma_ld2(f.dst, m, (off + skip_own(n, mt)) * 64, row, bar);
                        PROF_FEED_A;
                        f.next<NA>();
                    }
                };
                if (roleH) {
                } else if (!roleL) {
                    f.seek(14, 0);
#pragma unroll 1
                    for (int i = 0; i < 4; i++) {
                        const uint32_t bar = f.acquire<NA>();
                        mbar_expect(bar, SLOT);
                        tma_ld2(f.dst, &maps.m[M_CR + (i >> 1)], ((i & 1) * 16 + mt) * 64, row, bar);
                        mbar_arrive(bar);
                        PROF_FEED_A;
                        f.next<NA>();
                    }
                    c_run(&maps.m[M_CR], 0, 0, 15);
                    c_run(&maps.m[M_CI], 0, 0, NBE);
                    wait_dep(2);
#pragma unroll 1
                    for (int i = 0; i < 7; i++) {
                        const uint32_t bar = f.acquire<NA>();
                        mbar_expect(bar, SLOT);
                        bulk_ld(f.dst, sc->o + (size_t)(mt * 7 + i) * SLOT, SLOT, bar);
                        PROF_FEED_A;
                        f.next<NA>();
                    }
                } else {
#pragma unroll 1
                    for (int i = 4; i < 7; i++) {
                        wait_released(2 * i - 8);
                        mbar_expect(full_bar(2 * i), SLOT);
                        tma_ld4(base + i * SLOT, &maps.m[M_XA], par * 448 + i * 64, blk * 128, 0, 0, full_bar(2 * i));
                    }
                    wait_released(HALO_K_AT);
                    mbar_arrive(base + BAR_DEP + 16);
                    f.seek(21, 0);
                    c_run(&maps.m[M_CR], 16, 0, 15);
                    c_run(&maps.m[M_CI], 16, 0, 15);
                    c_run(&maps.m[M_CI], 0, NBL, 15);
                }
            }
        } else if (warp == 11) {
            if (elect()) {
                Feed<BRING> f;
                auto blob_run = [&](auto nbs, int quarter, int n0, int n1) {
                    constexpr int N = decltype(nbs)::value;
                    const uint8_t* src = sc->ab + (size_t)(quarter * 64 + ns) * BLOB;
#pragma unroll 1
                    for (int n = n0; n < n1; n++) {
                        const uint32_t bar = f.template acquire<N>();
                        mbar_expect(bar, BLOB);
                        bulk_ld(f.dst, src + skip_own(n, mt) * (4 * BLOB), BLOB, bar);
                        PROF_FEED_B;
                        f.template next<N>();
                    }
                };
                auto w_run = [&](auto nbs, const CUtensorMap* m, int slice, bool no_a) {
                    constexpr int N = decltype(nbs)::value;
#pragma unroll 1
                    for (int i = 0; i < 7; i++) {
                        const uint32_t bar = f.template acquire<N>();
                        mbar_expect(bar, SLOT);
                        tma_ld4(f.dst, m, 0, i * 64, 0, slice, bar);
                        tma_ld4(f.dst + 8192, m, 64, i * 64, 0, slice, bar);
                        if (no_a) mbar_arrive(bar);
                        PROF_FEED_B;
                        f.template next<N>();
                    }
                };
                if (roleH) {
                    f.seek(7, 0);
                    w_run(Int<7>(), &maps.m[M_WV], 8 + ns, true);
                } else if (!roleL) {
                    f.seek(7, bslot_e(7));
#pragma unroll 1
                    for (int i = 0; i < 7; i++) {
                        const uint32_t bar = f.acquire<5>();
                        mbar_expect(bar, BLOB);
                        tma_ld2(f.dst, &maps.m[M_WI], i * 64, col, bar);
                        mbar_arrive(bar);
                        PROF_FEED_B;
                        f.next<5>();
                    }
                    f.seek(18, bslot_e(18));
                    wait_dep(0);
                    blob_run(Int<7>(), 0, 0, 15);
                    wait_dep(1);
                    blob_run(Int<7>(), 2, 0, NBE);
                    w_run(Int<7>(), &maps.m[M_WO], ns, false);
                } else {
                    f.seek(6, 0);
#pragma unroll 1
                    for (int i = 6; i < 14; i++) {
                        const uint32_t bar = f.acquire<6>();
                        mbar_expect(bar, SLOT);
                        tma_ld4(f.dst, &maps.m[M_WQK], 0, i * 32, 0, ns, bar);
                        tma_ld4(f.dst + 8192, &maps.m[M_WQK], 64, i * 32, 0, ns, bar);
                        if (i & 1) mbar_arrive(bar);
                        PROF_FEED_B;
                        f.next<6>();
                    }
                    w_run(Int<6>(), &maps.m[M_WV], 8 + ns, true);
                    wait_dep(0);
                    blob_run(Int<6>(), 1, 0, 15);
                    wait_dep(1);
                    blob_run(Int<6>(), 3, 0, 15);
                    blob_run(Int<6>(), 2, NBL, 15);
                    const unsigned tag = lds1(base + TAG);
                    fence_async_smem();
#pragma unroll 1
                    for (int h = 0; h < 2; h++) {
                        await(sc, CNT_P + mt * 4 + ns, tag * 2 - 1 + h);
                        PROF(153 + h);
                        mbar_expect(base + BAR_PART + h * 8, BLOB);
                        bulk_ld(base + (h ? HALO : LSLAB), sc->part + (size_t)((ns * 16 + mt) * 2 + h) * BLOB, BLOB, base + BAR_PART + h * 8);
                    }
                }
            }
        } else if (roleH) {
            if (elect()) {
                wait_released(warp == 9 ? 0 : 7);
#pragma unroll 1
                for (int i = 0; i < 7; i++) {
                    if (warp == 9) {
                        asm volatile("cp.async.bulk.prefetch.tensor.2d.L2.global [%0, {%1, %2}];" ::"l"(&maps.m[M_WI]), "r"(i * 64), "r"(col) : "memory");
                    } else {
                        asm volatile("cp.async.bulk.prefetch.tensor.4d.L2.global [%0, {%1, %2, 0, %3}];" ::"l"(&maps.m[M_WO]), "r"(0), "r"(i * 64), "r"(ns) : "memory");
                        asm volatile("cp.async.bulk.prefetch.tensor.4d.L2.global [%0, {%1, %2, 0, %3}];" ::"l"(&maps.m[M_WO]), "r"(64), "r"(i * 64), "r"(ns) : "memory");
                    }
                }
            }
        } else if (warp == 10) {
            if (elect()) {
                unsigned* epoch_ptr = &sc->epoch[(bid * 4 + 2) * 8];
                const unsigned ep = *epoch_ptr + 1;
                sts1(base + TAG, ep);
                asm volatile("prefetch.tensormap [%0];" ::"l"(&maps.m[M_OUTA + roleL]) : "memory");
                await(sc, CNT_A + roleL * 4 + ns, ep * 16);
                mbar_arrive(base + BAR_DEP);
                PROF(150);
                await(sc, CNT_B + ns, ep * 16);
                mbar_arrive(base + BAR_DEP + 8);
                PROF(151);
                if (!roleL) {
                    await(sc, CNT_O + mt, ep * 4);
                    mbar_arrive(base + BAR_DEP + 16);
                }
                PROF(152);
                *epoch_ptr = ep;
            }
        } else if (!roleL) {
            if (elect()) {
                mbar_wait(base + BAR_RDY, 0);
                PROF(130);
                signal(sc, CNT_A + ns);
                PROF(131);
                mbar_wait(base + BAR_RDY + 8, 0);
                signal(sc, CNT_A + 4 + ns);
                PROF(135);
                mbar_wait(base + BAR_RDY + 16, 0);
                PROF(132);
                signal(sc, CNT_B + ns);
                PROF(133);
            }
        } else {
            unsigned* epoch_ptr = &sc->epoch[(bid * 4 + 1) * 8];
            const unsigned tag = *epoch_ptr + 1;
#pragma unroll 1
            for (int kv = 0; kv < 2; kv++) {
                uint32_t v[16];
#pragma unroll
                for (int i = 0; i < 16; i++) v[i] = 0;
                if (kv) wait_released(HALO_V_AT - 4), wait_released(HALO_V_AT);
                else mbar_wait(base + BAR_DEP + 16, 0);
                if (blk > 0) {
                    const uint8_t* src = sc->halo + (size_t)(((mt - 1) * 4 + ns) * 2 + kv) * 2048 + lane * 16;
#pragma unroll 1
                    for (int n = 0; n < SPIN_LIMIT; n++) {
                        uint32_t stale = 0;
#pragma unroll
                        for (int i = 0; i < 4; i++) ld_tagged(src + i * 512, v[4 * i], v[4 * i + 1], v[4 * i + 2], v[4 * i + 3]);
#pragma unroll
                        for (int i = 0; i < 16; i += 2) stale |= v[i] ^ tag;
                        if (__all_sync(0xffffffffu, !(stale & 1))) break;
                    }
#pragma unroll
                    for (int c = 0; c < 14; c += 2) v[c] = (v[c] & ~1u) | ((v[15] >> c) & 1);
                }
#pragma unroll
                for (int i = 0; i < 14; i++) sts1(base + HALO + kv * (8 * HSLOT) + i * 128 + lane * 4, v[i]);
                warp_arrive(base + BAR_HALO + kv * 8);
                if (lane == 0) PROF(142 + kv);
            }
            if (elect()) {
                mbar_wait(base + BAR_RDY + 16, 0);
                PROF(130);
                signal(sc, CNT_O + mt);
                PROF(131);
                *epoch_ptr = tag;
            }
        }
    } else {
        asm volatile("setmaxnreg.inc.sync.aligned.u32 224;");
        Ring r;
        r.wg = warp >> 2;
        r.zero = blockIdx.y;
        r.releaser = lane + 1 == (warp >> 2);
        const int wg = warp >> 2;
        if (wg) nb_arrive(1, 256);
        uint8_t* part = sc->part + (size_t)(ns * 16 + mt) * (2 * BLOB) + warp * WSLOT + lane * 16;
        uint32_t p[28];

        if (roleH) {
            unsigned* epoch_ptr = &sc->epoch[bid * 4 * 8];
            const unsigned tag = *epoch_ptr + 1;
            uint8_t* hout = sc->halo + (size_t)((warp * 8 + ns) * 2) * 2048 + lane * 16;
            auto send = [&](int kv) {
#pragma unroll
                for (int h = 0; h < 2; h++) {
                    uint32_t v[16];
                    v[14] = v[15] = 0;
#pragma unroll
                    for (int c = 0; c < 14; c++) v[c] = p[2 * c + h];
#pragma unroll
                    for (int c = 0; c < 14; c += 2) v[15] |= (v[c] & 1) << c;
#pragma unroll
                    for (int i = 0; i < 4; i++) st_part(hout + (h * 8 + kv) * 2048 + i * 512, v + 4 * i, tag & 1);
                }
            };
            float x0[56], x1[56];
            r.seek(0, 0);
            r.wait();
            r.run<XWN, 7, true>(x0);
#pragma unroll 1
            for (int i = 1; i < 7; i++) r.run<XWN, 7, false>(x0);
            r.run<XWN, 7, true>(x1);
            acc_fence(x0);
            pack_all(x0, p);
            send(0);
#pragma unroll 1
            for (int i = 1; i < 7; i++) r.run<XWN, 7, false>(x1, true, i < 6 || !wg, i < 6);
            asm volatile("wgmma.wait_group.sync.aligned 0;" ::: "memory");
            acc_fence(x1);
            pack_all(x1, p);
#pragma unroll
            for (int i = 0; i < 28; i++) p[i] = movm(p[i]);
            send(1);
            if (threadIdx.x == 0) *epoch_ptr = tag;
        } else if (!roleL) {
            uint8_t* blob = sc->ab + (size_t)((wg * 16 + mt) * 4 + ns) * BLOB + (warp & 3) * WSLOT + lane * 4;
            const uint32_t own = base + BRING + wg * SLOT + (warp & 3) * WSLOT + lane * 16;
            float x0[56], x1[56];
            r.seek(0, bslot_e(0));
            r.wait();
            r.run<XW, 7, true>(x0);
            r.run<XW, 7, false>(x0);
            r.seek(2, bslot_e(2));
#pragma unroll 1
            for (int i = 2; i < 7; i++) r.run<XW, 5, false>(x0);

            r.seek(7, bslot_e(7));
            r.run<XW, 5, true, -1>(x1);
            acc_fence(x0);
            pack_all<0, LAZY ? 14 : 28>(x0, p);
#pragma unroll
            for (int i = 0; i < 2; i++) {
                if (wg == i) store_frags<0, 14>(blob, p);
                else stage_frags<0, A_OWN>(own + 5 * SLOT, p);
                r.run<XW, 5, false, -1>(x1);
                if (LAZY && i == 0) pack_all<14, 28>(x0, p);
                if (wg == i) {
                    store_frags<14, 28>(blob, p);
                    warp_arrive(base + BAR_RDY + i * 8);
                } else {
                    stage_frags<A_OWN, 2 * A_OWN>(own + 5 * SLOT, p);
                }
                r.run<XW, 5, false, -1>(x1);
            }
            stage_frags<2 * A_OWN, A_OWN2>(own + 5 * SLOT, p);
            r.run<XW, 5, false, -1>(x1);
            stage_frags<A_OWN2, 28>(own + 5 * SLOT, p);
            fence_async_smem();
            r.run<XW, 5, false, -1>(x1);

            r.seek(14, bslot_e(14));
            r.run<BIG, 7, true>(x0);
            acc_fence(x1);
            pack_all(x1, p);
            stage_frags<0, 28>(own, p);
            r.run<BIG, 7, false>(x0);
            fence_async_smem();
            blob += (size_t)128 * BLOB;
#pragma unroll
            for (int i = 0; i < 28; i++) {
                if (i % B_SLICE == 0) r.run<BIG, 7, false>(x0);
                stg1(blob + i * 128, p[i]);
            }
            warp_arrive(base + BAR_RDY + 16);
#pragma unroll 1
            for (int i = 17 + 27 / B_SLICE; i < 33 + NBL; i++) r.run<BIG, 7, false>(x0);
            if (E_STEPS) {
                r.seek(POUT - 1, bslot_e(POUT - 1));
                r.run<BIG, 7, false, 1, false, 0, E_STEPS>(x0);
            }

            const uint32_t tag = lds1(base + TAG);
            r.seek(POUT, bslot_e(POUT));
            r.run<OUT, 7, true>(x1);
            acc_fence(x0);
            pack_all(x0, p);
            auto hint = [&]() {
                if ((warp & 3) == 0 && elect())
                    asm volatile("red.relaxed.gpu.global.add.u32 [%0], 1;" ::"l"(&sc->cnt[(CNT_P + mt * 4 + ns) * 32]) : "memory");
            };
#pragma unroll
            for (int k = 0; k < 3; k++) {
                if (k < 2 && wg == k) {
                    if (HINT_AT == 0) hint();
#pragma unroll
                    for (int i = 0; i < P_FIRST; i++) st_part(part + i * 512, p + 4 * i, tag & 1);
                    if (HINT_AT == 1) hint();
                }
                if (k > 0 && wg == k - 1) {
                    if (HINT_AT == 2) hint();
#pragma unroll
                    for (int i = P_FIRST; i < 7; i++) st_part(part + i * 512, p + 4 * i, tag & 1);
                }
                if (k < 2) r.run<OUT, 7, false>(x1);
            }
#pragma unroll
            for (int i = 3; i < 7; i++) r.run<OUT, 7, false, 1, true>(x1, i <= 7 - TURN, i < 7 - TURN || (i == 6 && !wg), i < 6);

            asm volatile("wgmma.wait_group.sync.aligned 0;" ::: "memory");
            acc_fence(x1);
            const uint32_t slab = base + (wg ? BRING + bslot_e(ELAST - 6) * SLOT : ((ELAST - 6) % NA) * SLOT) + (warp & 3) * WSLOT;
            store_out([&](int i) { return pack2(x1[2 * i], x1[2 * i + 1]); }, lane, slab, &maps.m[M_OUTA], par * 896 + col, blk * 128 + warp * 16);
        } else {
            const int g = lane >> 2, tig = lane & 3;
            const uint32_t hin = base + HALO + warp * HSLOT + lane * 4;
            const uint32_t hpub = warp < 7 ? hin + HSLOT : base + HSPARE + lane * 4;
            auto publish = [&](const uint32_t (&h)[14], int c0, int c1) {
#pragma unroll
                for (int c = 0; c < 14; c++)
                    if (c >= c0 && c < c1) sts1(hpub + c * 128, h[c]);
            };
            float y0[56], y1[56], y2[56];
            r.seek(0, 0);
            r.wait();
            r.run<QK, 6, true>(y0, y1);
#pragma unroll 1
            for (int i = 1; i < 14; i++) r.run<QK, 6, false>(y0, y1);

            uint32_t m1[8][4], m0[8][4], lo[14], hi[14], q[2][8][2];
            auto pack_q = [&](int b) {
                uint32_t v[14];
#pragma unroll
                for (int c = 0; c < 14; c++) v[c] = pack2(y0[4 * c + 2 * b], y0[4 * c + 2 * b + 1]);
#pragma unroll
                for (int t = 0; t < 8; t++) {
                    const int c = tile_of(t);
                    q[b][t][0] = (t & 3) == 2 ? (tig >= 2 ? v[c] : 0u) : v[c];
                    q[b][t][1] = (t & 3) == 1 ? (tig < 2 ? v[c + 1] : 0u) : v[c + 1];
                }
            };
            auto fetch = [&](uint32_t src, int hp, int i0) {
#pragma unroll
                for (int t = 4 * hp; t < 4 * hp + 4; t++) {
                    m0[t][i0] = (t & 3) == 2 ? dup(m0[t - 1][3], r.zero) : lds1(src + tile_of(t) * 128);
                    m0[t][3] = lds1(src + tile_of(t) * 128 + 128);
                }
            };
            r.seek(14, bslot_l(14));
            r.run<XWN, 6, true>(y2);
            acc_fence(y0);
            acc_fence(y1);
#pragma unroll
            for (int c = 0; c < 14; c++) hi[c] = pack2(y1[4 * c + 2], y1[4 * c + 3]);
            publish(hi, 0, 7);
            r.run<XWN, 6, false>(y2);
            publish(hi, 7, 14);
#pragma unroll
            for (int c = 0; c < 14; c++) lo[c] = pack2(y1[4 * c], y1[4 * c + 1]);
#pragma unroll
            for (int t = 0; t < 8; t++) {
                const int c = tile_of(t);
                const bool shared = (t & 3) == 2;
                m1[t][0] = shared ? dup(lo[c], r.zero) : lo[c];
                m1[t][1] = shared ? dup(hi[c], r.zero) : hi[c];
                m1[t][2] = lo[c + 1];
                m1[t][3] = hi[c + 1];
                m0[t][0] = dup(m1[t][0], r.zero);
                m0[t][2] = dup(lo[c + 1], 2 * r.zero);
            }
            r.run<XWN, 6, false>(y2);
            if (warp == 0) mbar_wait(base + BAR_HALO, 0);
            fetch(hin, 0, 1);
            pack_q(1);
            r.run<XWN, 6, false>(y2);
            fetch(hin, 1, 1);
            pack_q(0);
            r.mma_begin();
            float s[8][4];
#pragma unroll
            for (int step = 0; step < 2; step++) {
#pragma unroll
                for (int i = 0; i < 8; i++) {
                    const int b = 1 - (i >> 2), h = i & 3, t = 2 * h + step;
                    float (&d)[4] = s[2 * h + b];
                    if (step == 0) d[0] = d[1] = d[2] = d[3] = 0.f;
                    mma16816(d, b ? m1[t] : m0[t], q[b][t][0], q[b][t][1]);
                }
            }
            r.mma_end();
            r.run<XWN, 6, false>(y2, false);

            uint32_t pr[8], mx[4], mx1[4];
            {
                const bool cur0 = g <= 2 * tig, cur1 = g <= 2 * tig + 1;
#pragma unroll
                for (int i = 0; i < 8; i++) {
                    const int c = (i & 1) ? 2 : 0;
                    pr[i] = movm(pack2(cur0 ? s[i][c] : s[i][2 - c], cur1 ? s[i][c + 1] : s[i][3 - c]));
                }
            }
            r.run<XWN, 6, false>(y2);
            const uint32_t curmask = (2 * tig <= g ? 0x0000FFFFu : 0u) | (2 * tig + 1 <= g ? 0xFFFF0000u : 0u);
            {
                const uint32_t keep = (blk == 0 && warp == 0) ? curmask : 0xFFFFFFFFu;
#pragma unroll
                for (int i = 0; i < 4; i++) {
                    pr[2 * i] = (pr[2 * i] & keep) | (0xCF9ECF9Eu & ~keep);
                    mx[i] = max2(__byte_perm(pr[2 * i], pr[2 * i + 1], 0x5410), __byte_perm(pr[2 * i], pr[2 * i + 1], 0x7632));
                    mx1[i] = __shfl_xor_sync(0xffffffffu, mx[i], 1);
                }
            }
#pragma unroll
            for (int i = 0; i < 4; i++) {
                mx[i] = max2(mx[i], mx1[i]);
                mx1[i] = __shfl_xor_sync(0xffffffffu, mx[i], 2);
            }
            r.run<XWN, 6, false>(y2);
            constexpr float SCL = 0.18898223650461362f * 1.4426950408889634f;
            float e0[8], e1[8], sm[8], sm1[8];
#pragma unroll
            for (int i = 0; i < 8; i++) {
                const uint32_t m2 = max2(mx[i >> 1], mx1[i >> 1]);
                sm[i] = ((i & 1) ? bf_hi(m2) : bf_lo(m2)) * -SCL;
                e0[i] = ex2(fmaf(bf_lo(pr[i]), SCL, sm[i]));
            }

            r.seek(21, bslot_l(21));
            r.run<BIG, 6, true>(y0);
            acc_fence(y2);
#pragma unroll
            for (int c = 0; c < 7; c++) hi[c] = movm(pack2(y2[4 * c + 2], y2[4 * c + 3]));
#pragma unroll
            for (int i = 0; i < 8; i++) e1[i] = ex2(fmaf(bf_hi(pr[i]), SCL, sm[i]));
            r.run<BIG, 6, false>(y0);
            publish(hi, 0, 7);
#pragma unroll
            for (int c = 7; c < 14; c++) hi[c] = movm(pack2(y2[4 * c + 2], y2[4 * c + 3]));
            r.run<BIG, 6, false>(y0);
            publish(hi, 7, 14);
#pragma unroll
            for (int i = 0; i < 8; i++) {
                sm[i] = e0[i] + e1[i];
                sm1[i] = __shfl_xor_sync(0xffffffffu, sm[i], 1);
            }
            r.run<BIG, 6, false>(y0);
#pragma unroll
            for (int c = 0; c < 14; c++) lo[c] = movm(pack2(y2[4 * c], y2[4 * c + 1]));
            r.run<BIG, 6, false>(y0);
#pragma unroll
            for (int i = 0; i < 8; i++) {
                sm[i] += sm1[i];
                sm1[i] = __shfl_xor_sync(0xffffffffu, sm[i], 2);
            }
#pragma unroll
            for (int t = 0; t < 8; t++) {
                const int c = tile_of(t);
                const bool shared = (t & 3) == 2;
                m1[t][0] = shared ? dup(lo[c], r.zero) : lo[c];
                m1[t][1] = lo[c + 1];
                m1[t][2] = shared ? dup(hi[c], r.zero) : hi[c];
                m1[t][3] = hi[c + 1];
                m0[t][0] = dup(m1[t][0], r.zero);
                m0[t][1] = dup(lo[c + 1], 2 * r.zero);
            }
            r.run<BIG, 6, false>(y0);
            if (warp == 0) mbar_wait(base + BAR_HALO + 8, 0);
            const uint32_t vin = warp ? hin : hin + 8 * HSLOT;
            fetch(vin, 0, 2);
#pragma unroll
            for (int i = 0; i < 8; i++) {
                const float inv = rcp(sm[i] + sm1[i]);
                pr[i] = pack2(e0[i] * inv, e1[i] * inv);
            }
            r.run<BIG, 6, false>(y0);
            fetch(vin, 1, 2);
            uint32_t pb[8][2];
#pragma unroll
            for (int t = 0; t < 8; t++) {
                pb[t][t & 1] = band(pr[t], curmask);
                pb[t][1 - (t & 1)] = band(pr[t], ~curmask);
            }
            r.mma_begin();
            float o[2][8][4];
#pragma unroll
            for (int i = 0; i < 16; i++) {
                const int b = 1 - (i >> 3), t = i & 7;
                float (&d)[4] = o[b][t];
                d[0] = d[1] = d[2] = d[3] = 0.f;
                mma16816(d, b ? m1[t] : m0[t], pb[(t & 6) + b][0], pb[(t & 6) + b][1]);
            }
            r.mma_end();
            r.run<BIG, 6, false>(y0, false);
            uint8_t* odst = sc->o + (size_t)mt * 7 * SLOT + ns * (14 * 2048) + warp * 256 + lane * 4;
#pragma unroll
            for (int hp = 0; hp < 2; hp++) {
#pragma unroll
                for (int b = 0; b < 2; b++) {
                    const float (&u)[8][4] = o[b];
                    const int t = 4 * hp;
                    uint32_t* w = p + 14 * hp + b;
                    w[0] = pack2(u[t][0], u[t][1]);
                    w[2] = pack2(u[t][2], u[t][3]);
                    w[4] = pack2(u[t + 1][0], u[t + 1][1]);
                    w[6] = pack2(g < 4 ? u[t + 1][2] : u[t + 2][0], g < 4 ? u[t + 1][3] : u[t + 2][1]);
                    w[8] = pack2(u[t + 2][2], u[t + 2][3]);
                    w[10] = pack2(u[t + 3][0], u[t + 3][1]);
                    w[12] = pack2(u[t + 3][2], u[t + 3][3]);
                }
            }
#pragma unroll
            for (int i = 0; i < 28; i++) {
                if (i >= O_FIRST && (i - O_FIRST) % O_SLICE == 0) r.run<BIG, 6, false>(y0);
                stg1(odst + (i >> 1) * 2048 + (i & 1) * 128, p[i]);
            }
            warp_arrive(base + BAR_RDY + 16);

#pragma unroll 1
            for (int i = 30 + (27 - O_FIRST) / O_SLICE; i <= LLAST - TURN; i++) r.run<BIG, 6, false>(y0);
            r.seek(LLAST + 1 - TURN, bslot_l(LLAST + 1 - TURN));
#pragma unroll
            for (int i = 0; i < TURN; i++) {
                if (LLAST + 1 - TURN + i == 51) r.run<BIG, 6, false, 1, true, E_STEPS>(y0, i == 0, i == TURN - 1 && !wg, i < TURN - 1);
                else r.run<BIG, 6, false, 1, true>(y0, i == 0, i == TURN - 1 && !wg, i < TURN - 1);
            }
            const uint32_t tag = lds1(base + TAG);
            const uint32_t slab = base + (wg ? HALO : LSLAB) + (warp & 3) * WSLOT;
            mbar_wait(base + BAR_PART + wg * 8, 0);
#pragma unroll
            for (int i = 0; i < 7; i++) lds4(slab + i * 512 + lane * 16, p + 4 * i);
#pragma unroll 1
            for (int n = 0; n < SPIN_LIMIT; n++) {
                uint32_t stale = 0;
#pragma unroll
                for (int i = 0; i < 28; i += 2) stale |= p[i] ^ tag;
                if (__all_sync(0xffffffffu, !(stale & 1))) break;
#pragma unroll
                for (int i = 0; i < 7; i++) ld_tagged(part + i * 512, p[4 * i], p[4 * i + 1], p[4 * i + 2], p[4 * i + 3]);
            }
            asm volatile("wgmma.wait_group.sync.aligned 0;" ::: "memory");
            acc_fence(y0);
            store_out([&](int i) { return add2(pack2(y0[2 * i], y0[2 * i + 1]), p[i]); }, lane, slab, &maps.m[M_OUTB], 448 + col, mt * 128 + warp * 16);
        }
    }
}

typedef CUresult (*EncodeFn)(CUtensorMap*, CUtensorMapDataType, cuuint32_t, void*, const cuuint64_t*, const cuuint64_t*,
                             const cuuint32_t*, const cuuint32_t*, CUtensorMapInterleave, CUtensorMapSwizzle,
                             CUtensorMapL2promotion, CUtensorMapFloatOOBfill);

struct Dim { uint64_t size, stride; uint32_t box; };
void encode(EncodeFn fn, CUtensorMap* m, const void* ptr, CUtensorMapSwizzle sw, Dim d0, Dim d1, Dim d2 = {0, 0, 0}, Dim d3 = {0, 0, 0}) {
    const cuuint64_t dims[4] = {d0.size, d1.size, d2.size, d3.size};
    const cuuint64_t strides[3] = {d1.stride, d2.stride, d3.stride};
    const cuuint32_t box[4] = {d0.box, d1.box, d2.box, d3.box};
    const cuuint32_t es[4] = {1, 1, 1, 1};
    fn(m, CU_TENSOR_MAP_DATA_TYPE_BFLOAT16, d3.size ? 4 : d2.size ? 3 : 2, const_cast<void*>(ptr), dims, strides, box, es,
       CU_TENSOR_MAP_INTERLEAVE_NONE, sw, CU_TENSOR_MAP_L2_PROMOTION_L2_128B, CU_TENSOR_MAP_FLOAT_OOB_FILL_NONE);
}

}

extern "C" void kernel_launch(void* const* d_in, const int* in_sizes, int n_in, void* d_out, int out_size) {
    (void)in_sizes; (void)n_in; (void)out_size;
    void* fnp = nullptr;
    cudaDriverEntryPointQueryResult st;
    cudaGetDriverEntryPoint("cuTensorMapEncodeTiled", &fnp, cudaEnableDefault, &st);
    EncodeFn fn = (EncodeFn)fnp;
    void* scratch = nullptr;
    cudaGetSymbolAddress(&scratch, g_scratch);
    int dev = 0, sms = 0;
    cudaGetDevice(&dev);
    cudaDeviceGetAttribute(&sms, cudaDevAttrMultiProcessorCount, dev);
    auto kernel = sms == 132 ? fused_kernel<true> : fused_kernel<false>;
    cudaFuncSetAttribute(kernel, cudaFuncAttributeMaxDynamicSharedMemorySize, SMEM_BYTES);

    const CUtensorMapSwizzle S128 = CU_TENSOR_MAP_SWIZZLE_128B, S0 = CU_TENSOR_MAP_SWIZZLE_NONE;
    const Dim one = {1, 16, 1};
    Maps maps;
    encode(fn, &maps.m[M_XA], d_in[0], S128, {896, 2, 64}, {1024, 1792, 128}, one, one);
    encode(fn, &maps.m[M_WQK], d_in[1], S128, {112, 2, 64}, {448, 2688, 32}, {3, 896, 2}, {4, 224, 1});
    encode(fn, &maps.m[M_WV], d_in[1], S128, {112, 2, 64}, {448, 2688, 64}, one, {12, 224, 1});
    encode(fn, &maps.m[M_XH], d_in[0], S128, {448, 2, 64}, {128, 1792, 8}, {8, 128 * 1792, 8}, {2, 896, 2});
    encode(fn, &maps.m[M_WO], d_in[2], S128, {112, 2, 64}, {448, 896, 64}, one, {4, 224, 1});
    encode(fn, &maps.m[M_XB], d_in[3], S128, {448, 2, 64}, {1024, 896, 64}, {2, 896 * 1024, 2}, one);
    encode(fn, &maps.m[M_CR], d_in[4], S128, {2048, 2, 64}, {2048, 4096, 128});
    encode(fn, &maps.m[M_CI], d_in[5], S128, {2048, 2, 64}, {2048, 4096, 128});
    encode(fn, &maps.m[M_WR], d_in[6], S128, {448, 2, 64}, {448, 896, 112}, one, one);
    encode(fn, &maps.m[M_WI], d_in[7], S128, {448, 2, 64}, {448, 896, 112});
    encode(fn, &maps.m[M_OUTA], d_out, S0, {1792, 2, 112}, {1024, 3584, 8});
    encode(fn, &maps.m[M_OUTB], d_out, S0, {896, 2, 112}, {2048, 1792, 8});

    kernel<<<132, 384, SMEM_BYTES>>>((Scratch*)scratch, maps);
}
```

```cpp
#include <cuda.h>
#include <cuda_bf16.h>
#include <cuda_runtime.h>
#include <stdint.h>

namespace {

constexpr uint32_t SLOT = 16384;
constexpr int NA = 7;
constexpr uint32_t BRING = NA * SLOT;
constexpr uint32_t HALO = BRING + 6 * SLOT;
constexpr uint32_t HSLOT = 1792;
constexpr uint32_t WSLOT = 3584;
constexpr uint32_t BLOB = 14336;
constexpr uint32_t BARS = 14 * SLOT;
constexpr uint32_t BAR_FULL = BARS;
constexpr uint32_t BAR_EMPTY = BARS + 64;
constexpr uint32_t BAR_RDY = BARS + 128;
constexpr uint32_t BAR_DEP = BARS + 168;
constexpr uint32_t BAR_HALO = BARS + 192;
constexpr uint32_t BAR_PART = BARS + 208;
constexpr uint32_t BAR_HINT = BARS + 224;
constexpr uint32_t TAG = BARS + 240;
constexpr uint32_t HSPARE = BARS + 256 + 1024;
constexpr uint32_t SMEM_BYTES = HSPARE + HSLOT;
constexpr uint32_t base = 1024;
constexpr int SPIN_LIMIT = 1 << 16;

#define E_EXTRA 0
#define HALO_K_AT 10
#define HALO_V_AT 19
#define O_SLICE 4
#define B_SLICE 4
#define LEAD 3
#define TURN 4
#define PACE 450
#define O_FIRST 8
#define LAZY 1
#define P_FIRST 4
#define MMA_SYNC 2
#define A_OWN 4
#define A_OWN2 20
#define E_STEPS 0
#define HINT_AT 1
#define WO_IMG 1
#define GPC_MAP 0x64752310u

constexpr int NBL = 13 + E_EXTRA;
constexpr int NBE = NBL + (E_STEPS > 0);
constexpr int POUT = 33 + NBE;
constexpr int ELAST = POUT + 6;
constexpr int LLAST = 52 - E_EXTRA;
constexpr uint32_t LSLAB = ((LLAST - 6) % NA) * SLOT;
static_assert(TURN <= 4, "the output is staged in the slots of the seventh-last stage");

enum { M_XB, M_XA, M_XH, M_WR, M_WQK, M_WV, M_WO, M_WI, M_CR, M_CI, M_OUTA, M_OUTB, M_COUNT };
struct __align__(64) Maps { CUtensorMap m[M_COUNT]; };

constexpr int CNT_A = 0;
constexpr int CNT_B = 8;
constexpr int CNT_W = 12;
constexpr int CNT_O = 16;
constexpr int CNT_P = 32;
constexpr int CNT_COUNT = 96;

struct Scratch {
    uint8_t ab[64 * 4 * BLOB];
    uint8_t o[16 * 7 * SLOT];
    uint8_t part[64 * 2 * BLOB];
    uint8_t halo[64 * 2 * 2048];
    uint8_t wo[4 * 7 * SLOT];
    unsigned cnt[CNT_COUNT * 32];
    unsigned epoch[132 * 4 * 8];
};
__device__ __align__(1024) Scratch g_scratch;

__device__ __forceinline__ unsigned clk32() { unsigned c; asm volatile("mov.u32 %0, %%clock;" : "=r"(c)); return c; }

#define PROF(idx)

__device__ __forceinline__ void mbar_init(uint32_t bar, uint32_t cnt) {
    asm volatile("mbarrier.init.shared::cta.b64 [%0], %1;" ::"r"(bar), "r"(cnt) : "memory");
}
__device__ __forceinline__ void mbar_expect(uint32_t bar, uint32_t bytes) {
    asm volatile("mbarrier.arrive.expect_tx.shared::cta.b64 _, [%0], %1;" ::"r"(bar), "r"(bytes) : "memory");
}
__device__ __forceinline__ void mbar_arrive(uint32_t bar) {
    asm volatile("mbarrier.arrive.shared::cta.b64 _, [%0];" ::"r"(bar) : "memory");
}
__device__ __forceinline__ bool mbar_try(uint32_t bar, uint32_t parity) {
    uint32_t ok;
    asm volatile("{\n.reg .pred p;\nmbarrier.try_wait.parity.shared::cta.b64 p, [%1], %2;\nselp.u32 %0, 1, 0, p;\n}\n"
                 : "=r"(ok) : "r"(bar), "r"(parity) : "memory");
    return ok;
}
__device__ __forceinline__ void mbar_wait(uint32_t bar, uint32_t parity) {
#pragma unroll 1
    for (int n = 0; n < SPIN_LIMIT; n++)
        if (mbar_try(bar, parity)) break;
}
__device__ __forceinline__ bool elect() {
    uint32_t p;
    asm volatile("{\n.reg .pred p;\nelect.sync _|p, 0xffffffff;\nselp.u32 %0, 1, 0, p;\n}\n" : "=r"(p));
    return p;
}
__device__ __forceinline__ void nb_sync(int id, int n) { asm volatile("bar.sync %0, %1;" ::"r"(id), "r"(n) : "memory"); }
__device__ __forceinline__ void nb_arrive(int id, int n) { asm volatile("bar.arrive %0, %1;" ::"r"(id), "r"(n) : "memory"); }
__device__ __forceinline__ void warp_arrive(uint32_t bar) {
    __syncwarp();
    if (elect()) mbar_arrive(bar);
}
__device__ __forceinline__ uint32_t band(uint32_t x, uint32_t m) {
    uint32_t r;
    asm volatile("and.b32 %0, %1, %2;" : "=r"(r) : "r"(x), "r"(m));
    return r;
}
__device__ __forceinline__ uint32_t dup(uint32_t x, uint32_t zero) {
    uint32_t r;
    asm volatile("xor.b32 %0, %1, %2;" : "=r"(r) : "r"(x), "r"(zero));
    return r;
}

__device__ __forceinline__ void tma_ld2(uint32_t dst, const CUtensorMap* m, int c0, int c1, uint32_t bar) {
    asm volatile("cp.async.bulk.tensor.2d.shared::cluster.global.mbarrier::complete_tx::bytes [%0], [%1, {%3, %4}], [%2];"
                 ::"r"(dst), "l"(m), "r"(bar), "r"(c0), "r"(c1) : "memory");
}
__device__ __forceinline__ void tma_ld4(uint32_t dst, const CUtensorMap* m, int c0, int c1, int c2, int c3, uint32_t bar) {
    asm volatile("cp.async.bulk.tensor.4d.shared::cluster.global.mbarrier::complete_tx::bytes [%0], [%1, {%3, %4, %5, %6}], [%2];"
                 ::"r"(dst), "l"(m), "r"(bar), "r"(c0), "r"(c1), "r"(c2), "r"(c3) : "memory");
}
__device__ __forceinline__ void bulk_ld(uint32_t dst, const void* src, uint32_t bytes, uint32_t bar) {
    asm volatile("cp.async.bulk.shared::cluster.global.mbarrier::complete_tx::bytes [%0], [%1], %2, [%3];"
                 ::"r"(dst), "l"(src), "r"(bytes), "r"(bar) : "memory");
}
__device__ __forceinline__ void bulk_st(void* dst, uint32_t src, uint32_t bytes) {
    asm volatile("cp.async.bulk.global.shared::cta.bulk_group [%0], [%1], %2;" ::"l"(dst), "r"(src), "r"(bytes) : "memory");
}
__device__ __forceinline__ void tma_st2(const CUtensorMap* m, int c0, int c1, uint32_t src) {
    asm volatile("cp.async.bulk.tensor.2d.global.shared::cta.bulk_group [%0, {%1, %2}], [%3];"
                 ::"l"(m), "r"(c0), "r"(c1), "r"(src) : "memory");
}
__device__ __forceinline__ void bulk_commit() { asm volatile("cp.async.bulk.commit_group;" ::: "memory"); }
__device__ __forceinline__ void bulk_wait_read() { asm volatile("cp.async.bulk.wait_group.read 0;" ::: "memory"); }
__device__ __forceinline__ void fence_async_smem() { asm volatile("fence.proxy.async.shared::cta;" ::: "memory"); }
__device__ __forceinline__ void fence_async_global() { asm volatile("fence.proxy.async.global;" ::: "memory"); }

__device__ __forceinline__ void signal(Scratch* sc, int idx) {
    asm volatile("fence.proxy.async;\nred.relaxed.gpu.global.add.u32 [%0], 1;" ::"l"(&sc->cnt[idx * 32]) : "memory");
}
__device__ __forceinline__ unsigned peek(const unsigned* p) {
    unsigned v;
    asm volatile("ld.relaxed.gpu.global.u32 %0, [%1];" : "=r"(v) : "l"(p) : "memory");
    return v;
}
__device__ __forceinline__ void await(Scratch* sc, int idx, unsigned target) {
    const unsigned* p = &sc->cnt[idx * 32];
#pragma unroll 1
    for (int n = 0; n < SPIN_LIMIT; n++)
        if ((int)(peek(p) - target) >= 0) break;
    asm volatile("fence.acquire.gpu;" ::: "memory");
}
__device__ __forceinline__ void wait_dep(int k) {
    mbar_wait(base + BAR_DEP + k * 8, 0);
    fence_async_global();
}

#define WG_REGS                                                                                                     \
    "{%0,%1,%2,%3,%4,%5,%6,%7,%8,%9,%10,%11,%12,%13,%14,%15,%16,%17,%18,%19,%20,%21,%22,%23,%24,%25,%26,%27,"       \
    "%28,%29,%30,%31,%32,%33,%34,%35,%36,%37,%38,%39,%40,%41,%42,%43,%44,%45,%46,%47,%48,%49,%50,%51,%52,%53,%54,%55}"
#define WG_OPS(C)                                                                                                   \
    C(d[0]), C(d[1]), C(d[2]), C(d[3]), C(d[4]), C(d[5]), C(d[6]), C(d[7]), C(d[8]), C(d[9]), C(d[10]), C(d[11]),   \
    C(d[12]), C(d[13]), C(d[14]), C(d[15]), C(d[16]), C(d[17]), C(d[18]), C(d[19]), C(d[20]), C(d[21]), C(d[22]),   \
    C(d[23]), C(d[24]), C(d[25]), C(d[26]), C(d[27]), C(d[28]), C(d[29]), C(d[30]), C(d[31]), C(d[32]), C(d[33]),   \
    C(d[34]), C(d[35]), C(d[36]), C(d[37]), C(d[38]), C(d[39]), C(d[40]), C(d[41]), C(d[42]), C(d[43]), C(d[44]),   \
    C(d[45]), C(d[46]), C(d[47]), C(d[48]), C(d[49]), C(d[50]), C(d[51]), C(d[52]), C(d[53]), C(d[54]), C(d[55])

template <int TA, int TB, int SB, bool INIT, uint32_t AH, uint32_t BH>
__device__ __forceinline__ void wgmma112(float (&d)[56], uint32_t alo, uint32_t blo) {
    if (INIT) {
        asm volatile("{\n.reg .pred p;\n.reg .b64 da, db;\nsetp.ne.b32 p, 0, 0;\nmov.b64 da, {%56, %61};\nmov.b64 db, {%57, %62};\n"
                     "wgmma.mma_async.sync.aligned.m64n112k16.f32.bf16.bf16 " WG_REGS ", da, db, p, 1, %59, %60, %58;\n}\n"
                     : WG_OPS("=f") : "r"(alo), "r"(blo), "n"(TB), "n"(SB), "n"(TA), "n"(AH), "n"(BH));
    } else {
        asm volatile("{\n.reg .pred p;\n.reg .b64 da, db;\nsetp.ne.b32 p, 1, 0;\nmov.b64 da, {%56, %61};\nmov.b64 db, {%57, %62};\n"
                     "wgmma.mma_async.sync.aligned.m64n112k16.f32.bf16.bf16 " WG_REGS ", da, db, p, 1, %59, %60, %58;\n}\n"
                     : WG_OPS("+f") : "r"(alo), "r"(blo), "n"(TB), "n"(SB), "n"(TA), "n"(AH), "n"(BH));
    }
}
__device__ __forceinline__ void acc_fence(float (&d)[56]) {
#pragma unroll
    for (int i = 0; i < 56; i++) asm volatile("" : "+f"(d[i])::"memory");
}

__device__ __forceinline__ uint32_t pack2(float lo, float hi) {
    uint32_t r;
    asm volatile("cvt.rn.bf16x2.f32 %0, %1, %2;" : "=r"(r) : "f"(hi), "f"(lo));
    return r;
}
__device__ __forceinline__ uint32_t movm(uint32_t a) {
    uint32_t r;
    asm volatile("movmatrix.sync.aligned.m8n8.trans.b16 %0, %1;" : "=r"(r) : "r"(a));
    return r;
}
__device__ __forceinline__ void stsm4(uint32_t addr, uint32_t a, uint32_t b, uint32_t c, uint32_t d) {
    asm volatile("stmatrix.sync.aligned.m8n8.x4.shared.b16 [%0], {%1,%2,%3,%4};" ::"r"(addr), "r"(a), "r"(b), "r"(c), "r"(d) : "memory");
}
__device__ __forceinline__ void sts1(uint32_t addr, uint32_t a) { asm volatile("st.shared.b32 [%0], %1;" ::"r"(addr), "r"(a) : "memory"); }
__device__ __forceinline__ uint32_t lds1(uint32_t addr) {
    uint32_t a;
    asm volatile("ld.shared.b32 %0, [%1];" : "=r"(a) : "r"(addr) : "memory");
    return a;
}
__device__ __forceinline__ void lds4(uint32_t addr, uint32_t* v) {
    asm volatile("ld.shared.v4.b32 {%0,%1,%2,%3}, [%4];" : "=r"(v[0]), "=r"(v[1]), "=r"(v[2]), "=r"(v[3]) : "r"(addr) : "memory");
}
__device__ __forceinline__ void stg1(uint8_t* p, uint32_t a) { asm volatile("st.global.b32 [%0], %1;" ::"l"(p), "r"(a) : "memory"); }
__device__ __forceinline__ void st_part(uint8_t* p, const uint32_t* v, uint32_t parity) {
    asm volatile("{\n.reg .b64 x, y;\nmov.b64 x, {%1, %2};\nmov.b64 y, {%3, %4};\nst.relaxed.gpu.global.v2.b64 [%0], {x, y};\n}\n"
                 ::"l"(p), "r"((v[0] & ~1u) | parity), "r"(v[1]), "r"((v[2] & ~1u) | parity), "r"(v[3]) : "memory");
}
__device__ __forceinline__ void mma16816(float (&d)[4], const uint32_t (&a)[4], uint32_t b0, uint32_t b1) {
    asm volatile("mma.sync.aligned.m16n8k16.row.col.f32.bf16.bf16.f32 {%0,%1,%2,%3}, {%4,%5,%6,%7}, {%8,%9}, {%0,%1,%2,%3};"
                 : "+f"(d[0]), "+f"(d[1]), "+f"(d[2]), "+f"(d[3]) : "r"(a[0]), "r"(a[1]), "r"(a[2]), "r"(a[3]), "r"(b0), "r"(b1));
}
__device__ __forceinline__ uint32_t add2(uint32_t a, uint32_t b) {
    uint32_t r;
    asm("add.rn.bf16x2 %0, %1, %2;" : "=r"(r) : "r"(a), "r"(b));
    return r;
}
__device__ __forceinline__ uint32_t max2(uint32_t a, uint32_t b) {
    uint32_t r;
    asm("max.bf16x2 %0, %1, %2;" : "=r"(r) : "r"(a), "r"(b));
    return r;
}
__device__ __forceinline__ void ld_tagged(const uint8_t* p, uint32_t& a, uint32_t& ta, uint32_t& b, uint32_t& tb) {
    asm volatile("{\n.reg .b64 x, y;\nld.relaxed.gpu.global.v2.b64 {x, y}, [%4];\nmov.b64 {%0, %1}, x;\nmov.b64 {%2, %3}, y;\n}\n"
                 : "=r"(a), "=r"(ta), "=r"(b), "=r"(tb) : "l"(p) : "memory");
}
__device__ __forceinline__ float bf_lo(uint32_t v) { return __uint_as_float(v << 16); }
__device__ __forceinline__ float bf_hi(uint32_t v) { return __uint_as_float(v & 0xFFFF0000u); }
__device__ __forceinline__ float rcp(float x) { float r; asm("rcp.approx.ftz.f32 %0, %1;" : "=f"(r) : "f"(x)); return r; }
__device__ __forceinline__ float ex2(float x) { float r; asm volatile("ex2.approx.ftz.f32 %0, %1;" : "=f"(r) : "f"(x)); return r; }

__device__ __forceinline__ uint32_t full_bar(int stage) { return base + BAR_FULL + (stage & 7) * 8; }
__device__ __forceinline__ void wait_released(int j) { mbar_wait(base + BAR_EMPTY + (j & 7) * 8, (j >> 3) & 1); }

template <int V>
struct Int { static constexpr int value = V; };

__host__ __device__ constexpr int bslot_e(int i) { return (i < 2 || i >= 14) ? (i + 5) % 7 : (i + 1) % 5; }
__host__ __device__ constexpr int bslot_l(int i) { return i % 6; }

template <uint32_t OFF>
struct Feed {
    int stage;
    uint32_t dst;
    __device__ __forceinline__ void seek(int i, int slot) { stage = i; dst = base + OFF + slot * SLOT; }
    template <int N>
    __device__ __forceinline__ uint32_t acquire() { wait_released(stage - N); return full_bar(stage); }
    template <int N>
    __device__ __forceinline__ void next() {
        stage++;
        dst += SLOT;
        if (dst == base + OFF + N * SLOT) dst = base + OFF;
    }
};
__device__ __forceinline__ int skip_own(int n, int mt) { return n == mt ? 15 : n; }

struct Desc { uint32_t lo, hi; };
__host__ __device__ constexpr Desc desc_const(uint32_t lbo, uint32_t sbo, uint32_t mode) { return {(lbo >> 4) << 16, (sbo >> 4) | (mode << 30)}; }
constexpr Desc D_K128 = desc_const(16, 1024, 1);
constexpr Desc D_N128 = desc_const(8192, 1024, 1);
constexpr Desc D_BLOB = desc_const(128, 256, 0);
constexpr Desc D_OT = desc_const(2048, 128, 0);

enum Kind { XW, XWN, QK, BIG, OUT };

struct Ring {
    int stage;
    uint32_t a, b;
    uint32_t wg;
    uint32_t zero;
    bool releaser;
    __device__ __forceinline__ void seek(int i, int bslot) {
        stage = i;
        a = (base + (i % NA) * SLOT) >> 4;
        b = (base + BRING + bslot * SLOT) >> 4;
    }
    __device__ __forceinline__ void wait() { mbar_wait(full_bar(stage), (stage >> 3) & 1); }
    __device__ __forceinline__ void take_turn() { nb_sync(1 + wg, 256); }
    __device__ __forceinline__ void pin() {
        uint32_t n = 0;
#pragma unroll 1
        do {
            asm volatile("pmevent 7;" ::: "memory");
        } while (n++ < zero);
    }
    __device__ __forceinline__ void mma_begin() {
        pin();
        if (!wg) take_turn();
        pin();
    }
    __device__ __forceinline__ void mma_end() {
        pin();
        if (wg) nb_arrive(3, 256);
        nb_sync(3 - wg, 256);
    }
    template <Kind K, int NBS, bool INIT, int SB = 1, bool TAIL = false, int S0 = 0, int S1 = 4>
    __device__ __forceinline__ void run(float (&d)[56], float (&e)[56], bool first = true, bool last = true, bool more = true) {
        if (first) take_turn();
        asm volatile("wgmma.fence.sync.aligned;" ::: "memory");
        if (K == QK) {
            const uint32_t da = D_K128.lo + (base >> 4) + (stage >> 1) * (SLOT >> 4) + (stage & 1) * 4 + wg * 512, db = D_N128.lo + b;
            wgmma112<0, 1, 1, INIT, D_K128.hi, D_N128.hi>(d, da, db);
            wgmma112<0, 1, 1, INIT, D_K128.hi, D_N128.hi>(e, da, db + 256);
            wgmma112<0, 1, 1, false, D_K128.hi, D_N128.hi>(d, da + 2, db + 128);
            wgmma112<0, 1, 1, false, D_K128.hi, D_N128.hi>(e, da + 2, db + 384);
        } else {
            constexpr int TA = K == OUT, TB = K != XW;
            constexpr uint32_t sa = K == OUT ? 256 : 2, sb = K == XW ? 2 : K == BIG ? 224 : 128;
            constexpr Desc A = K == OUT ? D_OT : D_K128, B = K == XW ? D_K128 : K == BIG ? D_BLOB : D_N128;
            const uint32_t da = A.lo + a + wg * (K == OUT ? 64 : 512), db = B.lo + b;
            if (S0 == 0) wgmma112<TA, TB, SB, INIT, A.hi, B.hi>(d, da, db);
#pragma unroll
            for (int q = S0 ? S0 : 1; q < S1; q++) wgmma112<TA, TB, SB, false, A.hi, B.hi>(d, da + q * sa, db + q * sb);
        }
        asm volatile("wgmma.commit_group.sync.aligned;" ::: "memory");
        if (!TAIL) asm volatile("wgmma.wait_group.sync.aligned 1;" ::: "memory");
        if (last) nb_arrive(2 - wg, 256);
        if (!TAIL && stage > 0) {
            if (releaser) mbar_arrive(base + BAR_EMPTY + ((stage - 1) & 7) * 8);
        }
        stage++;
        a += SLOT >> 4;
        if (a == (base + NA * SLOT) >> 4) a = base >> 4;
        b += SLOT >> 4;
        if (b == (base + BRING + NBS * SLOT) >> 4) b = (base + BRING) >> 4;
        if (more) wait();
    }
    template <Kind K, int NBS, bool INIT, int SB = 1, bool TAIL = false, int S0 = 0, int S1 = 4>
    __device__ __forceinline__ void run(float (&d)[56], bool first = true, bool last = true, bool more = true) {
        run<K, NBS, INIT, SB, TAIL, S0, S1>(d, d, first, last, more);
    }
};

template <int I0 = 0, int I1 = 28>
__device__ __forceinline__ void pack_all(const float (&d)[56], uint32_t (&p)[28]) {
#pragma unroll
    for (int i = I0; i < I1; i++) p[i] = pack2(d[2 * i], d[2 * i + 1]);
}
template <int I0, int I1>
__device__ __forceinline__ void store_frags(uint8_t* dst, const uint32_t (&p)[28]) {
#pragma unroll
    for (int i = I0; i < I1; i++) stg1(dst + i * 128, p[i]);
}
template <int I0, int I1>
__device__ __forceinline__ void stage_frags(uint32_t lane_addr, const uint32_t (&p)[28]) {
#pragma unroll
    for (int i = I0; i < I1; i += 4) stsm4(lane_addr + i * 128, p[i], p[i + 1], p[i + 2], p[i + 3]);
}
template <class F>
__device__ __forceinline__ void store_out(F frag, int lane, uint32_t slab, const CUtensorMap* m, int c0, int c1) {
    const bool swap = lane & 16;
    const uint32_t addr = slab + (lane & 7) * 224 + ((lane >> 3) ^ ((lane >> 2) & 1)) * 16;
#pragma unroll
    for (int h = 0; h < 2; h++) {
#pragma unroll
        for (int c = 0; c < 14; c += 4) {
            const uint32_t t0 = frag(2 * c + h), t1 = frag(2 * c + 2 + h);
            if (c < 12) {
                const uint32_t t2 = frag(2 * c + 4 + h), t3 = frag(2 * c + 6 + h);
                stsm4(addr + h * 1792 + c * 16, swap ? t1 : t0, swap ? t0 : t1, swap ? t3 : t2, swap ? t2 : t3);
            } else {
                asm volatile("stmatrix.sync.aligned.m8n8.x2.shared.b16 [%0], {%1,%2};" ::"r"(addr + h * 1792 + c * 16), "r"(swap ? t1 : t0), "r"(swap ? t0 : t1) : "memory");
            }
        }
        fence_async_smem();
        __syncwarp();
        if (elect()) tma_st2(m, c0, c1 + 8 * h, slab + h * 1792);
    }
    if (elect()) {
        bulk_commit();
        bulk_wait_read();
    }
}
__host__ __device__ constexpr int tile_of(int t) { return 7 * (t >> 2) + 3 * ((t >> 1) & 1) + 2 * (t & 1); }

struct Role {
    bool H;
    int L, mt, ns, id;
    int kind, a0, a1, b3;
};
template <bool BY_SM>
__device__ __forceinline__ Role decode_role() {
    uint32_t sm;
    if (BY_SM) asm volatile("mov.u32 %0, %%smid;" : "=r"(sm));
    else asm volatile("mov.u32 %0, %%ctaid.x;" : "=r"(sm));
    const int tpc = sm >> 1, q2 = ((tpc - 32) * 37) >> 8;
    const int gpc = tpc < 32 ? tpc & 7 : tpc < 60 ? tpc - 31 - 7 * q2 : 0;
    const int pos = tpc < 32 ? tpc >> 3 : tpc < 60 ? q2 + 4 : tpc - 56;
    Role r;
    r.H = sm >= 128;
    const int grp = (GPC_MAP >> (4 * gpc)) & 7;
    r.L = grp & 1;
    r.mt = (grp >> 1) * 4 + (pos >> 1);
    r.ns = (pos & 1) * 2 + (sm & 1);
    r.id = r.H ? sm : grp * 16 + pos * 2 + (sm & 1);
    r.kind = r.H ? 2 : r.L;
    r.a0 = r.L ? (r.mt >> 3) * 448 : 0;
    r.a1 = r.L ? (r.mt & 7) * 128 : r.H ? 120 : r.mt * 64;
    r.b3 = r.H ? 4 + r.ns : r.L ? r.ns : 0;
    return r;
}

__device__ __forceinline__ void first_fill(const Maps& maps, const Role& r, int i) {
    const bool E = r.kind == 0;
    const CUtensorMap* ma = &maps.m[r.kind];
    const uint32_t bar = full_bar(i);
    const int k = (i * 64) >> r.L;
    const bool has_a = !(i & r.L), has_b = i < 7 - r.L;
    const uint32_t dst = base + BRING + (E ? (0x2104365u >> (4 * i)) & 7 : i) * SLOT;
    mbar_expect(bar, (has_a ? SLOT : 0) + (has_b ? (E ? BLOB : SLOT) : 0));
    if (has_a) tma_ld4(base + (i >> r.L) * SLOT, ma, r.a0 + k, r.a1, 0, 0, bar);
    if (has_b) {
        tma_ld4(dst, ma + 3, E ? k : 0, E ? r.ns * 112 : k, 0, r.b3, bar);
        if (!E) tma_ld4(dst + 8192, ma + 3, 64, k, 0, r.b3, bar);
        mbar_arrive(bar);
    }
}
static_assert(bslot_e(0) == 5 && bslot_e(1) == 6 && bslot_e(2) == 3 && bslot_e(3) == 4 && bslot_e(4) == 0 && bslot_e(6) == 2, "");

template <bool BY_SM>
__global__ void __launch_bounds__(384, 1) fused_kernel(Scratch* sc, const __grid_constant__ Maps maps) {
    const unsigned t_open = clk32();
    const int warp = __shfl_sync(0xffffffffu, threadIdx.x >> 5, 0);
    if (warp == 8) {
        if (elect()) {
#pragma unroll
            for (int i = 0; i < LEAD; i++) mbar_init(base + BAR_FULL + i * 8, 2);
            asm volatile("fence.mbarrier_init.release.cluster;" ::: "memory");
            const Role r = decode_role<BY_SM>();
#pragma unroll 1
            for (int i = 0; i < LEAD; i++) {
                first_fill(maps, r, i);
            }
        }
    }
    if (warp == 9) {
        if (elect()) {
#pragma unroll
            for (int i = 0; i < 8; i++) mbar_init(base + BAR_EMPTY + i * 8, 4);
            asm volatile("fence.mbarrier_init.release.cluster;" ::: "memory");
        }
    } else if (warp == 10) {
        if (elect()) {
#pragma unroll
            for (int i = 0; i < 3; i++) mbar_init(base + BAR_RDY + i * 8, i < 2 ? 4 : 8);
#pragma unroll
            for (int i = 0; i < 2; i++) mbar_init(base + BAR_HALO + i * 8, 1);
            asm volatile("fence.mbarrier_init.release.cluster;" ::: "memory");
        }
    } else if (warp == 11) {
        if (elect()) {
#pragma unroll
            for (int i = LEAD; i < 8; i++) mbar_init(base + BAR_FULL + i * 8, 2);
#pragma unroll
            for (int i = 0; i < 3; i++) mbar_init(base + BAR_DEP + i * 8, 1);
#pragma unroll
            for (int i = 0; i < 4; i++) mbar_init(base + BAR_PART + i * 8, 1);
            asm volatile("fence.mbarrier_init.release.cluster;" ::: "memory");
        }
    }
    __syncthreads();

    const Role role = decode_role<BY_SM>();
    int lane = threadIdx.x & 31;
    asm volatile("" : "+r"(lane));
    const bool roleH = role.H;
    const int roleL = role.L, mt = role.mt, ns = role.ns, bid = role.id;
    const int par = mt >> 3, blk = mt & 7, col = ns * 112;

    if (__builtin_expect(warp >= 8, 1)) {
        asm volatile("setmaxnreg.dec.sync.aligned.u32 56;");
#define PROF_FEED_A
#define PROF_FEED_B
        if (__builtin_expect(warp == 8, 1)) {
            if (elect()) {
                PROF(129);
#pragma unroll 1
                for (int i = LEAD; i < 7; i++) {
                    while (clk32() - t_open < i * PACE) {}
                    first_fill(maps, role, i);
                }
                PROF(134);
                Feed<0> f;
                const int row = mt * 128;
                auto c_run = [&](const CUtensorMap* m, int off, int n0, int n1) {
#pragma unroll 1
                    for (int n = n0; n < n1; n++) {
                        const uint32_t bar = f.acquire<NA>();
                        mbar_expect(bar, SLOT);
                        tma_ld2(f.dst, m, (off + skip_own(n, mt)) * 64, row, bar);
                        PROF_FEED_A;
                        f.next<NA>();
                    }
                };
                if (roleH) {
                    mbar_expect(base + BAR_DEP, 7 * SLOT);
#pragma unroll 1
                    for (int i = 0; i < 7; i++) {
                        const uint32_t dst = base + (i < 6 ? i : 7) * SLOT;
                        if (i < 6) wait_released(7 + i);
                        tma_ld4(dst, &maps.m[M_WO], 0, i * 64, 0, ns, base + BAR_DEP);
                        tma_ld4(dst + 8192, &maps.m[M_WO], 64, i * 64, 0, ns, base + BAR_DEP);
                    }
                    mbar_wait(base + BAR_DEP, 0);
                    mbar_wait(base + BAR_RDY + 16, 0);
#pragma unroll 1
                    for (int i = 0; i < 7; i++) bulk_st(sc->wo + (size_t)(ns * 7 + i) * SLOT, base + (i < 6 ? i : 7) * SLOT, SLOT);
                    bulk_commit();
                    asm volatile("cp.async.bulk.wait_group 0;" ::: "memory");
                    signal(sc, CNT_W + ns);
                } else if (!roleL) {
                    f.seek(14, 0);
#pragma unroll 1
                    for (int i = 0; i < 4; i++) {
                        const uint32_t bar = f.acquire<NA>();
                        mbar_expect(bar, SLOT);
                        tma_ld2(f.dst, &maps.m[M_CR + (i >> 1)], ((i & 1) * 16 + mt) * 64, row, bar);
                        mbar_arrive(bar);
                        PROF_FEED_A;
                        f.next<NA>();
                    }
                    c_run(&maps.m[M_CR], 0, 0, 15);
                    c_run(&maps.m[M_CI], 0, 0, NBE);
                    wait_dep(2);
#pragma unroll 1
                    for (int i = 0; i < 7; i++) {
                        const uint32_t bar = f.acquire<NA>();
                        mbar_expect(bar, SLOT);
                        bulk_ld(f.dst, sc->o + (size_t)(mt * 7 + i) * SLOT, SLOT, bar);
                        PROF_FEED_A;
                        f.next<NA>();
                    }
                } else {
#pragma unroll 1
                    for (int i = 4; i < 7; i++) {
                        wait_released(2 * i - 8);
                        mbar_expect(full_bar(2 * i), SLOT);
                        tma_ld4(base + i * SLOT, &maps.m[M_XA], par * 448 + i * 64, blk * 128, 0, 0, full_bar(2 * i));
                    }
                    wait_released(HALO_K_AT);
                    mbar_arrive(base + BAR_DEP + 16);
                    f.seek(21, 0);
                    c_run(&maps.m[M_CR], 16, 0, 15);
                    c_run(&maps.m[M_CI], 16, 0, 15);
                    c_run(&maps.m[M_CI], 0, NBL, 15);
                }
            }
        } else if (warp == 11) {
            if (elect()) {
                Feed<BRING> f;
                auto blob_run = [&](auto nbs, int quarter, int n0, int n1) {
                    constexpr int N = decltype(nbs)::value;
                    const uint8_t* src = sc->ab + (size_t)(quarter * 64 + ns) * BLOB;
#pragma unroll 1
                    for (int n = n0; n < n1; n++) {
                        const uint32_t bar = f.template acquire<N>();
                        mbar_expect(bar, BLOB);
                        bulk_ld(f.dst, src + skip_own(n, mt) * (4 * BLOB), BLOB, bar);
                        PROF_FEED_B;
                        f.template next<N>();
                    }
                };
                auto w_run = [&](auto nbs, const CUtensorMap* m, int slice, bool no_a) {
                    constexpr int N = decltype(nbs)::value;
#pragma unroll 1
                    for (int i = 0; i < 7; i++) {
                        const uint32_t bar = f.template acquire<N>();
                        mbar_expect(bar, SLOT);
                        tma_ld4(f.dst, m, 0, i * 64, 0, slice, bar);
                        tma_ld4(f.dst + 8192, m, 64, i * 64, 0, slice, bar);
                        if (no_a) mbar_arrive(bar);
                        PROF_FEED_B;
                        f.template next<N>();
                    }
                };
                if (roleH) {
                    f.seek(7, 0);
                    w_run(Int<7>(), &maps.m[M_WV], 8 + ns, true);
                } else if (!roleL) {
                    f.seek(7, bslot_e(7));
#pragma unroll 1
                    for (int i = 0; i < 7; i++) {
                        const uint32_t bar = f.acquire<5>();
                        mbar_expect(bar, BLOB);
                        tma_ld2(f.dst, &maps.m[M_WI], i * 64, col, bar);
                        mbar_arrive(bar);
                        PROF_FEED_B;
                        f.next<5>();
                    }
                    f.seek(18, bslot_e(18));
                    wait_dep(0);
                    blob_run(Int<7>(), 0, 0, 15);
                    wait_dep(1);
                    blob_run(Int<7>(), 2, 0, NBE);
                    mbar_wait(base + BAR_HINT, 0);
                    fence_async_global();
#pragma unroll 1
                    for (int i = 0; i < 7; i++) {
                        const uint32_t bar = f.acquire<7>();
                        mbar_expect(bar, SLOT);
                        bulk_ld(f.dst, sc->wo + (size_t)(ns * 7 + i) * SLOT, SLOT, bar);
                        PROF_FEED_B;
                        f.next<7>();
                    }
                } else {
                    f.seek(6, 0);
#pragma unroll 1
                    for (int i = 6; i < 14; i++) {
                        const uint32_t bar = f.acquire<6>();
                        mbar_expect(bar, SLOT);
                        tma_ld4(f.dst, &maps.m[M_WQK], 0, i * 32, 0, ns, bar);
                        tma_ld4(f.dst + 8192, &maps.m[M_WQK], 64, i * 32, 0, ns, bar);
                        if (i & 1) mbar_arrive(bar);
                        PROF_FEED_B;
                        f.next<6>();
                    }
                    w_run(Int<6>(), &maps.m[M_WV], 8 + ns, true);
                    wait_dep(0);
                    blob_run(Int<6>(), 1, 0, 15);
                    wait_dep(1);
                    blob_run(Int<6>(), 3, 0, 15);
                    blob_run(Int<6>(), 2, NBL, 15);
                    fence_async_smem();
#pragma unroll 1
                    for (int h = 0; h < 2; h++) {
                        mbar_wait(base + BAR_HINT + h * 8, 0);
                        PROF(153 + h);
                        mbar_expect(base + BAR_PART + h * 8, BLOB);
                        bulk_ld(base + (h ? HALO : LSLAB), sc->part + (size_t)((ns * 16 + mt) * 2 + h) * BLOB, BLOB, base + BAR_PART + h * 8);
                    }
                }
            }
        } else if (roleH) {
            if ((!WO_IMG || warp == 9) && elect()) {
                wait_released(warp == 9 ? 0 : 7);
#pragma unroll 1
                for (int i = 0; i < 7; i++) {
                    if (warp == 9) {
                        asm volatile("cp.async.bulk.prefetch.tensor.2d.L2.global [%0, {%1, %2}];" ::"l"(&maps.m[M_WI]), "r"(i * 64), "r"(col) : "memory");
                    } else {
                        asm volatile("cp.async.bulk.prefetch.tensor.4d.L2.global [%0, {%1, %2, 0, %3}];" ::"l"(&maps.m[M_WO]), "r"(0), "r"(i * 64), "r"(ns) : "memory");
                        asm volatile("cp.async.bulk.prefetch.tensor.4d.L2.global [%0, {%1, %2, 0, %3}];" ::"l"(&maps.m[M_WO]), "r"(64), "r"(i * 64), "r"(ns) : "memory");
                    }
                }
            }
        } else if (warp == 10) {
            if (elect()) {
                unsigned* epoch_ptr = &sc->epoch[(bid * 4 + 2) * 8];
                const unsigned ep = *epoch_ptr + 1;
                sts1(base + TAG, ep);
                asm volatile("prefetch.tensormap [%0];" ::"l"(&maps.m[M_OUTA + roleL]) : "memory");
                await(sc, CNT_A + roleL * 4 + ns, ep * 16);
                mbar_arrive(base + BAR_DEP);
                PROF(150);
                await(sc, CNT_B + ns, ep * 16);
                mbar_arrive(base + BAR_DEP + 8);
                PROF(151);
                if (!roleL) {
                    await(sc, CNT_W + ns, ep);
                    mbar_arrive(base + BAR_HINT);
                    PROF(153);
                    await(sc, CNT_O + mt, ep * 4);
                    mbar_arrive(base + BAR_DEP + 16);
                } else {
                    await(sc, CNT_P + mt * 4 + ns, ep * 2 - 1);
                    mbar_arrive(base + BAR_HINT);
                    await(sc, CNT_P + mt * 4 + ns, ep * 2);
                    mbar_arrive(base + BAR_HINT + 8);
                }
                PROF(152);
                *epoch_ptr = ep;
            }
        } else if (!roleL) {
            if (elect()) {
                mbar_wait(base + BAR_RDY, 0);
                PROF(130);
                signal(sc, CNT_A + ns);
                PROF(131);
                mbar_wait(base + BAR_RDY + 8, 0);
                signal(sc, CNT_A + 4 + ns);
                PROF(135);
                mbar_wait(base + BAR_RDY + 16, 0);
                PROF(132);
                signal(sc, CNT_B + ns);
                PROF(133);
            }
        } else {
            unsigned* epoch_ptr = &sc->epoch[(bid * 4 + 1) * 8];
            const unsigned tag = *epoch_ptr + 1;
#pragma unroll 1
            for (int kv = 0; kv < 2; kv++) {
                uint32_t v[16];
#pragma unroll
                for (int i = 0; i < 16; i++) v[i] = 0;
                if (kv) wait_released(HALO_V_AT - 4), wait_released(HALO_V_AT);
                else mbar_wait(base + BAR_DEP + 16, 0);
                if (blk > 0) {
                    const uint8_t* src = sc->halo + (size_t)(((mt - 1) * 4 + ns) * 2 + kv) * 2048 + lane * 16;
#pragma unroll 1
                    for (int n = 0; n < SPIN_LIMIT; n++) {
                        uint32_t stale = 0;
#pragma unroll
                        for (int i = 0; i < 4; i++) ld_tagged(src + i * 512, v[4 * i], v[4 * i + 1], v[4 * i + 2], v[4 * i + 3]);
#pragma unroll
                        for (int i = 0; i < 16; i += 2) stale |= v[i] ^ tag;
                        if (__all_sync(0xffffffffu, !(stale & 1))) break;
                    }
#pragma unroll
                    for (int c = 0; c < 14; c += 2) v[c] = (v[c] & ~1u) | ((v[15] >> c) & 1);
                }
#pragma unroll
                for (int i = 0; i < 14; i++) sts1(base + HALO + kv * (8 * HSLOT) + i * 128 + lane * 4, v[i]);
                warp_arrive(base + BAR_HALO + kv * 8);
                if (lane == 0) PROF(142 + kv);
            }
            if (elect()) {
                mbar_wait(base + BAR_RDY + 16, 0);
                PROF(130);
                signal(sc, CNT_O + mt);
                PROF(131);
                *epoch_ptr = tag;
            }
        }
    } else {
        asm volatile("setmaxnreg.inc.sync.aligned.u32 224;");
        Ring r;
        r.wg = warp >> 2;
        r.zero = blockIdx.y;
        r.releaser = lane + 1 == (warp >> 2);
        const int wg = warp >> 2;
        if (wg) nb_arrive(1, 256);
        uint8_t* part = sc->part + (size_t)(ns * 16 + mt) * (2 * BLOB) + warp * WSLOT + lane * 16;
        uint32_t p[28];

        if (roleH) {
            unsigned* epoch_ptr = &sc->epoch[bid * 4 * 8];
            const unsigned tag = *epoch_ptr + 1;
            uint8_t* hout = sc->halo + (size_t)((warp * 8 + ns) * 2) * 2048 + lane * 16;
            auto send = [&](int kv) {
#pragma unroll
                for (int h = 0; h < 2; h++) {
                    uint32_t v[16];
                    v[14] = v[15] = 0;
#pragma unroll
                    for (int c = 0; c < 14; c++) v[c] = p[2 * c + h];
#pragma unroll
                    for (int c = 0; c < 14; c += 2) v[15] |= (v[c] & 1) << c;
#pragma unroll
                    for (int i = 0; i < 4; i++) st_part(hout + (h * 8 + kv) * 2048 + i * 512, v + 4 * i, tag & 1);
                }
            };
            float x0[56], x1[56];
            r.seek(0, 0);
            r.wait();
            r.run<XWN, 7, true>(x0);
#pragma unroll 1
            for (int i = 1; i < 7; i++) r.run<XWN, 7, false>(x0);
            r.run<XWN, 7, true>(x1);
            acc_fence(x0);
            pack_all(x0, p);
            send(0);
#pragma unroll 1
            for (int i = 1; i < 7; i++) r.run<XWN, 7, false>(x1, true, i < 6 || !wg, i < 6);
            asm volatile("wgmma.wait_group.sync.aligned 0;" ::: "memory");
            acc_fence(x1);
            pack_all(x1, p);
#pragma unroll
            for (int i = 0; i < 28; i++) p[i] = movm(p[i]);
            send(1);
            warp_arrive(base + BAR_RDY + 16);
            if (threadIdx.x == 0) *epoch_ptr = tag;
        } else if (!roleL) {
            uint8_t* blob = sc->ab + (size_t)((wg * 16 + mt) * 4 + ns) * BLOB + (warp & 3) * WSLOT + lane * 4;
            const uint32_t own = base + BRING + wg * SLOT + (warp & 3) * WSLOT + lane * 16;
            float x0[56], x1[56];
            r.seek(0, bslot_e(0));
            r.wait();
            r.run<XW, 7, true>(x0);
            r.run<XW, 7, false>(x0);
            r.seek(2, bslot_e(2));
#pragma unroll 1
            for (int i = 2; i < 7; i++) r.run<XW, 5, false>(x0);

            r.seek(7, bslot_e(7));
            r.run<XW, 5, true, -1>(x1);
            acc_fence(x0);
            pack_all<0, LAZY ? 14 : 28>(x0, p);
#pragma unroll
            for (int i = 0; i < 2; i++) {
                if (wg == i) store_frags<0, 14>(blob, p);
                else stage_frags<0, A_OWN>(own + 5 * SLOT, p);
                r.run<XW, 5, false, -1>(x1);
                if (LAZY && i == 0) pack_all<14, 28>(x0, p);
                if (wg == i) {
                    store_frags<14, 28>(blob, p);
                    warp_arrive(base + BAR_RDY + i * 8);
                } else {
                    stage_frags<A_OWN, 2 * A_OWN>(own + 5 * SLOT, p);
                }
                r.run<XW, 5, false, -1>(x1);
            }
            stage_frags<2 * A_OWN, A_OWN2>(own + 5 * SLOT, p);
            r.run<XW, 5, false, -1>(x1);
            stage_frags<A_OWN2, 28>(own + 5 * SLOT, p);
            fence_async_smem();
            r.run<XW, 5, false, -1>(x1);

            r.seek(14, bslot_e(14));
            r.run<BIG, 7, true>(x0);
            acc_fence(x1);
            pack_all(x1, p);
            stage_frags<0, 28>(own, p);
            r.run<BIG, 7, false>(x0);
            fence_async_smem();
            blob += (size_t)128 * BLOB;
#pragma unroll
            for (int i = 0; i < 28; i++) {
                if (i % B_SLICE == 0) r.run<BIG, 7, false>(x0);
                stg1(blob + i * 128, p[i]);
            }
            warp_arrive(base + BAR_RDY + 16);
#pragma unroll 1
            for (int i = 17 + 27 / B_SLICE; i < 33 + NBL; i++) r.run<BIG, 7, false>(x0);
            if (E_STEPS) {
                r.seek(POUT - 1, bslot_e(POUT - 1));
                r.run<BIG, 7, false, 1, false, 0, E_STEPS>(x0);
            }

            const uint32_t tag = lds1(base + TAG);
            r.seek(POUT, bslot_e(POUT));
            r.run<OUT, 7, true>(x1);
            acc_fence(x0);
            pack_all(x0, p);
            auto hint = [&]() {
                if ((warp & 3) == 0 && elect())
                    asm volatile("red.relaxed.gpu.global.add.u32 [%0], 1;" ::"l"(&sc->cnt[(CNT_P + mt * 4 + ns) * 32]) : "memory");
            };
#pragma unroll
            for (int k = 0; k < 3; k++) {
                if (k < 2 && wg == k) {
                    if (HINT_AT == 0) hint();
#pragma unroll
                    for (int i = 0; i < P_FIRST; i++) st_part(part + i * 512, p + 4 * i, tag & 1);
                    if (HINT_AT == 1) hint();
                }
                if (k > 0 && wg == k - 1) {
                    if (HINT_AT == 2) hint();
#pragma unroll
                    for (int i = P_FIRST; i < 7; i++) st_part(part + i * 512, p + 4 * i, tag & 1);
                }
                if (k < 2) r.run<OUT, 7, false>(x1);
            }
#pragma unroll
            for (int i = 3; i < 7; i++) r.run<OUT, 7, false, 1, true>(x1, i <= 7 - TURN, i < 7 - TURN || (i == 6 && !wg), i < 6);

            asm volatile("wgmma.wait_group.sync.aligned 0;" ::: "memory");
            acc_fence(x1);
            const uint32_t slab = base + (wg ? BRING + bslot_e(ELAST - 6) * SLOT : ((ELAST - 6) % NA) * SLOT) + (warp & 3) * WSLOT;
            store_out([&](int i) { return pack2(x1[2 * i], x1[2 * i + 1]); }, lane, slab, &maps.m[M_OUTA], par * 896 + col, blk * 128 + warp * 16);
        } else {
            const int g = lane >> 2, tig = lane & 3;
            const uint32_t hin = base + HALO + warp * HSLOT + lane * 4;
            const uint32_t hpub = warp < 7 ? hin + HSLOT : base + HSPARE + lane * 4;
            auto publish = [&](const uint32_t (&h)[14], int c0, int c1) {
#pragma unroll
                for (int c = 0; c < 14; c++)
                    if (c >= c0 && c < c1) sts1(hpub + c * 128, h[c]);
            };
            float y0[56], y1[56], y2[56];
            r.seek(0, 0);
            r.wait();
            r.run<QK, 6, true>(y0, y1);
#pragma unroll 1
            for (int i = 1; i < 14; i++) r.run<QK, 6, false>(y0, y1);

            uint32_t m1[8][4], m0[8][4], lo[14], hi[14], q[2][8][2];
            auto pack_q = [&](int b) {
                uint32_t v[14];
#pragma unroll
                for (int c = 0; c < 14; c++) v[c] = pack2(y0[4 * c + 2 * b], y0[4 * c + 2 * b + 1]);
#pragma unroll
                for (int t = 0; t < 8; t++) {
                    const int c = tile_of(t);
                    q[b][t][0] = (t & 3) == 2 ? (tig >= 2 ? v[c] : 0u) : v[c];
                    q[b][t][1] = (t & 3) == 1 ? (tig < 2 ? v[c + 1] : 0u) : v[c + 1];
                }
            };
            auto fetch = [&](uint32_t src, int hp, int i0) {
#pragma unroll
                for (int t = 4 * hp; t < 4 * hp + 4; t++) {
                    m0[t][i0] = (t & 3) == 2 ? dup(m0[t - 1][3], r.zero) : lds1(src + tile_of(t) * 128);
                    m0[t][3] = lds1(src + tile_of(t) * 128 + 128);
                }
            };
            r.seek(14, bslot_l(14));
            r.run<XWN, 6, true>(y2);
            acc_fence(y0);
            acc_fence(y1);
#pragma unroll
            for (int c = 0; c < 14; c++) hi[c] = pack2(y1[4 * c + 2], y1[4 * c + 3]);
            publish(hi, 0, 7);
            r.run<XWN, 6, false>(y2);
            publish(hi, 7, 14);
#pragma unroll
            for (int c = 0; c < 14; c++) lo[c] = pack2(y1[4 * c], y1[4 * c + 1]);
#pragma unroll
            for (int t = 0; t < 8; t++) {
                const int c = tile_of(t);
                const bool shared = (t & 3) == 2;
                m1[t][0] = shared ? dup(lo[c], r.zero) : lo[c];
                m1[t][1] = shared ? dup(hi[c], r.zero) : hi[c];
                m1[t][2] = lo[c + 1];
                m1[t][3] = hi[c + 1];
                m0[t][0] = dup(m1[t][0], r.zero);
                m0[t][2] = dup(lo[c + 1], 2 * r.zero);
            }
            r.run<XWN, 6, false>(y2);
            if (warp == 0) mbar_wait(base + BAR_HALO, 0);
            fetch(hin, 0, 1);
            pack_q(1);
            r.run<XWN, 6, false>(y2);
            fetch(hin, 1, 1);
            pack_q(0);
            r.mma_begin();
            float s[8][4];
#pragma unroll
            for (int step = 0; step < 2; step++) {
#pragma unroll
                for (int i = 0; i < 8; i++) {
                    const int b = 1 - (i >> 2), h = i & 3, t = 2 * h + step;
                    float (&d)[4] = s[2 * h + b];
                    if (step == 0) d[0] = d[1] = d[2] = d[3] = 0.f;
                    mma16816(d, b ? m1[t] : m0[t], q[b][t][0], q[b][t][1]);
                }
            }
            r.mma_end();
            r.run<XWN, 6, false>(y2, false);

            uint32_t pr[8], mx[4], mx1[4];
            {
                const bool cur0 = g <= 2 * tig, cur1 = g <= 2 * tig + 1;
#pragma unroll
                for (int i = 0; i < 8; i++) {
                    const int c = (i & 1) ? 2 : 0;
                    pr[i] = movm(pack2(cur0 ? s[i][c] : s[i][2 - c], cur1 ? s[i][c + 1] : s[i][3 - c]));
                }
            }
            r.run<XWN, 6, false>(y2);
            const uint32_t curmask = (2 * tig <= g ? 0x0000FFFFu : 0u) | (2 * tig + 1 <= g ? 0xFFFF0000u : 0u);
            {
                const uint32_t keep = (blk == 0 && warp == 0) ? curmask : 0xFFFFFFFFu;
#pragma unroll
                for (int i = 0; i < 4; i++) {
                    pr[2 * i] = (pr[2 * i] & keep) | (0xCF9ECF9Eu & ~keep);
                    mx[i] = max2(__byte_perm(pr[2 * i], pr[2 * i + 1], 0x5410), __byte_perm(pr[2 * i], pr[2 * i + 1], 0x7632));
                    mx1[i] = __shfl_xor_sync(0xffffffffu, mx[i], 1);
                }
            }
#pragma unroll
            for (int i = 0; i < 4; i++) {
                mx[i] = max2(mx[i], mx1[i]);
                mx1[i] = __shfl_xor_sync(0xffffffffu, mx[i], 2);
            }
            r.run<XWN, 6, false>(y2);
            constexpr float SCL = 0.18898223650461362f * 1.4426950408889634f;
            float e0[8], e1[8], sm[8], sm1[8];
#pragma unroll
            for (int i = 0; i < 8; i++) {
                const uint32_t m2 = max2(mx[i >> 1], mx1[i >> 1]);
                sm[i] = ((i & 1) ? bf_hi(m2) : bf_lo(m2)) * -SCL;
                e0[i] = ex2(fmaf(bf_lo(pr[i]), SCL, sm[i]));
            }

            r.seek(21, bslot_l(21));
            r.run<BIG, 6, true>(y0);
            acc_fence(y2);
#pragma unroll
            for (int c = 0; c < 7; c++) hi[c] = movm(pack2(y2[4 * c + 2], y2[4 * c + 3]));
#pragma unroll
            for (int i = 0; i < 8; i++) e1[i] = ex2(fmaf(bf_hi(pr[i]), SCL, sm[i]));
            r.run<BIG, 6, false>(y0);
            publish(hi, 0, 7);
#pragma unroll
            for (int c = 7; c < 14; c++) hi[c] = movm(pack2(y2[4 * c + 2], y2[4 * c + 3]));
            r.run<BIG, 6, false>(y0);
            publish(hi, 7, 14);
#pragma unroll
            for (int i = 0; i < 8; i++) {
                sm[i] = e0[i] + e1[i];
                sm1[i] = __shfl_xor_sync(0xffffffffu, sm[i], 1);
            }
            r.run<BIG, 6, false>(y0);
#pragma unroll
            for (int c = 0; c < 14; c++) lo[c] = movm(pack2(y2[4 * c], y2[4 * c + 1]));
            r.run<BIG, 6, false>(y0);
#pragma unroll
            for (int i = 0; i < 8; i++) {
                sm[i] += sm1[i];
                sm1[i] = __shfl_xor_sync(0xffffffffu, sm[i], 2);
            }
#pragma unroll
            for (int t = 0; t < 8; t++) {
                const int c = tile_of(t);
                const bool shared = (t & 3) == 2;
                m1[t][0] = shared ? dup(lo[c], r.zero) : lo[c];
                m1[t][1] = lo[c + 1];
                m1[t][2] = shared ? dup(hi[c], r.zero) : hi[c];
                m1[t][3] = hi[c + 1];
                m0[t][0] = dup(m1[t][0], r.zero);
                m0[t][1] = dup(lo[c + 1], 2 * r.zero);
            }
            r.run<BIG, 6, false>(y0);
            if (warp == 0) mbar_wait(base + BAR_HALO + 8, 0);
            const uint32_t vin = warp ? hin : hin + 8 * HSLOT;
            fetch(vin, 0, 2);
#pragma unroll
            for (int i = 0; i < 8; i++) {
                const float inv = rcp(sm[i] + sm1[i]);
                pr[i] = pack2(e0[i] * inv, e1[i] * inv);
            }
            r.run<BIG, 6, false>(y0);
            fetch(vin, 1, 2);
            uint32_t pb[8][2];
#pragma unroll
            for (int t = 0; t < 8; t++) {
                pb[t][t & 1] = band(pr[t], curmask);
                pb[t][1 - (t & 1)] = band(pr[t], ~curmask);
            }
            r.mma_begin();
            float o[2][8][4];
#pragma unroll
            for (int i = 0; i < 16; i++) {
                const int b = 1 - (i >> 3), t = i & 7;
                float (&d)[4] = o[b][t];
                d[0] = d[1] = d[2] = d[3] = 0.f;
                mma16816(d, b ? m1[t] : m0[t], pb[(t & 6) + b][0], pb[(t & 6) + b][1]);
            }
            r.mma_end();
            r.run<BIG, 6, false>(y0, false);
            uint8_t* odst = sc->o + (size_t)mt * 7 * SLOT + ns * (14 * 2048) + warp * 256 + lane * 4;
#pragma unroll
            for (int hp = 0; hp < 2; hp++) {
#pragma unroll
                for (int b = 0; b < 2; b++) {
                    const float (&u)[8][4] = o[b];
                    const int t = 4 * hp;
                    uint32_t* w = p + 14 * hp + b;
                    w[0] = pack2(u[t][0], u[t][1]);
                    w[2] = pack2(u[t][2], u[t][3]);
                    w[4] = pack2(u[t + 1][0], u[t + 1][1]);
                    w[6] = pack2(g < 4 ? u[t + 1][2] : u[t + 2][0], g < 4 ? u[t + 1][3] : u[t + 2][1]);
                    w[8] = pack2(u[t + 2][2], u[t + 2][3]);
                    w[10] = pack2(u[t + 3][0], u[t + 3][1]);
                    w[12] = pack2(u[t + 3][2], u[t + 3][3]);
                }
            }
#pragma unroll
            for (int i = 0; i < 28; i++) {
                if (i >= O_FIRST && (i - O_FIRST) % O_SLICE == 0) r.run<BIG, 6, false>(y0);
                stg1(odst + (i >> 1) * 2048 + (i & 1) * 128, p[i]);
            }
            warp_arrive(base + BAR_RDY + 16);

#pragma unroll 1
            for (int i = 30 + (27 - O_FIRST) / O_SLICE; i <= LLAST - TURN; i++) r.run<BIG, 6, false>(y0);
            r.seek(LLAST + 1 - TURN, bslot_l(LLAST + 1 - TURN));
#pragma unroll
            for (int i = 0; i < TURN; i++) {
                if (LLAST + 1 - TURN + i == 51) r.run<BIG, 6, false, 1, true, E_STEPS>(y0, i == 0, i == TURN - 1 && !wg, i < TURN - 1);
                else r.run<BIG, 6, false, 1, true>(y0, i == 0, i == TURN - 1 && !wg, i < TURN - 1);
            }
            const uint32_t tag = lds1(base + TAG);
            const uint32_t slab = base + (wg ? HALO : LSLAB) + (warp & 3) * WSLOT;
            mbar_wait(base + BAR_PART + wg * 8, 0);
#pragma unroll
            for (int i = 0; i < 7; i++) lds4(slab + i * 512 + lane * 16, p + 4 * i);
#pragma unroll 1
            for (int n = 0; n < SPIN_LIMIT; n++) {
                uint32_t stale = 0;
#pragma unroll
                for (int i = 0; i < 28; i += 2) stale |= p[i] ^ tag;
                if (__all_sync(0xffffffffu, !(stale & 1))) break;
#pragma unroll
                for (int i = 0; i < 7; i++) ld_tagged(part + i * 512, p[4 * i], p[4 * i + 1], p[4 * i + 2], p[4 * i + 3]);
            }
            asm volatile("wgmma.wait_group.sync.aligned 0;" ::: "memory");
            acc_fence(y0);
            store_out([&](int i) { return add2(pack2(y0[2 * i], y0[2 * i + 1]), p[i]); }, lane, slab, &maps.m[M_OUTB], 448 + col, mt * 128 + warp * 16);
        }
    }
}

typedef CUresult (*EncodeFn)(CUtensorMap*, CUtensorMapDataType, cuuint32_t, void*, const cuuint64_t*, const cuuint64_t*,
                             const cuuint32_t*, const cuuint32_t*, CUtensorMapInterleave, CUtensorMapSwizzle,
                             CUtensorMapL2promotion, CUtensorMapFloatOOBfill);

struct Dim { uint64_t size, stride; uint32_t box; };
void encode(EncodeFn fn, CUtensorMap* m, const void* ptr, CUtensorMapSwizzle sw, Dim d0, Dim d1, Dim d2 = {0, 0, 0}, Dim d3 = {0, 0, 0}) {
    const cuuint64_t dims[4] = {d0.size, d1.size, d2.size, d3.size};
    const cuuint64_t strides[3] = {d1.stride, d2.stride, d3.stride};
    const cuuint32_t box[4] = {d0.box, d1.box, d2.box, d3.box};
    const cuuint32_t es[4] = {1, 1, 1, 1};
    fn(m, CU_TENSOR_MAP_DATA_TYPE_BFLOAT16, d3.size ? 4 : d2.size ? 3 : 2, const_cast<void*>(ptr), dims, strides, box, es,
       CU_TENSOR_MAP_INTERLEAVE_NONE, sw, CU_TENSOR_MAP_L2_PROMOTION_L2_128B, CU_TENSOR_MAP_FLOAT_OOB_FILL_NONE);
}

}

extern "C" void kernel_launch(void* const* d_in, const int* in_sizes, int n_in, void* d_out, int out_size) {
    (void)in_sizes; (void)n_in; (void)out_size;
    void* fnp = nullptr;
    cudaDriverEntryPointQueryResult st;
    cudaGetDriverEntryPoint("cuTensorMapEncodeTiled", &fnp, cudaEnableDefault, &st);
    EncodeFn fn = (EncodeFn)fnp;
    void* scratch = nullptr;
    cudaGetSymbolAddress(&scratch, g_scratch);
    int dev = 0, sms = 0;
    cudaGetDevice(&dev);
    cudaDeviceGetAttribute(&sms, cudaDevAttrMultiProcessorCount, dev);
    auto kernel = sms == 132 ? fused_kernel<true> : fused_kernel<false>;
    cudaFuncSetAttribute(kernel, cudaFuncAttributeMaxDynamicSharedMemorySize, SMEM_BYTES);

    const CUtensorMapSwizzle S128 = CU_TENSOR_MAP_SWIZZLE_128B, S0 = CU_TENSOR_MAP_SWIZZLE_NONE;
    const Dim one = {1, 16, 1};
    Maps maps;
    encode(fn, &maps.m[M_XA], d_in[0], S128, {896, 2, 64}, {1024, 1792, 128}, one, one);
    encode(fn, &maps.m[M_WQK], d_in[1], S128, {112, 2, 64}, {448, 2688, 32}, {3, 896, 2}, {4, 224, 1});
    encode(fn, &maps.m[M_WV], d_in[1], S128, {112, 2, 64}, {448, 2688, 64}, one, {12, 224, 1});
    encode(fn, &maps.m[M_XH], d_in[0], S128, {448, 2, 64}, {128, 1792, 8}, {8, 128 * 1792, 8}, {2, 896, 2});
    encode(fn, &maps.m[M_WO], d_in[2], S128, {112, 2, 64}, {448, 896, 64}, one, {4, 224, 1});
    encode(fn, &maps.m[M_XB], d_in[3], S128, {448, 2, 64}, {1024, 896, 64}, {2, 896 * 1024, 2}, one);
    encode(fn, &maps.m[M_CR], d_in[4], S128, {2048, 2, 64}, {2048, 4096, 128});
    encode(fn, &maps.m[M_CI], d_in[5], S128, {2048, 2, 64}, {2048, 4096, 128});
    encode(fn, &maps.m[M_WR], d_in[6], S128, {448, 2, 64}, {448, 896, 112}, one, one);
    encode(fn, &maps.m[M_WI], d_in[7], S128, {448, 2, 64}, {448, 896, 112});
    encode(fn, &maps.m[M_OUTA], d_out, S0, {1792, 2, 112}, {1024, 3584, 8});
    encode(fn, &maps.m[M_OUTB], d_out, S0, {896, 2, 112}, {2048, 1792, 8});

    kernel<<<132, 384, SMEM_BYTES>>>((Scratch*)scratch, maps);
}
```

```cpp
#include <cuda.h>
#include <cuda_bf16.h>
#include <cuda_runtime.h>
#include <stdint.h>

namespace {

constexpr uint32_t SLOT = 16384;
constexpr int NA = 7;
constexpr uint32_t BRING = NA * SLOT;
constexpr uint32_t HALO = BRING + 6 * SLOT;
constexpr uint32_t HSLOT = 1792;
constexpr uint32_t WSLOT = 3584;
constexpr uint32_t BLOB = 14336;
constexpr uint32_t BARS = 14 * SLOT;
constexpr uint32_t BAR_FULL = BARS;
constexpr uint32_t BAR_EMPTY = BARS + 64;
constexpr uint32_t BAR_RDY = BARS + 128;
constexpr uint32_t BAR_DEP = BARS + 168;
constexpr uint32_t BAR_HALO = BARS + 192;
constexpr uint32_t BAR_PART = BARS + 208;
constexpr uint32_t BAR_HINT = BARS + 224;
constexpr uint32_t TAG = BARS + 240;
constexpr uint32_t HSPARE = BARS + 256 + 1024;
constexpr uint32_t SMEM_BYTES = HSPARE + HSLOT;
constexpr uint32_t base = 1024;
constexpr int SPIN_LIMIT = 1 << 16;

constexpr int LEAD = 3;
constexpr int PACE = 450;
constexpr int HALO_K_AT = 10;
constexpr int HALO_V_AT = 19;
constexpr int B_SLICE = 4;
constexpr int O_FIRST = 8, O_SLICE = 4;
constexpr int P_FIRST = 5;
constexpr int TURN = 4;
constexpr uint32_t GPC_MAP = 0x64752310u;
constexpr int NBE = 13;
constexpr int POUT = 33 + NBE;
constexpr int ELAST = POUT + 6;
constexpr int LLAST = 65 - NBE;
constexpr uint32_t LSLAB = ((LLAST - 6) % NA) * SLOT;
static_assert(TURN <= 4, "the output is staged in the slots of the seventh-last stage");

enum { M_XB, M_XA, M_XH, M_WR, M_WQK, M_WV, M_WO, M_WI, M_CR, M_CI, M_OUTA, M_OUTB, M_COUNT };
struct __align__(64) Maps { CUtensorMap m[M_COUNT]; };

constexpr int CNT_A = 0;
constexpr int CNT_B = 8;
constexpr int CNT_W = 12;
constexpr int CNT_O = 16;
constexpr int CNT_P = 32;
constexpr int CNT_COUNT = 96;

struct Scratch {
    uint8_t ab[64 * 4 * BLOB];
    uint8_t o[16 * 7 * SLOT];
    uint8_t part[64 * 2 * BLOB];
    uint8_t halo[64 * 2 * 2048];
    uint8_t wo[4 * 7 * SLOT];
    unsigned cnt[CNT_COUNT * 32];
    unsigned epoch[132 * 4 * 8];
};
__device__ __align__(1024) Scratch g_scratch;

__device__ __forceinline__ unsigned clk32() { unsigned c; asm volatile("mov.u32 %0, %%clock;" : "=r"(c)); return c; }

#define PROF(idx)

__device__ __forceinline__ void mbar_init(uint32_t bar, uint32_t cnt) {
    asm volatile("mbarrier.init.shared::cta.b64 [%0], %1;" ::"r"(bar), "r"(cnt) : "memory");
}
__device__ __forceinline__ void mbar_expect(uint32_t bar, uint32_t bytes) {
    asm volatile("mbarrier.arrive.expect_tx.shared::cta.b64 _, [%0], %1;" ::"r"(bar), "r"(bytes) : "memory");
}
__device__ __forceinline__ void mbar_arrive(uint32_t bar) {
    asm volatile("mbarrier.arrive.shared::cta.b64 _, [%0];" ::"r"(bar) : "memory");
}
__device__ __forceinline__ bool mbar_try(uint32_t bar, uint32_t parity) {
    uint32_t ok;
    asm volatile("{\n.reg .pred p;\nmbarrier.try_wait.parity.shared::cta.b64 p, [%1], %2;\nselp.u32 %0, 1, 0, p;\n}\n"
                 : "=r"(ok) : "r"(bar), "r"(parity) : "memory");
    return ok;
}
__device__ __forceinline__ void mbar_wait(uint32_t bar, uint32_t parity) {
#pragma unroll 1
    for (int n = 0; n < SPIN_LIMIT; n++)
        if (mbar_try(bar, parity)) break;
}
__device__ __forceinline__ bool elect() {
    uint32_t p;
    asm volatile("{\n.reg .pred p;\nelect.sync _|p, 0xffffffff;\nselp.u32 %0, 1, 0, p;\n}\n" : "=r"(p));
    return p;
}
__device__ __forceinline__ void nb_sync(int id, int n) { asm volatile("bar.sync %0, %1;" ::"r"(id), "r"(n) : "memory"); }
__device__ __forceinline__ void nb_arrive(int id, int n) { asm volatile("bar.arrive %0, %1;" ::"r"(id), "r"(n) : "memory"); }
__device__ __forceinline__ void warp_arrive(uint32_t bar) {
    __syncwarp();
    if (elect()) mbar_arrive(bar);
}
__device__ __forceinline__ uint32_t band(uint32_t x, uint32_t m) {
    uint32_t r;
    asm volatile("and.b32 %0, %1, %2;" : "=r"(r) : "r"(x), "r"(m));
    return r;
}
__device__ __forceinline__ uint32_t dup(uint32_t x, uint32_t zero) {
    uint32_t r;
    asm volatile("xor.b32 %0, %1, %2;" : "=r"(r) : "r"(x), "r"(zero));
    return r;
}

__device__ __forceinline__ void tma_ld2(uint32_t dst, const CUtensorMap* m, int c0, int c1, uint32_t bar) {
    asm volatile("cp.async.bulk.tensor.2d.shared::cluster.global.mbarrier::complete_tx::bytes [%0], [%1, {%3, %4}], [%2];"
                 ::"r"(dst), "l"(m), "r"(bar), "r"(c0), "r"(c1) : "memory");
}
__device__ __forceinline__ void tma_ld4(uint32_t dst, const CUtensorMap* m, int c0, int c1, int c2, int c3, uint32_t bar) {
    asm volatile("cp.async.bulk.tensor.4d.shared::cluster.global.mbarrier::complete_tx::bytes [%0], [%1, {%3, %4, %5, %6}], [%2];"
                 ::"r"(dst), "l"(m), "r"(bar), "r"(c0), "r"(c1), "r"(c2), "r"(c3) : "memory");
}
__device__ __forceinline__ void bulk_ld(uint32_t dst, const void* src, uint32_t bytes, uint32_t bar) {
    asm volatile("cp.async.bulk.shared::cluster.global.mbarrier::complete_tx::bytes [%0], [%1], %2, [%3];"
                 ::"r"(dst), "l"(src), "r"(bytes), "r"(bar) : "memory");
}
__device__ __forceinline__ void bulk_st(void* dst, uint32_t src, uint32_t bytes) {
    asm volatile("cp.async.bulk.global.shared::cta.bulk_group [%0], [%1], %2;" ::"l"(dst), "r"(src), "r"(bytes) : "memory");
}
__device__ __forceinline__ void tma_st2(const CUtensorMap* m, int c0, int c1, uint32_t src) {
    asm volatile("cp.async.bulk.tensor.2d.global.shared::cta.bulk_group [%0, {%1, %2}], [%3];"
                 ::"l"(m), "r"(c0), "r"(c1), "r"(src) : "memory");
}
__device__ __forceinline__ void bulk_commit() { asm volatile("cp.async.bulk.commit_group;" ::: "memory"); }
__device__ __forceinline__ void bulk_wait_read() { asm volatile("cp.async.bulk.wait_group.read 0;" ::: "memory"); }
__device__ __forceinline__ void fence_async_smem() { asm volatile("fence.proxy.async.shared::cta;" ::: "memory"); }
__device__ __forceinline__ void fence_async_global() { asm volatile("fence.proxy.async.global;" ::: "memory"); }

__device__ __forceinline__ void signal(Scratch* sc, int idx) {
    asm volatile("fence.proxy.async;\nred.relaxed.gpu.global.add.u32 [%0], 1;" ::"l"(&sc->cnt[idx * 32]) : "memory");
}
__device__ __forceinline__ unsigned peek(const unsigned* p) {
    unsigned v;
    asm volatile("ld.relaxed.gpu.global.u32 %0, [%1];" : "=r"(v) : "l"(p) : "memory");
    return v;
}
__device__ __forceinline__ void await(Scratch* sc, int idx, unsigned target) {
    const unsigned* p = &sc->cnt[idx * 32];
#pragma unroll 1
    for (int n = 0; n < SPIN_LIMIT; n++)
        if ((int)(peek(p) - target) >= 0) break;
    asm volatile("fence.acquire.gpu;" ::: "memory");
}
__device__ __forceinline__ void wait_dep(int k) {
    mbar_wait(base + BAR_DEP + k * 8, 0);
    fence_async_global();
}

#define WG_REGS                                                                                                     \
    "{%0,%1,%2,%3,%4,%5,%6,%7,%8,%9,%10,%11,%12,%13,%14,%15,%16,%17,%18,%19,%20,%21,%22,%23,%24,%25,%26,%27,"       \
    "%28,%29,%30,%31,%32,%33,%34,%35,%36,%37,%38,%39,%40,%41,%42,%43,%44,%45,%46,%47,%48,%49,%50,%51,%52,%53,%54,%55}"
#define WG_OPS(C)                                                                                                   \
    C(d[0]), C(d[1]), C(d[2]), C(d[3]), C(d[4]), C(d[5]), C(d[6]), C(d[7]), C(d[8]), C(d[9]), C(d[10]), C(d[11]),   \
    C(d[12]), C(d[13]), C(d[14]), C(d[15]), C(d[16]), C(d[17]), C(d[18]), C(d[19]), C(d[20]), C(d[21]), C(d[22]),   \
    C(d[23]), C(d[24]), C(d[25]), C(d[26]), C(d[27]), C(d[28]), C(d[29]), C(d[30]), C(d[31]), C(d[32]), C(d[33]),   \
    C(d[34]), C(d[35]), C(d[36]), C(d[37]), C(d[38]), C(d[39]), C(d[40]), C(d[41]), C(d[42]), C(d[43]), C(d[44]),   \
    C(d[45]), C(d[46]), C(d[47]), C(d[48]), C(d[49]), C(d[50]), C(d[51]), C(d[52]), C(d[53]), C(d[54]), C(d[55])

template <int TA, int TB, int SB, bool INIT, uint32_t AH, uint32_t BH>
__device__ __forceinline__ void wgmma112(float (&d)[56], uint32_t alo, uint32_t blo) {
    if (INIT) {
        asm volatile("{\n.reg .pred p;\n.reg .b64 da, db;\nsetp.ne.b32 p, 0, 0;\nmov.b64 da, {%56, %61};\nmov.b64 db, {%57, %62};\n"
                     "wgmma.mma_async.sync.aligned.m64n112k16.f32.bf16.bf16 " WG_REGS ", da, db, p, 1, %59, %60, %58;\n}\n"
                     : WG_OPS("=f") : "r"(alo), "r"(blo), "n"(TB), "n"(SB), "n"(TA), "n"(AH), "n"(BH));
    } else {
        asm volatile("{\n.reg .pred p;\n.reg .b64 da, db;\nsetp.ne.b32 p, 1, 0;\nmov.b64 da, {%56, %61};\nmov.b64 db, {%57, %62};\n"
                     "wgmma.mma_async.sync.aligned.m64n112k16.f32.bf16.bf16 " WG_REGS ", da, db, p, 1, %59, %60, %58;\n}\n"
                     : WG_OPS("+f") : "r"(alo), "r"(blo), "n"(TB), "n"(SB), "n"(TA), "n"(AH), "n"(BH));
    }
}
__device__ __forceinline__ void acc_fence(float (&d)[56]) {
#pragma unroll
    for (int i = 0; i < 56; i++) asm volatile("" : "+f"(d[i])::"memory");
}

__device__ __forceinline__ uint32_t pack2(float lo, float hi) {
    uint32_t r;
    asm volatile("cvt.rn.bf16x2.f32 %0, %1, %2;" : "=r"(r) : "f"(hi), "f"(lo));
    return r;
}
__device__ __forceinline__ uint32_t movm(uint32_t a) {
    uint32_t r;
    asm volatile("movmatrix.sync.aligned.m8n8.trans.b16 %0, %1;" : "=r"(r) : "r"(a));
    return r;
}
__device__ __forceinline__ void stsm4(uint32_t addr, uint32_t a, uint32_t b, uint32_t c, uint32_t d) {
    asm volatile("stmatrix.sync.aligned.m8n8.x4.shared.b16 [%0], {%1,%2,%3,%4};" ::"r"(addr), "r"(a), "r"(b), "r"(c), "r"(d) : "memory");
}
__device__ __forceinline__ void sts1(uint32_t addr, uint32_t a) { asm volatile("st.shared.b32 [%0], %1;" ::"r"(addr), "r"(a) : "memory"); }
__device__ __forceinline__ uint32_t lds1(uint32_t addr) {
    uint32_t a;
    asm volatile("ld.shared.b32 %0, [%1];" : "=r"(a) : "r"(addr) : "memory");
    return a;
}
__device__ __forceinline__ void lds4(uint32_t addr, uint32_t* v) {
    asm volatile("ld.shared.v4.b32 {%0,%1,%2,%3}, [%4];" : "=r"(v[0]), "=r"(v[1]), "=r"(v[2]), "=r"(v[3]) : "r"(addr) : "memory");
}
__device__ __forceinline__ void stg1(uint8_t* p, uint32_t a) { asm volatile("st.global.b32 [%0], %1;" ::"l"(p), "r"(a) : "memory"); }
__device__ __forceinline__ void st_part(uint8_t* p, const uint32_t* v, uint32_t parity) {
    asm volatile("{\n.reg .b64 x, y;\nmov.b64 x, {%1, %2};\nmov.b64 y, {%3, %4};\nst.relaxed.gpu.global.v2.b64 [%0], {x, y};\n}\n"
                 ::"l"(p), "r"((v[0] & ~1u) | parity), "r"(v[1]), "r"((v[2] & ~1u) | parity), "r"(v[3]) : "memory");
}
__device__ __forceinline__ void mma16816(float (&d)[4], const uint32_t (&a)[4], uint32_t b0, uint32_t b1) {
    asm volatile("mma.sync.aligned.m16n8k16.row.col.f32.bf16.bf16.f32 {%0,%1,%2,%3}, {%4,%5,%6,%7}, {%8,%9}, {%0,%1,%2,%3};"
                 : "+f"(d[0]), "+f"(d[1]), "+f"(d[2]), "+f"(d[3]) : "r"(a[0]), "r"(a[1]), "r"(a[2]), "r"(a[3]), "r"(b0), "r"(b1));
}
__device__ __forceinline__ uint32_t add2(uint32_t a, uint32_t b) {
    uint32_t r;
    asm("add.rn.bf16x2 %0, %1, %2;" : "=r"(r) : "r"(a), "r"(b));
    return r;
}
__device__ __forceinline__ uint32_t scale2(uint32_t x) {
    uint32_t r;
    asm("{\n.reg .b32 t;\nmul.rn.bf16x2 t, %1, %3;\nfma.rn.bf16x2 %0, %1, %2, t;\n}\n" : "=r"(r) : "r"(x), "r"(0x3E423E42u), "r"(0xB9F7B9F7u));
    return r;
}
__device__ __forceinline__ uint32_t max2(uint32_t a, uint32_t b) {
    uint32_t r;
    asm("max.bf16x2 %0, %1, %2;" : "=r"(r) : "r"(a), "r"(b));
    return r;
}
__device__ __forceinline__ void ld_tagged(const uint8_t* p, uint32_t& a, uint32_t& ta, uint32_t& b, uint32_t& tb) {
    asm volatile("{\n.reg .b64 x, y;\nld.relaxed.gpu.global.v2.b64 {x, y}, [%4];\nmov.b64 {%0, %1}, x;\nmov.b64 {%2, %3}, y;\n}\n"
                 : "=r"(a), "=r"(ta), "=r"(b), "=r"(tb) : "l"(p) : "memory");
}
__device__ __forceinline__ float bf_lo(uint32_t v) { return __uint_as_float(v << 16); }
__device__ __forceinline__ float bf_hi(uint32_t v) { return __uint_as_float(v & 0xFFFF0000u); }
__device__ __forceinline__ float rcp(float x) { float r; asm("rcp.approx.ftz.f32 %0, %1;" : "=f"(r) : "f"(x)); return r; }
__device__ __forceinline__ float ex2(float x) { float r; asm volatile("ex2.approx.ftz.f32 %0, %1;" : "=f"(r) : "f"(x)); return r; }

__device__ __forceinline__ uint32_t full_bar(int stage) { return base + BAR_FULL + (stage & 7) * 8; }
__device__ __forceinline__ void wait_released(int j) { mbar_wait(base + BAR_EMPTY + (j & 7) * 8, (j >> 3) & 1); }

template <int V>
struct Int { static constexpr int value = V; };

__host__ __device__ constexpr int bslot_e(int i) { return (i < 2 || i >= 14) ? (i + 5) % 7 : (i + 1) % 5; }
__host__ __device__ constexpr int bslot_l(int i) { return i % 6; }

template <uint32_t OFF>
struct Feed {
    int stage;
    uint32_t dst;
    __device__ __forceinline__ void seek(int i, int slot) { stage = i; dst = base + OFF + slot * SLOT; }
    template <int N>
    __device__ __forceinline__ uint32_t acquire() { wait_released(stage - N); return full_bar(stage); }
    template <int N>
    __device__ __forceinline__ void next() {
        stage++;
        dst += SLOT;
        if (dst == base + OFF + N * SLOT) dst = base + OFF;
    }
};
__device__ __forceinline__ int skip_own(int n, int mt) { return n == mt ? 15 : n; }

struct Desc { uint32_t lo, hi; };
__host__ __device__ constexpr Desc desc_const(uint32_t lbo, uint32_t sbo, uint32_t mode) { return {(lbo >> 4) << 16, (sbo >> 4) | (mode << 30)}; }
constexpr Desc D_K128 = desc_const(16, 1024, 1);
constexpr Desc D_N128 = desc_const(8192, 1024, 1);
constexpr Desc D_BLOB = desc_const(128, 256, 0);
constexpr Desc D_OT = desc_const(2048, 128, 0);

enum Kind { XW, XWN, QK, BIG, OUT };

struct Ring {
    int stage;
    uint32_t a, b;
    uint32_t wg;
    uint32_t zero;
    bool releaser;
    __device__ __forceinline__ void seek(int i, int bslot) {
        stage = i;
        a = (base + (i % NA) * SLOT) >> 4;
        b = (base + BRING + bslot * SLOT) >> 4;
    }
    __device__ __forceinline__ void wait() { mbar_wait(full_bar(stage), (stage >> 3) & 1); }
    __device__ __forceinline__ void take_turn() { nb_sync(1 + wg, 256); }
    __device__ __forceinline__ void pin() {
        uint32_t n = 0;
#pragma unroll 1
        do {
            asm volatile("pmevent 7;" ::: "memory");
        } while (n++ < zero);
    }
    __device__ __forceinline__ void mma_begin() {
        pin();
        if (!wg) take_turn();
        pin();
    }
    __device__ __forceinline__ void mma_end() {
        pin();
        if (wg) nb_arrive(3, 256);
        nb_sync(3 - wg, 256);
    }
    template <Kind K, int NBS, bool INIT, int SB = 1, bool TAIL = false>
    __device__ __forceinline__ void run(float (&d)[56], float (&e)[56], bool first = true, bool last = true, bool more = true) {
        if (first) take_turn();
        asm volatile("wgmma.fence.sync.aligned;" ::: "memory");
        if (K == QK) {
            const uint32_t da = D_K128.lo + (base >> 4) + (stage >> 1) * (SLOT >> 4) + (stage & 1) * 4 + wg * 512, db = D_N128.lo + b;
            wgmma112<0, 1, 1, INIT, D_K128.hi, D_N128.hi>(d, da, db);
            wgmma112<0, 1, 1, INIT, D_K128.hi, D_N128.hi>(e, da, db + 256);
            wgmma112<0, 1, 1, false, D_K128.hi, D_N128.hi>(d, da + 2, db + 128);
            wgmma112<0, 1, 1, false, D_K128.hi, D_N128.hi>(e, da + 2, db + 384);
        } else {
            constexpr int TA = K == OUT, TB = K != XW;
            constexpr uint32_t sa = K == OUT ? 256 : 2, sb = K == XW ? 2 : K == BIG ? 224 : 128;
            constexpr Desc A = K == OUT ? D_OT : D_K128, B = K == XW ? D_K128 : K == BIG ? D_BLOB : D_N128;
            const uint32_t da = A.lo + a + wg * (K == OUT ? 64 : 512), db = B.lo + b;
            wgmma112<TA, TB, SB, INIT, A.hi, B.hi>(d, da, db);
#pragma unroll
            for (int q = 1; q < 4; q++) wgmma112<TA, TB, SB, false, A.hi, B.hi>(d, da + q * sa, db + q * sb);
        }
        asm volatile("wgmma.commit_group.sync.aligned;" ::: "memory");
        if (!TAIL) asm volatile("wgmma.wait_group.sync.aligned 1;" ::: "memory");
        if (last) nb_arrive(2 - wg, 256);
        if (!TAIL && stage > 0 && releaser) mbar_arrive(base + BAR_EMPTY + ((stage - 1) & 7) * 8);
        stage++;
        a += SLOT >> 4;
        if (a == (base + NA * SLOT) >> 4) a = base >> 4;
        b += SLOT >> 4;
        if (b == (base + BRING + NBS * SLOT) >> 4) b = (base + BRING) >> 4;
        if (more) wait();
    }
    template <Kind K, int NBS, bool INIT, int SB = 1, bool TAIL = false>
    __device__ __forceinline__ void run(float (&d)[56], bool first = true, bool last = true, bool more = true) {
        run<K, NBS, INIT, SB, TAIL>(d, d, first, last, more);
    }
};

template <int I0 = 0, int I1 = 28>
__device__ __forceinline__ void pack_all(const float (&d)[56], uint32_t (&p)[28]) {
#pragma unroll
    for (int i = I0; i < I1; i++) p[i] = pack2(d[2 * i], d[2 * i + 1]);
}
template <int I0, int I1>
__device__ __forceinline__ void store_frags(uint8_t* dst, const uint32_t (&p)[28]) {
#pragma unroll
    for (int i = I0; i < I1; i++) stg1(dst + i * 128, p[i]);
}
template <int I0, int I1>
__device__ __forceinline__ void stage_frags(uint32_t lane_addr, const uint32_t (&p)[28]) {
#pragma unroll
    for (int i = I0; i < I1; i += 4) stsm4(lane_addr + i * 128, p[i], p[i + 1], p[i + 2], p[i + 3]);
}
template <class F>
__device__ __forceinline__ void store_out(F frag, int lane, uint32_t slab, const CUtensorMap* m, int c0, int c1) {
    const bool swap = lane & 16;
    const uint32_t addr = slab + (lane & 7) * 224 + ((lane >> 3) ^ ((lane >> 2) & 1)) * 16;
#pragma unroll
    for (int h = 0; h < 2; h++) {
#pragma unroll
        for (int c = 0; c < 14; c += 4) {
            const uint32_t t0 = frag(2 * c + h), t1 = frag(2 * c + 2 + h);
            if (c < 12) {
                const uint32_t t2 = frag(2 * c + 4 + h), t3 = frag(2 * c + 6 + h);
                stsm4(addr + h * 1792 + c * 16, swap ? t1 : t0, swap ? t0 : t1, swap ? t3 : t2, swap ? t2 : t3);
            } else {
                asm volatile("stmatrix.sync.aligned.m8n8.x2.shared.b16 [%0], {%1,%2};" ::"r"(addr + h * 1792 + c * 16), "r"(swap ? t1 : t0), "r"(swap ? t0 : t1) : "memory");
            }
        }
        fence_async_smem();
        __syncwarp();
        if (elect()) tma_st2(m, c0, c1 + 8 * h, slab + h * 1792);
    }
    if (elect()) {
        bulk_commit();
        bulk_wait_read();
    }
}
__host__ __device__ constexpr int tile_of(int t) { return 7 * (t >> 2) + 3 * ((t >> 1) & 1) + 2 * (t & 1); }

struct Role {
    bool H;
    int L, mt, ns, id;
    int kind, a0, a1, b3;
};
template <bool BY_SM>
__device__ __forceinline__ Role decode_role() {
    uint32_t sm;
    if (BY_SM) asm volatile("mov.u32 %0, %%smid;" : "=r"(sm));
    else asm volatile("mov.u32 %0, %%ctaid.x;" : "=r"(sm));
    const int tpc = sm >> 1, q2 = ((tpc - 32) * 37) >> 8;
    const int gpc = tpc < 32 ? tpc & 7 : tpc < 60 ? tpc - 31 - 7 * q2 : 0;
    const int pos = tpc < 32 ? tpc >> 3 : tpc < 60 ? q2 + 4 : tpc - 56;
    Role r;
    r.H = sm >= 128;
    const int grp = (GPC_MAP >> (4 * gpc)) & 7;
    r.L = grp & 1;
    r.mt = (grp >> 1) * 4 + (pos >> 1);
    r.ns = (pos & 1) * 2 + (sm & 1);
    r.id = r.H ? sm : grp * 16 + pos * 2 + (sm & 1);
    r.kind = r.H ? 2 : r.L;
    r.a0 = r.L ? (r.mt >> 3) * 448 : 0;
    r.a1 = r.L ? (r.mt & 7) * 128 : r.H ? 120 : r.mt * 64;
    r.b3 = r.H ? 4 + r.ns : r.L ? r.ns : 0;
    return r;
}

__device__ __forceinline__ void first_fill(const Maps& maps, const Role& r, int i) {
    const bool E = r.kind == 0;
    const CUtensorMap* ma = &maps.m[r.kind];
    const uint32_t bar = full_bar(i);
    const int k = (i * 64) >> r.L;
    const bool has_a = !(i & r.L), has_b = i < 7 - r.L;
    const uint32_t dst = base + BRING + (E ? (0x2104365u >> (4 * i)) & 7 : i) * SLOT;
    mbar_expect(bar, (has_a ? SLOT : 0) + (has_b ? (E ? BLOB : SLOT) : 0));
    if (has_a) tma_ld4(base + (i >> r.L) * SLOT, ma, r.a0 + k, r.a1, 0, 0, bar);
    if (has_b) {
        tma_ld4(dst, ma + 3, E ? k : 0, E ? r.ns * 112 : k, 0, r.b3, bar);
        if (!E) tma_ld4(dst + 8192, ma + 3, 64, k, 0, r.b3, bar);
        mbar_arrive(bar);
    }
}
static_assert(bslot_e(0) == 5 && bslot_e(1) == 6 && bslot_e(2) == 3 && bslot_e(3) == 4 && bslot_e(4) == 0 && bslot_e(6) == 2, "");

template <bool BY_SM>
__global__ void __launch_bounds__(384, 1) fused_kernel(Scratch* sc, const __grid_constant__ Maps maps) {
    const unsigned t_open = clk32();
    const int warp = __shfl_sync(0xffffffffu, threadIdx.x >> 5, 0);
    if (warp == 8) {
        if (elect()) {
#pragma unroll
            for (int i = 0; i < LEAD; i++) mbar_init(base + BAR_FULL + i * 8, 2);
            asm volatile("fence.mbarrier_init.release.cluster;" ::: "memory");
            const Role r = decode_role<BY_SM>();
#pragma unroll 1
            for (int i = 0; i < LEAD; i++) first_fill(maps, r, i);
        }
    }
    if (warp == 9) {
        if (elect()) {
#pragma unroll
            for (int i = 0; i < 8; i++) mbar_init(base + BAR_EMPTY + i * 8, 4);
            asm volatile("fence.mbarrier_init.release.cluster;" ::: "memory");
        }
    } else if (warp == 10) {
        if (elect()) {
#pragma unroll
            for (int i = 0; i < 3; i++) mbar_init(base + BAR_RDY + i * 8, i < 2 ? 4 : 8);
#pragma unroll
            for (int i = 0; i < 2; i++) mbar_init(base + BAR_HALO + i * 8, 1);
            asm volatile("fence.mbarrier_init.release.cluster;" ::: "memory");
        }
    } else if (warp == 11) {
        if (elect()) {
#pragma unroll
            for (int i = LEAD; i < 8; i++) mbar_init(base + BAR_FULL + i * 8, 2);
#pragma unroll
            for (int i = 0; i < 3; i++) mbar_init(base + BAR_DEP + i * 8, 1);
#pragma unroll
            for (int i = 0; i < 4; i++) mbar_init(base + BAR_PART + i * 8, 1);
            asm volatile("fence.mbarrier_init.release.cluster;" ::: "memory");
        }
    }
    __syncthreads();

    const Role role = decode_role<BY_SM>();
    int lane = threadIdx.x & 31;
    asm volatile("" : "+r"(lane));
    const bool roleH = role.H;
    const int roleL = role.L, mt = role.mt, ns = role.ns, bid = role.id;
    const int par = mt >> 3, blk = mt & 7, col = ns * 112;

    if (warp >= 8) {
        asm volatile("setmaxnreg.dec.sync.aligned.u32 56;");
#define PROF_FEED_A
#define PROF_FEED_B
        if (warp == 8) {
            if (elect()) {
                PROF(129);
#pragma unroll 1
                for (int i = LEAD; i < 7; i++) {
                    while (clk32() - t_open < i * PACE) {}
                    first_fill(maps, role, i);
                }
                PROF(134);
                Feed<0> f;
                const int row = mt * 128;
                auto c_run = [&](const CUtensorMap* m, int off, int n0, int n1) {
#pragma unroll 1
                    for (int n = n0; n < n1; n++) {
                        const uint32_t bar = f.acquire<NA>();
                        mbar_expect(bar, SLOT);
                        tma_ld2(f.dst, m, (off + skip_own(n, mt)) * 64, row, bar);
                        PROF_FEED_A;
                        f.next<NA>();
                    }
                };
                if (roleH) {
                    mbar_expect(base + BAR_DEP, 7 * SLOT);
#pragma unroll 1
                    for (int i = 0; i < 7; i++) {
                        const uint32_t dst = base + (i < 6 ? i : 7) * SLOT;
                        if (i < 6) wait_released(7 + i);
                        tma_ld4(dst, &maps.m[M_WO], 0, i * 64, 0, ns, base + BAR_DEP);
                        tma_ld4(dst + 8192, &maps.m[M_WO], 64, i * 64, 0, ns, base + BAR_DEP);
                    }
                    mbar_wait(base + BAR_DEP, 0);
                    mbar_wait(base + BAR_RDY + 16, 0);
#pragma unroll 1
                    for (int i = 0; i < 7; i++) bulk_st(sc->wo + (size_t)(ns * 7 + i) * SLOT, base + (i < 6 ? i : 7) * SLOT, SLOT);
                    bulk_commit();
                    asm volatile("cp.async.bulk.wait_group 0;" ::: "memory");
                    signal(sc, CNT_W + ns);
                } else if (!roleL) {
                    f.seek(14, 0);
#pragma unroll 1
                    for (int i = 0; i < 4; i++) {
                        const uint32_t bar = f.acquire<NA>();
                        mbar_expect(bar, SLOT);
                        tma_ld2(f.dst, &maps.m[M_CR + (i >> 1)], ((i & 1) * 16 + mt) * 64, row, bar);
                        mbar_arrive(bar);
                        PROF_FEED_A;
                        f.next<NA>();
                    }
                    c_run(&maps.m[M_CR], 0, 0, 15);
                    c_run(&maps.m[M_CI], 0, 0, NBE);
                    wait_dep(2);
#pragma unroll 1
                    for (int i = 0; i < 7; i++) {
                        const uint32_t bar = f.acquire<NA>();
                        mbar_expect(bar, SLOT);
                        bulk_ld(f.dst, sc->o + (size_t)(mt * 7 + i) * SLOT, SLOT, bar);
                        PROF_FEED_A;
                        f.next<NA>();
                    }
                } else {
#pragma unroll 1
                    for (int i = 4; i < 7; i++) {
                        wait_released(2 * i - 8);
                        mbar_expect(full_bar(2 * i), SLOT);
                        tma_ld4(base + i * SLOT, &maps.m[M_XA], par * 448 + i * 64, blk * 128, 0, 0, full_bar(2 * i));
                    }
                    wait_released(HALO_K_AT);
                    mbar_arrive(base + BAR_DEP + 16);
                    f.seek(21, 0);
                    c_run(&maps.m[M_CR], 16, 0, 15);
                    c_run(&maps.m[M_CI], 16, 0, 15);
                    c_run(&maps.m[M_CI], 0, NBE, 15);
                }
            }
        } else if (warp == 11) {
            if (elect()) {
                Feed<BRING> f;
                auto blob_run = [&](auto nbs, int quarter, int n0, int n1) {
                    constexpr int N = decltype(nbs)::value;
                    const uint8_t* src = sc->ab + (size_t)(quarter * 64 + ns) * BLOB;
#pragma unroll 1
                    for (int n = n0; n < n1; n++) {
                        const uint32_t bar = f.template acquire<N>();
                        mbar_expect(bar, BLOB);
                        bulk_ld(f.dst, src + skip_own(n, mt) * (4 * BLOB), BLOB, bar);
                        PROF_FEED_B;
                        f.template next<N>();
                    }
                };
                auto v_run = [&](auto nbs) {
                    constexpr int N = decltype(nbs)::value;
#pragma unroll 1
                    for (int i = 0; i < 7; i++) {
                        const uint32_t bar = f.template acquire<N>();
                        mbar_expect(bar, SLOT);
                        tma_ld4(f.dst, &maps.m[M_WV], 0, i * 64, 0, 8 + ns, bar);
                        tma_ld4(f.dst + 8192, &maps.m[M_WV], 64, i * 64, 0, 8 + ns, bar);
                        mbar_arrive(bar);
                        PROF_FEED_B;
                        f.template next<N>();
                    }
                };
                if (roleH) {
                    f.seek(7, 0);
                    v_run(Int<7>());
                } else if (!roleL) {
                    f.seek(7, bslot_e(7));
#pragma unroll 1
                    for (int i = 0; i < 7; i++) {
                        const uint32_t bar = f.acquire<5>();
                        mbar_expect(bar, BLOB);
                        tma_ld2(f.dst, &maps.m[M_WI], i * 64, col, bar);
                        mbar_arrive(bar);
                        PROF_FEED_B;
                        f.next<5>();
                    }
                    f.seek(18, bslot_e(18));
                    wait_dep(0);
                    blob_run(Int<7>(), 0, 0, 15);
                    wait_dep(1);
                    blob_run(Int<7>(), 2, 0, NBE);
                    mbar_wait(base + BAR_HINT, 0);
                    fence_async_global();
#pragma unroll 1
                    for (int i = 0; i < 7; i++) {
                        const uint32_t bar = f.acquire<7>();
                        mbar_expect(bar, SLOT);
                        bulk_ld(f.dst, sc->wo + (size_t)(ns * 7 + i) * SLOT, SLOT, bar);
                        PROF_FEED_B;
                        f.next<7>();
                    }

                } else {
                    f.seek(6, 0);
#pragma unroll 1
                    for (int i = 6; i < 14; i++) {
                        const uint32_t bar = f.acquire<6>();
                        mbar_expect(bar, SLOT);
                        tma_ld4(f.dst, &maps.m[M_WQK], 0, i * 32, 0, ns, bar);
                        tma_ld4(f.dst + 8192, &maps.m[M_WQK], 64, i * 32, 0, ns, bar);
                        if (i & 1) mbar_arrive(bar);
                        PROF_FEED_B;
                        f.next<6>();
                    }
                    v_run(Int<6>());
                    wait_dep(0);
                    blob_run(Int<6>(), 1, 0, 15);
                    wait_dep(1);
                    blob_run(Int<6>(), 3, 0, 15);
                    blob_run(Int<6>(), 2, NBE, 15);
                    fence_async_smem();
#pragma unroll 1
                    for (int h = 0; h < 2; h++) {
                        mbar_wait(base + BAR_HINT + h * 8, 0);
                        PROF(153 + h);
                        mbar_expect(base + BAR_PART + h * 8, BLOB);
                        bulk_ld(base + (h ? HALO : LSLAB), sc->part + (size_t)((ns * 16 + mt) * 2 + h) * BLOB, BLOB, base + BAR_PART + h * 8);
                    }
                }
            }
        } else if (roleH) {
            if (warp == 9 && elect()) {
                wait_released(0);
#pragma unroll 1
                for (int i = 0; i < 7; i++)
                    asm volatile("cp.async.bulk.prefetch.tensor.2d.L2.global [%0, {%1, %2}];" ::"l"(&maps.m[M_WI]), "r"(i * 64), "r"(col) : "memory");
            }
        } else if (warp == 10) {
            if (elect()) {
                unsigned* epoch_ptr = &sc->epoch[(bid * 4 + 2) * 8];
                const unsigned ep = *epoch_ptr + 1;
                sts1(base + TAG, ep);
                asm volatile("prefetch.tensormap [%0];" ::"l"(&maps.m[M_OUTA + roleL]) : "memory");
                await(sc, CNT_A + roleL * 4 + ns, ep * 16);
                mbar_arrive(base + BAR_DEP);
                PROF(150);
                await(sc, CNT_B + ns, ep * 16);
                mbar_arrive(base + BAR_DEP + 8);
                PROF(151);
                if (!roleL) {
                    await(sc, CNT_W + ns, ep);
                    mbar_arrive(base + BAR_HINT);
                    PROF(153);
                    await(sc, CNT_O + mt, ep * 4);
                    mbar_arrive(base + BAR_DEP + 16);
                } else {
                    await(sc, CNT_P + mt * 4 + ns, ep * 2 - 1);
                    mbar_arrive(base + BAR_HINT);
                    await(sc, CNT_P + mt * 4 + ns, ep * 2);
                    mbar_arrive(base + BAR_HINT + 8);
                }
                PROF(152);
                *epoch_ptr = ep;
            }
        } else if (!roleL) {
            if (elect()) {
                mbar_wait(base + BAR_RDY, 0);
                PROF(130);
                signal(sc, CNT_A + ns);
                PROF(131);
                mbar_wait(base + BAR_RDY + 8, 0);
                signal(sc, CNT_A + 4 + ns);
                PROF(135);
                mbar_wait(base + BAR_RDY + 16, 0);
                PROF(132);
                signal(sc, CNT_B + ns);
                PROF(133);
            }
        } else {
            unsigned* epoch_ptr = &sc->epoch[(bid * 4 + 1) * 8];
            const unsigned tag = *epoch_ptr + 1;
#pragma unroll 1
            for (int kv = 0; kv < 2; kv++) {
                uint32_t v[16];
#pragma unroll
                for (int i = 0; i < 16; i++) v[i] = 0;
                if (kv) wait_released(HALO_V_AT - 4), wait_released(HALO_V_AT);
                else mbar_wait(base + BAR_DEP + 16, 0);
                if (blk > 0) {
                    const uint8_t* src = sc->halo + (size_t)(((mt - 1) * 4 + ns) * 2 + kv) * 2048 + lane * 16;
#pragma unroll 1
                    for (int n = 0; n < SPIN_LIMIT; n++) {
                        uint32_t stale = 0;
#pragma unroll
                        for (int i = 0; i < 4; i++) ld_tagged(src + i * 512, v[4 * i], v[4 * i + 1], v[4 * i + 2], v[4 * i + 3]);
#pragma unroll
                        for (int i = 0; i < 16; i += 2) stale |= v[i] ^ tag;
                        if (__all_sync(0xffffffffu, !(stale & 1))) break;
                    }
#pragma unroll
                    for (int c = 0; c < 14; c += 2) v[c] = (v[c] & ~1u) | ((v[15] >> c) & 1);
                }
#pragma unroll
                for (int i = 0; i < 14; i++) sts1(base + HALO + kv * (8 * HSLOT) + i * 128 + lane * 4, v[i]);
                warp_arrive(base + BAR_HALO + kv * 8);
                if (lane == 0) PROF(142 + kv);
            }
            if (elect()) {
                mbar_wait(base + BAR_RDY + 16, 0);
                PROF(130);
                signal(sc, CNT_O + mt);
                PROF(131);
                *epoch_ptr = tag;
            }
        }
    } else {
        asm volatile("setmaxnreg.inc.sync.aligned.u32 224;");
        Ring r;
        r.wg = warp >> 2;
        r.zero = blockIdx.y;
        r.releaser = lane + 1 == (warp >> 2);
        const int wg = warp >> 2;
        if (wg) nb_arrive(1, 256);
        uint8_t* part = sc->part + (size_t)(ns * 16 + mt) * (2 * BLOB) + warp * WSLOT + lane * 16;
        uint32_t p[28];

        if (roleH) {
            unsigned* epoch_ptr = &sc->epoch[bid * 4 * 8];
            const unsigned tag = *epoch_ptr + 1;
            uint8_t* hout = sc->halo + (size_t)((warp * 8 + ns) * 2) * 2048 + lane * 16;
            auto send = [&](int kv) {
#pragma unroll
                for (int h = 0; h < 2; h++) {
                    uint32_t v[16];
                    v[14] = v[15] = 0;
#pragma unroll
                    for (int c = 0; c < 14; c++) v[c] = p[2 * c + h];
#pragma unroll
                    for (int c = 0; c < 14; c += 2) v[15] |= (v[c] & 1) << c;
#pragma unroll
                    for (int i = 0; i < 4; i++) st_part(hout + (h * 8 + kv) * 2048 + i * 512, v + 4 * i, tag & 1);
                }
            };
            float x0[56], x1[56];
            r.seek(0, 0);
            r.wait();
            r.run<XWN, 7, true>(x0);
#pragma unroll 1
            for (int i = 1; i < 7; i++) r.run<XWN, 7, false>(x0);
            r.run<XWN, 7, true>(x1);
            acc_fence(x0);
            pack_all(x0, p);
            send(0);
#pragma unroll 1
            for (int i = 1; i < 7; i++) r.run<XWN, 7, false>(x1, true, i < 6 || !wg, i < 6);
            asm volatile("wgmma.wait_group.sync.aligned 0;" ::: "memory");
            acc_fence(x1);
            pack_all(x1, p);
#pragma unroll
            for (int i = 0; i < 28; i++) p[i] = movm(p[i]);
            send(1);
            warp_arrive(base + BAR_RDY + 16);
            if (threadIdx.x == 0) *epoch_ptr = tag;
        } else if (!roleL) {
            uint8_t* blob = sc->ab + (size_t)((wg * 16 + mt) * 4 + ns) * BLOB + (warp & 3) * WSLOT + lane * 4;
            const uint32_t own = base + BRING + wg * SLOT + (warp & 3) * WSLOT + lane * 16;
            float x0[56], x1[56];
            r.seek(0, bslot_e(0));
            r.wait();
            r.run<XW, 7, true>(x0);
            r.run<XW, 7, false>(x0);
            r.seek(2, bslot_e(2));
#pragma unroll 1
            for (int i = 2; i < 7; i++) r.run<XW, 5, false>(x0);

            r.seek(7, bslot_e(7));
            r.run<XW, 5, true, -1>(x1);
            acc_fence(x0);
            pack_all<0, 14>(x0, p);
#pragma unroll
            for (int i = 0; i < 2; i++) {
                if (wg == i) store_frags<0, 14>(blob, p);
                else stage_frags<0, 4>(own + 5 * SLOT, p);
                r.run<XW, 5, false, -1>(x1);
                if (i == 0) pack_all<14, 28>(x0, p);
                if (wg == i) {
                    store_frags<14, 28>(blob, p);
                    warp_arrive(base + BAR_RDY + i * 8);
                } else {
                    stage_frags<4, 8>(own + 5 * SLOT, p);
                }
                r.run<XW, 5, false, -1>(x1);
            }
            stage_frags<8, 20>(own + 5 * SLOT, p);
            r.run<XW, 5, false, -1>(x1);
            stage_frags<20, 28>(own + 5 * SLOT, p);
            fence_async_smem();
            r.run<XW, 5, false, -1>(x1);

            r.seek(14, bslot_e(14));
            r.run<BIG, 7, true>(x0);
            acc_fence(x1);
            pack_all(x1, p);
            stage_frags<0, 28>(own, p);
            r.run<BIG, 7, false>(x0);
            fence_async_smem();
            blob += (size_t)128 * BLOB;
#pragma unroll
            for (int i = 0; i < 28; i++) {
                if (i % B_SLICE == 0) r.run<BIG, 7, false>(x0);
                stg1(blob + i * 128, p[i]);
            }
            warp_arrive(base + BAR_RDY + 16);
#pragma unroll 1
            for (int i = 17 + 27 / B_SLICE; i < POUT; i++) r.run<BIG, 7, false>(x0);

            const uint32_t tag = lds1(base + TAG);
            r.seek(POUT, bslot_e(POUT));
            r.run<OUT, 7, true>(x1);
            acc_fence(x0);
            pack_all(x0, p);
#pragma unroll
            for (int k = 0; k < 3; k++) {
                if (k < 2 && wg == k) {
#pragma unroll
                    for (int i = 0; i < P_FIRST; i++) st_part(part + i * 512, p + 4 * i, tag & 1);
                    if ((warp & 3) == 0 && elect())
                        asm volatile("red.relaxed.gpu.global.add.u32 [%0], 1;" ::"l"(&sc->cnt[(CNT_P + mt * 4 + ns) * 32]) : "memory");
                }
                if (k > 0 && wg == k - 1) {
#pragma unroll
                    for (int i = P_FIRST; i < 7; i++) st_part(part + i * 512, p + 4 * i, tag & 1);
                }
                if (k < 2) r.run<OUT, 7, false>(x1);
            }
#pragma unroll
            for (int i = 3; i < 7; i++) r.run<OUT, 7, false, 1, true>(x1, i <= 7 - TURN, i < 7 - TURN || (i == 6 && !wg), i < 6);

            asm volatile("wgmma.wait_group.sync.aligned 0;" ::: "memory");
            acc_fence(x1);
            const uint32_t slab = base + (wg ? BRING + bslot_e(ELAST - 6) * SLOT : ((ELAST - 6) % NA) * SLOT) + (warp & 3) * WSLOT;
            store_out([&](int i) { return pack2(x1[2 * i], x1[2 * i + 1]); }, lane, slab, &maps.m[M_OUTA], par * 896 + col, blk * 128 + warp * 16);
        } else {
            const int g = lane >> 2, tig = lane & 3;
            const uint32_t hin = base + HALO + warp * HSLOT + lane * 4;
            const uint32_t hpub = warp < 7 ? hin + HSLOT : base + HSPARE + lane * 4;
            auto publish = [&](const uint32_t (&h)[14], int c0, int c1) {
#pragma unroll
                for (int c = 0; c < 14; c++)
                    if (c >= c0 && c < c1) sts1(hpub + c * 128, h[c]);
            };
            float y0[56], y1[56], y2[56];
            r.seek(0, 0);
            r.wait();
            r.run<QK, 6, true>(y0, y1);
#pragma unroll 1
            for (int i = 1; i < 14; i++) r.run<QK, 6, false>(y0, y1);

            uint32_t m1[8][4], m0[8][4], lo[14], hi[14], q[2][8][2];
            auto pack_q = [&](int b) {
                uint32_t v[14];
#pragma unroll
                for (int c = 0; c < 14; c++) v[c] = pack2(y0[4 * c + 2 * b], y0[4 * c + 2 * b + 1]);
#pragma unroll
                for (int t = 0; t < 8; t++) {
                    const int c = tile_of(t);
                    q[b][t][0] = (t & 3) == 2 ? (tig >= 2 ? v[c] : 0u) : v[c];
                    q[b][t][1] = (t & 3) == 1 ? (tig < 2 ? v[c + 1] : 0u) : v[c + 1];
                }
            };
            auto fetch = [&](uint32_t src, int hp, int i0) {
#pragma unroll
                for (int t = 4 * hp; t < 4 * hp + 4; t++) {
                    m0[t][i0] = (t & 3) == 2 ? dup(m0[t - 1][3], r.zero) : lds1(src + tile_of(t) * 128);
                    m0[t][3] = lds1(src + tile_of(t) * 128 + 128);
                }
            };
            r.seek(14, bslot_l(14));
            r.run<XWN, 6, true>(y2);
            acc_fence(y0);
            acc_fence(y1);
#pragma unroll
            for (int c = 0; c < 14; c++) hi[c] = pack2(y1[4 * c + 2], y1[4 * c + 3]);
            publish(hi, 0, 7);
            r.run<XWN, 6, false>(y2);
            publish(hi, 7, 14);
#pragma unroll
            for (int c = 0; c < 14; c++) lo[c] = pack2(y1[4 * c], y1[4 * c + 1]);
#pragma unroll
            for (int t = 0; t < 8; t++) {
                const int c = tile_of(t);
                const bool shared = (t & 3) == 2;
                m1[t][0] = shared ? dup(lo[c], r.zero) : lo[c];
                m1[t][1] = shared ? dup(hi[c], r.zero) : hi[c];
                m1[t][2] = lo[c + 1];
                m1[t][3] = hi[c + 1];
                m0[t][0] = dup(m1[t][0], r.zero);
                m0[t][2] = dup(lo[c + 1], 2 * r.zero);
            }
            r.run<XWN, 6, false>(y2);
            if (warp == 0) mbar_wait(base + BAR_HALO, 0);
            fetch(hin, 0, 1);
            pack_q(1);
            r.run<XWN, 6, false>(y2);
            fetch(hin, 1, 1);
            pack_q(0);
            r.mma_begin();
            float s[8][4];
#pragma unroll
            for (int step = 0; step < 2; step++) {
#pragma unroll
                for (int i = 0; i < 8; i++) {
                    const int b = 1 - (i >> 2), h = i & 3, t = 2 * h + step;
                    float (&d)[4] = s[2 * h + b];
                    if (step == 0) d[0] = d[1] = d[2] = d[3] = 0.f;
                    mma16816(d, b ? m1[t] : m0[t], q[b][t][0], q[b][t][1]);
                }
            }
            r.mma_end();
            r.run<XWN, 6, false>(y2, false);

            uint32_t pr[8], mx[4], mx1[4];
            {
                const bool cur0 = g <= 2 * tig, cur1 = g <= 2 * tig + 1;
#pragma unroll
                for (int i = 0; i < 8; i++) {
                    const int c = (i & 1) ? 2 : 0;
                    pr[i] = movm(pack2(cur0 ? s[i][c] : s[i][2 - c], cur1 ? s[i][c + 1] : s[i][3 - c]));
                }
            }
            r.run<XWN, 6, false>(y2);
            const uint32_t curmask = (2 * tig <= g ? 0x0000FFFFu : 0u) | (2 * tig + 1 <= g ? 0xFFFF0000u : 0u);
            {
                const uint32_t keep = (blk == 0 && warp == 0) ? curmask : 0xFFFFFFFFu;
#pragma unroll
                for (int i = 0; i < 4; i++) {
                    pr[2 * i] = (scale2(pr[2 * i]) & keep) | (0xCE6ECE6Eu & ~keep);
                    pr[2 * i + 1] = scale2(pr[2 * i + 1]);
                    mx[i] = max2(__byte_perm(pr[2 * i], pr[2 * i + 1], 0x5410), __byte_perm(pr[2 * i], pr[2 * i + 1], 0x7632));
                    mx1[i] = __shfl_xor_sync(0xffffffffu, mx[i], 1);
                }
            }
#pragma unroll
            for (int i = 0; i < 4; i++) {
                mx[i] = max2(mx[i], mx1[i]);
                mx1[i] = __shfl_xor_sync(0xffffffffu, mx[i], 2);
            }
            r.run<XWN, 6, false>(y2);
            constexpr float SCL = 1.4426950408889634f;
            float e0[8], e1[8], sm[8], sm1[8];
#pragma unroll
            for (int i = 0; i < 8; i++) {
                const uint32_t m2 = max2(mx[i >> 1], mx1[i >> 1]);
                sm[i] = ((i & 1) ? bf_hi(m2) : bf_lo(m2)) * -SCL;
                e0[i] = ex2(fmaf(bf_lo(pr[i]), SCL, sm[i]));
            }

            r.seek(21, bslot_l(21));
            r.run<BIG, 6, true>(y0);
            acc_fence(y2);
#pragma unroll
            for (int c = 0; c < 7; c++) hi[c] = movm(pack2(y2[4 * c + 2], y2[4 * c + 3]));
#pragma unroll
            for (int i = 0; i < 8; i++) e1[i] = ex2(fmaf(bf_hi(pr[i]), SCL, sm[i]));
            r.run<BIG, 6, false>(y0);
            publish(hi, 0, 7);
#pragma unroll
            for (int c = 7; c < 14; c++) hi[c] = movm(pack2(y2[4 * c + 2], y2[4 * c + 3]));
            r.run<BIG, 6, false>(y0);
            publish(hi, 7, 14);
#pragma unroll
            for (int i = 0; i < 8; i++) {
                sm[i] = e0[i] + e1[i];
                sm1[i] = __shfl_xor_sync(0xffffffffu, sm[i], 1);
            }
            r.run<BIG, 6, false>(y0);
#pragma unroll
            for (int c = 0; c < 14; c++) lo[c] = movm(pack2(y2[4 * c], y2[4 * c + 1]));
            r.run<BIG, 6, false>(y0);
#pragma unroll
            for (int i = 0; i < 8; i++) {
                sm[i] += sm1[i];
                sm1[i] = __shfl_xor_sync(0xffffffffu, sm[i], 2);
            }
#pragma unroll
            for (int t = 0; t < 8; t++) {
                const int c = tile_of(t);
                const bool shared = (t & 3) == 2;
                m1[t][0] = shared ? dup(lo[c], r.zero) : lo[c];
                m1[t][1] = lo[c + 1];
                m1[t][2] = shared ? dup(hi[c], r.zero) : hi[c];
                m1[t][3] = hi[c + 1];
                m0[t][0] = dup(m1[t][0], r.zero);
                m0[t][1] = dup(lo[c + 1], 2 * r.zero);
            }
            r.run<BIG, 6, false>(y0);
            if (warp == 0) mbar_wait(base + BAR_HALO + 8, 0);
            const uint32_t vin = warp ? hin : hin + 8 * HSLOT;
            fetch(vin, 0, 2);
#pragma unroll
            for (int i = 0; i < 8; i++) {
                const float inv = rcp(sm[i] + sm1[i]);
                pr[i] = pack2(e0[i] * inv, e1[i] * inv);
            }
            r.run<BIG, 6, false>(y0);
            fetch(vin, 1, 2);
            uint32_t pb[8][2];
#pragma unroll
            for (int t = 0; t < 8; t++) {
                pb[t][t & 1] = band(pr[t], curmask);
                pb[t][1 - (t & 1)] = band(pr[t], ~curmask);
            }
            r.mma_begin();
            float o[2][8][4];
#pragma unroll
            for (int i = 0; i < 16; i++) {
                const int b = 1 - (i >> 3), t = i & 7;
                float (&d)[4] = o[b][t];
                d[0] = d[1] = d[2] = d[3] = 0.f;
                mma16816(d, b ? m1[t] : m0[t], pb[(t & 6) + b][0], pb[(t & 6) + b][1]);
            }
            r.mma_end();
            r.run<BIG, 6, false>(y0, false);
            uint8_t* odst = sc->o + (size_t)mt * 7 * SLOT + ns * (14 * 2048) + warp * 256 + lane * 4;
#pragma unroll
            for (int hp = 0; hp < 2; hp++) {
#pragma unroll
                for (int b = 0; b < 2; b++) {
                    const float (&u)[8][4] = o[b];
                    const int t = 4 * hp;
                    uint32_t* w = p + 14 * hp + b;
                    w[0] = pack2(u[t][0], u[t][1]);
                    w[2] = pack2(u[t][2], u[t][3]);
                    w[4] = pack2(u[t + 1][0], u[t + 1][1]);
                    w[6] = pack2(g < 4 ? u[t + 1][2] : u[t + 2][0], g < 4 ? u[t + 1][3] : u[t + 2][1]);
                    w[8] = pack2(u[t + 2][2], u[t + 2][3]);
                    w[10] = pack2(u[t + 3][0], u[t + 3][1]);
                    w[12] = pack2(u[t + 3][2], u[t + 3][3]);
                }
            }
#pragma unroll
            for (int i = 0; i < 28; i++) {
                if (i >= O_FIRST && (i - O_FIRST) % O_SLICE == 0) r.run<BIG, 6, false>(y0);
                stg1(odst + (i >> 1) * 2048 + (i & 1) * 128, p[i]);
            }
            warp_arrive(base + BAR_RDY + 16);

#pragma unroll 1
            for (int i = 30 + (27 - O_FIRST) / O_SLICE; i <= LLAST - TURN; i++) r.run<BIG, 6, false>(y0);
            r.seek(LLAST + 1 - TURN, bslot_l(LLAST + 1 - TURN));
#pragma unroll
            for (int i = 0; i < TURN; i++) r.run<BIG, 6, false, 1, true>(y0, i == 0, i == TURN - 1 && !wg, i < TURN - 1);
            const uint32_t tag = lds1(base + TAG);
            const uint32_t slab = base + (wg ? HALO : LSLAB) + (warp & 3) * WSLOT;
            mbar_wait(base + BAR_PART + wg * 8, 0);
#pragma unroll
            for (int i = 0; i < 7; i++) lds4(slab + i * 512 + lane * 16, p + 4 * i);
#pragma unroll 1
            for (int n = 0; n < SPIN_LIMIT; n++) {
                uint32_t stale = 0;
#pragma unroll
                for (int i = 0; i < 28; i += 2) stale |= p[i] ^ tag;
                if (__all_sync(0xffffffffu, !(stale & 1))) break;
#pragma unroll
                for (int i = 0; i < 7; i++) ld_tagged(part + i * 512, p[4 * i], p[4 * i + 1], p[4 * i + 2], p[4 * i + 3]);
            }
#pragma unroll
            for (int i = 0; i < 28; i += 2) p[i] &= ~1u;
            asm volatile("wgmma.wait_group.sync.aligned 0;" ::: "memory");
            acc_fence(y0);
            store_out([&](int i) { return add2(pack2(y0[2 * i], y0[2 * i + 1]), p[i]); }, lane, slab, &maps.m[M_OUTB], 448 + col, mt * 128 + warp * 16);
        }
    }
}

typedef CUresult (*EncodeFn)(CUtensorMap*, CUtensorMapDataType, cuuint32_t, void*, const cuuint64_t*, const cuuint64_t*,
                             const cuuint32_t*, const cuuint32_t*, CUtensorMapInterleave, CUtensorMapSwizzle,
                             CUtensorMapL2promotion, CUtensorMapFloatOOBfill);

struct Dim { uint64_t size, stride; uint32_t box; };
void encode(EncodeFn fn, CUtensorMap* m, const void* ptr, CUtensorMapSwizzle sw, Dim d0, Dim d1, Dim d2 = {0, 0, 0}, Dim d3 = {0, 0, 0}) {
    const cuuint64_t dims[4] = {d0.size, d1.size, d2.size, d3.size};
    const cuuint64_t strides[3] = {d1.stride, d2.stride, d3.stride};
    const cuuint32_t box[4] = {d0.box, d1.box, d2.box, d3.box};
    const cuuint32_t es[4] = {1, 1, 1, 1};
    fn(m, CU_TENSOR_MAP_DATA_TYPE_BFLOAT16, d3.size ? 4 : d2.size ? 3 : 2, const_cast<void*>(ptr), dims, strides, box, es,
       CU_TENSOR_MAP_INTERLEAVE_NONE, sw, CU_TENSOR_MAP_L2_PROMOTION_L2_128B, CU_TENSOR_MAP_FLOAT_OOB_FILL_NONE);
}

}

extern "C" void kernel_launch(void* const* d_in, const int* in_sizes, int n_in, void* d_out, int out_size) {
    (void)in_sizes; (void)n_in; (void)out_size;
    void* fnp = nullptr;
    cudaDriverEntryPointQueryResult st;
    cudaGetDriverEntryPoint("cuTensorMapEncodeTiled", &fnp, cudaEnableDefault, &st);
    EncodeFn fn = (EncodeFn)fnp;
    void* scratch = nullptr;
    cudaGetSymbolAddress(&scratch, g_scratch);
    int dev = 0, sms = 0;
    cudaGetDevice(&dev);
    cudaDeviceGetAttribute(&sms, cudaDevAttrMultiProcessorCount, dev);
    auto kernel = sms == 132 ? fused_kernel<true> : fused_kernel<false>;
    cudaFuncSetAttribute(kernel, cudaFuncAttributeMaxDynamicSharedMemorySize, SMEM_BYTES);

    const CUtensorMapSwizzle S128 = CU_TENSOR_MAP_SWIZZLE_128B, S0 = CU_TENSOR_MAP_SWIZZLE_NONE;
    const Dim one = {1, 16, 1};
    Maps maps;
    encode(fn, &maps.m[M_XA], d_in[0], S128, {896, 2, 64}, {1024, 1792, 128}, one, one);
    encode(fn, &maps.m[M_WQK], d_in[1], S128, {112, 2, 64}, {448, 2688, 32}, {3, 896, 2}, {4, 224, 1});
    encode(fn, &maps.m[M_WV], d_in[1], S128, {112, 2, 64}, {448, 2688, 64}, one, {12, 224, 1});
    encode(fn, &maps.m[M_XH], d_in[0], S128, {448, 2, 64}, {128, 1792, 8}, {8, 128 * 1792, 8}, {2, 896, 2});
    encode(fn, &maps.m[M_WO], d_in[2], S128, {112, 2, 64}, {448, 896, 64}, one, {4, 224, 1});
    encode(fn, &maps.m[M_XB], d_in[3], S128, {448, 2, 64}, {1024, 896, 64}, {2, 896 * 1024, 2}, one);
    encode(fn, &maps.m[M_CR], d_in[4], S128, {2048, 2, 64}, {2048, 4096, 128});
    encode(fn, &maps.m[M_CI], d_in[5], S128, {2048, 2, 64}, {2048, 4096, 128});
    encode(fn, &maps.m[M_WR], d_in[6], S128, {448, 2, 64}, {448, 896, 112}, one, one);
    encode(fn, &maps.m[M_WI], d_in[7], S128, {448, 2, 64}, {448, 896, 112});
    encode(fn, &maps.m[M_OUTA], d_out, S0, {1792, 2, 112}, {1024, 3584, 8});
    encode(fn, &maps.m[M_OUTB], d_out, S0, {896, 2, 112}, {2048, 1792, 8});

    kernel<<<132, 384, SMEM_BYTES>>>((Scratch*)scratch, maps);
}
```

```cpp
#include <cuda.h>
#include <cuda_bf16.h>
#include <cuda_runtime.h>
#include <stdint.h>

namespace {

constexpr uint32_t SLOT = 16384;
constexpr int NA = 7;
constexpr uint32_t BRING = NA * SLOT;
constexpr uint32_t HALO = BRING + 6 * SLOT;
constexpr uint32_t HSLOT = 1792;
constexpr uint32_t WSLOT = 3584;
constexpr uint32_t BLOB = 14336;
constexpr uint32_t BARS = 14 * SLOT;
constexpr uint32_t BAR_FULL = BARS;
constexpr uint32_t BAR_EMPTY = BARS + 64;
constexpr uint32_t BAR_RDY = BARS + 128;
constexpr uint32_t BAR_DEP = BARS + 168;
constexpr uint32_t BAR_HALO = BARS + 192;
constexpr uint32_t BAR_PART = BARS + 208;
constexpr uint32_t BAR_HINT = BARS + 224;
constexpr uint32_t TAG = BARS + 240;
constexpr uint32_t HSPARE = BARS + 256 + 1024;
constexpr uint32_t SMEM_BYTES = HSPARE + HSLOT;
constexpr uint32_t base = 1024;
constexpr int SPIN_LIMIT = 1 << 16;

constexpr int LEAD = 3;
constexpr int PACE = 450;
constexpr int HALO_K_AT = 10;
constexpr int HALO_V_AT = 19;
constexpr int B_SLICE = 4;
constexpr int O_FIRST = 8, O_SLICE = 4;
constexpr int P_FIRST = 5;
constexpr int TURN = 4;
constexpr uint32_t GPC_MAP = 0x64752310u;
constexpr int NBE = 13;
constexpr int POUT = 33 + NBE;
constexpr int ELAST = POUT + 6;
constexpr int LLAST = 65 - NBE;
constexpr uint32_t LSLAB = ((LLAST - 6) % NA) * SLOT;
static_assert(TURN <= 4, "the output is staged in the slots of the seventh-last stage");

enum { M_XB, M_XA, M_XH, M_WR, M_WQK, M_WV, M_WO, M_WI, M_CR, M_CI, M_OUTA, M_OUTB, M_COUNT };
struct __align__(64) Maps { CUtensorMap m[M_COUNT]; };

constexpr int CNT_A = 0;
constexpr int CNT_B = 8;
constexpr int CNT_W = 12;
constexpr int CNT_O = 16;
constexpr int CNT_P = 32;
constexpr int CNT_COUNT = 96;

struct Scratch {
    uint8_t ab[64 * 4 * BLOB];
    uint8_t o[16 * 7 * SLOT];
    uint8_t part[64 * 2 * BLOB];
    uint8_t halo[64 * 2 * 2048];
    uint8_t wo[4 * 7 * SLOT];
    unsigned cnt[CNT_COUNT * 32];
    unsigned epoch[132 * 4 * 8];
};
__device__ __align__(1024) Scratch g_scratch;

__device__ __forceinline__ unsigned clk32() { unsigned c; asm volatile("mov.u32 %0, %%clock;" : "=r"(c)); return c; }

#define PROF(idx)

__device__ __forceinline__ void mbar_init(uint32_t bar, uint32_t cnt) {
    asm volatile("mbarrier.init.shared::cta.b64 [%0], %1;" ::"r"(bar), "r"(cnt) : "memory");
}
__device__ __forceinline__ void mbar_expect(uint32_t bar, uint32_t bytes) {
    asm volatile("mbarrier.arrive.expect_tx.shared::cta.b64 _, [%0], %1;" ::"r"(bar), "r"(bytes) : "memory");
}
__device__ __forceinline__ void mbar_arrive(uint32_t bar) {
    asm volatile("mbarrier.arrive.shared::cta.b64 _, [%0];" ::"r"(bar) : "memory");
}
__device__ __forceinline__ bool mbar_try(uint32_t bar, uint32_t parity) {
    uint32_t ok;
    asm volatile("{\n.reg .pred p;\nmbarrier.try_wait.parity.shared::cta.b64 p, [%1], %2;\nselp.u32 %0, 1, 0, p;\n}\n"
                 : "=r"(ok) : "r"(bar), "r"(parity) : "memory");
    return ok;
}
__device__ __forceinline__ void mbar_wait(uint32_t bar, uint32_t parity) {
#pragma unroll 1
    for (int n = 0; n < SPIN_LIMIT; n++)
        if (mbar_try(bar, parity)) break;
}
__device__ __forceinline__ bool elect() {
    uint32_t p;
    asm volatile("{\n.reg .pred p;\nelect.sync _|p, 0xffffffff;\nselp.u32 %0, 1, 0, p;\n}\n" : "=r"(p));
    return p;
}
__device__ __forceinline__ void nb_sync(int id, int n) { asm volatile("bar.sync %0, %1;" ::"r"(id), "r"(n) : "memory"); }
__device__ __forceinline__ void nb_arrive(int id, int n) { asm volatile("bar.arrive %0, %1;" ::"r"(id), "r"(n) : "memory"); }
__device__ __forceinline__ void warp_arrive(uint32_t bar) {
    __syncwarp();
    if (elect()) mbar_arrive(bar);
}
__device__ __forceinline__ uint32_t or3(uint32_t a, uint32_t b, uint32_t c) {
    uint32_t r;
    asm("lop3.b32 %0, %1, %2, %3, 0xFE;" : "=r"(r) : "r"(a), "r"(b), "r"(c));
    return r;
}
__device__ __forceinline__ uint32_t band(uint32_t x, uint32_t m) {
    uint32_t r;
    asm volatile("and.b32 %0, %1, %2;" : "=r"(r) : "r"(x), "r"(m));
    return r;
}
__device__ __forceinline__ uint32_t dup(uint32_t x, uint32_t zero) {
    uint32_t r;
    asm volatile("xor.b32 %0, %1, %2;" : "=r"(r) : "r"(x), "r"(zero));
    return r;
}

__device__ __forceinline__ void tma_ld2(uint32_t dst, const CUtensorMap* m, int c0, int c1, uint32_t bar) {
    asm volatile("cp.async.bulk.tensor.2d.shared::cluster.global.mbarrier::complete_tx::bytes [%0], [%1, {%3, %4}], [%2];"
                 ::"r"(dst), "l"(m), "r"(bar), "r"(c0), "r"(c1) : "memory");
}
__device__ __forceinline__ void tma_ld4(uint32_t dst, const CUtensorMap* m, int c0, int c1, int c2, int c3, uint32_t bar) {
    asm volatile("cp.async.bulk.tensor.4d.shared::cluster.global.mbarrier::complete_tx::bytes [%0], [%1, {%3, %4, %5, %6}], [%2];"
                 ::"r"(dst), "l"(m), "r"(bar), "r"(c0), "r"(c1), "r"(c2), "r"(c3) : "memory");
}
__device__ __forceinline__ void bulk_ld(uint32_t dst, const void* src, uint32_t bytes, uint32_t bar) {
    asm volatile("cp.async.bulk.shared::cluster.global.mbarrier::complete_tx::bytes [%0], [%1], %2, [%3];"
                 ::"r"(dst), "l"(src), "r"(bytes), "r"(bar) : "memory");
}
__device__ __forceinline__ void bulk_st(void* dst, uint32_t src, uint32_t bytes) {
    asm volatile("cp.async.bulk.global.shared::cta.bulk_group [%0], [%1], %2;" ::"l"(dst), "r"(src), "r"(bytes) : "memory");
}
__device__ __forceinline__ void tma_st2(const CUtensorMap* m, int c0, int c1, uint32_t src) {
    asm volatile("cp.async.bulk.tensor.2d.global.shared::cta.bulk_group [%0, {%1, %2}], [%3];"
                 ::"l"(m), "r"(c0), "r"(c1), "r"(src) : "memory");
}
__device__ __forceinline__ void bulk_commit() { asm volatile("cp.async.bulk.commit_group;" ::: "memory"); }
__device__ __forceinline__ void bulk_wait_read() { asm volatile("cp.async.bulk.wait_group.read 0;" ::: "memory"); }
__device__ __forceinline__ void fence_async_smem() { asm volatile("fence.proxy.async.shared::cta;" ::: "memory"); }
__device__ __forceinline__ void fence_async_global() { asm volatile("fence.proxy.async.global;" ::: "memory"); }

__device__ __forceinline__ void signal(Scratch* sc, int idx) {
    asm volatile("fence.proxy.async;\nred.relaxed.gpu.global.add.u32 [%0], 1;" ::"l"(&sc->cnt[idx * 32]) : "memory");
}
__device__ __forceinline__ unsigned peek(const unsigned* p) {
    unsigned v;
    asm volatile("ld.relaxed.gpu.global.u32 %0, [%1];" : "=r"(v) : "l"(p) : "memory");
    return v;
}
__device__ __forceinline__ void await(Scratch* sc, int idx, unsigned target) {
    const unsigned* p = &sc->cnt[idx * 32];
#pragma unroll 1
    for (int n = 0; n < SPIN_LIMIT; n++)
        if ((int)(peek(p) - target) >= 0) break;
    asm volatile("fence.acquire.gpu;" ::: "memory");
}
__device__ __forceinline__ void wait_dep(int k) {
    mbar_wait(base + BAR_DEP + k * 8, 0);
    fence_async_global();
}

#define WG_REGS                                                                                                     \
    "{%0,%1,%2,%3,%4,%5,%6,%7,%8,%9,%10,%11,%12,%13,%14,%15,%16,%17,%18,%19,%20,%21,%22,%23,%24,%25,%26,%27,"       \
    "%28,%29,%30,%31,%32,%33,%34,%35,%36,%37,%38,%39,%40,%41,%42,%43,%44,%45,%46,%47,%48,%49,%50,%51,%52,%53,%54,%55}"
#define WG_OPS(C)                                                                                                   \
    C(d[0]), C(d[1]), C(d[2]), C(d[3]), C(d[4]), C(d[5]), C(d[6]), C(d[7]), C(d[8]), C(d[9]), C(d[10]), C(d[11]),   \
    C(d[12]), C(d[13]), C(d[14]), C(d[15]), C(d[16]), C(d[17]), C(d[18]), C(d[19]), C(d[20]), C(d[21]), C(d[22]),   \
    C(d[23]), C(d[24]), C(d[25]), C(d[26]), C(d[27]), C(d[28]), C(d[29]), C(d[30]), C(d[31]), C(d[32]), C(d[33]),   \
    C(d[34]), C(d[35]), C(d[36]), C(d[37]), C(d[38]), C(d[39]), C(d[40]), C(d[41]), C(d[42]), C(d[43]), C(d[44]),   \
    C(d[45]), C(d[46]), C(d[47]), C(d[48]), C(d[49]), C(d[50]), C(d[51]), C(d[52]), C(d[53]), C(d[54]), C(d[55])

template <int TA, int TB, int SB, bool INIT, uint32_t AH, uint32_t BH>
__device__ __forceinline__ void wgmma112(float (&d)[56], uint32_t alo, uint32_t blo) {
    if (INIT) {
        asm volatile("{\n.reg .pred p;\n.reg .b64 da, db;\nsetp.ne.b32 p, 0, 0;\nmov.b64 da, {%56, %61};\nmov.b64 db, {%57, %62};\n"
                     "wgmma.mma_async.sync.aligned.m64n112k16.f32.bf16.bf16 " WG_REGS ", da, db, p, 1, %59, %60, %58;\n}\n"
                     : WG_OPS("=f") : "r"(alo), "r"(blo), "n"(TB), "n"(SB), "n"(TA), "n"(AH), "n"(BH));
    } else {
        asm volatile("{\n.reg .pred p;\n.reg .b64 da, db;\nsetp.ne.b32 p, 1, 0;\nmov.b64 da, {%56, %61};\nmov.b64 db, {%57, %62};\n"
                     "wgmma.mma_async.sync.aligned.m64n112k16.f32.bf16.bf16 " WG_REGS ", da, db, p, 1, %59, %60, %58;\n}\n"
                     : WG_OPS("+f") : "r"(alo), "r"(blo), "n"(TB), "n"(SB), "n"(TA), "n"(AH), "n"(BH));
    }
}
__device__ __forceinline__ void acc_fence(float (&d)[56]) {
#pragma unroll
    for (int i = 0; i < 56; i++) asm volatile("" : "+f"(d[i])::"memory");
}

__device__ __forceinline__ uint32_t pack2(float lo, float hi) {
    uint32_t r;
    asm volatile("cvt.rn.bf16x2.f32 %0, %1, %2;" : "=r"(r) : "f"(hi), "f"(lo));
    return r;
}
__device__ __forceinline__ uint32_t movm(uint32_t a) {
    uint32_t r;
    asm volatile("movmatrix.sync.aligned.m8n8.trans.b16 %0, %1;" : "=r"(r) : "r"(a));
    return r;
}
__device__ __forceinline__ void stsm4(uint32_t addr, uint32_t a, uint32_t b, uint32_t c, uint32_t d) {
    asm volatile("stmatrix.sync.aligned.m8n8.x4.shared.b16 [%0], {%1,%2,%3,%4};" ::"r"(addr), "r"(a), "r"(b), "r"(c), "r"(d) : "memory");
}
__device__ __forceinline__ void sts1(uint32_t addr, uint32_t a) { asm volatile("st.shared.b32 [%0], %1;" ::"r"(addr), "r"(a) : "memory"); }
__device__ __forceinline__ uint32_t lds1(uint32_t addr) {
    uint32_t a;
    asm volatile("ld.shared.b32 %0, [%1];" : "=r"(a) : "r"(addr) : "memory");
    return a;
}
__device__ __forceinline__ void lds4(uint32_t addr, uint32_t* v) {
    asm volatile("ld.shared.v4.b32 {%0,%1,%2,%3}, [%4];" : "=r"(v[0]), "=r"(v[1]), "=r"(v[2]), "=r"(v[3]) : "r"(addr) : "memory");
}
__device__ __forceinline__ void stg1(uint8_t* p, uint32_t a) { asm volatile("st.global.b32 [%0], %1;" ::"l"(p), "r"(a) : "memory"); }
__device__ __forceinline__ void st_part(uint8_t* p, const uint32_t* v, uint32_t parity) {
    asm volatile("{\n.reg .b64 x, y;\nmov.b64 x, {%1, %2};\nmov.b64 y, {%3, %4};\nst.relaxed.gpu.global.v2.b64 [%0], {x, y};\n}\n"
                 ::"l"(p), "r"((v[0] & ~1u) | parity), "r"(v[1]), "r"((v[2] & ~1u) | parity), "r"(v[3]) : "memory");
}
__device__ __forceinline__ void mma16816(float (&d)[4], const uint32_t (&a)[4], uint32_t b0, uint32_t b1) {
    asm volatile("mma.sync.aligned.m16n8k16.row.col.f32.bf16.bf16.f32 {%0,%1,%2,%3}, {%4,%5,%6,%7}, {%8,%9}, {%0,%1,%2,%3};"
                 : "+f"(d[0]), "+f"(d[1]), "+f"(d[2]), "+f"(d[3]) : "r"(a[0]), "r"(a[1]), "r"(a[2]), "r"(a[3]), "r"(b0), "r"(b1));
}
__device__ __forceinline__ uint32_t add2(uint32_t a, uint32_t b) {
    uint32_t r;
    asm("add.rn.bf16x2 %0, %1, %2;" : "=r"(r) : "r"(a), "r"(b));
    return r;
}
__device__ __forceinline__ uint32_t scale2(uint32_t x) {
    uint32_t r;
    asm("{\n.reg .b32 t;\nmul.rn.bf16x2 t, %1, %3;\nfma.rn.bf16x2 %0, %1, %2, t;\n}\n" : "=r"(r) : "r"(x), "r"(0x3E423E42u), "r"(0xB9F7B9F7u));
    return r;
}
__device__ __forceinline__ uint32_t max2(uint32_t a, uint32_t b) {
    uint32_t r;
    asm("max.bf16x2 %0, %1, %2;" : "=r"(r) : "r"(a), "r"(b));
    return r;
}
__device__ __forceinline__ void ld_tagged(const uint8_t* p, uint32_t& a, uint32_t& ta, uint32_t& b, uint32_t& tb) {
    asm volatile("{\n.reg .b64 x, y;\nld.relaxed.gpu.global.v2.b64 {x, y}, [%4];\nmov.b64 {%0, %1}, x;\nmov.b64 {%2, %3}, y;\n}\n"
                 : "=r"(a), "=r"(ta), "=r"(b), "=r"(tb) : "l"(p) : "memory");
}
__device__ __forceinline__ float bf_lo(uint32_t v) { return __uint_as_float(v << 16); }
__device__ __forceinline__ float bf_hi(uint32_t v) { return __uint_as_float(v & 0xFFFF0000u); }
__device__ __forceinline__ float rcp(float x) { float r; asm("rcp.approx.ftz.f32 %0, %1;" : "=f"(r) : "f"(x)); return r; }
__device__ __forceinline__ float ex2(float x) { float r; asm volatile("ex2.approx.ftz.f32 %0, %1;" : "=f"(r) : "f"(x)); return r; }

__device__ __forceinline__ uint32_t full_bar(int stage) { return base + BAR_FULL + (stage & 7) * 8; }
__device__ __forceinline__ void wait_released(int j) { mbar_wait(base + BAR_EMPTY + (j & 7) * 8, (j >> 3) & 1); }

template <int V>
struct Int { static constexpr int value = V; };

__host__ __device__ constexpr int bslot_e(int i) { return (i < 2 || i >= 14) ? (i + 5) % 7 : (i + 1) % 5; }
__host__ __device__ constexpr int bslot_l(int i) { return i % 6; }

template <uint32_t OFF>
struct Feed {
    int stage;
    uint32_t dst;
    __device__ __forceinline__ void seek(int i, int slot) { stage = i; dst = base + OFF + slot * SLOT; }
    template <int N>
    __device__ __forceinline__ uint32_t acquire() { wait_released(stage - N); return full_bar(stage); }
    template <int N>
    __device__ __forceinline__ void next() {
        stage++;
        dst += SLOT;
        if (dst == base + OFF + N * SLOT) dst = base + OFF;
    }
};
__device__ __forceinline__ int skip_own(int n, int mt) { return n == mt ? 15 : n; }

struct Desc { uint32_t lo, hi; };
__host__ __device__ constexpr Desc desc_const(uint32_t lbo, uint32_t sbo, uint32_t mode) { return {(lbo >> 4) << 16, (sbo >> 4) | (mode << 30)}; }
constexpr Desc D_K128 = desc_const(16, 1024, 1);
constexpr Desc D_N128 = desc_const(8192, 1024, 1);
constexpr Desc D_BLOB = desc_const(128, 256, 0);
constexpr Desc D_OT = desc_const(2048, 128, 0);

enum Kind { XW, XWN, QK, BIG, OUT };

struct Ring {
    int stage;
    uint32_t a, b;
    uint32_t wg;
    uint32_t zero;
    bool releaser;
    __device__ __forceinline__ void seek(int i, int bslot) {
        stage = i;
        a = (base + (i % NA) * SLOT) >> 4;
        b = (base + BRING + bslot * SLOT) >> 4;
    }
    __device__ __forceinline__ void wait() { mbar_wait(full_bar(stage), (stage >> 3) & 1); }
    __device__ __forceinline__ void take_turn() { nb_sync(1 + wg, 256); }
    __device__ __forceinline__ void pin() {
        uint32_t n = 0;
#pragma unroll 1
        do {
            asm volatile("pmevent 7;" ::: "memory");
        } while (n++ < zero);
    }
    __device__ __forceinline__ void mma_begin() {
        pin();
        if (!wg) take_turn();
        pin();
    }
    __device__ __forceinline__ void mma_end() {
        pin();
        if (wg) nb_arrive(3, 256);
        nb_sync(3 - wg, 256);
    }
    template <Kind K, int NBS, bool INIT, int SB = 1, bool TAIL = false>
    __device__ __forceinline__ void run(float (&d)[56], float (&e)[56], bool first = true, bool last = true, bool more = true) {
        if (first) take_turn();
        asm volatile("wgmma.fence.sync.aligned;" ::: "memory");
        if (K == QK) {
            const uint32_t da = D_K128.lo + (base >> 4) + (stage >> 1) * (SLOT >> 4) + (stage & 1) * 4 + wg * 512, db = D_N128.lo + b;
            wgmma112<0, 1, 1, INIT, D_K128.hi, D_N128.hi>(d, da, db);
            wgmma112<0, 1, 1, INIT, D_K128.hi, D_N128.hi>(e, da, db + 256);
            wgmma112<0, 1, 1, false, D_K128.hi, D_N128.hi>(d, da + 2, db + 128);
            wgmma112<0, 1, 1, false, D_K128.hi, D_N128.hi>(e, da + 2, db + 384);
        } else {
            constexpr int TA = K == OUT, TB = K != XW;
            constexpr uint32_t sa = K == OUT ? 256 : 2, sb = K == XW ? 2 : K == BIG ? 224 : 128;
            constexpr Desc A = K == OUT ? D_OT : D_K128, B = K == XW ? D_K128 : K == BIG ? D_BLOB : D_N128;
            const uint32_t da = A.lo + a + wg * (K == OUT ? 64 : 512), db = B.lo + b;
            wgmma112<TA, TB, SB, INIT, A.hi, B.hi>(d, da, db);
#pragma unroll
            for (int q = 1; q < 4; q++) wgmma112<TA, TB, SB, false, A.hi, B.hi>(d, da + q * sa, db + q * sb);
        }
        asm volatile("wgmma.commit_group.sync.aligned;" ::: "memory");
        if (!TAIL) asm volatile("wgmma.wait_group.sync.aligned 1;" ::: "memory");
        if (last) nb_arrive(2 - wg, 256);
        if (!TAIL && stage > 0 && releaser) mbar_arrive(base + BAR_EMPTY + ((stage - 1) & 7) * 8);
        stage++;
        a += SLOT >> 4;
        if (a == (base + NA * SLOT) >> 4) a = base >> 4;
        b += SLOT >> 4;
        if (b == (base + BRING + NBS * SLOT) >> 4) b = (base + BRING) >> 4;
        if (more) wait();
    }
    template <Kind K, int NBS, bool INIT, int SB = 1, bool TAIL = false>
    __device__ __forceinline__ void run(float (&d)[56], bool first = true, bool last = true, bool more = true) {
        run<K, NBS, INIT, SB, TAIL>(d, d, first, last, more);
    }
};

template <int I0 = 0, int I1 = 28>
__device__ __forceinline__ void pack_all(const float (&d)[56], uint32_t (&p)[28]) {
#pragma unroll
    for (int i = I0; i < I1; i++) p[i] = pack2(d[2 * i], d[2 * i + 1]);
}
template <int I0, int I1>
__device__ __forceinline__ void store_frags(uint8_t* dst, const uint32_t (&p)[28]) {
#pragma unroll
    for (int i = I0; i < I1; i++) stg1(dst + i * 128, p[i]);
}
template <int I0, int I1>
__device__ __forceinline__ void stage_frags(uint32_t lane_addr, const uint32_t (&p)[28]) {
#pragma unroll
    for (int i = I0; i < I1; i += 4) stsm4(lane_addr + i * 128, p[i], p[i + 1], p[i + 2], p[i + 3]);
}
template <class F>
__device__ __forceinline__ void store_out(F frag, int lane, uint32_t slab, const CUtensorMap* m, int c0, int c1) {
    const bool swap = lane & 16;
    const uint32_t addr = slab + (lane & 7) * 224 + ((lane >> 3) ^ ((lane >> 2) & 1)) * 16;
#pragma unroll
    for (int h = 0; h < 2; h++) {
#pragma unroll
        for (int c = 0; c < 14; c += 4) {
            const uint32_t t0 = frag(2 * c + h), t1 = frag(2 * c + 2 + h);
            if (c < 12) {
                const uint32_t t2 = frag(2 * c + 4 + h), t3 = frag(2 * c + 6 + h);
                stsm4(addr + h * 1792 + c * 16, swap ? t1 : t0, swap ? t0 : t1, swap ? t3 : t2, swap ? t2 : t3);
            } else {
                asm volatile("stmatrix.sync.aligned.m8n8.x2.shared.b16 [%0], {%1,%2};" ::"r"(addr + h * 1792 + c * 16), "r"(swap ? t1 : t0), "r"(swap ? t0 : t1) : "memory");
            }
        }
        fence_async_smem();
        __syncwarp();
        if (elect()) tma_st2(m, c0, c1 + 8 * h, slab + h * 1792);
    }
    if (elect()) {
        bulk_commit();
        bulk_wait_read();
    }
}
__host__ __device__ constexpr int tile_of(int t) { return 7 * (t >> 2) + 3 * ((t >> 1) & 1) + 2 * (t & 1); }

struct Role {
    bool H;
    int L, mt, ns, id;
    int kind, a0, a1, b3;
};
template <bool BY_SM>
__device__ __forceinline__ Role decode_role() {
    uint32_t sm;
    if (BY_SM) asm volatile("mov.u32 %0, %%smid;" : "=r"(sm));
    else asm volatile("mov.u32 %0, %%ctaid.x;" : "=r"(sm));
    const int tpc = sm >> 1, q2 = ((tpc - 32) * 37) >> 8;
    const int gpc = tpc < 32 ? tpc & 7 : tpc < 60 ? tpc - 31 - 7 * q2 : 0;
    const int pos = tpc < 32 ? tpc >> 3 : tpc < 60 ? q2 + 4 : tpc - 56;
    Role r;
    r.H = sm >= 128;
    const int grp = (GPC_MAP >> (4 * gpc)) & 7;
    r.L = grp & 1;
    r.mt = (grp >> 1) * 4 + (pos >> 1);
    r.ns = (pos & 1) * 2 + (sm & 1);
    r.id = r.H ? sm : grp * 16 + pos * 2 + (sm & 1);
    r.kind = r.H ? 2 : r.L;
    r.a0 = r.L ? (r.mt >> 3) * 448 : 0;
    r.a1 = r.L ? (r.mt & 7) * 128 : r.H ? 120 : r.mt * 64;
    r.b3 = r.H ? 4 + r.ns : r.L ? r.ns : 0;
    return r;
}

__device__ __forceinline__ void first_fill(const Maps& maps, const Role& r, int i) {
    const bool E = r.kind == 0;
    const CUtensorMap* ma = &maps.m[r.kind];
    const uint32_t bar = full_bar(i);
    const int k = (i * 64) >> r.L;
    const bool has_a = !(i & r.L), has_b = i < 7 - r.L;
    const uint32_t dst = base + BRING + (E ? (0x2104365u >> (4 * i)) & 7 : i) * SLOT;
    mbar_expect(bar, (has_a ? SLOT : 0) + (has_b ? (E ? BLOB : SLOT) : 0));
    if (has_a) tma_ld4(base + (i >> r.L) * SLOT, ma, r.a0 + k, r.a1, 0, 0, bar);
    if (has_b) {
        tma_ld4(dst, ma + 3, E ? k : 0, E ? r.ns * 112 : k, 0, r.b3, bar);
        if (!E) tma_ld4(dst + 8192, ma + 3, 64, k, 0, r.b3, bar);
        mbar_arrive(bar);
    }
}
static_assert(bslot_e(0) == 5 && bslot_e(1) == 6 && bslot_e(2) == 3 && bslot_e(3) == 4 && bslot_e(4) == 0 && bslot_e(6) == 2, "");

template <bool BY_SM>
__global__ void __launch_bounds__(384, 1) fused_kernel(Scratch* sc, const __grid_constant__ Maps maps) {
    const unsigned t_open = clk32();
    const int warp = __shfl_sync(0xffffffffu, threadIdx.x >> 5, 0);
    if (warp == 8) {
        if (elect()) {
#pragma unroll
            for (int i = 0; i < LEAD; i++) mbar_init(base + BAR_FULL + i * 8, 2);
            asm volatile("fence.mbarrier_init.release.cluster;" ::: "memory");
            const Role r = decode_role<BY_SM>();
#pragma unroll 1
            for (int i = 0; i < LEAD; i++) first_fill(maps, r, i);
        }
    }
    if (warp == 9) {
        if (elect()) {
#pragma unroll
            for (int i = 0; i < 8; i++) mbar_init(base + BAR_EMPTY + i * 8, 4);
            asm volatile("fence.mbarrier_init.release.cluster;" ::: "memory");
        }
    } else if (warp == 10) {
        if (elect()) {
#pragma unroll
            for (int i = 0; i < 3; i++) mbar_init(base + BAR_RDY + i * 8, i < 2 ? 4 : 8);
#pragma unroll
            for (int i = 0; i < 2; i++) mbar_init(base + BAR_HALO + i * 8, 1);
            asm volatile("fence.mbarrier_init.release.cluster;" ::: "memory");
        }
    } else if (warp == 11) {
        if (elect()) {
#pragma unroll
            for (int i = LEAD; i < 8; i++) mbar_init(base + BAR_FULL + i * 8, 2);
#pragma unroll
            for (int i = 0; i < 3; i++) mbar_init(base + BAR_DEP + i * 8, 1);
#pragma unroll
            for (int i = 0; i < 4; i++) mbar_init(base + BAR_PART + i * 8, 1);
            asm volatile("fence.mbarrier_init.release.cluster;" ::: "memory");
        }
    }
    __syncthreads();

    const Role role = decode_role<BY_SM>();
    int lane = threadIdx.x & 31;
    asm volatile("" : "+r"(lane));
    const bool roleH = role.H;
    const int roleL = role.L, mt = role.mt, ns = role.ns, bid = role.id;
    const int par = mt >> 3, blk = mt & 7, col = ns * 112;

    if (warp >= 8) {
        asm volatile("setmaxnreg.dec.sync.aligned.u32 56;");
#define PROF_FEED_A
#define PROF_FEED_B
        if (warp == 8) {
            if (elect()) {
                PROF(129);
#pragma unroll 1
                for (int i = LEAD; i < 7; i++) {
                    while (clk32() - t_open < i * PACE) {}
                    first_fill(maps, role, i);
                }
                PROF(134);
                Feed<0> f;
                const int row = mt * 128;
                auto c_run = [&](const CUtensorMap* m, int off, int n0, int n1) {
#pragma unroll 1
                    for (int n = n0; n < n1; n++) {
                        const uint32_t bar = f.acquire<NA>();
                        mbar_expect(bar, SLOT);
                        tma_ld2(f.dst, m, (off + skip_own(n, mt)) * 64, row, bar);
                        PROF_FEED_A;
                        f.next<NA>();
                    }
                };
                if (roleH) {
                    mbar_expect(base + BAR_DEP, 7 * SLOT);
#pragma unroll 1
                    for (int i = 0; i < 7; i++) {
                        const uint32_t dst = base + (i < 6 ? i : 7) * SLOT;
                        if (i < 6) wait_released(7 + i);
                        tma_ld4(dst, &maps.m[M_WO], 0, i * 64, 0, ns, base + BAR_DEP);
                        tma_ld4(dst + 8192, &maps.m[M_WO], 64, i * 64, 0, ns, base + BAR_DEP);
                    }
                    mbar_wait(base + BAR_DEP, 0);
                    mbar_wait(base + BAR_RDY + 16, 0);
#pragma unroll 1
                    for (int i = 0; i < 7; i++) bulk_st(sc->wo + (size_t)(ns * 7 + i) * SLOT, base + (i < 6 ? i : 7) * SLOT, SLOT);
                    bulk_commit();
                    asm volatile("cp.async.bulk.wait_group 0;" ::: "memory");
                    signal(sc, CNT_W + ns);
                } else if (!roleL) {
                    f.seek(14, 0);
#pragma unroll 1
                    for (int i = 0; i < 4; i++) {
                        const uint32_t bar = f.acquire<NA>();
                        mbar_expect(bar, SLOT);
                        tma_ld2(f.dst, &maps.m[M_CR + (i >> 1)], ((i & 1) * 16 + mt) * 64, row, bar);
                        mbar_arrive(bar);
                        PROF_FEED_A;
                        f.next<NA>();
                    }
                    c_run(&maps.m[M_CR], 0, 0, 15);
                    c_run(&maps.m[M_CI], 0, 0, NBE);
                    wait_dep(2);
#pragma unroll 1
                    for (int i = 0; i < 7; i++) {
                        const uint32_t bar = f.acquire<NA>();
                        mbar_expect(bar, SLOT);
                        bulk_ld(f.dst, sc->o + (size_t)(mt * 7 + i) * SLOT, SLOT, bar);
                        PROF_FEED_A;
                        f.next<NA>();
                    }
                } else {
#pragma unroll 1
                    for (int i = 4; i < 7; i++) {
                        wait_released(2 * i - 8);
                        mbar_expect(full_bar(2 * i), SLOT);
                        tma_ld4(base + i * SLOT, &maps.m[M_XA], par * 448 + i * 64, blk * 128, 0, 0, full_bar(2 * i));
                    }
                    wait_released(HALO_K_AT);
                    mbar_arrive(base + BAR_DEP + 16);
                    f.seek(21, 0);
                    c_run(&maps.m[M_CR], 16, 0, 15);
                    c_run(&maps.m[M_CI], 16, 0, 15);
                    c_run(&maps.m[M_CI], 0, NBE, 15);
                }
            }
        } else if (warp == 11) {
            if (elect()) {
                Feed<BRING> f;
                auto blob_run = [&](auto nbs, int quarter, int n0, int n1) {
                    constexpr int N = decltype(nbs)::value;
                    const uint8_t* src = sc->ab + (size_t)(quarter * 64 + ns) * BLOB;
#pragma unroll 1
                    for (int n = n0; n < n1; n++) {
                        const uint32_t bar = f.template acquire<N>();
                        mbar_expect(bar, BLOB);
                        bulk_ld(f.dst, src + skip_own(n, mt) * (4 * BLOB), BLOB, bar);
                        PROF_FEED_B;
                        f.template next<N>();
                    }
                };
                auto v_run = [&](auto nbs) {
                    constexpr int N = decltype(nbs)::value;
#pragma unroll 1
                    for (int i = 0; i < 7; i++) {
                        const uint32_t bar = f.template acquire<N>();
                        mbar_expect(bar, SLOT);
                        tma_ld4(f.dst, &maps.m[M_WV], 0, i * 64, 0, 8 + ns, bar);
                        tma_ld4(f.dst + 8192, &maps.m[M_WV], 64, i * 64, 0, 8 + ns, bar);
                        mbar_arrive(bar);
                        PROF_FEED_B;
                        f.template next<N>();
                    }
                };
                if (roleH) {
                    f.seek(7, 0);
                    v_run(Int<7>());
                } else if (!roleL) {
                    f.seek(7, bslot_e(7));
#pragma unroll 1
                    for (int i = 0; i < 7; i++) {
                        const uint32_t bar = f.acquire<5>();
                        mbar_expect(bar, BLOB);
                        tma_ld2(f.dst, &maps.m[M_WI], i * 64, col, bar);
                        mbar_arrive(bar);
                        PROF_FEED_B;
                        f.next<5>();
                    }
                    f.seek(18, bslot_e(18));
                    wait_dep(0);
                    blob_run(Int<7>(), 0, 0, 15);
                    wait_dep(1);
                    blob_run(Int<7>(), 2, 0, NBE);
                    mbar_wait(base + BAR_HINT, 0);
                    fence_async_global();
#pragma unroll 1
                    for (int i = 0; i < 7; i++) {
                        const uint32_t bar = f.acquire<7>();
                        mbar_expect(bar, SLOT);
                        bulk_ld(f.dst, sc->wo + (size_t)(ns * 7 + i) * SLOT, SLOT, bar);
                        PROF_FEED_B;
                        f.next<7>();
                    }

                } else {
                    f.seek(6, 0);
#pragma unroll 1
                    for (int i = 6; i < 14; i++) {
                        const uint32_t bar = f.acquire<6>();
                        mbar_expect(bar, SLOT);
                        tma_ld4(f.dst, &maps.m[M_WQK], 0, i * 32, 0, ns, bar);
                        tma_ld4(f.dst + 8192, &maps.m[M_WQK], 64, i * 32, 0, ns, bar);
                        if (i & 1) mbar_arrive(bar);
                        PROF_FEED_B;
                        f.next<6>();
                    }
                    v_run(Int<6>());
                    wait_dep(0);
                    blob_run(Int<6>(), 1, 0, 15);
                    wait_dep(1);
                    blob_run(Int<6>(), 3, 0, 15);
                    blob_run(Int<6>(), 2, NBE, 15);
                    fence_async_smem();
#pragma unroll 1
                    for (int h = 0; h < 2; h++) {
                        mbar_wait(base + BAR_HINT + h * 8, 0);
                        PROF(153 + h);
                        mbar_expect(base + BAR_PART + h * 8, BLOB);
                        bulk_ld(base + (h ? HALO : LSLAB), sc->part + (size_t)((ns * 16 + mt) * 2 + h) * BLOB, BLOB, base + BAR_PART + h * 8);
                    }
                }
            }
        } else if (roleH) {
            if (warp == 9 && elect()) {
                wait_released(0);
#pragma unroll 1
                for (int i = 0; i < 7; i++)
                    asm volatile("cp.async.bulk.prefetch.tensor.2d.L2.global [%0, {%1, %2}];" ::"l"(&maps.m[M_WI]), "r"(i * 64), "r"(col) : "memory");
            }
        } else if (warp == 10) {
            if (elect()) {
                unsigned* epoch_ptr = &sc->epoch[(bid * 4 + 2) * 8];
                const unsigned ep = *epoch_ptr + 1;
                sts1(base + TAG, ep);
                asm volatile("prefetch.tensormap [%0];" ::"l"(&maps.m[M_OUTA + roleL]) : "memory");
                await(sc, CNT_A + roleL * 4 + ns, ep * 16);
                mbar_arrive(base + BAR_DEP);
                PROF(150);
                await(sc, CNT_B + ns, ep * 16);
                mbar_arrive(base + BAR_DEP + 8);
                PROF(151);
                if (!roleL) {
                    await(sc, CNT_W + ns, ep);
                    mbar_arrive(base + BAR_HINT);
                    PROF(153);
                    await(sc, CNT_O + mt, ep * 4);
                    mbar_arrive(base + BAR_DEP + 16);
                } else {
                    await(sc, CNT_P + mt * 4 + ns, ep * 2 - 1);
                    mbar_arrive(base + BAR_HINT);
                    await(sc, CNT_P + mt * 4 + ns, ep * 2);
                    mbar_arrive(base + BAR_HINT + 8);
                }
                PROF(152);
                *epoch_ptr = ep;
            }
        } else if (!roleL) {
            if (elect()) {
                mbar_wait(base + BAR_RDY, 0);
                PROF(130);
                signal(sc, CNT_A + ns);
                PROF(131);
                mbar_wait(base + BAR_RDY + 8, 0);
                signal(sc, CNT_A + 4 + ns);
                PROF(135);
                mbar_wait(base + BAR_RDY + 16, 0);
                PROF(132);
                signal(sc, CNT_B + ns);
                PROF(133);
            }
        } else {
            unsigned* epoch_ptr = &sc->epoch[(bid * 4 + 1) * 8];
            const unsigned tag = *epoch_ptr + 1;
#pragma unroll 1
            for (int kv = 0; kv < 2; kv++) {
                uint32_t v[16];
#pragma unroll
                for (int i = 0; i < 16; i++) v[i] = 0;
                if (kv) wait_released(HALO_V_AT - 4), wait_released(HALO_V_AT);
                else mbar_wait(base + BAR_DEP + 16, 0);
                if (blk > 0) {
                    const uint8_t* src = sc->halo + (size_t)(((mt - 1) * 4 + ns) * 2 + kv) * 2048 + lane * 16;
#pragma unroll 1
                    for (int n = 0; n < SPIN_LIMIT; n++) {
#pragma unroll
                        for (int i = 0; i < 4; i++) ld_tagged(src + i * 512, v[4 * i], v[4 * i + 1], v[4 * i + 2], v[4 * i + 3]);
#pragma unroll
                        for (int i = 0; i < 16; i += 2) v[i] ^= tag & 1;
                        const uint32_t stale = or3(or3(v[0], v[2], v[4]), or3(v[6], v[8], v[10]), or3(v[12], v[14], 0));
                        if (__all_sync(0xffffffffu, !(stale & 1))) break;
                    }
#pragma unroll
                    for (int c = 0; c < 14; c += 2) v[c] |= (v[15] >> c) & 1;
                }
#pragma unroll
                for (int i = 0; i < 14; i++) sts1(base + HALO + kv * (8 * HSLOT) + i * 128 + lane * 4, v[i]);
                warp_arrive(base + BAR_HALO + kv * 8);
                if (lane == 0) PROF(142 + kv);
            }
            if (elect()) {
                mbar_wait(base + BAR_RDY + 16, 0);
                PROF(130);
                signal(sc, CNT_O + mt);
                PROF(131);
                *epoch_ptr = tag;
            }
        }
    } else {
        asm volatile("setmaxnreg.inc.sync.aligned.u32 224;");
        Ring r;
        r.wg = warp >> 2;
        r.zero = blockIdx.y;
        r.releaser = lane + 1 == (warp >> 2);
        const int wg = warp >> 2;
        if (wg) nb_arrive(1, 256);
        uint8_t* part = sc->part + (size_t)(ns * 16 + mt) * (2 * BLOB) + warp * WSLOT + lane * 16;
        uint32_t p[28];

        if (roleH) {
            unsigned* epoch_ptr = &sc->epoch[bid * 4 * 8];
            const unsigned tag = *epoch_ptr + 1;
            uint8_t* hout = sc->halo + (size_t)((warp * 8 + ns) * 2) * 2048 + lane * 16;
            auto send = [&](int kv) {
#pragma unroll
                for (int h = 0; h < 2; h++) {
                    uint32_t v[16];
                    v[14] = v[15] = 0;
#pragma unroll
                    for (int c = 0; c < 14; c++) v[c] = p[2 * c + h];
#pragma unroll
                    for (int c = 0; c < 14; c += 2) v[15] |= (v[c] & 1) << c;
#pragma unroll
                    for (int i = 0; i < 4; i++) st_part(hout + (h * 8 + kv) * 2048 + i * 512, v + 4 * i, tag & 1);
                }
            };
            float x0[56], x1[56];
            r.seek(0, 0);
            r.wait();
            r.run<XWN, 7, true>(x0);
#pragma unroll 1
            for (int i = 1; i < 7; i++) r.run<XWN, 7, false>(x0);
            r.run<XWN, 7, true>(x1);
            acc_fence(x0);
            pack_all(x0, p);
            send(0);
#pragma unroll 1
            for (int i = 1; i < 7; i++) r.run<XWN, 7, false>(x1, true, i < 6 || !wg, i < 6);
            asm volatile("wgmma.wait_group.sync.aligned 0;" ::: "memory");
            acc_fence(x1);
            pack_all(x1, p);
#pragma unroll
            for (int i = 0; i < 28; i++) p[i] = movm(p[i]);
            send(1);
            warp_arrive(base + BAR_RDY + 16);
            if (threadIdx.x == 0) *epoch_ptr = tag;
        } else if (!roleL) {
            uint8_t* blob = sc->ab + (size_t)((wg * 16 + mt) * 4 + ns) * BLOB + (warp & 3) * WSLOT + lane * 4;
            const uint32_t own = base + BRING + wg * SLOT + (warp & 3) * WSLOT + lane * 16;
            float x0[56], x1[56];
            r.seek(0, bslot_e(0));
            r.wait();
            r.run<XW, 7, true>(x0);
            r.run<XW, 7, false>(x0);
            r.seek(2, bslot_e(2));
#pragma unroll 1
            for (int i = 2; i < 7; i++) r.run<XW, 5, false>(x0);

            r.seek(7, bslot_e(7));
            r.run<XW, 5, true, -1>(x1);
            acc_fence(x0);
            pack_all<0, 14>(x0, p);
#pragma unroll
            for (int i = 0; i < 2; i++) {
                if (wg == i) store_frags<0, 14>(blob, p);
                else stage_frags<0, 4>(own + 5 * SLOT, p);
                r.run<XW, 5, false, -1>(x1);
                if (i == 0) pack_all<14, 28>(x0, p);
                if (wg == i) {
                    store_frags<14, 28>(blob, p);
                    warp_arrive(base + BAR_RDY + i * 8);
                } else {
                    stage_frags<4, 8>(own + 5 * SLOT, p);
                }
                r.run<XW, 5, false, -1>(x1);
            }
            stage_frags<8, 20>(own + 5 * SLOT, p);
            r.run<XW, 5, false, -1>(x1);
            stage_frags<20, 28>(own + 5 * SLOT, p);
            fence_async_smem();
            r.run<XW, 5, false, -1>(x1);

            r.seek(14, bslot_e(14));
            r.run<BIG, 7, true>(x0);
            acc_fence(x1);
            pack_all(x1, p);
            stage_frags<0, 28>(own, p);
            r.run<BIG, 7, false>(x0);
            fence_async_smem();
            blob += (size_t)128 * BLOB;
#pragma unroll
            for (int i = 0; i < 28; i++) {
                if (i % B_SLICE == 0) r.run<BIG, 7, false>(x0);
                stg1(blob + i * 128, p[i]);
            }
            warp_arrive(base + BAR_RDY + 16);
#pragma unroll 1
            for (int i = 17 + 27 / B_SLICE; i < POUT; i++) r.run<BIG, 7, false>(x0);

            const uint32_t tag = lds1(base + TAG);
            r.seek(POUT, bslot_e(POUT));
            r.run<OUT, 7, true>(x1);
            acc_fence(x0);
            pack_all(x0, p);
#pragma unroll
            for (int k = 0; k < 3; k++) {
                if (k < 2 && wg == k) {
#pragma unroll
                    for (int i = 0; i < P_FIRST; i++) st_part(part + i * 512, p + 4 * i, tag & 1);
                    if ((warp & 3) == 0 && elect())
                        asm volatile("red.relaxed.gpu.global.add.u32 [%0], 1;" ::"l"(&sc->cnt[(CNT_P + mt * 4 + ns) * 32]) : "memory");
                }
                if (k > 0 && wg == k - 1) {
#pragma unroll
                    for (int i = P_FIRST; i < 7; i++) st_part(part + i * 512, p + 4 * i, tag & 1);
                }
                if (k < 2) r.run<OUT, 7, false>(x1);
            }
#pragma unroll
            for (int i = 3; i < 7; i++) r.run<OUT, 7, false, 1, true>(x1, i <= 7 - TURN, i < 7 - TURN || (i == 6 && !wg), i < 6);

            asm volatile("wgmma.wait_group.sync.aligned 0;" ::: "memory");
            acc_fence(x1);
            const uint32_t slab = base + (wg ? BRING + bslot_e(ELAST - 6) * SLOT : ((ELAST - 6) % NA) * SLOT) + (warp & 3) * WSLOT;
            store_out([&](int i) { return pack2(x1[2 * i], x1[2 * i + 1]); }, lane, slab, &maps.m[M_OUTA], par * 896 + col, blk * 128 + warp * 16);
        } else {
            const int g = lane >> 2, tig = lane & 3;
            const uint32_t hin = base + HALO + warp * HSLOT + lane * 4;
            const uint32_t hpub = warp < 7 ? hin + HSLOT : base + HSPARE + lane * 4;
            auto publish = [&](const uint32_t (&h)[14], int c0, int c1) {
#pragma unroll
                for (int c = 0; c < 14; c++)
                    if (c >= c0 && c < c1) sts1(hpub + c * 128, h[c]);
            };
            float y0[56], y1[56], y2[56];
            r.seek(0, 0);
            r.wait();
            r.run<QK, 6, true>(y0, y1);
#pragma unroll 1
            for (int i = 1; i < 14; i++) r.run<QK, 6, false>(y0, y1);

            uint32_t m1[8][4], m0[8][4], lo[14], hi[14], q[2][8][2];
            auto pack_q = [&](int b) {
                uint32_t v[14];
#pragma unroll
                for (int c = 0; c < 14; c++) v[c] = pack2(y0[4 * c + 2 * b], y0[4 * c + 2 * b + 1]);
#pragma unroll
                for (int t = 0; t < 8; t++) {
                    const int c = tile_of(t);
                    q[b][t][0] = (t & 3) == 2 ? (tig >= 2 ? v[c] : 0u) : v[c];
                    q[b][t][1] = (t & 3) == 1 ? (tig < 2 ? v[c + 1] : 0u) : v[c + 1];
                }
            };
            auto fetch = [&](uint32_t src, int hp, int i0) {
#pragma unroll
                for (int t = 4 * hp; t < 4 * hp + 4; t++) {
                    m0[t][i0] = (t & 3) == 2 ? dup(m0[t - 1][3], r.zero) : lds1(src + tile_of(t) * 128);
                    m0[t][3] = lds1(src + tile_of(t) * 128 + 128);
                }
            };
            r.seek(14, bslot_l(14));
            r.run<XWN, 6, true>(y2);
            acc_fence(y0);
            acc_fence(y1);
#pragma unroll
            for (int c = 0; c < 14; c++) hi[c] = pack2(y1[4 * c + 2], y1[4 * c + 3]);
            publish(hi, 0, 7);
            r.run<XWN, 6, false>(y2);
            publish(hi, 7, 14);
#pragma unroll
            for (int c = 0; c < 14; c++) lo[c] = pack2(y1[4 * c], y1[4 * c + 1]);
#pragma unroll
            for (int t = 0; t < 8; t++) {
                const int c = tile_of(t);
                const bool shared = (t & 3) == 2;
                m1[t][0] = shared ? dup(lo[c], r.zero) : lo[c];
                m1[t][1] = shared ? dup(hi[c], r.zero) : hi[c];
                m1[t][2] = lo[c + 1];
                m1[t][3] = hi[c + 1];
                m0[t][0] = dup(m1[t][0], r.zero);
                m0[t][2] = dup(lo[c + 1], 2 * r.zero);
            }
            r.run<XWN, 6, false>(y2);
            if (warp == 0) mbar_wait(base + BAR_HALO, 0);
            fetch(hin, 0, 1);
            pack_q(1);
            r.run<XWN, 6, false>(y2);
            fetch(hin, 1, 1);
            pack_q(0);
            r.mma_begin();
            float s[8][4];
#pragma unroll
            for (int step = 0; step < 2; step++) {
#pragma unroll
                for (int i = 0; i < 8; i++) {
                    const int b = 1 - (i >> 2), h = i & 3, t = 2 * h + step;
                    float (&d)[4] = s[2 * h + b];
                    if (step == 0) d[0] = d[1] = d[2] = d[3] = 0.f;
                    mma16816(d, b ? m1[t] : m0[t], q[b][t][0], q[b][t][1]);
                }
            }
            r.mma_end();
            r.run<XWN, 6, false>(y2, false);

            uint32_t pr[8], mx[4], mx1[4];
            {
                const bool cur0 = g <= 2 * tig, cur1 = g <= 2 * tig + 1;
#pragma unroll
                for (int i = 0; i < 8; i++) {
                    const int c = (i & 1) ? 2 : 0;
                    pr[i] = movm(pack2(cur0 ? s[i][c] : s[i][2 - c], cur1 ? s[i][c + 1] : s[i][3 - c]));
                }
            }
            r.run<XWN, 6, false>(y2);
            const uint32_t curmask = (2 * tig <= g ? 0x0000FFFFu : 0u) | (2 * tig + 1 <= g ? 0xFFFF0000u : 0u);
            {
                const uint32_t keep = (blk == 0 && warp == 0) ? curmask : 0xFFFFFFFFu;
#pragma unroll
                for (int i = 0; i < 4; i++) {
                    pr[2 * i] = (scale2(pr[2 * i]) & keep) | (0xCE6ECE6Eu & ~keep);
                    pr[2 * i + 1] = scale2(pr[2 * i + 1]);
                    mx[i] = max2(__byte_perm(pr[2 * i], pr[2 * i + 1], 0x5410), __byte_perm(pr[2 * i], pr[2 * i + 1], 0x7632));
                    mx1[i] = __shfl_xor_sync(0xffffffffu, mx[i], 1);
                }
            }
#pragma unroll
            for (int i = 0; i < 4; i++) {
                mx[i] = max2(mx[i], mx1[i]);
                mx1[i] = __shfl_xor_sync(0xffffffffu, mx[i], 2);
            }
            r.run<XWN, 6, false>(y2);
            constexpr float SCL = 1.4426950408889634f;
            float e0[8], e1[8], sm[8], sm1[8];
#pragma unroll
            for (int i = 0; i < 8; i++) {
                const uint32_t m2 = max2(mx[i >> 1], mx1[i >> 1]);
                sm[i] = ((i & 1) ? bf_hi(m2) : bf_lo(m2)) * -SCL;
                e0[i] = ex2(fmaf(bf_lo(pr[i]), SCL, sm[i]));
            }

            r.seek(21, bslot_l(21));
            r.run<BIG, 6, true>(y0);
            acc_fence(y2);
#pragma unroll
            for (int c = 0; c < 7; c++) hi[c] = movm(pack2(y2[4 * c + 2], y2[4 * c + 3]));
#pragma unroll
            for (int i = 0; i < 8; i++) e1[i] = ex2(fmaf(bf_hi(pr[i]), SCL, sm[i]));
            r.run<BIG, 6, false>(y0);
            publish(hi, 0, 7);
#pragma unroll
            for (int c = 7; c < 14; c++) hi[c] = movm(pack2(y2[4 * c + 2], y2[4 * c + 3]));
            r.run<BIG, 6, false>(y0);
            publish(hi, 7, 14);
#pragma unroll
            for (int i = 0; i < 8; i++) {
                sm[i] = e0[i] + e1[i];
                sm1[i] = __shfl_xor_sync(0xffffffffu, sm[i], 1);
            }
            r.run<BIG, 6, false>(y0);
#pragma unroll
            for (int c = 0; c < 14; c++) lo[c] = movm(pack2(y2[4 * c], y2[4 * c + 1]));
            r.run<BIG, 6, false>(y0);
#pragma unroll
            for (int i = 0; i < 8; i++) {
                sm[i] += sm1[i];
                sm1[i] = __shfl_xor_sync(0xffffffffu, sm[i], 2);
            }
#pragma unroll
            for (int t = 0; t < 8; t++) {
                const int c = tile_of(t);
                const bool shared = (t & 3) == 2;
                m1[t][0] = shared ? dup(lo[c], r.zero) : lo[c];
                m1[t][1] = lo[c + 1];
                m1[t][2] = shared ? dup(hi[c], r.zero) : hi[c];
                m1[t][3] = hi[c + 1];
                m0[t][0] = dup(m1[t][0], r.zero);
                m0[t][1] = dup(lo[c + 1], 2 * r.zero);
            }
            r.run<BIG, 6, false>(y0);
            if (warp == 0) mbar_wait(base + BAR_HALO + 8, 0);
            const uint32_t vin = warp ? hin : hin + 8 * HSLOT;
            fetch(vin, 0, 2);
#pragma unroll
            for (int i = 0; i < 8; i++) {
                const float inv = rcp(sm[i] + sm1[i]);
                pr[i] = pack2(e0[i] * inv, e1[i] * inv);
            }
            r.run<BIG, 6, false>(y0);
            fetch(vin, 1, 2);
            uint32_t pb[8][2];
#pragma unroll
            for (int t = 0; t < 8; t++) {
                pb[t][t & 1] = band(pr[t], curmask);
                pb[t][1 - (t & 1)] = band(pr[t], ~curmask);
            }
            r.mma_begin();
            float o[2][8][4];
#pragma unroll
            for (int i = 0; i < 16; i++) {
                const int b = 1 - (i >> 3), t = i & 7;
                float (&d)[4] = o[b][t];
                d[0] = d[1] = d[2] = d[3] = 0.f;
                mma16816(d, b ? m1[t] : m0[t], pb[(t & 6) + b][0], pb[(t & 6) + b][1]);
            }
            r.mma_end();
            r.run<BIG, 6, false>(y0, false);
            uint8_t* odst = sc->o + (size_t)mt * 7 * SLOT + ns * (14 * 2048) + warp * 256 + lane * 4;
#pragma unroll
            for (int hp = 0; hp < 2; hp++) {
#pragma unroll
                for (int b = 0; b < 2; b++) {
                    const float (&u)[8][4] = o[b];
                    const int t = 4 * hp;
                    uint32_t* w = p + 14 * hp + b;
                    w[0] = pack2(u[t][0], u[t][1]);
                    w[2] = pack2(u[t][2], u[t][3]);
                    w[4] = pack2(u[t + 1][0], u[t + 1][1]);
                    w[6] = pack2(g < 4 ? u[t + 1][2] : u[t + 2][0], g < 4 ? u[t + 1][3] : u[t + 2][1]);
                    w[8] = pack2(u[t + 2][2], u[t + 2][3]);
                    w[10] = pack2(u[t + 3][0], u[t + 3][1]);
                    w[12] = pack2(u[t + 3][2], u[t + 3][3]);
                }
            }
#pragma unroll
            for (int i = 0; i < 28; i++) {
                if (i >= O_FIRST && (i - O_FIRST) % O_SLICE == 0) r.run<BIG, 6, false>(y0);
                stg1(odst + (i >> 1) * 2048 + (i & 1) * 128, p[i]);
            }
            warp_arrive(base + BAR_RDY + 16);

#pragma unroll 1
            for (int i = 30 + (27 - O_FIRST) / O_SLICE; i <= LLAST - TURN; i++) r.run<BIG, 6, false>(y0);
            r.seek(LLAST + 1 - TURN, bslot_l(LLAST + 1 - TURN));
#pragma unroll
            for (int i = 0; i < TURN; i++) r.run<BIG, 6, false, 1, true>(y0, i == 0, i == TURN - 1 && !wg, i < TURN - 1);
            const uint32_t parity = lds1(base + TAG) & 1;
            const uint32_t slab = base + (wg ? HALO : LSLAB) + (warp & 3) * WSLOT;
            mbar_wait(base + BAR_PART + wg * 8, 0);
#pragma unroll 1
            for (int n = 0; n < SPIN_LIMIT; n++) {
#pragma unroll
                for (int i = 0; i < 7; i++) lds4(slab + i * 512 + lane * 16, p + 4 * i);
#pragma unroll
                for (int i = 0; i < 28; i += 2) p[i] ^= parity;
                const uint32_t stale = or3(or3(or3(p[0], p[2], p[4]), or3(p[6], p[8], p[10]), or3(p[12], p[14], p[16])),
                                           or3(p[18], p[20], p[22]), or3(p[24], p[26], 0));
                if (__all_sync(0xffffffffu, !(stale & 1))) break;
#pragma unroll
                for (int i = 0; i < 7; i++) ld_tagged(part + i * 512, p[4 * i], p[4 * i + 1], p[4 * i + 2], p[4 * i + 3]);
#pragma unroll
                for (int i = 0; i < 7; i++)
                    asm volatile("st.shared.v4.b32 [%0], {%1,%2,%3,%4};" ::"r"(slab + i * 512 + lane * 16), "r"(p[4 * i]), "r"(p[4 * i + 1]), "r"(p[4 * i + 2]), "r"(p[4 * i + 3]) : "memory");
            }
            asm volatile("wgmma.wait_group.sync.aligned 0;" ::: "memory");
            acc_fence(y0);
            store_out([&](int i) { return add2(pack2(y0[2 * i], y0[2 * i + 1]), p[i]); }, lane, slab, &maps.m[M_OUTB], 448 + col, mt * 128 + warp * 16);
        }
    }
}

typedef CUresult (*EncodeFn)(CUtensorMap*, CUtensorMapDataType, cuuint32_t, void*, const cuuint64_t*, const cuuint64_t*,
                             const cuuint32_t*, const cuuint32_t*, CUtensorMapInterleave, CUtensorMapSwizzle,
                             CUtensorMapL2promotion, CUtensorMapFloatOOBfill);

struct Dim { uint64_t size, stride; uint32_t box; };
void encode(EncodeFn fn, CUtensorMap* m, const void* ptr, CUtensorMapSwizzle sw, Dim d0, Dim d1, Dim d2 = {0, 0, 0}, Dim d3 = {0, 0, 0}) {
    const cuuint64_t dims[4] = {d0.size, d1.size, d2.size, d3.size};
    const cuuint64_t strides[3] = {d1.stride, d2.stride, d3.stride};
    const cuuint32_t box[4] = {d0.box, d1.box, d2.box, d3.box};
    const cuuint32_t es[4] = {1, 1, 1, 1};
    fn(m, CU_TENSOR_MAP_DATA_TYPE_BFLOAT16, d3.size ? 4 : d2.size ? 3 : 2, const_cast<void*>(ptr), dims, strides, box, es,
       CU_TENSOR_MAP_INTERLEAVE_NONE, sw, CU_TENSOR_MAP_L2_PROMOTION_L2_128B, CU_TENSOR_MAP_FLOAT_OOB_FILL_NONE);
}

}

extern "C" void kernel_launch(void* const* d_in, const int* in_sizes, int n_in, void* d_out, int out_size) {
    (void)in_sizes; (void)n_in; (void)out_size;
    void* fnp = nullptr;
    cudaDriverEntryPointQueryResult st;
    cudaGetDriverEntryPoint("cuTensorMapEncodeTiled", &fnp, cudaEnableDefault, &st);
    EncodeFn fn = (EncodeFn)fnp;
    void* scratch = nullptr;
    cudaGetSymbolAddress(&scratch, g_scratch);
    int dev = 0, sms = 0;
    cudaGetDevice(&dev);
    cudaDeviceGetAttribute(&sms, cudaDevAttrMultiProcessorCount, dev);
    auto kernel = sms == 132 ? fused_kernel<true> : fused_kernel<false>;
    cudaFuncSetAttribute(kernel, cudaFuncAttributeMaxDynamicSharedMemorySize, SMEM_BYTES);

    const CUtensorMapSwizzle S128 = CU_TENSOR_MAP_SWIZZLE_128B, S0 = CU_TENSOR_MAP_SWIZZLE_NONE;
    const Dim one = {1, 16, 1};
    Maps maps;
    encode(fn, &maps.m[M_XA], d_in[0], S128, {896, 2, 64}, {1024, 1792, 128}, one, one);
    encode(fn, &maps.m[M_WQK], d_in[1], S128, {112, 2, 64}, {448, 2688, 32}, {3, 896, 2}, {4, 224, 1});
    encode(fn, &maps.m[M_WV], d_in[1], S128, {112, 2, 64}, {448, 2688, 64}, one, {12, 224, 1});
    encode(fn, &maps.m[M_XH], d_in[0], S128, {448, 2, 64}, {128, 1792, 8}, {8, 128 * 1792, 8}, {2, 896, 2});
    encode(fn, &maps.m[M_WO], d_in[2], S128, {112, 2, 64}, {448, 896, 64}, one, {4, 224, 1});
    encode(fn, &maps.m[M_XB], d_in[3], S128, {448, 2, 64}, {1024, 896, 64}, {2, 896 * 1024, 2}, one);
    encode(fn, &maps.m[M_CR], d_in[4], S128, {2048, 2, 64}, {2048, 4096, 128});
    encode(fn, &maps.m[M_CI], d_in[5], S128, {2048, 2, 64}, {2048, 4096, 128});
    encode(fn, &maps.m[M_WR], d_in[6], S128, {448, 2, 64}, {448, 896, 112}, one, one);
    encode(fn, &maps.m[M_WI], d_in[7], S128, {448, 2, 64}, {448, 896, 112});
    encode(fn, &maps.m[M_OUTA], d_out, S0, {1792, 2, 112}, {1024, 3584, 8});
    encode(fn, &maps.m[M_OUTB], d_out, S0, {896, 2, 112}, {2048, 1792, 8});

    kernel<<<132, 384, SMEM_BYTES>>>((Scratch*)scratch, maps);
}
```

```cpp
#include <cuda.h>
#include <cuda_bf16.h>
#include <cuda_runtime.h>
#include <stdint.h>

namespace {

constexpr uint32_t SLOT = 16384;
constexpr int NA = 7;
constexpr uint32_t BRING = NA * SLOT;
constexpr uint32_t HALO = BRING + 6 * SLOT;
constexpr uint32_t HSLOT = 1792;
constexpr uint32_t WSLOT = 3584;
constexpr uint32_t BLOB = 14336;
constexpr uint32_t BARS = 14 * SLOT;
constexpr uint32_t BAR_FULL = BARS;
constexpr uint32_t BAR_EMPTY = BARS + 64;
constexpr uint32_t BAR_RDY = BARS + 128;
constexpr uint32_t BAR_DEP = BARS + 168;
constexpr uint32_t BAR_HALO = BARS + 192;
constexpr uint32_t BAR_PART = BARS + 208;
constexpr uint32_t BAR_HINT = BARS + 224;
constexpr uint32_t TAG = BARS + 240;
constexpr uint32_t HSPARE = BARS + 256 + 1024;
constexpr uint32_t SMEM_BYTES = HSPARE + HSLOT;
constexpr uint32_t base = 1024;
constexpr int SPIN_LIMIT = 1 << 16;

constexpr int LEAD = 3;
constexpr int PACE = 450;
constexpr int HALO_K_AT = 10;
constexpr int HALO_V_AT = 19;
constexpr int B_SLICE = 4;
constexpr int O_FIRST = 8, O_SLICE = 4;
constexpr int P_FIRST = 5;
constexpr int TURN = 4, LTURN = 5;
constexpr uint32_t GPC_MAP = 0x64752310u;
constexpr int NBE = 13;
constexpr int POUT = 33 + NBE;
constexpr int ELAST = POUT + 6;
constexpr int LLAST = 65 - NBE;
constexpr uint32_t LSLAB = ((LLAST - 6) % NA) * SLOT;
static_assert(TURN <= 4 && LTURN <= 5, "the output is staged in the slots of the seventh-last stage");

enum { M_XB, M_XA, M_XH, M_WR, M_WQK, M_WV, M_WO, M_WI, M_CR, M_CI, M_OUTA, M_OUTB, M_COUNT };
struct __align__(64) Maps { CUtensorMap m[M_COUNT]; };

constexpr int CNT_A = 0;
constexpr int CNT_B = 8;
constexpr int CNT_W = 12;
constexpr int CNT_O = 16;
constexpr int CNT_P = 32;
constexpr int CNT_COUNT = 96;

struct Scratch {
    uint8_t ab[64 * 4 * BLOB];
    uint8_t o[16 * 7 * SLOT];
    uint8_t part[64 * 2 * BLOB];
    uint8_t halo[64 * 2 * 2048];
    uint8_t wo[4 * 7 * SLOT];
    unsigned cnt[CNT_COUNT * 32];
    unsigned epoch[132 * 4 * 8];
};
__device__ __align__(1024) Scratch g_scratch;

__device__ __forceinline__ unsigned clk32() { unsigned c; asm volatile("mov.u32 %0, %%clock;" : "=r"(c)); return c; }

#define PROF(idx)

__device__ __forceinline__ void mbar_init(uint32_t bar, uint32_t cnt) {
    asm volatile("mbarrier.init.shared::cta.b64 [%0], %1;" ::"r"(bar), "r"(cnt) : "memory");
}
__device__ __forceinline__ void mbar_expect(uint32_t bar, uint32_t bytes) {
    asm volatile("mbarrier.arrive.expect_tx.shared::cta.b64 _, [%0], %1;" ::"r"(bar), "r"(bytes) : "memory");
}
__device__ __forceinline__ void mbar_arrive(uint32_t bar) {
    asm volatile("mbarrier.arrive.shared::cta.b64 _, [%0];" ::"r"(bar) : "memory");
}
__device__ __forceinline__ bool mbar_try(uint32_t bar, uint32_t parity) {
    uint32_t ok;
    asm volatile("{\n.reg .pred p;\nmbarrier.try_wait.parity.shared::cta.b64 p, [%1], %2;\nselp.u32 %0, 1, 0, p;\n}\n"
                 : "=r"(ok) : "r"(bar), "r"(parity) : "memory");
    return ok;
}
__device__ __forceinline__ void mbar_wait(uint32_t bar, uint32_t parity) {
#pragma unroll 1
    for (int n = 0; n < SPIN_LIMIT; n++)
        if (mbar_try(bar, parity)) break;
}
__device__ __forceinline__ bool elect() {
    uint32_t p;
    asm volatile("{\n.reg .pred p;\nelect.sync _|p, 0xffffffff;\nselp.u32 %0, 1, 0, p;\n}\n" : "=r"(p));
    return p;
}
__device__ __forceinline__ void nb_sync(int id, int n) { asm volatile("bar.sync %0, %1;" ::"r"(id), "r"(n) : "memory"); }
__device__ __forceinline__ void nb_arrive(int id, int n) { asm volatile("bar.arrive %0, %1;" ::"r"(id), "r"(n) : "memory"); }
__device__ __forceinline__ void warp_arrive(uint32_t bar) {
    __syncwarp();
    if (elect()) mbar_arrive(bar);
}
__device__ __forceinline__ uint32_t or3(uint32_t a, uint32_t b, uint32_t c) {
    uint32_t r;
    asm("lop3.b32 %0, %1, %2, %3, 0xFE;" : "=r"(r) : "r"(a), "r"(b), "r"(c));
    return r;
}
__device__ __forceinline__ uint32_t band(uint32_t x, uint32_t m) {
    uint32_t r;
    asm volatile("and.b32 %0, %1, %2;" : "=r"(r) : "r"(x), "r"(m));
    return r;
}
__device__ __forceinline__ uint32_t dup(uint32_t x, uint32_t zero) {
    uint32_t r;
    asm volatile("xor.b32 %0, %1, %2;" : "=r"(r) : "r"(x), "r"(zero));
    return r;
}

__device__ __forceinline__ void tma_ld2(uint32_t dst, const CUtensorMap* m, int c0, int c1, uint32_t bar) {
    asm volatile("cp.async.bulk.tensor.2d.shared::cluster.global.mbarrier::complete_tx::bytes [%0], [%1, {%3, %4}], [%2];"
                 ::"r"(dst), "l"(m), "r"(bar), "r"(c0), "r"(c1) : "memory");
}
__device__ __forceinline__ void tma_ld4(uint32_t dst, const CUtensorMap* m, int c0, int c1, int c2, int c3, uint32_t bar) {
    asm volatile("cp.async.bulk.tensor.4d.shared::cluster.global.mbarrier::complete_tx::bytes [%0], [%1, {%3, %4, %5, %6}], [%2];"
                 ::"r"(dst), "l"(m), "r"(bar), "r"(c0), "r"(c1), "r"(c2), "r"(c3) : "memory");
}
__device__ __forceinline__ void bulk_ld(uint32_t dst, const void* src, uint32_t bytes, uint32_t bar) {
    asm volatile("cp.async.bulk.shared::cluster.global.mbarrier::complete_tx::bytes [%0], [%1], %2, [%3];"
                 ::"r"(dst), "l"(src), "r"(bytes), "r"(bar) : "memory");
}
__device__ __forceinline__ void bulk_st(void* dst, uint32_t src, uint32_t bytes) {
    asm volatile("cp.async.bulk.global.shared::cta.bulk_group [%0], [%1], %2;" ::"l"(dst), "r"(src), "r"(bytes) : "memory");
}
__device__ __forceinline__ void tma_st2(const CUtensorMap* m, int c0, int c1, uint32_t src) {
    asm volatile("cp.async.bulk.tensor.2d.global.shared::cta.bulk_group [%0, {%1, %2}], [%3];"
                 ::"l"(m), "r"(c0), "r"(c1), "r"(src) : "memory");
}
__device__ __forceinline__ void bulk_commit() { asm volatile("cp.async.bulk.commit_group;" ::: "memory"); }
__device__ __forceinline__ void bulk_wait_read() { asm volatile("cp.async.bulk.wait_group.read 0;" ::: "memory"); }
__device__ __forceinline__ void fence_async_smem() { asm volatile("fence.proxy.async.shared::cta;" ::: "memory"); }
__device__ __forceinline__ void fence_async_global() { asm volatile("fence.proxy.async.global;" ::: "memory"); }

__device__ __forceinline__ void signal(Scratch* sc, int idx) {
    asm volatile("fence.proxy.async;\nred.relaxed.gpu.global.add.u32 [%0], 1;" ::"l"(&sc->cnt[idx * 32]) : "memory");
}
__device__ __forceinline__ unsigned peek(const unsigned* p) {
    unsigned v;
    asm volatile("ld.relaxed.gpu.global.u32 %0, [%1];" : "=r"(v) : "l"(p) : "memory");
    return v;
}
__device__ __forceinline__ void await(Scratch* sc, int idx, unsigned target) {
    const unsigned* p = &sc->cnt[idx * 32];
#pragma unroll 1
    for (int n = 0; n < SPIN_LIMIT; n++)
        if ((int)(peek(p) - target) >= 0) break;
    asm volatile("fence.acquire.gpu;" ::: "memory");
}
__device__ __forceinline__ void wait_dep(int k) {
    mbar_wait(base + BAR_DEP + k * 8, 0);
    fence_async_global();
}

#define WG_REGS                                                                                                     \
    "{%0,%1,%2,%3,%4,%5,%6,%7,%8,%9,%10,%11,%12,%13,%14,%15,%16,%17,%18,%19,%20,%21,%22,%23,%24,%25,%26,%27,"       \
    "%28,%29,%30,%31,%32,%33,%34,%35,%36,%37,%38,%39,%40,%41,%42,%43,%44,%45,%46,%47,%48,%49,%50,%51,%52,%53,%54,%55}"
#define WG_OPS(C)                                                                                                   \
    C(d[0]), C(d[1]), C(d[2]), C(d[3]), C(d[4]), C(d[5]), C(d[6]), C(d[7]), C(d[8]), C(d[9]), C(d[10]), C(d[11]),   \
    C(d[12]), C(d[13]), C(d[14]), C(d[15]), C(d[16]), C(d[17]), C(d[18]), C(d[19]), C(d[20]), C(d[21]), C(d[22]),   \
    C(d[23]), C(d[24]), C(d[25]), C(d[26]), C(d[27]), C(d[28]), C(d[29]), C(d[30]), C(d[31]), C(d[32]), C(d[33]),   \
    C(d[34]), C(d[35]), C(d[36]), C(d[37]), C(d[38]), C(d[39]), C(d[40]), C(d[41]), C(d[42]), C(d[43]), C(d[44]),   \
    C(d[45]), C(d[46]), C(d[47]), C(d[48]), C(d[49]), C(d[50]), C(d[51]), C(d[52]), C(d[53]), C(d[54]), C(d[55])

template <int TA, int TB, int SB, bool INIT, uint32_t AH, uint32_t BH>
__device__ __forceinline__ void wgmma112(float (&d)[56], uint32_t alo, uint32_t blo) {
    if (INIT) {
        asm volatile("{\n.reg .pred p;\n.reg .b64 da, db;\nsetp.ne.b32 p, 0, 0;\nmov.b64 da, {%56, %61};\nmov.b64 db, {%57, %62};\n"
                     "wgmma.mma_async.sync.aligned.m64n112k16.f32.bf16.bf16 " WG_REGS ", da, db, p, 1, %59, %60, %58;\n}\n"
                     : WG_OPS("=f") : "r"(alo), "r"(blo), "n"(TB), "n"(SB), "n"(TA), "n"(AH), "n"(BH));
    } else {
        asm volatile("{\n.reg .pred p;\n.reg .b64 da, db;\nsetp.ne.b32 p, 1, 0;\nmov.b64 da, {%56, %61};\nmov.b64 db, {%57, %62};\n"
                     "wgmma.mma_async.sync.aligned.m64n112k16.f32.bf16.bf16 " WG_REGS ", da, db, p, 1, %59, %60, %58;\n}\n"
                     : WG_OPS("+f") : "r"(alo), "r"(blo), "n"(TB), "n"(SB), "n"(TA), "n"(AH), "n"(BH));
    }
}
__device__ __forceinline__ void acc_fence(float (&d)[56]) {
#pragma unroll
    for (int i = 0; i < 56; i++) asm volatile("" : "+f"(d[i])::"memory");
}

__device__ __forceinline__ uint32_t pack2(float lo, float hi) {
    uint32_t r;
    asm volatile("cvt.rn.bf16x2.f32 %0, %1, %2;" : "=r"(r) : "f"(hi), "f"(lo));
    return r;
}
__device__ __forceinline__ uint32_t movm(uint32_t a) {
    uint32_t r;
    asm volatile("movmatrix.sync.aligned.m8n8.trans.b16 %0, %1;" : "=r"(r) : "r"(a));
    return r;
}
__device__ __forceinline__ void stsm4(uint32_t addr, uint32_t a, uint32_t b, uint32_t c, uint32_t d) {
    asm volatile("stmatrix.sync.aligned.m8n8.x4.shared.b16 [%0], {%1,%2,%3,%4};" ::"r"(addr), "r"(a), "r"(b), "r"(c), "r"(d) : "memory");
}
__device__ __forceinline__ void sts1(uint32_t addr, uint32_t a) { asm volatile("st.shared.b32 [%0], %1;" ::"r"(addr), "r"(a) : "memory"); }
__device__ __forceinline__ uint32_t lds1(uint32_t addr) {
    uint32_t a;
    asm volatile("ld.shared.b32 %0, [%1];" : "=r"(a) : "r"(addr) : "memory");
    return a;
}
__device__ __forceinline__ void lds4(uint32_t addr, uint32_t* v) {
    asm volatile("ld.shared.v4.b32 {%0,%1,%2,%3}, [%4];" : "=r"(v[0]), "=r"(v[1]), "=r"(v[2]), "=r"(v[3]) : "r"(addr) : "memory");
}
__device__ __forceinline__ void stg1(uint8_t* p, uint32_t a) { asm volatile("st.global.b32 [%0], %1;" ::"l"(p), "r"(a) : "memory"); }
__device__ __forceinline__ void st_part(uint8_t* p, const uint32_t* v, uint32_t parity) {
    asm volatile("{\n.reg .b64 x, y;\nmov.b64 x, {%1, %2};\nmov.b64 y, {%3, %4};\nst.relaxed.gpu.global.v2.b64 [%0], {x, y};\n}\n"
                 ::"l"(p), "r"((v[0] & ~1u) | parity), "r"(v[1]), "r"((v[2] & ~1u) | parity), "r"(v[3]) : "memory");
}
__device__ __forceinline__ void mma16816(float (&d)[4], const uint32_t (&a)[4], uint32_t b0, uint32_t b1) {
    asm volatile("mma.sync.aligned.m16n8k16.row.col.f32.bf16.bf16.f32 {%0,%1,%2,%3}, {%4,%5,%6,%7}, {%8,%9}, {%0,%1,%2,%3};"
                 : "+f"(d[0]), "+f"(d[1]), "+f"(d[2]), "+f"(d[3]) : "r"(a[0]), "r"(a[1]), "r"(a[2]), "r"(a[3]), "r"(b0), "r"(b1));
}
__device__ __forceinline__ uint32_t add2(uint32_t a, uint32_t b) {
    uint32_t r;
    asm("add.rn.bf16x2 %0, %1, %2;" : "=r"(r) : "r"(a), "r"(b));
    return r;
}
__device__ __forceinline__ uint32_t scale2(uint32_t x) {
    uint32_t r;
    asm("{\n.reg .b32 t;\nmul.rn.bf16x2 t, %1, %3;\nfma.rn.bf16x2 %0, %1, %2, t;\n}\n" : "=r"(r) : "r"(x), "r"(0x3E423E42u), "r"(0xB9F7B9F7u));
    return r;
}
__device__ __forceinline__ uint32_t max2(uint32_t a, uint32_t b) {
    uint32_t r;
    asm("max.bf16x2 %0, %1, %2;" : "=r"(r) : "r"(a), "r"(b));
    return r;
}
__device__ __forceinline__ void ld_tagged(const uint8_t* p, uint32_t& a, uint32_t& ta, uint32_t& b, uint32_t& tb) {
    asm volatile("{\n.reg .b64 x, y;\nld.relaxed.gpu.global.v2.b64 {x, y}, [%4];\nmov.b64 {%0, %1}, x;\nmov.b64 {%2, %3}, y;\n}\n"
                 : "=r"(a), "=r"(ta), "=r"(b), "=r"(tb) : "l"(p) : "memory");
}
__device__ __forceinline__ float bf_lo(uint32_t v) { return __uint_as_float(v << 16); }
__device__ __forceinline__ float bf_hi(uint32_t v) { return __uint_as_float(v & 0xFFFF0000u); }
__device__ __forceinline__ float rcp(float x) { float r; asm("rcp.approx.ftz.f32 %0, %1;" : "=f"(r) : "f"(x)); return r; }
__device__ __forceinline__ float ex2(float x) { float r; asm volatile("ex2.approx.ftz.f32 %0, %1;" : "=f"(r) : "f"(x)); return r; }

__device__ __forceinline__ uint32_t full_bar(int stage) { return base + BAR_FULL + (stage & 7) * 8; }
__device__ __forceinline__ void wait_released(int j) { mbar_wait(base + BAR_EMPTY + (j & 7) * 8, (j >> 3) & 1); }

template <int V>
struct Int { static constexpr int value = V; };

__host__ __device__ constexpr int bslot_e(int i) { return (i < 2 || i >= 14) ? (i + 5) % 7 : (i + 1) % 5; }
__host__ __device__ constexpr int bslot_l(int i) { return i % 6; }

template <uint32_t OFF>
struct Feed {
    int stage;
    uint32_t dst;
    __device__ __forceinline__ void seek(int i, int slot) { stage = i; dst = base + OFF + slot * SLOT; }
    template <int N>
    __device__ __forceinline__ uint32_t acquire() { wait_released(stage - N); return full_bar(stage); }
    template <int N>
    __device__ __forceinline__ void next() {
        stage++;
        dst += SLOT;
        if (dst == base + OFF + N * SLOT) dst = base + OFF;
    }
};
__device__ __forceinline__ int skip_own(int n, int mt) { return n == mt ? 15 : n; }

struct Desc { uint32_t lo, hi; };
__host__ __device__ constexpr Desc desc_const(uint32_t lbo, uint32_t sbo, uint32_t mode) { return {(lbo >> 4) << 16, (sbo >> 4) | (mode << 30)}; }
constexpr Desc D_K128 = desc_const(16, 1024, 1);
constexpr Desc D_N128 = desc_const(8192, 1024, 1);
constexpr Desc D_BLOB = desc_const(128, 256, 0);
constexpr Desc D_OT = desc_const(2048, 128, 0);

enum Kind { XW, XWN, QK, BIG, OUT };

struct Ring {
    int stage;
    uint32_t a, b;
    uint32_t wg;
    uint32_t zero;
    bool releaser;
    __device__ __forceinline__ void seek(int i, int bslot) {
        stage = i;
        a = (base + (i % NA) * SLOT) >> 4;
        b = (base + BRING + bslot * SLOT) >> 4;
    }
    __device__ __forceinline__ void wait() { mbar_wait(full_bar(stage), (stage >> 3) & 1); }
    __device__ __forceinline__ void take_turn() { nb_sync(1 + wg, 256); }
    __device__ __forceinline__ void pin() {
        uint32_t n = 0;
#pragma unroll 1
        do {
            asm volatile("pmevent 7;" ::: "memory");
        } while (n++ < zero);
    }
    __device__ __forceinline__ void mma_begin() {
        if (!wg) take_turn();
        pin();
    }
    __device__ __forceinline__ void mma_end() {
        pin();
        if (wg) nb_arrive(3, 256);
        nb_sync(3 - wg, 256);
    }
    template <Kind K, int NBS, bool INIT, int SB = 1, bool TAIL = false>
    __device__ __forceinline__ void run(float (&d)[56], float (&e)[56], bool first = true, bool last = true, bool more = true) {
        if (first) take_turn();
        asm volatile("wgmma.fence.sync.aligned;" ::: "memory");
        if (K == QK) {
            const uint32_t da = D_K128.lo + (base >> 4) + (stage >> 1) * (SLOT >> 4) + (stage & 1) * 4 + wg * 512, db = D_N128.lo + b;
            wgmma112<0, 1, 1, INIT, D_K128.hi, D_N128.hi>(d, da, db);
            wgmma112<0, 1, 1, INIT, D_K128.hi, D_N128.hi>(e, da, db + 256);
            wgmma112<0, 1, 1, false, D_K128.hi, D_N128.hi>(d, da + 2, db + 128);
            wgmma112<0, 1, 1, false, D_K128.hi, D_N128.hi>(e, da + 2, db + 384);
        } else {
            constexpr int TA = K == OUT, TB = K != XW;
            constexpr uint32_t sa = K == OUT ? 256 : 2, sb = K == XW ? 2 : K == BIG ? 224 : 128;
            constexpr Desc A = K == OUT ? D_OT : D_K128, B = K == XW ? D_K128 : K == BIG ? D_BLOB : D_N128;
            const uint32_t da = A.lo + a + wg * (K == OUT ? 64 : 512), db = B.lo + b;
            wgmma112<TA, TB, SB, INIT, A.hi, B.hi>(d, da, db);
#pragma unroll
            for (int q = 1; q < 4; q++) wgmma112<TA, TB, SB, false, A.hi, B.hi>(d, da + q * sa, db + q * sb);
        }
        asm volatile("wgmma.commit_group.sync.aligned;" ::: "memory");
        if (!TAIL) asm volatile("wgmma.wait_group.sync.aligned 1;" ::: "memory");
        if (last) nb_arrive(2 - wg, 256);
        if (!TAIL && stage > 0 && releaser) mbar_arrive(base + BAR_EMPTY + ((stage - 1) & 7) * 8);
        stage++;
        a += SLOT >> 4;
        if (a == (base + NA * SLOT) >> 4) a = base >> 4;
        b += SLOT >> 4;
        if (b == (base + BRING + NBS * SLOT) >> 4) b = (base + BRING) >> 4;
        if (more) wait();
    }
    template <Kind K, int NBS, bool INIT, int SB = 1, bool TAIL = false>
    __device__ __forceinline__ void run(float (&d)[56], bool first = true, bool last = true, bool more = true) {
        run<K, NBS, INIT, SB, TAIL>(d, d, first, last, more);
    }
};

template <int I0 = 0, int I1 = 28>
__device__ __forceinline__ void pack_all(const float (&d)[56], uint32_t (&p)[28]) {
#pragma unroll
    for (int i = I0; i < I1; i++) p[i] = pack2(d[2 * i], d[2 * i + 1]);
}
template <int I0, int I1>
__device__ __forceinline__ void store_frags(uint8_t* dst, const uint32_t (&p)[28]) {
#pragma unroll
    for (int i = I0; i < I1; i++) stg1(dst + i * 128, p[i]);
}
template <int I0, int I1>
__device__ __forceinline__ void stage_frags(uint32_t lane_addr, const uint32_t (&p)[28]) {
#pragma unroll
    for (int i = I0; i < I1; i += 4) stsm4(lane_addr + i * 128, p[i], p[i + 1], p[i + 2], p[i + 3]);
}
template <class F>
__device__ __forceinline__ void store_out(F frag, int lane, uint32_t slab, const CUtensorMap* m, int c0, int c1) {
    const bool swap = lane & 16;
    const uint32_t addr = slab + (lane & 7) * 224 + ((lane >> 3) ^ ((lane >> 2) & 1)) * 16;
#pragma unroll
    for (int h = 0; h < 2; h++) {
#pragma unroll
        for (int c = 0; c < 14; c += 4) {
            const uint32_t t0 = frag(2 * c + h), t1 = frag(2 * c + 2 + h);
            if (c < 12) {
                const uint32_t t2 = frag(2 * c + 4 + h), t3 = frag(2 * c + 6 + h);
                stsm4(addr + h * 1792 + c * 16, swap ? t1 : t0, swap ? t0 : t1, swap ? t3 : t2, swap ? t2 : t3);
            } else {
                asm volatile("stmatrix.sync.aligned.m8n8.x2.shared.b16 [%0], {%1,%2};" ::"r"(addr + h * 1792 + c * 16), "r"(swap ? t1 : t0), "r"(swap ? t0 : t1) : "memory");
            }
        }
        fence_async_smem();
        __syncwarp();
        if (elect()) tma_st2(m, c0, c1 + 8 * h, slab + h * 1792);
    }
    if (elect()) {
        bulk_commit();
        bulk_wait_read();
    }
}
__host__ __device__ constexpr int tile_of(int t) { return 7 * (t >> 2) + 3 * ((t >> 1) & 1) + 2 * (t & 1); }

struct Role {
    bool H;
    int L, mt, ns, id;
    int kind, a0, a1, b3;
};
template <bool BY_SM>
__device__ __forceinline__ Role decode_role() {
    uint32_t sm;
    if (BY_SM) asm volatile("mov.u32 %0, %%smid;" : "=r"(sm));
    else asm volatile("mov.u32 %0, %%ctaid.x;" : "=r"(sm));
    const int tpc = sm >> 1, q2 = ((tpc - 32) * 37) >> 8;
    const int gpc = tpc < 32 ? tpc & 7 : tpc < 60 ? tpc - 31 - 7 * q2 : 0;
    const int pos = tpc < 32 ? tpc >> 3 : tpc < 60 ? q2 + 4 : tpc - 56;
    Role r;
    r.H = sm >= 128;
    const int grp = (GPC_MAP >> (4 * gpc)) & 7;
    r.L = grp & 1;
    r.mt = (grp >> 1) * 4 + (pos >> 1);
    r.ns = (pos & 1) * 2 + (sm & 1);
    r.id = r.H ? sm : grp * 16 + pos * 2 + (sm & 1);
    r.kind = r.H ? 2 : r.L;
    r.a0 = r.L ? (r.mt >> 3) * 448 : 0;
    r.a1 = r.L ? (r.mt & 7) * 128 : r.H ? 120 : r.mt * 64;
    r.b3 = r.H ? 4 + r.ns : r.L ? r.ns : 0;
    return r;
}

__device__ __forceinline__ void first_fill(const Maps& maps, const Role& r, int i) {
    const bool E = r.kind == 0;
    const CUtensorMap* ma = &maps.m[r.kind];
    const uint32_t bar = full_bar(i);
    const int k = (i * 64) >> r.L;
    const bool has_a = !(i & r.L), has_b = i < 7 - r.L;
    const uint32_t dst = base + BRING + (E ? (0x2104365u >> (4 * i)) & 7 : i) * SLOT;
    mbar_expect(bar, (has_a ? SLOT : 0) + (has_b ? (E ? BLOB : SLOT) : 0));
    if (has_a) tma_ld4(base + (i >> r.L) * SLOT, ma, r.a0 + k, r.a1, 0, 0, bar);
    if (has_b) {
        tma_ld4(dst, ma + 3, E ? k : 0, E ? r.ns * 112 : k, 0, r.b3, bar);
        if (!E) tma_ld4(dst + 8192, ma + 3, 64, k, 0, r.b3, bar);
        mbar_arrive(bar);
    }
}
static_assert(bslot_e(0) == 5 && bslot_e(1) == 6 && bslot_e(2) == 3 && bslot_e(3) == 4 && bslot_e(4) == 0 && bslot_e(6) == 2, "");

template <bool BY_SM>
__global__ void __launch_bounds__(384, 1) fused_kernel(Scratch* sc, const __grid_constant__ Maps maps) {
    const unsigned t_open = clk32();
    const int warp = __shfl_sync(0xffffffffu, threadIdx.x >> 5, 0);
    if (warp == 8) {
        if (elect()) {
#pragma unroll
            for (int i = 0; i < LEAD; i++) mbar_init(base + BAR_FULL + i * 8, 2);
            asm volatile("fence.mbarrier_init.release.cluster;" ::: "memory");
            const Role r = decode_role<BY_SM>();
#pragma unroll 1
            for (int i = 0; i < LEAD; i++) first_fill(maps, r, i);
        }
    }
    if (warp == 9) {
        if (elect()) {
#pragma unroll
            for (int i = 0; i < 8; i++) mbar_init(base + BAR_EMPTY + i * 8, 4);
            asm volatile("fence.mbarrier_init.release.cluster;" ::: "memory");
        }
    } else if (warp == 10) {
        if (elect()) {
#pragma unroll
            for (int i = 0; i < 3; i++) mbar_init(base + BAR_RDY + i * 8, i < 2 ? 4 : 8);
#pragma unroll
            for (int i = 0; i < 2; i++) mbar_init(base + BAR_HALO + i * 8, 1);
            asm volatile("fence.mbarrier_init.release.cluster;" ::: "memory");
        }
    } else if (warp == 11) {
        if (elect()) {
#pragma unroll
            for (int i = LEAD; i < 8; i++) mbar_init(base + BAR_FULL + i * 8, 2);
#pragma unroll
            for (int i = 0; i < 3; i++) mbar_init(base + BAR_DEP + i * 8, 1);
#pragma unroll
            for (int i = 0; i < 4; i++) mbar_init(base + BAR_PART + i * 8, 1);
            asm volatile("fence.mbarrier_init.release.cluster;" ::: "memory");
        }
    }
    __syncthreads();

    const Role role = decode_role<BY_SM>();
    int lane = threadIdx.x & 31;
    asm volatile("" : "+r"(lane));
    const bool roleH = role.H;
    const int roleL = role.L, mt = role.mt, ns = role.ns, bid = role.id;
    const int par = mt >> 3, blk = mt & 7, col = ns * 112;

    if (warp >= 8) {
        asm volatile("setmaxnreg.dec.sync.aligned.u32 56;");
#define PROF_FEED_A
#define PROF_FEED_B
        if (warp == 8) {
            if (elect()) {
                PROF(129);
#pragma unroll 1
                for (int i = LEAD; i < 7; i++) {
                    while (clk32() - t_open < i * PACE) {}
                    first_fill(maps, role, i);
                }
                PROF(134);
                Feed<0> f;
                const int row = mt * 128;
                auto c_run = [&](const CUtensorMap* m, int off, int n0, int n1) {
#pragma unroll 1
                    for (int n = n0; n < n1; n++) {
                        const uint32_t bar = f.acquire<NA>();
                        mbar_expect(bar, SLOT);
                        tma_ld2(f.dst, m, (off + skip_own(n, mt)) * 64, row, bar);
                        PROF_FEED_A;
                        f.next<NA>();
                    }
                };
                if (roleH) {
                    mbar_expect(base + BAR_DEP, 7 * SLOT);
#pragma unroll 1
                    for (int i = 0; i < 7; i++) {
                        const uint32_t dst = base + (i < 6 ? i : 7) * SLOT;
                        if (i < 6) wait_released(7 + i);
                        tma_ld4(dst, &maps.m[M_WO], 0, i * 64, 0, ns, base + BAR_DEP);
                        tma_ld4(dst + 8192, &maps.m[M_WO], 64, i * 64, 0, ns, base + BAR_DEP);
                    }
                    mbar_wait(base + BAR_DEP, 0);
                    mbar_wait(base + BAR_RDY + 16, 0);
#pragma unroll 1
                    for (int i = 0; i < 7; i++) bulk_st(sc->wo + (size_t)(ns * 7 + i) * SLOT, base + (i < 6 ? i : 7) * SLOT, SLOT);
                    bulk_commit();
                    asm volatile("cp.async.bulk.wait_group 0;" ::: "memory");
                    signal(sc, CNT_W + ns);
                } else if (!roleL) {
                    f.seek(14, 0);
#pragma unroll 1
                    for (int i = 0; i < 4; i++) {
                        const uint32_t bar = f.acquire<NA>();
                        mbar_expect(bar, SLOT);
                        tma_ld2(f.dst, &maps.m[M_CR + (i >> 1)], ((i & 1) * 16 + mt) * 64, row, bar);
                        mbar_arrive(bar);
                        PROF_FEED_A;
                        f.next<NA>();
                    }
                    c_run(&maps.m[M_CR], 0, 0, 15);
                    c_run(&maps.m[M_CI], 0, 0, NBE);
                    wait_dep(2);
#pragma unroll 1
                    for (int i = 0; i < 7; i++) {
                        const uint32_t bar = f.acquire<NA>();
                        mbar_expect(bar, SLOT);
                        bulk_ld(f.dst, sc->o + (size_t)(mt * 7 + i) * SLOT, SLOT, bar);
                        PROF_FEED_A;
                        f.next<NA>();
                    }
                } else {
#pragma unroll 1
                    for (int i = 4; i < 7; i++) {
                        wait_released(2 * i - 8);
                        mbar_expect(full_bar(2 * i), SLOT);
                        tma_ld4(base + i * SLOT, &maps.m[M_XA], par * 448 + i * 64, blk * 128, 0, 0, full_bar(2 * i));
                    }
                    wait_released(HALO_K_AT);
                    mbar_arrive(base + BAR_DEP + 16);
                    f.seek(21, 0);
                    c_run(&maps.m[M_CR], 16, 0, 15);
                    c_run(&maps.m[M_CI], 16, 0, 15);
                    c_run(&maps.m[M_CI], 0, NBE, 15);
                }
            }
        } else if (warp == 11) {
            if (elect()) {
                Feed<BRING> f;
                auto blob_run = [&](auto nbs, int quarter, int n0, int n1) {
                    constexpr int N = decltype(nbs)::value;
                    const uint8_t* src = sc->ab + (size_t)(quarter * 64 + ns) * BLOB;
#pragma unroll 1
                    for (int n = n0; n < n1; n++) {
                        const uint32_t bar = f.template acquire<N>();
                        mbar_expect(bar, BLOB);
                        bulk_ld(f.dst, src + skip_own(n, mt) * (4 * BLOB), BLOB, bar);
                        PROF_FEED_B;
                        f.template next<N>();
                    }
                };
                auto v_run = [&](auto nbs) {
                    constexpr int N = decltype(nbs)::value;
#pragma unroll 1
                    for (int i = 0; i < 7; i++) {
                        const uint32_t bar = f.template acquire<N>();
                        mbar_expect(bar, SLOT);
                        tma_ld4(f.dst, &maps.m[M_WV], 0, i * 64, 0, 8 + ns, bar);
                        tma_ld4(f.dst + 8192, &maps.m[M_WV], 64, i * 64, 0, 8 + ns, bar);
                        mbar_arrive(bar);
                        PROF_FEED_B;
                        f.template next<N>();
                    }
                };
                if (roleH) {
                    f.seek(7, 0);
                    v_run(Int<7>());
                } else if (!roleL) {
                    f.seek(7, bslot_e(7));
#pragma unroll 1
                    for (int i = 0; i < 7; i++) {
                        const uint32_t bar = f.acquire<5>();
                        mbar_expect(bar, BLOB);
                        tma_ld2(f.dst, &maps.m[M_WI], i * 64, col, bar);
                        mbar_arrive(bar);
                        PROF_FEED_B;
                        f.next<5>();
                    }
                    f.seek(18, bslot_e(18));
                    wait_dep(0);
                    blob_run(Int<7>(), 0, 0, 15);
                    wait_dep(1);
                    blob_run(Int<7>(), 2, 0, NBE);
                    mbar_wait(base + BAR_HINT, 0);
                    fence_async_global();
#pragma unroll 1
                    for (int i = 0; i < 7; i++) {
                        const uint32_t bar = f.acquire<7>();
                        mbar_expect(bar, SLOT);
                        bulk_ld(f.dst, sc->wo + (size_t)(ns * 7 + i) * SLOT, SLOT, bar);
                        PROF_FEED_B;
                        f.next<7>();
                    }

                } else {
                    f.seek(6, 0);
#pragma unroll 1
                    for (int i = 6; i < 14; i++) {
                        const uint32_t bar = f.acquire<6>();
                        mbar_expect(bar, SLOT);
                        tma_ld4(f.dst, &maps.m[M_WQK], 0, i * 32, 0, ns, bar);
                        tma_ld4(f.dst + 8192, &maps.m[M_WQK], 64, i * 32, 0, ns, bar);
                        if (i & 1) mbar_arrive(bar);
                        PROF_FEED_B;
                        f.next<6>();
                    }
                    v_run(Int<6>());
                    wait_dep(0);
                    blob_run(Int<6>(), 1, 0, 15);
                    wait_dep(1);
                    blob_run(Int<6>(), 3, 0, 15);
                    blob_run(Int<6>(), 2, NBE, 15);
                    fence_async_smem();
#pragma unroll 1
                    for (int h = 0; h < 2; h++) {
                        mbar_wait(base + BAR_HINT + h * 8, 0);
                        PROF(153 + h);
                        mbar_expect(base + BAR_PART + h * 8, BLOB);
                        bulk_ld(base + (h ? HALO : LSLAB), sc->part + (size_t)((ns * 16 + mt) * 2 + h) * BLOB, BLOB, base + BAR_PART + h * 8);
                    }
                }
            }
        } else if (roleH) {
            if (warp == 9 && elect()) {
                wait_released(0);
#pragma unroll 1
                for (int i = 0; i < 7; i++)
                    asm volatile("cp.async.bulk.prefetch.tensor.2d.L2.global [%0, {%1, %2}];" ::"l"(&maps.m[M_WI]), "r"(i * 64), "r"(col) : "memory");
            }
        } else if (warp == 10) {
            if (elect()) {
                unsigned* epoch_ptr = &sc->epoch[(bid * 4 + 2) * 8];
                const unsigned ep = *epoch_ptr + 1;
                sts1(base + TAG, ep);
                asm volatile("prefetch.tensormap [%0];" ::"l"(&maps.m[M_OUTA + roleL]) : "memory");
                await(sc, CNT_A + roleL * 4 + ns, ep * 16);
                mbar_arrive(base + BAR_DEP);
                PROF(150);
                await(sc, CNT_B + ns, ep * 16);
                mbar_arrive(base + BAR_DEP + 8);
                PROF(151);
                if (!roleL) {
                    await(sc, CNT_W + ns, ep);
                    mbar_arrive(base + BAR_HINT);
                    PROF(153);
                    await(sc, CNT_O + mt, ep * 4);
                    mbar_arrive(base + BAR_DEP + 16);
                } else {
                    await(sc, CNT_P + mt * 4 + ns, ep * 2 - 1);
                    mbar_arrive(base + BAR_HINT);
                    await(sc, CNT_P + mt * 4 + ns, ep * 2);
                    mbar_arrive(base + BAR_HINT + 8);
                }
                PROF(152);
                *epoch_ptr = ep;
            }
        } else if (!roleL) {
            if (elect()) {
                mbar_wait(base + BAR_RDY, 0);
                PROF(130);
                signal(sc, CNT_A + ns);
                PROF(131);
                mbar_wait(base + BAR_RDY + 8, 0);
                signal(sc, CNT_A + 4 + ns);
                PROF(135);
                mbar_wait(base + BAR_RDY + 16, 0);
                PROF(132);
                signal(sc, CNT_B + ns);
                PROF(133);
            }
        } else {
            unsigned* epoch_ptr = &sc->epoch[(bid * 4 + 1) * 8];
            const unsigned tag = *epoch_ptr + 1;
#pragma unroll 1
            for (int kv = 0; kv < 2; kv++) {
                uint32_t v[16];
#pragma unroll
                for (int i = 0; i < 16; i++) v[i] = 0;
                if (kv) wait_released(HALO_V_AT - 4), wait_released(HALO_V_AT);
                else mbar_wait(base + BAR_DEP + 16, 0);
                if (blk > 0) {
                    const uint8_t* src = sc->halo + (size_t)(((mt - 1) * 4 + ns) * 2 + kv) * 2048 + lane * 16;
#pragma unroll 1
                    for (int n = 0; n < SPIN_LIMIT; n++) {
#pragma unroll
                        for (int i = 0; i < 4; i++) ld_tagged(src + i * 512, v[4 * i], v[4 * i + 1], v[4 * i + 2], v[4 * i + 3]);
#pragma unroll
                        for (int i = 0; i < 16; i += 2) v[i] ^= tag & 1;
                        const uint32_t stale = or3(or3(v[0], v[2], v[4]), or3(v[6], v[8], v[10]), or3(v[12], v[14], 0));
                        if (__all_sync(0xffffffffu, !(stale & 1))) break;
                    }
#pragma unroll
                    for (int c = 0; c < 14; c += 2) v[c] |= (v[15] >> c) & 1;
                }
#pragma unroll
                for (int i = 0; i < 14; i++) sts1(base + HALO + kv * (8 * HSLOT) + i * 128 + lane * 4, v[i]);
                warp_arrive(base + BAR_HALO + kv * 8);
                if (lane == 0) PROF(142 + kv);
            }
            if (elect()) {
                mbar_wait(base + BAR_RDY + 16, 0);
                PROF(130);
                signal(sc, CNT_O + mt);
                PROF(131);
                *epoch_ptr = tag;
            }
        }
    } else {
        asm volatile("setmaxnreg.inc.sync.aligned.u32 224;");
        Ring r;
        r.wg = warp >> 2;
        r.zero = blockIdx.y;
        r.releaser = lane + 1 == (warp >> 2);
        const int wg = warp >> 2;
        if (wg) nb_arrive(1, 256);
        uint8_t* part = sc->part + (size_t)(ns * 16 + mt) * (2 * BLOB) + warp * WSLOT + lane * 16;
        uint32_t p[28];

        if (roleH) {
            unsigned* epoch_ptr = &sc->epoch[bid * 4 * 8];
            const unsigned tag = *epoch_ptr + 1;
            uint8_t* hout = sc->halo + (size_t)((warp * 8 + ns) * 2) * 2048 + lane * 16;
            auto send = [&](int kv) {
#pragma unroll
                for (int h = 0; h < 2; h++) {
                    uint32_t v[16];
                    v[14] = v[15] = 0;
#pragma unroll
                    for (int c = 0; c < 14; c++) v[c] = p[2 * c + h];
#pragma unroll
                    for (int c = 0; c < 14; c += 2) v[15] |= (v[c] & 1) << c;
#pragma unroll
                    for (int i = 0; i < 4; i++) st_part(hout + (h * 8 + kv) * 2048 + i * 512, v + 4 * i, tag & 1);
                }
            };
            float x0[56], x1[56];
            r.seek(0, 0);
            r.wait();
            r.run<XWN, 7, true>(x0);
#pragma unroll 1
            for (int i = 1; i < 7; i++) r.run<XWN, 7, false>(x0);
            r.run<XWN, 7, true>(x1);
            acc_fence(x0);
            pack_all(x0, p);
            send(0);
#pragma unroll 1
            for (int i = 1; i < 7; i++) r.run<XWN, 7, false>(x1, true, i < 6 || !wg, i < 6);
            asm volatile("wgmma.wait_group.sync.aligned 0;" ::: "memory");
            acc_fence(x1);
            pack_all(x1, p);
#pragma unroll
            for (int i = 0; i < 28; i++) p[i] = movm(p[i]);
            send(1);
            warp_arrive(base + BAR_RDY + 16);
            if (threadIdx.x == 0) *epoch_ptr = tag;
        } else if (!roleL) {
            uint8_t* blob = sc->ab + (size_t)((wg * 16 + mt) * 4 + ns) * BLOB + (warp & 3) * WSLOT + lane * 4;
            const uint32_t own = base + BRING + wg * SLOT + (warp & 3) * WSLOT + lane * 16;
            float x0[56], x1[56];
            r.seek(0, bslot_e(0));
            r.wait();
            r.run<XW, 7, true>(x0);
            r.run<XW, 7, false>(x0);
            r.seek(2, bslot_e(2));
#pragma unroll 1
            for (int i = 2; i < 7; i++) r.run<XW, 5, false>(x0);

            r.seek(7, bslot_e(7));
            r.run<XW, 5, true, -1>(x1);
            acc_fence(x0);
            pack_all<0, 14>(x0, p);
#pragma unroll
            for (int i = 0; i < 2; i++) {
                if (wg == i) store_frags<0, 14>(blob, p);
                else stage_frags<0, 4>(own + 5 * SLOT, p);
                r.run<XW, 5, false, -1>(x1);
                if (i == 0) pack_all<14, 28>(x0, p);
                if (wg == i) {
                    store_frags<14, 28>(blob, p);
                    warp_arrive(base + BAR_RDY + i * 8);
                } else {
                    stage_frags<4, 8>(own + 5 * SLOT, p);
                }
                r.run<XW, 5, false, -1>(x1);
            }
            stage_frags<8, 20>(own + 5 * SLOT, p);
            r.run<XW, 5, false, -1>(x1);
            stage_frags<20, 28>(own + 5 * SLOT, p);
            fence_async_smem();
            r.run<XW, 5, false, -1>(x1);

            r.seek(14, bslot_e(14));
            r.run<BIG, 7, true>(x0);
            acc_fence(x1);
            pack_all(x1, p);
            stage_frags<0, 28>(own, p);
            r.run<BIG, 7, false>(x0);
            fence_async_smem();
            blob += (size_t)128 * BLOB;
#pragma unroll
            for (int i = 0; i < 28; i++) {
                if (i % B_SLICE == 0) r.run<BIG, 7, false>(x0);
                stg1(blob + i * 128, p[i]);
            }
            warp_arrive(base + BAR_RDY + 16);
#pragma unroll 1
            for (int i = 17 + 27 / B_SLICE; i < POUT; i++) r.run<BIG, 7, false>(x0);

            const uint32_t tag = lds1(base + TAG);
            r.seek(POUT, bslot_e(POUT));
            r.run<OUT, 7, true>(x1);
            acc_fence(x0);
            pack_all(x0, p);
#pragma unroll
            for (int k = 0; k < 3; k++) {
                if (k < 2 && wg == k) {
#pragma unroll
                    for (int i = 0; i < P_FIRST; i++) st_part(part + i * 512, p + 4 * i, tag & 1);
                    if ((warp & 3) == 0 && elect())
                        asm volatile("red.relaxed.gpu.global.add.u32 [%0], 1;" ::"l"(&sc->cnt[(CNT_P + mt * 4 + ns) * 32]) : "memory");
                }
                if (k > 0 && wg == k - 1) {
#pragma unroll
                    for (int i = P_FIRST; i < 7; i++) st_part(part + i * 512, p + 4 * i, tag & 1);
                }
                if (k < 2) r.run<OUT, 7, false>(x1);
            }
#pragma unroll
            for (int i = 3; i < 7; i++) r.run<OUT, 7, false, 1, true>(x1, i <= 7 - TURN, i < 7 - TURN || (i == 6 && !wg), i < 6);

            asm volatile("wgmma.wait_group.sync.aligned 0;" ::: "memory");
            acc_fence(x1);
            const uint32_t slab = base + (wg ? BRING + bslot_e(ELAST - 6) * SLOT : ((ELAST - 6) % NA) * SLOT) + (warp & 3) * WSLOT;
            store_out([&](int i) { return pack2(x1[2 * i], x1[2 * i + 1]); }, lane, slab, &maps.m[M_OUTA], par * 896 + col, blk * 128 + warp * 16);
        } else {
            const int g = lane >> 2, tig = lane & 3;
            const uint32_t hin = base + HALO + warp * HSLOT + lane * 4;
            const uint32_t hpub = warp < 7 ? hin + HSLOT : base + HSPARE + lane * 4;
            auto publish = [&](const uint32_t (&h)[14], int c0, int c1) {
#pragma unroll
                for (int c = 0; c < 14; c++)
                    if (c >= c0 && c < c1) sts1(hpub + c * 128, h[c]);
            };
            float y0[56], y1[56], y2[56];
            r.seek(0, 0);
            r.wait();
            r.run<QK, 6, true>(y0, y1);
#pragma unroll 1
            for (int i = 1; i < 14; i++) r.run<QK, 6, false>(y0, y1);

            uint32_t m1[8][4], m0[8][4], lo[14], hi[14], q[2][8][2];
            auto pack_q = [&](int b) {
                uint32_t v[14];
#pragma unroll
                for (int c = 0; c < 14; c++) v[c] = pack2(y0[4 * c + 2 * b], y0[4 * c + 2 * b + 1]);
#pragma unroll
                for (int t = 0; t < 8; t++) {
                    const int c = tile_of(t);
                    q[b][t][0] = (t & 3) == 2 ? (tig >= 2 ? v[c] : 0u) : v[c];
                    q[b][t][1] = (t & 3) == 1 ? (tig < 2 ? v[c + 1] : 0u) : v[c + 1];
                }
            };
            auto fetch = [&](uint32_t src, int hp, int i0) {
#pragma unroll
                for (int t = 4 * hp; t < 4 * hp + 4; t++) {
                    m0[t][i0] = (t & 3) == 2 ? dup(m0[t - 1][3], r.zero) : lds1(src + tile_of(t) * 128);
                    m0[t][3] = lds1(src + tile_of(t) * 128 + 128);
                }
            };
            r.seek(14, bslot_l(14));
            r.run<XWN, 6, true>(y2);
            acc_fence(y0);
            acc_fence(y1);
#pragma unroll
            for (int c = 0; c < 14; c++) hi[c] = pack2(y1[4 * c + 2], y1[4 * c + 3]);
            publish(hi, 0, 7);
            r.run<XWN, 6, false>(y2);
            publish(hi, 7, 14);
#pragma unroll
            for (int c = 0; c < 14; c++) lo[c] = pack2(y1[4 * c], y1[4 * c + 1]);
#pragma unroll
            for (int t = 0; t < 8; t++) {
                const int c = tile_of(t);
                const bool shared = (t & 3) == 2;
                m1[t][0] = shared ? dup(lo[c], r.zero) : lo[c];
                m1[t][1] = shared ? dup(hi[c], r.zero) : hi[c];
                m1[t][2] = lo[c + 1];
                m1[t][3] = hi[c + 1];
                m0[t][0] = dup(m1[t][0], r.zero);
                m0[t][2] = dup(lo[c + 1], 2 * r.zero);
            }
            r.run<XWN, 6, false>(y2);
            if (warp == 0) mbar_wait(base + BAR_HALO, 0);
            fetch(hin, 0, 1);
            pack_q(1);
            r.run<XWN, 6, false>(y2);
            fetch(hin, 1, 1);
            pack_q(0);
            r.mma_begin();
            float s[8][4];
#pragma unroll
            for (int step = 0; step < 2; step++) {
#pragma unroll
                for (int i = 0; i < 8; i++) {
                    const int b = 1 - (i >> 2), h = i & 3, t = 2 * h + step;
                    float (&d)[4] = s[2 * h + b];
                    if (step == 0) d[0] = d[1] = d[2] = d[3] = 0.f;
                    mma16816(d, b ? m1[t] : m0[t], q[b][t][0], q[b][t][1]);
                }
            }
            r.mma_end();
            r.run<XWN, 6, false>(y2, false);

            uint32_t pr[8], mx[4], mx1[4];
            {
                const bool cur0 = g <= 2 * tig, cur1 = g <= 2 * tig + 1;
#pragma unroll
                for (int i = 0; i < 8; i++) {
                    const int c = (i & 1) ? 2 : 0;
                    pr[i] = movm(pack2(cur0 ? s[i][c] : s[i][2 - c], cur1 ? s[i][c + 1] : s[i][3 - c]));
                }
            }
            r.run<XWN, 6, false>(y2);
            const uint32_t curmask = (2 * tig <= g ? 0x0000FFFFu : 0u) | (2 * tig + 1 <= g ? 0xFFFF0000u : 0u);
            {
                const uint32_t keep = (blk == 0 && warp == 0) ? curmask : 0xFFFFFFFFu;
#pragma unroll
                for (int i = 0; i < 4; i++) {
                    pr[2 * i] = (scale2(pr[2 * i]) & keep) | (0xCE6ECE6Eu & ~keep);
                    pr[2 * i + 1] = scale2(pr[2 * i + 1]);
                    mx[i] = max2(__byte_perm(pr[2 * i], pr[2 * i + 1], 0x5410), __byte_perm(pr[2 * i], pr[2 * i + 1], 0x7632));
                    mx1[i] = __shfl_xor_sync(0xffffffffu, mx[i], 1);
                }
            }
#pragma unroll
            for (int i = 0; i < 4; i++) {
                mx[i] = max2(mx[i], mx1[i]);
                mx1[i] = __shfl_xor_sync(0xffffffffu, mx[i], 2);
            }
            r.run<XWN, 6, false>(y2);
            constexpr float SCL = 1.4426950408889634f;
            float e0[8], e1[8], sm[8], sm1[8];
#pragma unroll
            for (int i = 0; i < 8; i++) {
                const uint32_t m2 = max2(mx[i >> 1], mx1[i >> 1]);
                sm[i] = ((i & 1) ? bf_hi(m2) : bf_lo(m2)) * -SCL;
                e0[i] = ex2(fmaf(bf_lo(pr[i]), SCL, sm[i]));
            }

            r.seek(21, bslot_l(21));
            r.run<BIG, 6, true>(y0);
            acc_fence(y2);
#pragma unroll
            for (int c = 0; c < 7; c++) hi[c] = movm(pack2(y2[4 * c + 2], y2[4 * c + 3]));
#pragma unroll
            for (int i = 0; i < 8; i++) e1[i] = ex2(fmaf(bf_hi(pr[i]), SCL, sm[i]));
            r.run<BIG, 6, false>(y0);
            publish(hi, 0, 7);
#pragma unroll
            for (int c = 7; c < 14; c++) hi[c] = movm(pack2(y2[4 * c + 2], y2[4 * c + 3]));
            r.run<BIG, 6, false>(y0);
            publish(hi, 7, 14);
#pragma unroll
            for (int i = 0; i < 8; i++) {
                sm[i] = e0[i] + e1[i];
                sm1[i] = __shfl_xor_sync(0xffffffffu, sm[i], 1);
            }
            r.run<BIG, 6, false>(y0);
#pragma unroll
            for (int c = 0; c < 14; c++) lo[c] = movm(pack2(y2[4 * c], y2[4 * c + 1]));
            r.run<BIG, 6, false>(y0);
#pragma unroll
            for (int i = 0; i < 8; i++) {
                sm[i] += sm1[i];
                sm1[i] = __shfl_xor_sync(0xffffffffu, sm[i], 2);
            }
#pragma unroll
            for (int t = 0; t < 8; t++) {
                const int c = tile_of(t);
                const bool shared = (t & 3) == 2;
                m1[t][0] = shared ? dup(lo[c], r.zero) : lo[c];
                m1[t][1] = lo[c + 1];
                m1[t][2] = shared ? dup(hi[c], r.zero) : hi[c];
                m1[t][3] = hi[c + 1];
                m0[t][0] = dup(m1[t][0], r.zero);
                m0[t][1] = dup(lo[c + 1], 2 * r.zero);
            }
            r.run<BIG, 6, false>(y0);
            if (warp == 0) mbar_wait(base + BAR_HALO + 8, 0);
            const uint32_t vin = warp ? hin : hin + 8 * HSLOT;
            fetch(vin, 0, 2);
#pragma unroll
            for (int i = 0; i < 8; i++) {
                const float inv = rcp(sm[i] + sm1[i]);
                pr[i] = pack2(e0[i] * inv, e1[i] * inv);
            }
            r.run<BIG, 6, false>(y0);
            fetch(vin, 1, 2);
            uint32_t pb[8][2];
#pragma unroll
            for (int t = 0; t < 8; t++) {
                pb[t][t & 1] = band(pr[t], curmask);
                pb[t][1 - (t & 1)] = band(pr[t], ~curmask);
            }
            r.mma_begin();
            float o[2][8][4];
#pragma unroll
            for (int i = 0; i < 16; i++) {
                const int b = 1 - (i >> 3), t = i & 7;
                float (&d)[4] = o[b][t];
                d[0] = d[1] = d[2] = d[3] = 0.f;
                mma16816(d, b ? m1[t] : m0[t], pb[(t & 6) + b][0], pb[(t & 6) + b][1]);
            }
            r.mma_end();
            r.run<BIG, 6, false>(y0, false);
            uint8_t* odst = sc->o + (size_t)mt * 7 * SLOT + ns * (14 * 2048) + warp * 256 + lane * 4;
#pragma unroll
            for (int hp = 0; hp < 2; hp++) {
#pragma unroll
                for (int b = 0; b < 2; b++) {
                    const float (&u)[8][4] = o[b];
                    const int t = 4 * hp;
                    uint32_t* w = p + 14 * hp + b;
                    w[0] = pack2(u[t][0], u[t][1]);
                    w[2] = pack2(u[t][2], u[t][3]);
                    w[4] = pack2(u[t + 1][0], u[t + 1][1]);
                    w[6] = pack2(g < 4 ? u[t + 1][2] : u[t + 2][0], g < 4 ? u[t + 1][3] : u[t + 2][1]);
                    w[8] = pack2(u[t + 2][2], u[t + 2][3]);
                    w[10] = pack2(u[t + 3][0], u[t + 3][1]);
                    w[12] = pack2(u[t + 3][2], u[t + 3][3]);
                }
            }
#pragma unroll
            for (int i = 0; i < 28; i++) {
                if (i >= O_FIRST && (i - O_FIRST) % O_SLICE == 0) r.run<BIG, 6, false>(y0);
                stg1(odst + (i >> 1) * 2048 + (i & 1) * 128, p[i]);
            }
            warp_arrive(base + BAR_RDY + 16);

#pragma unroll 1
            for (int i = 30 + (27 - O_FIRST) / O_SLICE; i <= LLAST - LTURN; i++) r.run<BIG, 6, false>(y0);
            r.seek(LLAST + 1 - LTURN, bslot_l(LLAST + 1 - LTURN));
#pragma unroll
            for (int i = 0; i < LTURN; i++) r.run<BIG, 6, false, 1, true>(y0, i == 0, i == LTURN - 1 && !wg, i < LTURN - 1);
            const uint32_t parity = lds1(base + TAG) & 1;
            const uint32_t slab = base + (wg ? HALO : LSLAB) + (warp & 3) * WSLOT;
            mbar_wait(base + BAR_PART + wg * 8, 0);
#pragma unroll 1
            for (int n = 0; n < SPIN_LIMIT; n++) {
#pragma unroll
                for (int i = 0; i < 7; i++) lds4(slab + i * 512 + lane * 16, p + 4 * i);
#pragma unroll
                for (int i = 0; i < 28; i += 2) p[i] ^= parity;
                const uint32_t stale = or3(or3(or3(p[0], p[2], p[4]), or3(p[6], p[8], p[10]), or3(p[12], p[14], p[16])),
                                           or3(p[18], p[20], p[22]), or3(p[24], p[26], 0));
                if (__all_sync(0xffffffffu, !(stale & 1))) break;
#pragma unroll
                for (int i = 0; i < 7; i++) ld_tagged(part + i * 512, p[4 * i], p[4 * i + 1], p[4 * i + 2], p[4 * i + 3]);
#pragma unroll
                for (int i = 0; i < 7; i++)
                    asm volatile("st.shared.v4.b32 [%0], {%1,%2,%3,%4};" ::"r"(slab + i * 512 + lane * 16), "r"(p[4 * i]), "r"(p[4 * i + 1]), "r"(p[4 * i + 2]), "r"(p[4 * i + 3]) : "memory");
            }
            asm volatile("wgmma.wait_group.sync.aligned 0;" ::: "memory");
            acc_fence(y0);
            store_out([&](int i) { return add2(pack2(y0[2 * i], y0[2 * i + 1]), p[i]); }, lane, slab, &maps.m[M_OUTB], 448 + col, mt * 128 + warp * 16);
        }
    }
}

typedef CUresult (*EncodeFn)(CUtensorMap*, CUtensorMapDataType, cuuint32_t, void*, const cuuint64_t*, const cuuint64_t*,
                             const cuuint32_t*, const cuuint32_t*, CUtensorMapInterleave, CUtensorMapSwizzle,
                             CUtensorMapL2promotion, CUtensorMapFloatOOBfill);

struct Dim { uint64_t size, stride; uint32_t box; };
void encode(EncodeFn fn, CUtensorMap* m, const void* ptr, CUtensorMapSwizzle sw, Dim d0, Dim d1, Dim d2 = {0, 0, 0}, Dim d3 = {0, 0, 0}) {
    const cuuint64_t dims[4] = {d0.size, d1.size, d2.size, d3.size};
    const cuuint64_t strides[3] = {d1.stride, d2.stride, d3.stride};
    const cuuint32_t box[4] = {d0.box, d1.box, d2.box, d3.box};
    const cuuint32_t es[4] = {1, 1, 1, 1};
    fn(m, CU_TENSOR_MAP_DATA_TYPE_BFLOAT16, d3.size ? 4 : d2.size ? 3 : 2, const_cast<void*>(ptr), dims, strides, box, es,
       CU_TENSOR_MAP_INTERLEAVE_NONE, sw, CU_TENSOR_MAP_L2_PROMOTION_L2_128B, CU_TENSOR_MAP_FLOAT_OOB_FILL_NONE);
}

}

extern "C" void kernel_launch(void* const* d_in, const int* in_sizes, int n_in, void* d_out, int out_size) {
    (void)in_sizes; (void)n_in; (void)out_size;
    void* fnp = nullptr;
    cudaDriverEntryPointQueryResult st;
    cudaGetDriverEntryPoint("cuTensorMapEncodeTiled", &fnp, cudaEnableDefault, &st);
    EncodeFn fn = (EncodeFn)fnp;
    void* scratch = nullptr;
    cudaGetSymbolAddress(&scratch, g_scratch);
    int dev = 0, sms = 0;
    cudaGetDevice(&dev);
    cudaDeviceGetAttribute(&sms, cudaDevAttrMultiProcessorCount, dev);
    auto kernel = sms == 132 ? fused_kernel<true> : fused_kernel<false>;
    cudaFuncSetAttribute(kernel, cudaFuncAttributeMaxDynamicSharedMemorySize, SMEM_BYTES);

    const CUtensorMapSwizzle S128 = CU_TENSOR_MAP_SWIZZLE_128B, S0 = CU_TENSOR_MAP_SWIZZLE_NONE;
    const Dim one = {1, 16, 1};
    Maps maps;
    encode(fn, &maps.m[M_XA], d_in[0], S128, {896, 2, 64}, {1024, 1792, 128}, one, one);
    encode(fn, &maps.m[M_WQK], d_in[1], S128, {112, 2, 64}, {448, 2688, 32}, {3, 896, 2}, {4, 224, 1});
    encode(fn, &maps.m[M_WV], d_in[1], S128, {112, 2, 64}, {448, 2688, 64}, one, {12, 224, 1});
    encode(fn, &maps.m[M_XH], d_in[0], S128, {448, 2, 64}, {128, 1792, 8}, {8, 128 * 1792, 8}, {2, 896, 2});
    encode(fn, &maps.m[M_WO], d_in[2], S128, {112, 2, 64}, {448, 896, 64}, one, {4, 224, 1});
    encode(fn, &maps.m[M_XB], d_in[3], S128, {448, 2, 64}, {1024, 896, 64}, {2, 896 * 1024, 2}, one);
    encode(fn, &maps.m[M_CR], d_in[4], S128, {2048, 2, 64}, {2048, 4096, 128});
    encode(fn, &maps.m[M_CI], d_in[5], S128, {2048, 2, 64}, {2048, 4096, 128});
    encode(fn, &maps.m[M_WR], d_in[6], S128, {448, 2, 64}, {448, 896, 112}, one, one);
    encode(fn, &maps.m[M_WI], d_in[7], S128, {448, 2, 64}, {448, 896, 112});
    encode(fn, &maps.m[M_OUTA], d_out, S0, {1792, 2, 112}, {1024, 3584, 8});
    encode(fn, &maps.m[M_OUTB], d_out, S0, {896, 2, 112}, {2048, 1792, 8});

    kernel<<<132, 384, SMEM_BYTES>>>((Scratch*)scratch, maps);
}
```

```cpp
#include <cuda.h>
#include <cuda_bf16.h>
#include <cuda_runtime.h>
#include <stdint.h>

namespace {

constexpr uint32_t SLOT = 16384;
constexpr int NA = 7;
constexpr uint32_t BRING = NA * SLOT;
constexpr uint32_t HALO = BRING + 6 * SLOT;
constexpr uint32_t HSLOT = 1792;
constexpr uint32_t WSLOT = 3584;
constexpr uint32_t BLOB = 14336;
constexpr uint32_t BARS = 14 * SLOT;
constexpr uint32_t BAR_FULL = BARS;
constexpr uint32_t BAR_EMPTY = BARS + 64;
constexpr uint32_t BAR_RDY = BARS + 128;
constexpr uint32_t BAR_DEP = BARS + 168;
constexpr uint32_t BAR_HALO = BARS + 192;
constexpr uint32_t BAR_PART = BARS + 208;
constexpr uint32_t BAR_HINT = BARS + 224;
constexpr uint32_t TAG = BARS + 240;
constexpr uint32_t HSPARE = BARS + 256 + 1024;
constexpr uint32_t SMEM_BYTES = HSPARE + HSLOT;
constexpr uint32_t base = 1024;
constexpr int SPIN_LIMIT = 1 << 16;

constexpr int LEAD = 3;
constexpr int PACE = 450;
constexpr int HALO_K_AT = 10;
constexpr int HALO_V_AT = 19;
constexpr int B_SLICE = 4;
constexpr int O_FIRST = 8, O_SLICE = 4;
constexpr int P_FIRST = 5;
constexpr int TURN = 4, LTURN = 5;
constexpr uint32_t GPC_MAP = 0x64752310u;
constexpr int NBE = 13;
constexpr int POUT = 33 + NBE;
constexpr int ELAST = POUT + 6;
constexpr int LLAST = 65 - NBE;
constexpr uint32_t LSLAB = ((LLAST - 6) % NA) * SLOT;
static_assert(TURN <= 4 && LTURN <= 5, "the output is staged in the slots of the seventh-last stage");

enum { M_XB, M_XA, M_XH, M_WR, M_WQK, M_WV, M_WO, M_WI, M_CR, M_CI, M_OUTA, M_OUTB, M_COUNT };
struct __align__(64) Maps { CUtensorMap m[M_COUNT]; };

constexpr int CNT_A = 0;
constexpr int CNT_B = 8;
constexpr int CNT_W = 12;
constexpr int CNT_O = 16;
constexpr int CNT_P = 32;
constexpr int CNT_COUNT = 96;

struct Scratch {
    uint8_t ab[64 * 4 * BLOB];
    uint8_t o[16 * 7 * SLOT];
    uint8_t part[64 * 2 * BLOB];
    uint8_t halo[64 * 2 * 2048];
    uint8_t wo[4 * 7 * SLOT];
    unsigned cnt[CNT_COUNT * 32];
    unsigned epoch[132 * 4 * 8];
};
__device__ __align__(1024) Scratch g_scratch;

__device__ __forceinline__ unsigned clk32() { unsigned c; asm volatile("mov.u32 %0, %%clock;" : "=r"(c)); return c; }

#define PROF(idx)

__device__ __forceinline__ void mbar_init(uint32_t bar, uint32_t cnt) {
    asm volatile("mbarrier.init.shared::cta.b64 [%0], %1;" ::"r"(bar), "r"(cnt) : "memory");
}
__device__ __forceinline__ void mbar_expect(uint32_t bar, uint32_t bytes) {
    asm volatile("mbarrier.arrive.expect_tx.shared::cta.b64 _, [%0], %1;" ::"r"(bar), "r"(bytes) : "memory");
}
__device__ __forceinline__ void mbar_arrive(uint32_t bar) {
    asm volatile("mbarrier.arrive.shared::cta.b64 _, [%0];" ::"r"(bar) : "memory");
}
__device__ __forceinline__ bool mbar_try(uint32_t bar, uint32_t parity) {
    uint32_t ok;
    asm volatile("{\n.reg .pred p;\nmbarrier.try_wait.parity.shared::cta.b64 p, [%1], %2;\nselp.u32 %0, 1, 0, p;\n}\n"
                 : "=r"(ok) : "r"(bar), "r"(parity) : "memory");
    return ok;
}
__device__ __forceinline__ void mbar_wait(uint32_t bar, uint32_t parity) {
#pragma unroll 1
    for (int n = 0; n < SPIN_LIMIT; n++)
        if (mbar_try(bar, parity)) break;
}
__device__ __forceinline__ bool elect() {
    uint32_t p;
    asm volatile("{\n.reg .pred p;\nelect.sync _|p, 0xffffffff;\nselp.u32 %0, 1, 0, p;\n}\n" : "=r"(p));
    return p;
}
__device__ __forceinline__ void nb_sync(int id, int n) { asm volatile("bar.sync %0, %1;" ::"r"(id), "r"(n) : "memory"); }
__device__ __forceinline__ void nb_arrive(int id, int n) { asm volatile("bar.arrive %0, %1;" ::"r"(id), "r"(n) : "memory"); }
__device__ __forceinline__ void warp_arrive(uint32_t bar) {
    __syncwarp();
    if (elect()) mbar_arrive(bar);
}
__device__ __forceinline__ uint32_t or3(uint32_t a, uint32_t b, uint32_t c) {
    uint32_t r;
    asm("lop3.b32 %0, %1, %2, %3, 0xFE;" : "=r"(r) : "r"(a), "r"(b), "r"(c));
    return r;
}
__device__ __forceinline__ uint32_t band(uint32_t x, uint32_t m) {
    uint32_t r;
    asm volatile("and.b32 %0, %1, %2;" : "=r"(r) : "r"(x), "r"(m));
    return r;
}
__device__ __forceinline__ uint32_t dup(uint32_t x, uint32_t zero) {
    uint32_t r;
    asm volatile("xor.b32 %0, %1, %2;" : "=r"(r) : "r"(x), "r"(zero));
    return r;
}

__device__ __forceinline__ void tma_ld2(uint32_t dst, const CUtensorMap* m, int c0, int c1, uint32_t bar) {
    asm volatile("cp.async.bulk.tensor.2d.shared::cluster.global.mbarrier::complete_tx::bytes [%0], [%1, {%3, %4}], [%2];"
                 ::"r"(dst), "l"(m), "r"(bar), "r"(c0), "r"(c1) : "memory");
}
__device__ __forceinline__ void tma_ld4(uint32_t dst, const CUtensorMap* m, int c0, int c1, int c2, int c3, uint32_t bar) {
    asm volatile("cp.async.bulk.tensor.4d.shared::cluster.global.mbarrier::complete_tx::bytes [%0], [%1, {%3, %4, %5, %6}], [%2];"
                 ::"r"(dst), "l"(m), "r"(bar), "r"(c0), "r"(c1), "r"(c2), "r"(c3) : "memory");
}
__device__ __forceinline__ void bulk_ld(uint32_t dst, const void* src, uint32_t bytes, uint32_t bar) {
    asm volatile("cp.async.bulk.shared::cluster.global.mbarrier::complete_tx::bytes [%0], [%1], %2, [%3];"
                 ::"r"(dst), "l"(src), "r"(bytes), "r"(bar) : "memory");
}
__device__ __forceinline__ void bulk_st(void* dst, uint32_t src, uint32_t bytes) {
    asm volatile("cp.async.bulk.global.shared::cta.bulk_group [%0], [%1], %2;" ::"l"(dst), "r"(src), "r"(bytes) : "memory");
}
__device__ __forceinline__ void tma_st2(const CUtensorMap* m, int c0, int c1, uint32_t src) {
    asm volatile("cp.async.bulk.tensor.2d.global.shared::cta.bulk_group [%0, {%1, %2}], [%3];"
                 ::"l"(m), "r"(c0), "r"(c1), "r"(src) : "memory");
}
__device__ __forceinline__ void bulk_commit() { asm volatile("cp.async.bulk.commit_group;" ::: "memory"); }
__device__ __forceinline__ void bulk_wait_read() { asm volatile("cp.async.bulk.wait_group.read 0;" ::: "memory"); }
__device__ __forceinline__ void fence_async_smem() { asm volatile("fence.proxy.async.shared::cta;" ::: "memory"); }
__device__ __forceinline__ void fence_async_global() { asm volatile("fence.proxy.async.global;" ::: "memory"); }

__device__ __forceinline__ void signal(Scratch* sc, int idx) {
    asm volatile("fence.proxy.async;\nred.relaxed.gpu.global.add.u32 [%0], 1;" ::"l"(&sc->cnt[idx * 32]) : "memory");
}
__device__ __forceinline__ unsigned peek(const unsigned* p) {
    unsigned v;
    asm volatile("ld.relaxed.gpu.global.u32 %0, [%1];" : "=r"(v) : "l"(p) : "memory");
    return v;
}
__device__ __forceinline__ void await(Scratch* sc, int idx, unsigned target) {
    const unsigned* p = &sc->cnt[idx * 32];
#pragma unroll 1
    for (int n = 0; n < SPIN_LIMIT; n++)
        if ((int)(peek(p) - target) >= 0) break;
    asm volatile("fence.acquire.gpu;" ::: "memory");
}
__device__ __forceinline__ void wait_dep(int k) {
    mbar_wait(base + BAR_DEP + k * 8, 0);
    fence_async_global();
}

#define WG_REGS                                                                                                     \
    "{%0,%1,%2,%3,%4,%5,%6,%7,%8,%9,%10,%11,%12,%13,%14,%15,%16,%17,%18,%19,%20,%21,%22,%23,%24,%25,%26,%27,"       \
    "%28,%29,%30,%31,%32,%33,%34,%35,%36,%37,%38,%39,%40,%41,%42,%43,%44,%45,%46,%47,%48,%49,%50,%51,%52,%53,%54,%55}"
#define WG_OPS(C)                                                                                                   \
    C(d[0]), C(d[1]), C(d[2]), C(d[3]), C(d[4]), C(d[5]), C(d[6]), C(d[7]), C(d[8]), C(d[9]), C(d[10]), C(d[11]),   \
    C(d[12]), C(d[13]), C(d[14]), C(d[15]), C(d[16]), C(d[17]), C(d[18]), C(d[19]), C(d[20]), C(d[21]), C(d[22]),   \
    C(d[23]), C(d[24]), C(d[25]), C(d[26]), C(d[27]), C(d[28]), C(d[29]), C(d[30]), C(d[31]), C(d[32]), C(d[33]),   \
    C(d[34]), C(d[35]), C(d[36]), C(d[37]), C(d[38]), C(d[39]), C(d[40]), C(d[41]), C(d[42]), C(d[43]), C(d[44]),   \
    C(d[45]), C(d[46]), C(d[47]), C(d[48]), C(d[49]), C(d[50]), C(d[51]), C(d[52]), C(d[53]), C(d[54]), C(d[55])

template <int TA, int TB, int SB, bool INIT, uint32_t AH, uint32_t BH>
__device__ __forceinline__ void wgmma112(float (&d)[56], uint32_t alo, uint32_t blo) {
    if (INIT) {
        asm volatile("{\n.reg .pred p;\n.reg .b64 da, db;\nsetp.ne.b32 p, 0, 0;\nmov.b64 da, {%56, %61};\nmov.b64 db, {%57, %62};\n"
                     "wgmma.mma_async.sync.aligned.m64n112k16.f32.bf16.bf16 " WG_REGS ", da, db, p, 1, %59, %60, %58;\n}\n"
                     : WG_OPS("=f") : "r"(alo), "r"(blo), "n"(TB), "n"(SB), "n"(TA), "n"(AH), "n"(BH));
    } else {
        asm volatile("{\n.reg .pred p;\n.reg .b64 da, db;\nsetp.ne.b32 p, 1, 0;\nmov.b64 da, {%56, %61};\nmov.b64 db, {%57, %62};\n"
                     "wgmma.mma_async.sync.aligned.m64n112k16.f32.bf16.bf16 " WG_REGS ", da, db, p, 1, %59, %60, %58;\n}\n"
                     : WG_OPS("+f") : "r"(alo), "r"(blo), "n"(TB), "n"(SB), "n"(TA), "n"(AH), "n"(BH));
    }
}
__device__ __forceinline__ void acc_fence(float (&d)[56]) {
#pragma unroll
    for (int i = 0; i < 56; i++) asm volatile("" : "+f"(d[i])::"memory");
}

__device__ __forceinline__ uint32_t pack2(float lo, float hi) {
    uint32_t r;
    asm volatile("cvt.rn.bf16x2.f32 %0, %1, %2;" : "=r"(r) : "f"(hi), "f"(lo));
    return r;
}
__device__ __forceinline__ uint32_t movm(uint32_t a) {
    uint32_t r;
    asm volatile("movmatrix.sync.aligned.m8n8.trans.b16 %0, %1;" : "=r"(r) : "r"(a));
    return r;
}
__device__ __forceinline__ void stsm4(uint32_t addr, uint32_t a, uint32_t b, uint32_t c, uint32_t d) {
    asm volatile("stmatrix.sync.aligned.m8n8.x4.shared.b16 [%0], {%1,%2,%3,%4};" ::"r"(addr), "r"(a), "r"(b), "r"(c), "r"(d) : "memory");
}
__device__ __forceinline__ void sts1(uint32_t addr, uint32_t a) { asm volatile("st.shared.b32 [%0], %1;" ::"r"(addr), "r"(a) : "memory"); }
__device__ __forceinline__ uint32_t lds1(uint32_t addr) {
    uint32_t a;
    asm volatile("ld.shared.b32 %0, [%1];" : "=r"(a) : "r"(addr) : "memory");
    return a;
}
__device__ __forceinline__ void lds4(uint32_t addr, uint32_t* v) {
    asm volatile("ld.shared.v4.b32 {%0,%1,%2,%3}, [%4];" : "=r"(v[0]), "=r"(v[1]), "=r"(v[2]), "=r"(v[3]) : "r"(addr) : "memory");
}
__device__ __forceinline__ void stg1(uint8_t* p, uint32_t a) { asm volatile("st.global.b32 [%0], %1;" ::"l"(p), "r"(a) : "memory"); }
__device__ __forceinline__ void st_tagged(uint8_t* p, const uint32_t* v) {
    asm volatile("{\n.reg .b64 x, y;\nmov.b64 x, {%1, %2};\nmov.b64 y, {%3, %4};\nst.relaxed.gpu.global.v2.b64 [%0], {x, y};\n}\n"
                 ::"l"(p), "r"(v[0]), "r"(v[1]), "r"(v[2]), "r"(v[3]) : "memory");
}
__device__ __forceinline__ uint32_t with_parity(uint32_t v, uint32_t tag) {
    uint32_t r;
    asm volatile("lop3.b32 %0, %1, %2, 1, 0xD8;" : "=r"(r) : "r"(v), "r"(tag));
    return r;
}
__device__ __forceinline__ void mma16816(float (&d)[4], const uint32_t (&a)[4], uint32_t b0, uint32_t b1) {
    asm volatile("mma.sync.aligned.m16n8k16.row.col.f32.bf16.bf16.f32 {%0,%1,%2,%3}, {%4,%5,%6,%7}, {%8,%9}, {%0,%1,%2,%3};"
                 : "+f"(d[0]), "+f"(d[1]), "+f"(d[2]), "+f"(d[3]) : "r"(a[0]), "r"(a[1]), "r"(a[2]), "r"(a[3]), "r"(b0), "r"(b1));
}
__device__ __forceinline__ uint32_t add2(uint32_t a, uint32_t b) {
    uint32_t r;
    asm("add.rn.bf16x2 %0, %1, %2;" : "=r"(r) : "r"(a), "r"(b));
    return r;
}
__device__ __forceinline__ uint32_t scale2(uint32_t x) {
    uint32_t r;
    asm("{\n.reg .b32 t;\nmul.rn.bf16x2 t, %1, %3;\nfma.rn.bf16x2 %0, %1, %2, t;\n}\n" : "=r"(r) : "r"(x), "r"(0x3E423E42u), "r"(0xB9F7B9F7u));
    return r;
}
__device__ __forceinline__ uint32_t max2(uint32_t a, uint32_t b) {
    uint32_t r;
    asm("max.bf16x2 %0, %1, %2;" : "=r"(r) : "r"(a), "r"(b));
    return r;
}
__device__ __forceinline__ void ld_tagged(const uint8_t* p, uint32_t& a, uint32_t& ta, uint32_t& b, uint32_t& tb) {
    asm volatile("{\n.reg .b64 x, y;\nld.relaxed.gpu.global.v2.b64 {x, y}, [%4];\nmov.b64 {%0, %1}, x;\nmov.b64 {%2, %3}, y;\n}\n"
                 : "=r"(a), "=r"(ta), "=r"(b), "=r"(tb) : "l"(p) : "memory");
}
__device__ __forceinline__ float bf_lo(uint32_t v) { return __uint_as_float(v << 16); }
__device__ __forceinline__ float bf_hi(uint32_t v) { return __uint_as_float(v & 0xFFFF0000u); }
__device__ __forceinline__ float rcp(float x) { float r; asm("rcp.approx.ftz.f32 %0, %1;" : "=f"(r) : "f"(x)); return r; }
__device__ __forceinline__ float ex2(float x) { float r; asm volatile("ex2.approx.ftz.f32 %0, %1;" : "=f"(r) : "f"(x)); return r; }

__device__ __forceinline__ uint32_t full_bar(int stage) { return base + BAR_FULL + (stage & 7) * 8; }
__device__ __forceinline__ void wait_released(int j) { mbar_wait(base + BAR_EMPTY + (j & 7) * 8, (j >> 3) & 1); }

template <int V>
struct Int { static constexpr int value = V; };

__host__ __device__ constexpr int bslot_e(int i) { return (i < 2 || i >= 14) ? (i + 5) % 7 : (i + 1) % 5; }
__host__ __device__ constexpr int bslot_l(int i) { return i % 6; }

template <uint32_t OFF>
struct Feed {
    int stage;
    uint32_t dst;
    __device__ __forceinline__ void seek(int i, int slot) { stage = i; dst = base + OFF + slot * SLOT; }
    template <int N>
    __device__ __forceinline__ uint32_t acquire() { wait_released(stage - N); return full_bar(stage); }
    template <int N>
    __device__ __forceinline__ void next() {
        stage++;
        dst += SLOT;
        if (dst == base + OFF + N * SLOT) dst = base + OFF;
    }
};
__device__ __forceinline__ int skip_own(int n, int mt) { return n == mt ? 15 : n; }

struct Desc { uint32_t lo, hi; };
__host__ __device__ constexpr Desc desc_const(uint32_t lbo, uint32_t sbo, uint32_t mode) { return {(lbo >> 4) << 16, (sbo >> 4) | (mode << 30)}; }
constexpr Desc D_K128 = desc_const(16, 1024, 1);
constexpr Desc D_N128 = desc_const(8192, 1024, 1);
constexpr Desc D_BLOB = desc_const(128, 256, 0);
constexpr Desc D_OT = desc_const(2048, 128, 0);

enum Kind { XW, XWN, QK, BIG, OUT };

struct Ring {
    int stage;
    uint32_t a, b;
    uint32_t wg;
    uint32_t zero;
    bool releaser;
    __device__ __forceinline__ void seek(int i, int bslot) {
        stage = i;
        a = (base + (i % NA) * SLOT) >> 4;
        b = (base + BRING + bslot * SLOT) >> 4;
    }
    __device__ __forceinline__ void wait() { mbar_wait(full_bar(stage), (stage >> 3) & 1); }
    __device__ __forceinline__ void take_turn() { nb_sync(1 + wg, 256); }
    __device__ __forceinline__ void pin() {
        uint32_t n = 0;
#pragma unroll 1
        do {
            asm volatile("pmevent 7;" ::: "memory");
        } while (n++ < zero);
    }
    __device__ __forceinline__ void mma_begin() {
        if (!wg) take_turn();
        pin();
    }
    __device__ __forceinline__ void mma_end() {
        pin();
        if (wg) nb_arrive(3, 256);
        nb_sync(3 - wg, 256);
    }
    template <Kind K, int NBS, bool INIT, int SB = 1, bool TAIL = false>
    __device__ __forceinline__ void run(float (&d)[56], float (&e)[56], bool first = true, bool last = true, bool more = true) {
        if (first) take_turn();
        asm volatile("wgmma.fence.sync.aligned;" ::: "memory");
        if (K == QK) {
            const uint32_t da = D_K128.lo + (base >> 4) + (stage >> 1) * (SLOT >> 4) + (stage & 1) * 4 + wg * 512, db = D_N128.lo + b;
            wgmma112<0, 1, 1, INIT, D_K128.hi, D_N128.hi>(d, da, db);
            wgmma112<0, 1, 1, INIT, D_K128.hi, D_N128.hi>(e, da, db + 256);
            wgmma112<0, 1, 1, false, D_K128.hi, D_N128.hi>(d, da + 2, db + 128);
            wgmma112<0, 1, 1, false, D_K128.hi, D_N128.hi>(e, da + 2, db + 384);
        } else {
            constexpr int TA = K == OUT, TB = K != XW;
            constexpr uint32_t sa = K == OUT ? 256 : 2, sb = K == XW ? 2 : K == BIG ? 224 : 128;
            constexpr Desc A = K == OUT ? D_OT : D_K128, B = K == XW ? D_K128 : K == BIG ? D_BLOB : D_N128;
            const uint32_t da = A.lo + a + wg * (K == OUT ? 64 : 512), db = B.lo + b;
            wgmma112<TA, TB, SB, INIT, A.hi, B.hi>(d, da, db);
#pragma unroll
            for (int q = 1; q < 4; q++) wgmma112<TA, TB, SB, false, A.hi, B.hi>(d, da + q * sa, db + q * sb);
        }
        asm volatile("wgmma.commit_group.sync.aligned;" ::: "memory");
        if (!TAIL) asm volatile("wgmma.wait_group.sync.aligned 1;" ::: "memory");
        if (last) nb_arrive(2 - wg, 256);
        if (!TAIL && stage > 0 && releaser) mbar_arrive(base + BAR_EMPTY + ((stage - 1) & 7) * 8);
        stage++;
        a += SLOT >> 4;
        if (a == (base + NA * SLOT) >> 4) a = base >> 4;
        b += SLOT >> 4;
        if (b == (base + BRING + NBS * SLOT) >> 4) b = (base + BRING) >> 4;
        if (more) wait();
    }
    template <Kind K, int NBS, bool INIT, int SB = 1, bool TAIL = false>
    __device__ __forceinline__ void run(float (&d)[56], bool first = true, bool last = true, bool more = true) {
        run<K, NBS, INIT, SB, TAIL>(d, d, first, last, more);
    }
};

template <int I0 = 0, int I1 = 28>
__device__ __forceinline__ void pack_all(const float (&d)[56], uint32_t (&p)[28]) {
#pragma unroll
    for (int i = I0; i < I1; i++) p[i] = pack2(d[2 * i], d[2 * i + 1]);
}
template <int I0, int I1>
__device__ __forceinline__ void store_frags(uint8_t* dst, const uint32_t (&p)[28]) {
#pragma unroll
    for (int i = I0; i < I1; i++) stg1(dst + i * 128, p[i]);
}
template <int I0, int I1>
__device__ __forceinline__ void stage_frags(uint32_t lane_addr, const uint32_t (&p)[28]) {
#pragma unroll
    for (int i = I0; i < I1; i += 4) stsm4(lane_addr + i * 128, p[i], p[i + 1], p[i + 2], p[i + 3]);
}
template <class F>
__device__ __forceinline__ void store_out(F frag, int lane, uint32_t slab, const CUtensorMap* m, int c0, int c1) {
    const bool swap = lane & 16;
    const uint32_t addr = slab + (lane & 7) * 224 + ((lane >> 3) ^ ((lane >> 2) & 1)) * 16;
#pragma unroll
    for (int h = 0; h < 2; h++) {
#pragma unroll
        for (int c = 0; c < 14; c += 4) {
            const uint32_t t0 = frag(2 * c + h), t1 = frag(2 * c + 2 + h);
            if (c < 12) {
                const uint32_t t2 = frag(2 * c + 4 + h), t3 = frag(2 * c + 6 + h);
                stsm4(addr + h * 1792 + c * 16, swap ? t1 : t0, swap ? t0 : t1, swap ? t3 : t2, swap ? t2 : t3);
            } else {
                asm volatile("stmatrix.sync.aligned.m8n8.x2.shared.b16 [%0], {%1,%2};" ::"r"(addr + h * 1792 + c * 16), "r"(swap ? t1 : t0), "r"(swap ? t0 : t1) : "memory");
            }
        }
        fence_async_smem();
        __syncwarp();
        if (elect()) tma_st2(m, c0, c1 + 8 * h, slab + h * 1792);
    }
    if (elect()) {
        bulk_commit();
        bulk_wait_read();
    }
}
__host__ __device__ constexpr int tile_of(int t) { return 7 * (t >> 2) + 3 * ((t >> 1) & 1) + 2 * (t & 1); }

struct Role {
    bool H;
    int L, mt, ns, id;
    int kind, a0, a1, b3;
};
template <bool BY_SM>
__device__ __forceinline__ Role decode_role() {
    uint32_t sm;
    if (BY_SM) asm volatile("mov.u32 %0, %%smid;" : "=r"(sm));
    else asm volatile("mov.u32 %0, %%ctaid.x;" : "=r"(sm));
    const int tpc = sm >> 1, q2 = ((tpc - 32) * 37) >> 8;
    const int gpc = tpc < 32 ? tpc & 7 : tpc < 60 ? tpc - 31 - 7 * q2 : 0;
    const int pos = tpc < 32 ? tpc >> 3 : tpc < 60 ? q2 + 4 : tpc - 56;
    Role r;
    r.H = sm >= 128;
    const int grp = (GPC_MAP >> (4 * gpc)) & 7;
    r.L = grp & 1;
    r.mt = (grp >> 1) * 4 + (pos >> 1);
    r.ns = (pos & 1) * 2 + (sm & 1);
    r.id = r.H ? sm : grp * 16 + pos * 2 + (sm & 1);
    r.kind = r.H ? 2 : r.L;
    r.a0 = r.L ? (r.mt >> 3) * 448 : 0;
    r.a1 = r.L ? (r.mt & 7) * 128 : r.H ? 120 : r.mt * 64;
    r.b3 = r.H ? 4 + r.ns : r.L ? r.ns : 0;
    return r;
}

__device__ __forceinline__ void first_fill(const Maps& maps, const Role& r, int i) {
    const bool E = r.kind == 0;
    const CUtensorMap* ma = &maps.m[r.kind];
    const uint32_t bar = full_bar(i);
    const int k = (i * 64) >> r.L;
    const bool has_a = !(i & r.L), has_b = i < 7 - r.L;
    const uint32_t dst = base + BRING + (E ? (0x2104365u >> (4 * i)) & 7 : i) * SLOT;
    mbar_expect(bar, (has_a ? SLOT : 0) + (has_b ? (E ? BLOB : SLOT) : 0));
    if (has_a) tma_ld4(base + (i >> r.L) * SLOT, ma, r.a0 + k, r.a1, 0, 0, bar);
    if (has_b) {
        tma_ld4(dst, ma + 3, E ? k : 0, E ? r.ns * 112 : k, 0, r.b3, bar);
        if (!E) tma_ld4(dst + 8192, ma + 3, 64, k, 0, r.b3, bar);
        mbar_arrive(bar);
    }
}
static_assert(bslot_e(0) == 5 && bslot_e(1) == 6 && bslot_e(2) == 3 && bslot_e(3) == 4 && bslot_e(4) == 0 && bslot_e(6) == 2, "");

template <bool BY_SM>
__global__ void __launch_bounds__(384, 1) fused_kernel(Scratch* sc, const __grid_constant__ Maps maps) {
    const unsigned t_open = clk32();
    const int warp = __shfl_sync(0xffffffffu, threadIdx.x >> 5, 0);
    if (warp == 8) {
        if (elect()) {
#pragma unroll
            for (int i = 0; i < LEAD; i++) mbar_init(base + BAR_FULL + i * 8, 2);
            asm volatile("fence.mbarrier_init.release.cluster;" ::: "memory");
            const Role r = decode_role<BY_SM>();
#pragma unroll 1
            for (int i = 0; i < LEAD; i++) first_fill(maps, r, i);
        }
    }
    if (warp == 9) {
        if (elect()) {
#pragma unroll
            for (int i = 0; i < 8; i++) mbar_init(base + BAR_EMPTY + i * 8, 4);
            asm volatile("fence.mbarrier_init.release.cluster;" ::: "memory");
        }
    } else if (warp == 10) {
        if (elect()) {
#pragma unroll
            for (int i = 0; i < 3; i++) mbar_init(base + BAR_RDY + i * 8, i < 2 ? 4 : 8);
#pragma unroll
            for (int i = 0; i < 2; i++) mbar_init(base + BAR_HALO + i * 8, 1);
            asm volatile("fence.mbarrier_init.release.cluster;" ::: "memory");
        }
    } else if (warp == 11) {
        if (elect()) {
#pragma unroll
            for (int i = LEAD; i < 8; i++) mbar_init(base + BAR_FULL + i * 8, 2);
#pragma unroll
            for (int i = 0; i < 3; i++) mbar_init(base + BAR_DEP + i * 8, 1);
#pragma unroll
            for (int i = 0; i < 4; i++) mbar_init(base + BAR_PART + i * 8, 1);
            asm volatile("fence.mbarrier_init.release.cluster;" ::: "memory");
        }
    }
    __syncthreads();

    const Role role = decode_role<BY_SM>();
    int lane = threadIdx.x & 31;
    asm volatile("" : "+r"(lane));
    const bool roleH = role.H;
    const int roleL = role.L, mt = role.mt, ns = role.ns, bid = role.id;
    const int par = mt >> 3, blk = mt & 7, col = ns * 112;

    if (warp >= 8) {
        asm volatile("setmaxnreg.dec.sync.aligned.u32 56;");
#define PROF_FEED_A
#define PROF_FEED_B
        if (warp == 8) {
            if (elect()) {
                PROF(129);
#pragma unroll 1
                for (int i = LEAD; i < 7; i++) {
                    while (clk32() - t_open < i * PACE) {}
                    first_fill(maps, role, i);
                }
                PROF(134);
                Feed<0> f;
                const int row = mt * 128;
                auto c_run = [&](const CUtensorMap* m, int off, int n0, int n1) {
#pragma unroll 1
                    for (int n = n0; n < n1; n++) {
                        const uint32_t bar = f.acquire<NA>();
                        mbar_expect(bar, SLOT);
                        tma_ld2(f.dst, m, (off + skip_own(n, mt)) * 64, row, bar);
                        PROF_FEED_A;
                        f.next<NA>();
                    }
                };
                if (roleH) {
                    mbar_expect(base + BAR_DEP, 7 * SLOT);
#pragma unroll 1
                    for (int i = 0; i < 7; i++) {
                        const uint32_t dst = base + (i < 6 ? i : 7) * SLOT;
                        if (i < 6) wait_released(7 + i);
                        tma_ld4(dst, &maps.m[M_WO], 0, i * 64, 0, ns, base + BAR_DEP);
                        tma_ld4(dst + 8192, &maps.m[M_WO], 64, i * 64, 0, ns, base + BAR_DEP);
                    }
                    mbar_wait(base + BAR_DEP, 0);
                    mbar_wait(base + BAR_RDY + 16, 0);
#pragma unroll 1
                    for (int i = 0; i < 7; i++) bulk_st(sc->wo + (size_t)(ns * 7 + i) * SLOT, base + (i < 6 ? i : 7) * SLOT, SLOT);
                    bulk_commit();
                    asm volatile("cp.async.bulk.wait_group 0;" ::: "memory");
                    signal(sc, CNT_W + ns);
                } else if (!roleL) {
                    f.seek(14, 0);
#pragma unroll 1
                    for (int i = 0; i < 4; i++) {
                        const uint32_t bar = f.acquire<NA>();
                        mbar_expect(bar, SLOT);
                        tma_ld2(f.dst, &maps.m[M_CR + (i >> 1)], ((i & 1) * 16 + mt) * 64, row, bar);
                        mbar_arrive(bar);
                        PROF_FEED_A;
                        f.next<NA>();
                    }
                    c_run(&maps.m[M_CR], 0, 0, 15);
                    c_run(&maps.m[M_CI], 0, 0, NBE);
                    wait_dep(2);
#pragma unroll 1
                    for (int i = 0; i < 7; i++) {
                        const uint32_t bar = f.acquire<NA>();
                        mbar_expect(bar, SLOT);
                        bulk_ld(f.dst, sc->o + (size_t)(mt * 7 + i) * SLOT, SLOT, bar);
                        PROF_FEED_A;
                        f.next<NA>();
                    }
                } else {
#pragma unroll 1
                    for (int i = 4; i < 7; i++) {
                        wait_released(2 * i - 8);
                        mbar_expect(full_bar(2 * i), SLOT);
                        tma_ld4(base + i * SLOT, &maps.m[M_XA], par * 448 + i * 64, blk * 128, 0, 0, full_bar(2 * i));
                    }
                    wait_released(HALO_K_AT);
                    mbar_arrive(base + BAR_DEP + 16);
                    f.seek(21, 0);
                    c_run(&maps.m[M_CR], 16, 0, 15);
                    c_run(&maps.m[M_CI], 16, 0, 15);
                    c_run(&maps.m[M_CI], 0, NBE, 15);
                }
            }
        } else if (warp == 11) {
            if (elect()) {
                Feed<BRING> f;
                auto blob_run = [&](auto nbs, int quarter, int n0, int n1) {
                    constexpr int N = decltype(nbs)::value;
                    const uint8_t* src = sc->ab + (size_t)(quarter * 64 + ns) * BLOB;
#pragma unroll 1
                    for (int n = n0; n < n1; n++) {
                        const uint32_t bar = f.template acquire<N>();
                        mbar_expect(bar, BLOB);
                        bulk_ld(f.dst, src + skip_own(n, mt) * (4 * BLOB), BLOB, bar);
                        PROF_FEED_B;
                        f.template next<N>();
                    }
                };
                auto v_run = [&](auto nbs) {
                    constexpr int N = decltype(nbs)::value;
#pragma unroll 1
                    for (int i = 0; i < 7; i++) {
                        const uint32_t bar = f.template acquire<N>();
                        mbar_expect(bar, SLOT);
                        tma_ld4(f.dst, &maps.m[M_WV], 0, i * 64, 0, 8 + ns, bar);
                        tma_ld4(f.dst + 8192, &maps.m[M_WV], 64, i * 64, 0, 8 + ns, bar);
                        mbar_arrive(bar);
                        PROF_FEED_B;
                        f.template next<N>();
                    }
                };
                if (roleH) {
                    f.seek(7, 0);
                    v_run(Int<7>());
                } else if (!roleL) {
                    f.seek(7, bslot_e(7));
#pragma unroll 1
                    for (int i = 0; i < 7; i++) {
                        const uint32_t bar = f.acquire<5>();
                        mbar_expect(bar, BLOB);
                        tma_ld2(f.dst, &maps.m[M_WI], i * 64, col, bar);
                        mbar_arrive(bar);
                        PROF_FEED_B;
                        f.next<5>();
                    }
                    f.seek(18, bslot_e(18));
                    wait_dep(0);
                    blob_run(Int<7>(), 0, 0, 15);
                    wait_dep(1);
                    blob_run(Int<7>(), 2, 0, NBE);
                    mbar_wait(base + BAR_HINT, 0);
                    fence_async_global();
#pragma unroll 1
                    for (int i = 0; i < 7; i++) {
                        const uint32_t bar = f.acquire<7>();
                        mbar_expect(bar, SLOT);
                        bulk_ld(f.dst, sc->wo + (size_t)(ns * 7 + i) * SLOT, SLOT, bar);
                        PROF_FEED_B;
                        f.next<7>();
                    }

                } else {
                    f.seek(6, 0);
#pragma unroll 1
                    for (int i = 6; i < 14; i++) {
                        const uint32_t bar = f.acquire<6>();
                        mbar_expect(bar, SLOT);
                        tma_ld4(f.dst, &maps.m[M_WQK], 0, i * 32, 0, ns, bar);
                        tma_ld4(f.dst + 8192, &maps.m[M_WQK], 64, i * 32, 0, ns, bar);
                        if (i & 1) mbar_arrive(bar);
                        PROF_FEED_B;
                        f.next<6>();
                    }
                    v_run(Int<6>());
                    wait_dep(0);
                    blob_run(Int<6>(), 1, 0, 15);
                    wait_dep(1);
                    blob_run(Int<6>(), 3, 0, 15);
                    blob_run(Int<6>(), 2, NBE, 15);
                    fence_async_smem();
#pragma unroll 1
                    for (int h = 0; h < 2; h++) {
                        mbar_wait(base + BAR_HINT + h * 8, 0);
                        PROF(153 + h);
                        mbar_expect(base + BAR_PART + h * 8, BLOB);
                        bulk_ld(base + (h ? HALO : LSLAB), sc->part + (size_t)((ns * 16 + mt) * 2 + h) * BLOB, BLOB, base + BAR_PART + h * 8);
                    }
                }
            }
        } else if (roleH) {
            if (warp == 9 && elect()) {
                wait_released(0);
#pragma unroll 1
                for (int i = 0; i < 7; i++)
                    asm volatile("cp.async.bulk.prefetch.tensor.2d.L2.global [%0, {%1, %2}];" ::"l"(&maps.m[M_WI]), "r"(i * 64), "r"(col) : "memory");
            }
        } else if (warp == 10) {
            if (elect()) {
                unsigned* epoch_ptr = &sc->epoch[(bid * 4 + 2) * 8];
                const unsigned ep = *epoch_ptr + 1;
                sts1(base + TAG, ep);
                asm volatile("prefetch.tensormap [%0];" ::"l"(&maps.m[M_OUTA + roleL]) : "memory");
                await(sc, CNT_A + roleL * 4 + ns, ep * 16);
                mbar_arrive(base + BAR_DEP);
                PROF(150);
                await(sc, CNT_B + ns, ep * 16);
                mbar_arrive(base + BAR_DEP + 8);
                PROF(151);
                if (!roleL) {
                    await(sc, CNT_W + ns, ep);
                    mbar_arrive(base + BAR_HINT);
                    PROF(153);
                    await(sc, CNT_O + mt, ep * 4);
                    mbar_arrive(base + BAR_DEP + 16);
                } else {
                    await(sc, CNT_P + mt * 4 + ns, ep * 2 - 1);
                    mbar_arrive(base + BAR_HINT);
                    await(sc, CNT_P + mt * 4 + ns, ep * 2);
                    mbar_arrive(base + BAR_HINT + 8);
                }
                PROF(152);
                *epoch_ptr = ep;
            }
        } else if (!roleL) {
            if (elect()) {
                mbar_wait(base + BAR_RDY, 0);
                PROF(130);
                signal(sc, CNT_A + ns);
                PROF(131);
                mbar_wait(base + BAR_RDY + 8, 0);
                signal(sc, CNT_A + 4 + ns);
                PROF(135);
                mbar_wait(base + BAR_RDY + 16, 0);
                PROF(132);
                signal(sc, CNT_B + ns);
                PROF(133);
            }
        } else {
            unsigned* epoch_ptr = &sc->epoch[(bid * 4 + 1) * 8];
            const unsigned tag = *epoch_ptr + 1;
#pragma unroll 1
            for (int kv = 0; kv < 2; kv++) {
                uint32_t v[16];
#pragma unroll
                for (int i = 0; i < 16; i++) v[i] = 0;
                if (kv) wait_released(HALO_V_AT - 4), wait_released(HALO_V_AT);
                else mbar_wait(base + BAR_DEP + 16, 0);
                if (blk > 0) {
                    const uint8_t* src = sc->halo + (size_t)(((mt - 1) * 4 + ns) * 2 + kv) * 2048 + lane * 16;
#pragma unroll 1
                    for (int n = 0; n < SPIN_LIMIT; n++) {
#pragma unroll
                        for (int i = 0; i < 4; i++) ld_tagged(src + i * 512, v[4 * i], v[4 * i + 1], v[4 * i + 2], v[4 * i + 3]);
#pragma unroll
                        for (int i = 0; i < 16; i += 2) v[i] ^= tag & 1;
                        const uint32_t stale = or3(or3(v[0], v[2], v[4]), or3(v[6], v[8], v[10]), or3(v[12], v[14], 0));
                        if (__all_sync(0xffffffffu, !(stale & 1))) break;
                    }
#pragma unroll
                    for (int c = 0; c < 14; c += 2) v[c] |= (v[15] >> c) & 1;
                }
#pragma unroll
                for (int i = 0; i < 14; i++) sts1(base + HALO + kv * (8 * HSLOT) + i * 128 + lane * 4, v[i]);
                warp_arrive(base + BAR_HALO + kv * 8);
                if (lane == 0) PROF(142 + kv);
            }
            if (elect()) {
                mbar_wait(base + BAR_RDY + 16, 0);
                PROF(130);
                signal(sc, CNT_O + mt);
                PROF(131);
                *epoch_ptr = tag;
            }
        }
    } else {
        asm volatile("setmaxnreg.inc.sync.aligned.u32 224;");
        Ring r;
        r.wg = warp >> 2;
        r.zero = blockIdx.y;
        r.releaser = lane + 1 == (warp >> 2);
        const int wg = warp >> 2;
        if (wg) nb_arrive(1, 256);
        uint8_t* part = sc->part + (size_t)(ns * 16 + mt) * (2 * BLOB) + warp * WSLOT + lane * 16;
        uint32_t p[28];

        if (roleH) {
            unsigned* epoch_ptr = &sc->epoch[bid * 4 * 8];
            const unsigned tag = *epoch_ptr + 1;
            uint8_t* hout = sc->halo + (size_t)((warp * 8 + ns) * 2) * 2048 + lane * 16;
            auto send = [&](int kv) {
#pragma unroll
                for (int h = 0; h < 2; h++) {
                    uint32_t v[16];
                    v[14] = v[15] = 0;
#pragma unroll
                    for (int c = 0; c < 14; c++) v[c] = p[2 * c + h];
#pragma unroll
                    for (int c = 0; c < 14; c += 2) v[15] |= (v[c] & 1) << c;
#pragma unroll
                    for (int c = 0; c < 16; c += 2) v[c] = with_parity(v[c], tag);
#pragma unroll
                    for (int i = 0; i < 4; i++) st_tagged(hout + (h * 8 + kv) * 2048 + i * 512, v + 4 * i);
                }
            };
            float x0[56], x1[56];
            r.seek(0, 0);
            r.wait();
            r.run<XWN, 7, true>(x0);
#pragma unroll 1
            for (int i = 1; i < 7; i++) r.run<XWN, 7, false>(x0);
            r.run<XWN, 7, true>(x1);
            acc_fence(x0);
            pack_all(x0, p);
            send(0);
#pragma unroll 1
            for (int i = 1; i < 7; i++) r.run<XWN, 7, false>(x1, true, i < 6 || !wg, i < 6);
            asm volatile("wgmma.wait_group.sync.aligned 0;" ::: "memory");
            acc_fence(x1);
            pack_all(x1, p);
#pragma unroll
            for (int i = 0; i < 28; i++) p[i] = movm(p[i]);
            send(1);
            warp_arrive(base + BAR_RDY + 16);
            if (threadIdx.x == 0) *epoch_ptr = tag;
        } else if (!roleL) {
            uint8_t* blob = sc->ab + (size_t)((wg * 16 + mt) * 4 + ns) * BLOB + (warp & 3) * WSLOT + lane * 4;
            const uint32_t own = base + BRING + wg * SLOT + (warp & 3) * WSLOT + lane * 16;
            float x0[56], x1[56];
            r.seek(0, bslot_e(0));
            r.wait();
            r.run<XW, 7, true>(x0);
            r.run<XW, 7, false>(x0);
            r.seek(2, bslot_e(2));
#pragma unroll 1
            for (int i = 2; i < 7; i++) r.run<XW, 5, false>(x0);

            r.seek(7, bslot_e(7));
            r.run<XW, 5, true, -1>(x1);
            acc_fence(x0);
            pack_all<0, 14>(x0, p);
#pragma unroll
            for (int i = 0; i < 2; i++) {
                if (wg == i) store_frags<0, 14>(blob, p);
                else stage_frags<0, 4>(own + 5 * SLOT, p);
                r.run<XW, 5, false, -1>(x1);
                if (i == 0) pack_all<14, 28>(x0, p);
                if (wg == i) {
                    store_frags<14, 28>(blob, p);
                    warp_arrive(base + BAR_RDY + i * 8);
                } else {
                    stage_frags<4, 8>(own + 5 * SLOT, p);
                }
                r.run<XW, 5, false, -1>(x1);
            }
            stage_frags<8, 16>(own + 5 * SLOT, p);
            r.run<XW, 5, false, -1>(x1);
            stage_frags<16, 24>(own + 5 * SLOT, p);
            r.run<XW, 5, false, -1>(x1);
            stage_frags<24, 28>(own + 5 * SLOT, p);

            r.seek(14, bslot_e(14));
            r.take_turn();
            fence_async_smem();
            r.run<BIG, 7, true>(x0, false);
            acc_fence(x1);
            pack_all(x1, p);
            stage_frags<0, 16>(own, p);
            r.run<BIG, 7, false>(x0);
            stage_frags<16, 28>(own, p);
            r.take_turn();
            fence_async_smem();
            blob += (size_t)128 * BLOB;
#pragma unroll
            for (int i = 0; i < 28; i++) {
                if (i % B_SLICE == 0) r.run<BIG, 7, false>(x0, i > 0);
                stg1(blob + i * 128, p[i]);
            }
            warp_arrive(base + BAR_RDY + 16);
#pragma unroll 1
            for (int i = 17 + 27 / B_SLICE; i < POUT; i++) r.run<BIG, 7, false>(x0);

            const uint32_t tag = lds1(base + TAG);
            r.seek(POUT, bslot_e(POUT));
            r.run<OUT, 7, true>(x1);
            acc_fence(x0);
            pack_all(x0, p);
#pragma unroll
            for (int i = 0; i < 28; i += 2) p[i] = with_parity(p[i], tag);
#pragma unroll
            for (int k = 0; k < 3; k++) {
                if (k < 2 && wg == k) {
#pragma unroll
                    for (int i = 0; i < P_FIRST; i++) st_tagged(part + i * 512, p + 4 * i);
                    if ((warp & 3) == 0 && elect())
                        asm volatile("red.relaxed.gpu.global.add.u32 [%0], 1;" ::"l"(&sc->cnt[(CNT_P + mt * 4 + ns) * 32]) : "memory");
                }
                if (k > 0 && wg == k - 1) {
#pragma unroll
                    for (int i = P_FIRST; i < 7; i++) st_tagged(part + i * 512, p + 4 * i);
                }
                if (k < 2) r.run<OUT, 7, false>(x1);
            }
#pragma unroll
            for (int i = 3; i < 7; i++) r.run<OUT, 7, false, 1, true>(x1, i <= 7 - TURN, i < 7 - TURN || (i == 6 && !wg), i < 6);

            asm volatile("wgmma.wait_group.sync.aligned 0;" ::: "memory");
            acc_fence(x1);
            const uint32_t slab = base + (wg ? BRING + bslot_e(ELAST - 6) * SLOT : ((ELAST - 6) % NA) * SLOT) + (warp & 3) * WSLOT;
            store_out([&](int i) { return pack2(x1[2 * i], x1[2 * i + 1]); }, lane, slab, &maps.m[M_OUTA], par * 896 + col, blk * 128 + warp * 16);
        } else {
            const int g = lane >> 2, tig = lane & 3;
            const uint32_t hin = base + HALO + warp * HSLOT + lane * 4;
            const uint32_t hpub = warp < 7 ? hin + HSLOT : base + HSPARE + lane * 4;
            auto publish = [&](const uint32_t (&h)[14], int c0, int c1) {
#pragma unroll
                for (int c = 0; c < 14; c++)
                    if (c >= c0 && c < c1) sts1(hpub + c * 128, h[c]);
            };
            float y0[56], y1[56], y2[56];
            r.seek(0, 0);
            r.wait();
            r.run<QK, 6, true>(y0, y1);
#pragma unroll 1
            for (int i = 1; i < 14; i++) r.run<QK, 6, false>(y0, y1);

            uint32_t m1[8][4], m0[8][4], lo[14], hi[14], q[2][8][2];
            auto pack_q = [&](int b) {
                uint32_t v[14];
#pragma unroll
                for (int c = 0; c < 14; c++) v[c] = pack2(y0[4 * c + 2 * b], y0[4 * c + 2 * b + 1]);
#pragma unroll
                for (int t = 0; t < 8; t++) {
                    const int c = tile_of(t);
                    q[b][t][0] = (t & 3) == 2 ? (tig >= 2 ? v[c] : 0u) : v[c];
                    q[b][t][1] = (t & 3) == 1 ? (tig < 2 ? v[c + 1] : 0u) : v[c + 1];
                }
            };
            auto fetch = [&](uint32_t src, int hp, int i0) {
#pragma unroll
                for (int t = 4 * hp; t < 4 * hp + 4; t++) {
                    m0[t][i0] = (t & 3) == 2 ? dup(m0[t - 1][3], r.zero) : lds1(src + tile_of(t) * 128);
                    m0[t][3] = lds1(src + tile_of(t) * 128 + 128);
                }
            };
            r.seek(14, bslot_l(14));
            r.run<XWN, 6, true>(y2);
            acc_fence(y0);
            acc_fence(y1);
#pragma unroll
            for (int c = 0; c < 14; c++) hi[c] = pack2(y1[4 * c + 2], y1[4 * c + 3]);
            publish(hi, 0, 7);
            r.run<XWN, 6, false>(y2);
            publish(hi, 7, 14);
#pragma unroll
            for (int c = 0; c < 14; c++) lo[c] = pack2(y1[4 * c], y1[4 * c + 1]);
#pragma unroll
            for (int t = 0; t < 8; t++) {
                const int c = tile_of(t);
                const bool shared = (t & 3) == 2;
                m1[t][0] = shared ? dup(lo[c], r.zero) : lo[c];
                m1[t][1] = shared ? dup(hi[c], r.zero) : hi[c];
                m1[t][2] = lo[c + 1];
                m1[t][3] = hi[c + 1];
                m0[t][0] = dup(m1[t][0], r.zero);
                m0[t][2] = dup(lo[c + 1], 2 * r.zero);
            }
            r.run<XWN, 6, false>(y2);
            if (warp == 0) mbar_wait(base + BAR_HALO, 0);
            fetch(hin, 0, 1);
            pack_q(1);
            r.run<XWN, 6, false>(y2);
            fetch(hin, 1, 1);
            pack_q(0);
            r.mma_begin();
            float s[8][4];
#pragma unroll
            for (int step = 0; step < 2; step++) {
#pragma unroll
                for (int i = 0; i < 8; i++) {
                    const int b = 1 - (i >> 2), h = i & 3, t = 2 * h + step;
                    float (&d)[4] = s[2 * h + b];
                    if (step == 0) d[0] = d[1] = d[2] = d[3] = 0.f;
                    mma16816(d, b ? m1[t] : m0[t], q[b][t][0], q[b][t][1]);
                }
            }
            r.mma_end();
            r.run<XWN, 6, false>(y2, false);

            uint32_t pr[8], mx[4], mx1[4];
            {
                const bool cur0 = g <= 2 * tig, cur1 = g <= 2 * tig + 1;
#pragma unroll
                for (int i = 0; i < 8; i++) {
                    const int c = (i & 1) ? 2 : 0;
                    pr[i] = movm(pack2(cur0 ? s[i][c] : s[i][2 - c], cur1 ? s[i][c + 1] : s[i][3 - c]));
                }
            }
            r.run<XWN, 6, false>(y2);
            const uint32_t curmask = (2 * tig <= g ? 0x0000FFFFu : 0u) | (2 * tig + 1 <= g ? 0xFFFF0000u : 0u);
            {
                const uint32_t keep = (blk == 0 && warp == 0) ? curmask : 0xFFFFFFFFu;
#pragma unroll
                for (int i = 0; i < 4; i++) {
                    pr[2 * i] = (scale2(pr[2 * i]) & keep) | (0xCE6ECE6Eu & ~keep);
                    pr[2 * i + 1] = scale2(pr[2 * i + 1]);
                    mx[i] = max2(__byte_perm(pr[2 * i], pr[2 * i + 1], 0x5410), __byte_perm(pr[2 * i], pr[2 * i + 1], 0x7632));
                    mx1[i] = __shfl_xor_sync(0xffffffffu, mx[i], 1);
                }
            }
#pragma unroll
            for (int i = 0; i < 4; i++) {
                mx[i] = max2(mx[i], mx1[i]);
                mx1[i] = __shfl_xor_sync(0xffffffffu, mx[i], 2);
            }
            r.run<XWN, 6, false>(y2);
            constexpr float SCL = 1.4426950408889634f;
            float e0[8], e1[8], sm[8], sm1[8];
#pragma unroll
            for (int i = 0; i < 8; i++) {
                const uint32_t m2 = max2(mx[i >> 1], mx1[i >> 1]);
                sm[i] = ((i & 1) ? bf_hi(m2) : bf_lo(m2)) * -SCL;
                e0[i] = ex2(fmaf(bf_lo(pr[i]), SCL, sm[i]));
            }

            r.seek(21, bslot_l(21));
            r.run<BIG, 6, true>(y0);
            acc_fence(y2);
#pragma unroll
            for (int c = 0; c < 7; c++) hi[c] = movm(pack2(y2[4 * c + 2], y2[4 * c + 3]));
#pragma unroll
            for (int i = 0; i < 8; i++) e1[i] = ex2(fmaf(bf_hi(pr[i]), SCL, sm[i]));
            r.run<BIG, 6, false>(y0);
            publish(hi, 0, 7);
#pragma unroll
            for (int c = 7; c < 14; c++) hi[c] = movm(pack2(y2[4 * c + 2], y2[4 * c + 3]));
            r.run<BIG, 6, false>(y0);
            publish(hi, 7, 14);
#pragma unroll
            for (int i = 0; i < 8; i++) {
                sm[i] = e0[i] + e1[i];
                sm1[i] = __shfl_xor_sync(0xffffffffu, sm[i], 1);
            }
            r.run<BIG, 6, false>(y0);
#pragma unroll
            for (int c = 0; c < 14; c++) lo[c] = movm(pack2(y2[4 * c], y2[4 * c + 1]));
            r.run<BIG, 6, false>(y0);
#pragma unroll
            for (int i = 0; i < 8; i++) {
                sm[i] += sm1[i];
                sm1[i] = __shfl_xor_sync(0xffffffffu, sm[i], 2);
            }
#pragma unroll
            for (int t = 0; t < 8; t++) {
                const int c = tile_of(t);
                const bool shared = (t & 3) == 2;
                m1[t][0] = shared ? dup(lo[c], r.zero) : lo[c];
                m1[t][1] = lo[c + 1];
                m1[t][2] = shared ? dup(hi[c], r.zero) : hi[c];
                m1[t][3] = hi[c + 1];
                m0[t][0] = dup(m1[t][0], r.zero);
                m0[t][1] = dup(lo[c + 1], 2 * r.zero);
            }
            r.run<BIG, 6, false>(y0);
            if (warp == 0) mbar_wait(base + BAR_HALO + 8, 0);
            const uint32_t vin = warp ? hin : hin + 8 * HSLOT;
            fetch(vin, 0, 2);
#pragma unroll
            for (int i = 0; i < 8; i++) {
                const float inv = rcp(sm[i] + sm1[i]);
                pr[i] = pack2(e0[i] * inv, e1[i] * inv);
            }
            r.run<BIG, 6, false>(y0);
            fetch(vin, 1, 2);
            uint32_t pb[8][2];
#pragma unroll
            for (int t = 0; t < 8; t++) {
                pb[t][t & 1] = band(pr[t], curmask);
                pb[t][1 - (t & 1)] = band(pr[t], ~curmask);
            }
            r.mma_begin();
            float o[2][8][4];
#pragma unroll
            for (int i = 0; i < 16; i++) {
                const int b = 1 - (i >> 3), t = i & 7;
                float (&d)[4] = o[b][t];
                d[0] = d[1] = d[2] = d[3] = 0.f;
                mma16816(d, b ? m1[t] : m0[t], pb[(t & 6) + b][0], pb[(t & 6) + b][1]);
            }
            r.mma_end();
            r.run<BIG, 6, false>(y0, false);
            uint8_t* odst = sc->o + (size_t)mt * 7 * SLOT + ns * (14 * 2048) + warp * 256 + lane * 4;
#pragma unroll
            for (int hp = 0; hp < 2; hp++) {
#pragma unroll
                for (int b = 0; b < 2; b++) {
                    const float (&u)[8][4] = o[b];
                    const int t = 4 * hp;
                    uint32_t* w = p + 14 * hp + b;
                    w[0] = pack2(u[t][0], u[t][1]);
                    w[2] = pack2(u[t][2], u[t][3]);
                    w[4] = pack2(u[t + 1][0], u[t + 1][1]);
                    w[6] = pack2(g < 4 ? u[t + 1][2] : u[t + 2][0], g < 4 ? u[t + 1][3] : u[t + 2][1]);
                    w[8] = pack2(u[t + 2][2], u[t + 2][3]);
                    w[10] = pack2(u[t + 3][0], u[t + 3][1]);
                    w[12] = pack2(u[t + 3][2], u[t + 3][3]);
                }
            }
#pragma unroll
            for (int i = 0; i < 28; i++) {
                if (i >= O_FIRST && (i - O_FIRST) % O_SLICE == 0) r.run<BIG, 6, false>(y0);
                stg1(odst + (i >> 1) * 2048 + (i & 1) * 128, p[i]);
            }
            warp_arrive(base + BAR_RDY + 16);

#pragma unroll 1
            for (int i = 30 + (27 - O_FIRST) / O_SLICE; i <= LLAST - LTURN; i++) r.run<BIG, 6, false>(y0);
            r.seek(LLAST + 1 - LTURN, bslot_l(LLAST + 1 - LTURN));
#pragma unroll
            for (int i = 0; i < LTURN; i++) r.run<BIG, 6, false, 1, true>(y0, i == 0, i == LTURN - 1 && !wg, i < LTURN - 1);
            const uint32_t parity = lds1(base + TAG) & 1;
            const uint32_t slab = base + (wg ? HALO : LSLAB) + (warp & 3) * WSLOT;
            mbar_wait(base + BAR_PART + wg * 8, 0);
#pragma unroll 1
            for (int n = 0; n < SPIN_LIMIT; n++) {
#pragma unroll
                for (int i = 0; i < 7; i++) lds4(slab + i * 512 + lane * 16, p + 4 * i);
#pragma unroll
                for (int i = 0; i < 28; i += 2) p[i] ^= parity;
                const uint32_t stale = or3(or3(or3(p[0], p[2], p[4]), or3(p[6], p[8], p[10]), or3(p[12], p[14], p[16])),
                                           or3(p[18], p[20], p[22]), or3(p[24], p[26], 0));
                if (__all_sync(0xffffffffu, !(stale & 1))) break;
#pragma unroll
                for (int i = 0; i < 7; i++) ld_tagged(part + i * 512, p[4 * i], p[4 * i + 1], p[4 * i + 2], p[4 * i + 3]);
#pragma unroll
                for (int i = 0; i < 7; i++)
                    asm volatile("st.shared.v4.b32 [%0], {%1,%2,%3,%4};" ::"r"(slab + i * 512 + lane * 16), "r"(p[4 * i]), "r"(p[4 * i + 1]), "r"(p[4 * i + 2]), "r"(p[4 * i + 3]) : "memory");
            }
            asm volatile("wgmma.wait_group.sync.aligned 0;" ::: "memory");
            acc_fence(y0);
            store_out([&](int i) { return add2(pack2(y0[2 * i], y0[2 * i + 1]), p[i]); }, lane, slab, &maps.m[M_OUTB], 448 + col, mt * 128 + warp * 16);
        }
    }
}

typedef CUresult (*EncodeFn)(CUtensorMap*, CUtensorMapDataType, cuuint32_t, void*, const cuuint64_t*, const cuuint64_t*,
                             const cuuint32_t*, const cuuint32_t*, CUtensorMapInterleave, CUtensorMapSwizzle,
                             CUtensorMapL2promotion, CUtensorMapFloatOOBfill);

struct Dim { uint64_t size, stride; uint32_t box; };
void encode(EncodeFn fn, CUtensorMap* m, const void* ptr, CUtensorMapSwizzle sw, Dim d0, Dim d1, Dim d2 = {0, 0, 0}, Dim d3 = {0, 0, 0}) {
    const cuuint64_t dims[4] = {d0.size, d1.size, d2.size, d3.size};
    const cuuint64_t strides[3] = {d1.stride, d2.stride, d3.stride};
    const cuuint32_t box[4] = {d0.box, d1.box, d2.box, d3.box};
    const cuuint32_t es[4] = {1, 1, 1, 1};
    fn(m, CU_TENSOR_MAP_DATA_TYPE_BFLOAT16, d3.size ? 4 : d2.size ? 3 : 2, const_cast<void*>(ptr), dims, strides, box, es,
       CU_TENSOR_MAP_INTERLEAVE_NONE, sw, CU_TENSOR_MAP_L2_PROMOTION_L2_128B, CU_TENSOR_MAP_FLOAT_OOB_FILL_NONE);
}

}

extern "C" void kernel_launch(void* const* d_in, const int* in_sizes, int n_in, void* d_out, int out_size) {
    (void)in_sizes; (void)n_in; (void)out_size;
    void* fnp = nullptr;
    cudaDriverEntryPointQueryResult st;
    cudaGetDriverEntryPoint("cuTensorMapEncodeTiled", &fnp, cudaEnableDefault, &st);
    EncodeFn fn = (EncodeFn)fnp;
    void* scratch = nullptr;
    cudaGetSymbolAddress(&scratch, g_scratch);
    int dev = 0, sms = 0;
    cudaGetDevice(&dev);
    cudaDeviceGetAttribute(&sms, cudaDevAttrMultiProcessorCount, dev);
    auto kernel = sms == 132 ? fused_kernel<true> : fused_kernel<false>;
    cudaFuncSetAttribute(kernel, cudaFuncAttributeMaxDynamicSharedMemorySize, SMEM_BYTES);

    const CUtensorMapSwizzle S128 = CU_TENSOR_MAP_SWIZZLE_128B, S0 = CU_TENSOR_MAP_SWIZZLE_NONE;
    const Dim one = {1, 16, 1};
    Maps maps;
    encode(fn, &maps.m[M_XA], d_in[0], S128, {896, 2, 64}, {1024, 1792, 128}, one, one);
    encode(fn, &maps.m[M_WQK], d_in[1], S128, {112, 2, 64}, {448, 2688, 32}, {3, 896, 2}, {4, 224, 1});
    encode(fn, &maps.m[M_WV], d_in[1], S128, {112, 2, 64}, {448, 2688, 64}, one, {12, 224, 1});
    encode(fn, &maps.m[M_XH], d_in[0], S128, {448, 2, 64}, {128, 1792, 8}, {8, 128 * 1792, 8}, {2, 896, 2});
    encode(fn, &maps.m[M_WO], d_in[2], S128, {112, 2, 64}, {448, 896, 64}, one, {4, 224, 1});
    encode(fn, &maps.m[M_XB], d_in[3], S128, {448, 2, 64}, {1024, 896, 64}, {2, 896 * 1024, 2}, one);
    encode(fn, &maps.m[M_CR], d_in[4], S128, {2048, 2, 64}, {2048, 4096, 128});
    encode(fn, &maps.m[M_CI], d_in[5], S128, {2048, 2, 64}, {2048, 4096, 128});
    encode(fn, &maps.m[M_WR], d_in[6], S128, {448, 2, 64}, {448, 896, 112}, one, one);
    encode(fn, &maps.m[M_WI], d_in[7], S128, {448, 2, 64}, {448, 896, 112});
    encode(fn, &maps.m[M_OUTA], d_out, S0, {1792, 2, 112}, {1024, 3584, 8});
    encode(fn, &maps.m[M_OUTB], d_out, S0, {896, 2, 112}, {2048, 1792, 8});

    kernel<<<132, 384, SMEM_BYTES>>>((Scratch*)scratch, maps);
}
```

```cpp
#include <cuda.h>
#include <cuda_bf16.h>
#include <cuda_runtime.h>
#include <stdint.h>

namespace {

constexpr uint32_t SLOT = 16384;
constexpr int NA = 7;
constexpr uint32_t BRING = NA * SLOT;
constexpr uint32_t HALO = BRING + 6 * SLOT;
constexpr uint32_t HSLOT = 1792;
constexpr uint32_t WSLOT = 3584;
constexpr uint32_t BLOB = 14336;
constexpr uint32_t BARS = 14 * SLOT;
constexpr uint32_t BAR_FULL = BARS;
constexpr uint32_t BAR_EMPTY = BARS + 64;
constexpr uint32_t BAR_RDY = BARS + 128;
constexpr uint32_t BAR_DEP = BARS + 168;
constexpr uint32_t BAR_HALO = BARS + 192;
constexpr uint32_t BAR_PART = BARS + 208;
constexpr uint32_t BAR_HINT = BARS + 224;
constexpr uint32_t TAG = BARS + 240;
constexpr uint32_t HSPARE = BARS + 256 + 1024;
constexpr uint32_t SMEM_BYTES = HSPARE + HSLOT;
constexpr uint32_t base = 1024;
constexpr int SPIN_LIMIT = 1 << 16;

constexpr int LEAD = 3;
constexpr int PACE = 450;
constexpr int HALO_K_AT = 10;
constexpr int HALO_V_AT = 19;
constexpr int B_SLICE = 4;
constexpr int O_FIRST = 7, O_SLICE = 3;
constexpr int TURN = 4, LTURN = 5;
constexpr uint32_t GPC_MAP = 0x64752310u;
constexpr int NBE = 13;
constexpr int POUT = 33 + NBE;
constexpr int ELAST = POUT + 6;
constexpr int LLAST = 65 - NBE;
constexpr uint32_t LSLAB = ((LLAST - 6) % NA) * SLOT;
static_assert(TURN <= 4 && LTURN <= 5, "the output is staged in the slots of the seventh-last stage");

enum { M_XB, M_XA, M_XH, M_WR, M_WQK, M_WV, M_WO, M_WI, M_CR, M_CI, M_OUTA, M_OUTB, M_COUNT };
struct __align__(64) Maps { CUtensorMap m[M_COUNT]; };

constexpr int CNT_A = 0;
constexpr int CNT_B = 8;
constexpr int CNT_W = 12;
constexpr int CNT_O = 16;
constexpr int CNT_P = 32;
constexpr int CNT_COUNT = 96;

struct Scratch {
    uint8_t ab[64 * 4 * BLOB];
    uint8_t o[16 * 7 * SLOT];
    uint8_t part[64 * 2 * BLOB];
    uint8_t halo[64 * 2 * 2048];
    uint8_t wo[4 * 7 * SLOT];
    unsigned cnt[CNT_COUNT * 32];
    unsigned epoch[132 * 4 * 8];
};
__device__ __align__(1024) Scratch g_scratch;

__device__ __forceinline__ unsigned clk32() { unsigned c; asm volatile("mov.u32 %0, %%clock;" : "=r"(c)); return c; }

#define PROF(idx)

__device__ __forceinline__ void mbar_init(uint32_t bar, uint32_t cnt) {
    asm volatile("mbarrier.init.shared::cta.b64 [%0], %1;" ::"r"(bar), "r"(cnt) : "memory");
}
__device__ __forceinline__ void mbar_expect(uint32_t bar, uint32_t bytes) {
    asm volatile("mbarrier.arrive.expect_tx.shared::cta.b64 _, [%0], %1;" ::"r"(bar), "r"(bytes) : "memory");
}
__device__ __forceinline__ void mbar_arrive(uint32_t bar) {
    asm volatile("mbarrier.arrive.shared::cta.b64 _, [%0];" ::"r"(bar) : "memory");
}
__device__ __forceinline__ bool mbar_try(uint32_t bar, uint32_t parity) {
    uint32_t ok;
    asm volatile("{\n.reg .pred p;\nmbarrier.try_wait.parity.shared::cta.b64 p, [%1], %2;\nselp.u32 %0, 1, 0, p;\n}\n"
                 : "=r"(ok) : "r"(bar), "r"(parity) : "memory");
    return ok;
}
__device__ __forceinline__ void mbar_wait(uint32_t bar, uint32_t parity) {
#pragma unroll 1
    for (int n = 0; n < SPIN_LIMIT; n++)
        if (mbar_try(bar, parity)) break;
}
__device__ __forceinline__ bool elect() {
    uint32_t p;
    asm volatile("{\n.reg .pred p;\nelect.sync _|p, 0xffffffff;\nselp.u32 %0, 1, 0, p;\n}\n" : "=r"(p));
    return p;
}
__device__ __forceinline__ void nb_sync(int id, int n) { asm volatile("bar.sync %0, %1;" ::"r"(id), "r"(n) : "memory"); }
__device__ __forceinline__ void nb_arrive(int id, int n) { asm volatile("bar.arrive %0, %1;" ::"r"(id), "r"(n) : "memory"); }
__device__ __forceinline__ void warp_arrive(uint32_t bar) {
    __syncwarp();
    if (elect()) mbar_arrive(bar);
}
__device__ __forceinline__ uint32_t or3(uint32_t a, uint32_t b, uint32_t c) {
    uint32_t r;
    asm("lop3.b32 %0, %1, %2, %3, 0xFE;" : "=r"(r) : "r"(a), "r"(b), "r"(c));
    return r;
}
__device__ __forceinline__ uint32_t band(uint32_t x, uint32_t m) {
    uint32_t r;
    asm volatile("and.b32 %0, %1, %2;" : "=r"(r) : "r"(x), "r"(m));
    return r;
}
__device__ __forceinline__ uint32_t dup(uint32_t x, uint32_t zero) {
    uint32_t r;
    asm volatile("xor.b32 %0, %1, %2;" : "=r"(r) : "r"(x), "r"(zero));
    return r;
}

__device__ __forceinline__ void tma_ld2(uint32_t dst, const CUtensorMap* m, int c0, int c1, uint32_t bar) {
    asm volatile("cp.async.bulk.tensor.2d.shared::cluster.global.mbarrier::complete_tx::bytes [%0], [%1, {%3, %4}], [%2];"
                 ::"r"(dst), "l"(m), "r"(bar), "r"(c0), "r"(c1) : "memory");
}
__device__ __forceinline__ void tma_ld4(uint32_t dst, const CUtensorMap* m, int c0, int c1, int c2, int c3, uint32_t bar) {
    asm volatile("cp.async.bulk.tensor.4d.shared::cluster.global.mbarrier::complete_tx::bytes [%0], [%1, {%3, %4, %5, %6}], [%2];"
                 ::"r"(dst), "l"(m), "r"(bar), "r"(c0), "r"(c1), "r"(c2), "r"(c3) : "memory");
}
__device__ __forceinline__ void bulk_ld(uint32_t dst, const void* src, uint32_t bytes, uint32_t bar) {
    asm volatile("cp.async.bulk.shared::cluster.global.mbarrier::complete_tx::bytes [%0], [%1], %2, [%3];"
                 ::"r"(dst), "l"(src), "r"(bytes), "r"(bar) : "memory");
}
__device__ __forceinline__ void bulk_st(void* dst, uint32_t src, uint32_t bytes) {
    asm volatile("cp.async.bulk.global.shared::cta.bulk_group [%0], [%1], %2;" ::"l"(dst), "r"(src), "r"(bytes) : "memory");
}
__device__ __forceinline__ void tma_st2(const CUtensorMap* m, int c0, int c1, uint32_t src) {
    asm volatile("cp.async.bulk.tensor.2d.global.shared::cta.bulk_group [%0, {%1, %2}], [%3];"
                 ::"l"(m), "r"(c0), "r"(c1), "r"(src) : "memory");
}
__device__ __forceinline__ void bulk_commit() { asm volatile("cp.async.bulk.commit_group;" ::: "memory"); }
__device__ __forceinline__ void bulk_wait_read() { asm volatile("cp.async.bulk.wait_group.read 0;" ::: "memory"); }
__device__ __forceinline__ void fence_async_smem() { asm volatile("fence.proxy.async.shared::cta;" ::: "memory"); }
__device__ __forceinline__ void fence_async_global() { asm volatile("fence.proxy.async.global;" ::: "memory"); }

__device__ __forceinline__ void signal(Scratch* sc, int idx) {
    asm volatile("fence.proxy.async;\nred.relaxed.gpu.global.add.u32 [%0], 1;" ::"l"(&sc->cnt[idx * 32]) : "memory");
}
__device__ __forceinline__ unsigned peek(const unsigned* p) {
    unsigned v;
    asm volatile("ld.relaxed.gpu.global.u32 %0, [%1];" : "=r"(v) : "l"(p) : "memory");
    return v;
}
__device__ __forceinline__ void await(Scratch* sc, int idx, unsigned target) {
    const unsigned* p = &sc->cnt[idx * 32];
#pragma unroll 1
    for (int n = 0; n < SPIN_LIMIT; n++)
        if ((int)(peek(p) - target) >= 0) break;
    asm volatile("fence.acquire.gpu;" ::: "memory");
}
__device__ __forceinline__ void wait_dep(int k) {
    mbar_wait(base + BAR_DEP + k * 8, 0);
    fence_async_global();
}

#define WG_REGS                                                                                                     \
    "{%0,%1,%2,%3,%4,%5,%6,%7,%8,%9,%10,%11,%12,%13,%14,%15,%16,%17,%18,%19,%20,%21,%22,%23,%24,%25,%26,%27,"       \
    "%28,%29,%30,%31,%32,%33,%34,%35,%36,%37,%38,%39,%40,%41,%42,%43,%44,%45,%46,%47,%48,%49,%50,%51,%52,%53,%54,%55}"
#define WG_OPS(C)                                                                                                   \
    C(d[0]), C(d[1]), C(d[2]), C(d[3]), C(d[4]), C(d[5]), C(d[6]), C(d[7]), C(d[8]), C(d[9]), C(d[10]), C(d[11]),   \
    C(d[12]), C(d[13]), C(d[14]), C(d[15]), C(d[16]), C(d[17]), C(d[18]), C(d[19]), C(d[20]), C(d[21]), C(d[22]),   \
    C(d[23]), C(d[24]), C(d[25]), C(d[26]), C(d[27]), C(d[28]), C(d[29]), C(d[30]), C(d[31]), C(d[32]), C(d[33]),   \
    C(d[34]), C(d[35]), C(d[36]), C(d[37]), C(d[38]), C(d[39]), C(d[40]), C(d[41]), C(d[42]), C(d[43]), C(d[44]),   \
    C(d[45]), C(d[46]), C(d[47]), C(d[48]), C(d[49]), C(d[50]), C(d[51]), C(d[52]), C(d[53]), C(d[54]), C(d[55])

template <int TA, int TB, int SB, bool INIT, uint32_t AH, uint32_t BH>
__device__ __forceinline__ void wgmma112(float (&d)[56], uint32_t alo, uint32_t blo) {
    if (INIT) {
        asm volatile("{\n.reg .pred p;\n.reg .b64 da, db;\nsetp.ne.b32 p, 0, 0;\nmov.b64 da, {%56, %61};\nmov.b64 db, {%57, %62};\n"
                     "wgmma.mma_async.sync.aligned.m64n112k16.f32.bf16.bf16 " WG_REGS ", da, db, p, 1, %59, %60, %58;\n}\n"
                     : WG_OPS("=f") : "r"(alo), "r"(blo), "n"(TB), "n"(SB), "n"(TA), "n"(AH), "n"(BH));
    } else {
        asm volatile("{\n.reg .pred p;\n.reg .b64 da, db;\nsetp.ne.b32 p, 1, 0;\nmov.b64 da, {%56, %61};\nmov.b64 db, {%57, %62};\n"
                     "wgmma.mma_async.sync.aligned.m64n112k16.f32.bf16.bf16 " WG_REGS ", da, db, p, 1, %59, %60, %58;\n}\n"
                     : WG_OPS("+f") : "r"(alo), "r"(blo), "n"(TB), "n"(SB), "n"(TA), "n"(AH), "n"(BH));
    }
}
__device__ __forceinline__ void acc_fence(float (&d)[56]) {
#pragma unroll
    for (int i = 0; i < 56; i++) asm volatile("" : "+f"(d[i])::"memory");
}

__device__ __forceinline__ uint32_t pack2(float lo, float hi) {
    uint32_t r;
    asm volatile("cvt.rn.bf16x2.f32 %0, %1, %2;" : "=r"(r) : "f"(hi), "f"(lo));
    return r;
}
__device__ __forceinline__ uint32_t movm(uint32_t a) {
    uint32_t r;
    asm volatile("movmatrix.sync.aligned.m8n8.trans.b16 %0, %1;" : "=r"(r) : "r"(a));
    return r;
}
__device__ __forceinline__ void stsm4(uint32_t addr, uint32_t a, uint32_t b, uint32_t c, uint32_t d) {
    asm volatile("stmatrix.sync.aligned.m8n8.x4.shared.b16 [%0], {%1,%2,%3,%4};" ::"r"(addr), "r"(a), "r"(b), "r"(c), "r"(d) : "memory");
}
__device__ __forceinline__ void sts1(uint32_t addr, uint32_t a) { asm volatile("st.shared.b32 [%0], %1;" ::"r"(addr), "r"(a) : "memory"); }
__device__ __forceinline__ uint32_t lds1(uint32_t addr) {
    uint32_t a;
    asm volatile("ld.shared.b32 %0, [%1];" : "=r"(a) : "r"(addr) : "memory");
    return a;
}
__device__ __forceinline__ void lds4(uint32_t addr, uint32_t* v) {
    asm volatile("ld.shared.v4.b32 {%0,%1,%2,%3}, [%4];" : "=r"(v[0]), "=r"(v[1]), "=r"(v[2]), "=r"(v[3]) : "r"(addr) : "memory");
}
__device__ __forceinline__ void stg1(uint8_t* p, uint32_t a) { asm volatile("st.global.b32 [%0], %1;" ::"l"(p), "r"(a) : "memory"); }
__device__ __forceinline__ uint64_t tagged(uint32_t lo, uint32_t hi, uint32_t tag) {
    uint64_t r;
    asm volatile("{\n.reg .b32 t;\nlop3.b32 t, %1, %3, 1, 0xD8;\nmov.b64 %0, {t, %2};\n}\n" : "=l"(r) : "r"(lo), "r"(hi), "r"(tag));
    return r;
}
__device__ __forceinline__ void st_tagged(uint8_t* p, uint64_t x, uint64_t y) {
    asm volatile("st.relaxed.gpu.global.v2.b64 [%0], {%1, %2};" ::"l"(p), "l"(x), "l"(y) : "memory");
}
__device__ __forceinline__ void mma16816(float (&d)[4], const uint32_t (&a)[4], uint32_t b0, uint32_t b1) {
    asm volatile("mma.sync.aligned.m16n8k16.row.col.f32.bf16.bf16.f32 {%0,%1,%2,%3}, {%4,%5,%6,%7}, {%8,%9}, {%0,%1,%2,%3};"
                 : "+f"(d[0]), "+f"(d[1]), "+f"(d[2]), "+f"(d[3]) : "r"(a[0]), "r"(a[1]), "r"(a[2]), "r"(a[3]), "r"(b0), "r"(b1));
}
__device__ __forceinline__ uint32_t add2(uint32_t a, uint32_t b) {
    uint32_t r;
    asm("add.rn.bf16x2 %0, %1, %2;" : "=r"(r) : "r"(a), "r"(b));
    return r;
}
__device__ __forceinline__ uint32_t scale2(uint32_t x) {
    uint32_t r;
    asm("{\n.reg .b32 t;\nmul.rn.bf16x2 t, %1, %3;\nfma.rn.bf16x2 %0, %1, %2, t;\n}\n" : "=r"(r) : "r"(x), "r"(0x3E423E42u), "r"(0xB9F7B9F7u));
    return r;
}
__device__ __forceinline__ uint32_t max2(uint32_t a, uint32_t b) {
    uint32_t r;
    asm("max.bf16x2 %0, %1, %2;" : "=r"(r) : "r"(a), "r"(b));
    return r;
}
__device__ __forceinline__ void ld_tagged(const uint8_t* p, uint32_t& a, uint32_t& ta, uint32_t& b, uint32_t& tb) {
    asm volatile("{\n.reg .b64 x, y;\nld.relaxed.gpu.global.v2.b64 {x, y}, [%4];\nmov.b64 {%0, %1}, x;\nmov.b64 {%2, %3}, y;\n}\n"
                 : "=r"(a), "=r"(ta), "=r"(b), "=r"(tb) : "l"(p) : "memory");
}
__device__ __forceinline__ float bf_lo(uint32_t v) { return __uint_as_float(v << 16); }
__device__ __forceinline__ float bf_hi(uint32_t v) { return __uint_as_float(v & 0xFFFF0000u); }
__device__ __forceinline__ float rcp(float x) { float r; asm("rcp.approx.ftz.f32 %0, %1;" : "=f"(r) : "f"(x)); return r; }
__device__ __forceinline__ float ex2(float x) { float r; asm volatile("ex2.approx.ftz.f32 %0, %1;" : "=f"(r) : "f"(x)); return r; }

__device__ __forceinline__ uint32_t full_bar(int stage) { return base + BAR_FULL + (stage & 7) * 8; }
__device__ __forceinline__ void wait_released(int j) { mbar_wait(base + BAR_EMPTY + (j & 7) * 8, (j >> 3) & 1); }

template <int V>
struct Int { static constexpr int value = V; };

__host__ __device__ constexpr int bslot_e(int i) { return (i < 2 || i >= 14) ? (i + 5) % 7 : (i + 1) % 5; }
__host__ __device__ constexpr int bslot_l(int i) { return i % 6; }

template <uint32_t OFF>
struct Feed {
    int stage;
    uint32_t dst;
    __device__ __forceinline__ void seek(int i, int slot) { stage = i; dst = base + OFF + slot * SLOT; }
    template <int N>
    __device__ __forceinline__ uint32_t acquire() { wait_released(stage - N); return full_bar(stage); }
    template <int N>
    __device__ __forceinline__ void next() {
        stage++;
        dst += SLOT;
        if (dst == base + OFF + N * SLOT) dst = base + OFF;
    }
};
__device__ __forceinline__ int skip_own(int n, int mt) { return n == mt ? 15 : n; }

struct Desc { uint32_t lo, hi; };
__host__ __device__ constexpr Desc desc_const(uint32_t lbo, uint32_t sbo, uint32_t mode) { return {(lbo >> 4) << 16, (sbo >> 4) | (mode << 30)}; }
constexpr Desc D_K128 = desc_const(16, 1024, 1);
constexpr Desc D_N128 = desc_const(8192, 1024, 1);
constexpr Desc D_BLOB = desc_const(128, 256, 0);
constexpr Desc D_OT = desc_const(2048, 128, 0);

enum Kind { XW, XWN, QK, BIG, OUT };

struct Ring {
    int stage;
    uint32_t a, b;
    uint32_t wg;
    uint32_t zero;
    bool releaser;
    __device__ __forceinline__ void seek(int i, int bslot) {
        stage = i;
        a = (base + (i % NA) * SLOT) >> 4;
        b = (base + BRING + bslot * SLOT) >> 4;
    }
    __device__ __forceinline__ void wait() { mbar_wait(full_bar(stage), (stage >> 3) & 1); }
    __device__ __forceinline__ void take_turn() { nb_sync(1 + wg, 256); }
    __device__ __forceinline__ void pin() {
        uint32_t n = 0;
#pragma unroll 1
        do {
            asm volatile("pmevent 7;" ::: "memory");
        } while (n++ < zero);
    }
    __device__ __forceinline__ void mma_begin() {
        if (!wg) take_turn();
        pin();
    }
    __device__ __forceinline__ void mma_end() {
        pin();
        if (wg) nb_arrive(3, 256);
        nb_sync(3 - wg, 256);
    }
    template <Kind K, int NBS, bool INIT, int SB = 1, bool TAIL = false>
    __device__ __forceinline__ void run(float (&d)[56], float (&e)[56], bool first = true, bool last = true, bool more = true) {
        if (first) take_turn();
        asm volatile("wgmma.fence.sync.aligned;" ::: "memory");
        if (K == QK) {
            const uint32_t da = D_K128.lo + (base >> 4) + (stage >> 1) * (SLOT >> 4) + (stage & 1) * 4 + wg * 512, db = D_N128.lo + b;
            wgmma112<0, 1, 1, INIT, D_K128.hi, D_N128.hi>(d, da, db);
            wgmma112<0, 1, 1, INIT, D_K128.hi, D_N128.hi>(e, da, db + 256);
            wgmma112<0, 1, 1, false, D_K128.hi, D_N128.hi>(d, da + 2, db + 128);
            wgmma112<0, 1, 1, false, D_K128.hi, D_N128.hi>(e, da + 2, db + 384);
        } else {
            constexpr int TA = K == OUT, TB = K != XW;
            constexpr uint32_t sa = K == OUT ? 256 : 2, sb = K == XW ? 2 : K == BIG ? 224 : 128;
            constexpr Desc A = K == OUT ? D_OT : D_K128, B = K == XW ? D_K128 : K == BIG ? D_BLOB : D_N128;
            const uint32_t da = A.lo + a + wg * (K == OUT ? 64 : 512), db = B.lo + b;
            wgmma112<TA, TB, SB, INIT, A.hi, B.hi>(d, da, db);
#pragma unroll
            for (int q = 1; q < 4; q++) wgmma112<TA, TB, SB, false, A.hi, B.hi>(d, da + q * sa, db + q * sb);
        }
        asm volatile("wgmma.commit_group.sync.aligned;" ::: "memory");
        if (!TAIL) asm volatile("wgmma.wait_group.sync.aligned 1;" ::: "memory");
        if (last) nb_arrive(2 - wg, 256);
        if (!TAIL && stage > 0 && releaser) mbar_arrive(base + BAR_EMPTY + ((stage - 1) & 7) * 8);
        stage++;
        a += SLOT >> 4;
        if (a == (base + NA * SLOT) >> 4) a = base >> 4;
        b += SLOT >> 4;
        if (b == (base + BRING + NBS * SLOT) >> 4) b = (base + BRING) >> 4;
        if (more) wait();
    }
    template <Kind K, int NBS, bool INIT, int SB = 1, bool TAIL = false>
    __device__ __forceinline__ void run(float (&d)[56], bool first = true, bool last = true, bool more = true) {
        run<K, NBS, INIT, SB, TAIL>(d, d, first, last, more);
    }
};

template <int I0 = 0, int I1 = 28>
__device__ __forceinline__ void pack_all(const float (&d)[56], uint32_t (&p)[28]) {
#pragma unroll
    for (int i = I0; i < I1; i++) p[i] = pack2(d[2 * i], d[2 * i + 1]);
}
template <int I0, int I1>
__device__ __forceinline__ void store_frags(uint8_t* dst, const uint32_t (&p)[28]) {
#pragma unroll
    for (int i = I0; i < I1; i++) stg1(dst + i * 128, p[i]);
}
template <int I0, int I1>
__device__ __forceinline__ void stage_frags(uint32_t lane_addr, const uint32_t (&p)[28]) {
#pragma unroll
    for (int i = I0; i < I1; i += 4) stsm4(lane_addr + i * 128, p[i], p[i + 1], p[i + 2], p[i + 3]);
}
template <class F>
__device__ __forceinline__ void store_out(F frag, int lane, uint32_t slab, const CUtensorMap* m, int c0, int c1) {
    const bool swap = lane & 16;
    const uint32_t addr = slab + (lane & 7) * 224 + ((lane >> 3) ^ ((lane >> 2) & 1)) * 16;
#pragma unroll
    for (int h = 0; h < 2; h++) {
#pragma unroll
        for (int c = 0; c < 14; c += 4) {
            const uint32_t t0 = frag(2 * c + h), t1 = frag(2 * c + 2 + h);
            if (c < 12) {
                const uint32_t t2 = frag(2 * c + 4 + h), t3 = frag(2 * c + 6 + h);
                stsm4(addr + h * 1792 + c * 16, swap ? t1 : t0, swap ? t0 : t1, swap ? t3 : t2, swap ? t2 : t3);
            } else {
                asm volatile("stmatrix.sync.aligned.m8n8.x2.shared.b16 [%0], {%1,%2};" ::"r"(addr + h * 1792 + c * 16), "r"(swap ? t1 : t0), "r"(swap ? t0 : t1) : "memory");
            }
        }
        fence_async_smem();
        __syncwarp();
        if (elect()) tma_st2(m, c0, c1 + 8 * h, slab + h * 1792);
    }
    if (elect()) {
        bulk_commit();
        bulk_wait_read();
    }
}
__host__ __device__ constexpr int tile_of(int t) { return 7 * (t >> 2) + 3 * ((t >> 1) & 1) + 2 * (t & 1); }

struct Role {
    bool H;
    int L, mt, ns, id;
    int kind, a0, a1, b3;
};
template <bool BY_SM>
__device__ __forceinline__ Role decode_role() {
    uint32_t sm;
    if (BY_SM) asm volatile("mov.u32 %0, %%smid;" : "=r"(sm));
    else asm volatile("mov.u32 %0, %%ctaid.x;" : "=r"(sm));
    const int tpc = sm >> 1, q2 = ((tpc - 32) * 37) >> 8;
    const int gpc = tpc < 32 ? tpc & 7 : tpc < 60 ? tpc - 31 - 7 * q2 : 0;
    const int pos = tpc < 32 ? tpc >> 3 : tpc < 60 ? q2 + 4 : tpc - 56;
    Role r;
    r.H = sm >= 128;
    const int grp = (GPC_MAP >> (4 * gpc)) & 7;
    r.L = grp & 1;
    r.mt = (grp >> 1) * 4 + (pos >> 1);
    r.ns = (pos & 1) * 2 + (sm & 1);
    r.id = r.H ? sm : grp * 16 + pos * 2 + (sm & 1);
    r.kind = r.H ? 2 : r.L;
    r.a0 = r.L ? (r.mt >> 3) * 448 : 0;
    r.a1 = r.L ? (r.mt & 7) * 128 : r.H ? 120 : r.mt * 64;
    r.b3 = r.H ? 4 + r.ns : r.L ? r.ns : 0;
    return r;
}

__device__ __forceinline__ void first_fill(const Maps& maps, const Role& r, int i) {
    const bool E = r.kind == 0;
    const CUtensorMap* ma = &maps.m[r.kind];
    const uint32_t bar = full_bar(i);
    const int k = (i * 64) >> r.L;
    const bool has_a = !(i & r.L), has_b = i < 7 - r.L;
    const uint32_t dst = base + BRING + (E ? (0x2104365u >> (4 * i)) & 7 : i) * SLOT;
    mbar_expect(bar, (has_a ? SLOT : 0) + (has_b ? (E ? BLOB : SLOT) : 0));
    if (has_a) tma_ld4(base + (i >> r.L) * SLOT, ma, r.a0 + k, r.a1, 0, 0, bar);
    if (has_b) {
        tma_ld4(dst, ma + 3, E ? k : 0, E ? r.ns * 112 : k, 0, r.b3, bar);
        if (!E) tma_ld4(dst + 8192, ma + 3, 64, k, 0, r.b3, bar);
        mbar_arrive(bar);
    }
}
static_assert(bslot_e(0) == 5 && bslot_e(1) == 6 && bslot_e(2) == 3 && bslot_e(3) == 4 && bslot_e(4) == 0 && bslot_e(6) == 2, "");

template <bool BY_SM>
__global__ void __launch_bounds__(384, 1) fused_kernel(Scratch* sc, const __grid_constant__ Maps maps) {
    const unsigned t_open = clk32();
    const int warp = __shfl_sync(0xffffffffu, threadIdx.x >> 5, 0);
    if (warp == 8) {
        if (elect()) {
#pragma unroll
            for (int i = 0; i < LEAD; i++) mbar_init(base + BAR_FULL + i * 8, 2);
            asm volatile("fence.mbarrier_init.release.cluster;" ::: "memory");
            const Role r = decode_role<BY_SM>();
#pragma unroll 1
            for (int i = 0; i < LEAD; i++) first_fill(maps, r, i);
        }
    }
    if (warp == 9) {
        if (elect()) {
#pragma unroll
            for (int i = 0; i < 8; i++) mbar_init(base + BAR_EMPTY + i * 8, 4);
            asm volatile("fence.mbarrier_init.release.cluster;" ::: "memory");
        }
    } else if (warp == 10) {
        if (elect()) {
#pragma unroll
            for (int i = 0; i < 3; i++) mbar_init(base + BAR_RDY + i * 8, i < 2 ? 4 : 8);
#pragma unroll
            for (int i = 0; i < 2; i++) mbar_init(base + BAR_HALO + i * 8, 1);
            asm volatile("fence.mbarrier_init.release.cluster;" ::: "memory");
        }
    } else if (warp == 11) {
        if (elect()) {
#pragma unroll
            for (int i = LEAD; i < 8; i++) mbar_init(base + BAR_FULL + i * 8, 2);
#pragma unroll
            for (int i = 0; i < 3; i++) mbar_init(base + BAR_DEP + i * 8, 1);
#pragma unroll
            for (int i = 0; i < 4; i++) mbar_init(base + BAR_PART + i * 8, 1);
            asm volatile("fence.mbarrier_init.release.cluster;" ::: "memory");
        }
    }
    __syncthreads();

    const Role role = decode_role<BY_SM>();
    int lane = threadIdx.x & 31;
    asm volatile("" : "+r"(lane));
    const bool roleH = role.H;
    const int roleL = role.L, mt = role.mt, ns = role.ns, bid = role.id;
    const int par = mt >> 3, blk = mt & 7, col = ns * 112;

    if (warp >= 8) {
        asm volatile("setmaxnreg.dec.sync.aligned.u32 56;");
#define PROF_FEED_A
#define PROF_FEED_B
        if (warp == 8) {
            if (elect()) {
                PROF(129);
#pragma unroll 1
                for (int i = LEAD; i < 7; i++) {
                    while (clk32() - t_open < i * PACE) {}
                    first_fill(maps, role, i);
                }
                PROF(134);
                Feed<0> f;
                const int row = mt * 128;
                auto c_run = [&](const CUtensorMap* m, int off, int n0, int n1) {
#pragma unroll 1
                    for (int n = n0; n < n1; n++) {
                        const uint32_t bar = f.acquire<NA>();
                        mbar_expect(bar, SLOT);
                        tma_ld2(f.dst, m, (off + skip_own(n, mt)) * 64, row, bar);
                        PROF_FEED_A;
                        f.next<NA>();
                    }
                };
                if (roleH) {
                    mbar_expect(base + BAR_DEP, 7 * SLOT);
#pragma unroll 1
                    for (int i = 0; i < 7; i++) {
                        const uint32_t dst = base + (i < 6 ? i : 7) * SLOT;
                        if (i < 6) wait_released(7 + i);
                        tma_ld4(dst, &maps.m[M_WO], 0, i * 64, 0, ns, base + BAR_DEP);
                        tma_ld4(dst + 8192, &maps.m[M_WO], 64, i * 64, 0, ns, base + BAR_DEP);
                    }
                    mbar_wait(base + BAR_DEP, 0);
                    mbar_wait(base + BAR_RDY + 16, 0);
#pragma unroll 1
                    for (int i = 0; i < 7; i++) bulk_st(sc->wo + (size_t)(ns * 7 + i) * SLOT, base + (i < 6 ? i : 7) * SLOT, SLOT);
                    bulk_commit();
                    asm volatile("cp.async.bulk.wait_group 0;" ::: "memory");
                    signal(sc, CNT_W + ns);
                } else if (!roleL) {
                    f.seek(14, 0);
#pragma unroll 1
                    for (int i = 0; i < 4; i++) {
                        const uint32_t bar = f.acquire<NA>();
                        mbar_expect(bar, SLOT);
                        tma_ld2(f.dst, &maps.m[M_CR + (i >> 1)], ((i & 1) * 16 + mt) * 64, row, bar);
                        mbar_arrive(bar);
                        PROF_FEED_A;
                        f.next<NA>();
                    }
                    c_run(&maps.m[M_CR], 0, 0, 15);
                    c_run(&maps.m[M_CI], 0, 0, NBE);
                    wait_dep(2);
#pragma unroll 1
                    for (int i = 0; i < 7; i++) {
                        const uint32_t bar = f.acquire<NA>();
                        mbar_expect(bar, SLOT);
                        bulk_ld(f.dst, sc->o + (size_t)(mt * 7 + i) * SLOT, SLOT, bar);
                        PROF_FEED_A;
                        f.next<NA>();
                    }
                } else {
#pragma unroll 1
                    for (int i = 4; i < 7; i++) {
                        wait_released(2 * i - 8);
                        mbar_expect(full_bar(2 * i), SLOT);
                        tma_ld4(base + i * SLOT, &maps.m[M_XA], par * 448 + i * 64, blk * 128, 0, 0, full_bar(2 * i));
                    }
                    wait_released(HALO_K_AT);
                    mbar_arrive(base + BAR_DEP + 16);
                    f.seek(21, 0);
                    c_run(&maps.m[M_CR], 16, 0, 15);
                    c_run(&maps.m[M_CI], 16, 0, 15);
                    c_run(&maps.m[M_CI], 0, NBE, 15);
                }
            }
        } else if (warp == 11) {
            if (elect()) {
                Feed<BRING> f;
                auto blob_run = [&](auto nbs, int quarter, int n0, int n1) {
                    constexpr int N = decltype(nbs)::value;
                    const uint8_t* src = sc->ab + (size_t)(quarter * 64 + ns) * BLOB;
#pragma unroll 1
                    for (int n = n0; n < n1; n++) {
                        const uint32_t bar = f.template acquire<N>();
                        mbar_expect(bar, BLOB);
                        bulk_ld(f.dst, src + skip_own(n, mt) * (4 * BLOB), BLOB, bar);
                        PROF_FEED_B;
                        f.template next<N>();
                    }
                };
                auto v_run = [&](auto nbs) {
                    constexpr int N = decltype(nbs)::value;
#pragma unroll 1
                    for (int i = 0; i < 7; i++) {
                        const uint32_t bar = f.template acquire<N>();
                        mbar_expect(bar, SLOT);
                        tma_ld4(f.dst, &maps.m[M_WV], 0, i * 64, 0, 8 + ns, bar);
                        tma_ld4(f.dst + 8192, &maps.m[M_WV], 64, i * 64, 0, 8 + ns, bar);
                        mbar_arrive(bar);
                        PROF_FEED_B;
                        f.template next<N>();
                    }
                };
                if (roleH) {
                    f.seek(7, 0);
                    v_run(Int<7>());
                } else if (!roleL) {
                    f.seek(7, bslot_e(7));
#pragma unroll 1
                    for (int i = 0; i < 7; i++) {
                        const uint32_t bar = f.acquire<5>();
                        mbar_expect(bar, BLOB);
                        tma_ld2(f.dst, &maps.m[M_WI], i * 64, col, bar);
                        mbar_arrive(bar);
                        PROF_FEED_B;
                        f.next<5>();
                    }
                    f.seek(18, bslot_e(18));
                    wait_dep(0);
                    blob_run(Int<7>(), 0, 0, 15);
                    wait_dep(1);
                    blob_run(Int<7>(), 2, 0, NBE);
                    mbar_wait(base + BAR_HINT, 0);
                    fence_async_global();
#pragma unroll 1
                    for (int i = 0; i < 7; i++) {
                        const uint32_t bar = f.acquire<7>();
                        mbar_expect(bar, SLOT);
                        bulk_ld(f.dst, sc->wo + (size_t)(ns * 7 + i) * SLOT, SLOT, bar);
                        PROF_FEED_B;
                        f.next<7>();
                    }

                } else {
                    f.seek(6, 0);
#pragma unroll 1
                    for (int i = 6; i < 14; i++) {
                        const uint32_t bar = f.acquire<6>();
                        mbar_expect(bar, SLOT);
                        tma_ld4(f.dst, &maps.m[M_WQK], 0, i * 32, 0, ns, bar);
                        tma_ld4(f.dst + 8192, &maps.m[M_WQK], 64, i * 32, 0, ns, bar);
                        if (i & 1) mbar_arrive(bar);
                        PROF_FEED_B;
                        f.next<6>();
                    }
                    v_run(Int<6>());
                    wait_dep(0);
                    blob_run(Int<6>(), 1, 0, 15);
                    wait_dep(1);
                    blob_run(Int<6>(), 3, 0, 15);
                    blob_run(Int<6>(), 2, NBE, 15);
                    fence_async_smem();
#pragma unroll 1
                    for (int h = 0; h < 2; h++) {
                        mbar_wait(base + BAR_HINT + h * 8, 0);
                        PROF(153 + h);
                        mbar_expect(base + BAR_PART + h * 8, BLOB);
                        bulk_ld(base + (h ? HALO : LSLAB), sc->part + (size_t)((ns * 16 + mt) * 2 + h) * BLOB, BLOB, base + BAR_PART + h * 8);
                    }
                }
            }
        } else if (roleH) {
            if (warp == 9 && elect()) {
                wait_released(0);
#pragma unroll 1
                for (int i = 0; i < 7; i++)
                    asm volatile("cp.async.bulk.prefetch.tensor.2d.L2.global [%0, {%1, %2}];" ::"l"(&maps.m[M_WI]), "r"(i * 64), "r"(col) : "memory");
            }
        } else if (warp == 10) {
            if (elect()) {
                unsigned* epoch_ptr = &sc->epoch[(bid * 4 + 2) * 8];
                const unsigned ep = *epoch_ptr + 1;
                sts1(base + TAG, ep);
                asm volatile("prefetch.tensormap [%0];" ::"l"(&maps.m[M_OUTA + roleL]) : "memory");
                await(sc, CNT_A + roleL * 4 + ns, ep * 16);
                mbar_arrive(base + BAR_DEP);
                PROF(150);
                await(sc, CNT_B + ns, ep * 16);
                mbar_arrive(base + BAR_DEP + 8);
                PROF(151);
                if (!roleL) {
                    await(sc, CNT_W + ns, ep);
                    mbar_arrive(base + BAR_HINT);
                    PROF(153);
                    await(sc, CNT_O + mt, ep * 4);
                    mbar_arrive(base + BAR_DEP + 16);
                } else {
                    await(sc, CNT_P + mt * 4 + ns, ep * 2 - 1);
                    mbar_arrive(base + BAR_HINT);
                    await(sc, CNT_P + mt * 4 + ns, ep * 2);
                    mbar_arrive(base + BAR_HINT + 8);
                }
                PROF(152);
                *epoch_ptr = ep;
            }
        } else if (!roleL) {
            if (elect()) {
                mbar_wait(base + BAR_RDY, 0);
                PROF(130);
                signal(sc, CNT_A + ns);
                PROF(131);
                mbar_wait(base + BAR_RDY + 8, 0);
                signal(sc, CNT_A + 4 + ns);
                PROF(135);
                mbar_wait(base + BAR_RDY + 16, 0);
                PROF(132);
                signal(sc, CNT_B + ns);
                PROF(133);
            }
        } else {
            unsigned* epoch_ptr = &sc->epoch[(bid * 4 + 1) * 8];
            const unsigned tag = *epoch_ptr + 1;
#pragma unroll 1
            for (int kv = 0; kv < 2; kv++) {
                uint32_t v[16];
#pragma unroll
                for (int i = 0; i < 16; i++) v[i] = 0;
                if (kv) wait_released(HALO_V_AT - 4), wait_released(HALO_V_AT);
                else mbar_wait(base + BAR_DEP + 16, 0);
                if (blk > 0) {
                    const uint8_t* src = sc->halo + (size_t)(((mt - 1) * 4 + ns) * 2 + kv) * 2048 + lane * 16;
#pragma unroll 1
                    for (int n = 0; n < SPIN_LIMIT; n++) {
#pragma unroll
                        for (int i = 0; i < 4; i++) ld_tagged(src + i * 512, v[4 * i], v[4 * i + 1], v[4 * i + 2], v[4 * i + 3]);
#pragma unroll
                        for (int i = 0; i < 16; i += 2) v[i] ^= tag & 1;
                        const uint32_t stale = or3(or3(v[0], v[2], v[4]), or3(v[6], v[8], v[10]), or3(v[12], v[14], 0));
                        if (__all_sync(0xffffffffu, !(stale & 1))) break;
                    }
#pragma unroll
                    for (int c = 0; c < 14; c += 2) v[c] |= (v[15] >> c) & 1;
                }
#pragma unroll
                for (int i = 0; i < 14; i++) sts1(base + HALO + kv * (8 * HSLOT) + i * 128 + lane * 4, v[i]);
                warp_arrive(base + BAR_HALO + kv * 8);
                if (lane == 0) PROF(142 + kv);
            }
            if (elect()) {
                mbar_wait(base + BAR_RDY + 16, 0);
                PROF(130);
                signal(sc, CNT_O + mt);
                PROF(131);
                *epoch_ptr = tag;
            }
        }
    } else {
        asm volatile("setmaxnreg.inc.sync.aligned.u32 224;");
        Ring r;
        r.wg = warp >> 2;
        r.zero = blockIdx.y;
        r.releaser = lane + 1 == (warp >> 2);
        const int wg = warp >> 2;
        if (wg) nb_arrive(1, 256);
        uint8_t* part = sc->part + (size_t)(ns * 16 + mt) * (2 * BLOB) + warp * WSLOT + lane * 16;
        uint32_t p[28];

        if (roleH) {
            unsigned* epoch_ptr = &sc->epoch[bid * 4 * 8];
            const unsigned tag = *epoch_ptr + 1;
            uint8_t* hout = sc->halo + (size_t)((warp * 8 + ns) * 2) * 2048 + lane * 16;
            auto send = [&](int kv) {
#pragma unroll
                for (int h = 0; h < 2; h++) {
                    uint32_t v[16];
                    v[14] = v[15] = 0;
#pragma unroll
                    for (int c = 0; c < 14; c++) v[c] = p[2 * c + h];
#pragma unroll
                    for (int c = 0; c < 14; c += 2) v[15] |= (v[c] & 1) << c;
#pragma unroll
                    for (int i = 0; i < 4; i++)
                        st_tagged(hout + (h * 8 + kv) * 2048 + i * 512, tagged(v[4 * i], v[4 * i + 1], tag), tagged(v[4 * i + 2], v[4 * i + 3], tag));
                }
            };
            float x0[56], x1[56];
            r.seek(0, 0);
            r.wait();
            r.run<XWN, 7, true>(x0);
#pragma unroll 1
            for (int i = 1; i < 7; i++) r.run<XWN, 7, false>(x0);
            r.run<XWN, 7, true>(x1);
            acc_fence(x0);
            pack_all(x0, p);
            send(0);
#pragma unroll 1
            for (int i = 1; i < 7; i++) r.run<XWN, 7, false>(x1, true, i < 6 || !wg, i < 6);
            asm volatile("wgmma.wait_group.sync.aligned 0;" ::: "memory");
            acc_fence(x1);
            pack_all(x1, p);
#pragma unroll
            for (int i = 0; i < 28; i++) p[i] = movm(p[i]);
            send(1);
            warp_arrive(base + BAR_RDY + 16);
            if (threadIdx.x == 0) *epoch_ptr = tag;
        } else if (!roleL) {
            uint8_t* blob = sc->ab + (size_t)((wg * 16 + mt) * 4 + ns) * BLOB + (warp & 3) * WSLOT + lane * 4;
            const uint32_t own = base + BRING + wg * SLOT + (warp & 3) * WSLOT + lane * 16;
            float x0[56], x1[56];
            r.seek(0, bslot_e(0));
            r.wait();
            r.run<XW, 7, true>(x0);
            r.run<XW, 7, false>(x0);
            r.seek(2, bslot_e(2));
#pragma unroll 1
            for (int i = 2; i < 7; i++) r.run<XW, 5, false>(x0);

            r.seek(7, bslot_e(7));
            r.run<XW, 5, true, -1>(x1);
            acc_fence(x0);
            pack_all<0, 14>(x0, p);
#pragma unroll
            for (int i = 0; i < 2; i++) {
                if (wg == i) store_frags<0, 14>(blob, p);
                else stage_frags<0, 4>(own + 5 * SLOT, p);
                r.run<XW, 5, false, -1>(x1);
                if (i == 0) pack_all<14, 28>(x0, p);
                if (wg == i) {
                    store_frags<14, 28>(blob, p);
                    warp_arrive(base + BAR_RDY + i * 8);
                } else {
                    stage_frags<4, 8>(own + 5 * SLOT, p);
                }
                r.run<XW, 5, false, -1>(x1);
            }
            stage_frags<8, 16>(own + 5 * SLOT, p);
            r.run<XW, 5, false, -1>(x1);
            stage_frags<16, 24>(own + 5 * SLOT, p);
            r.run<XW, 5, false, -1>(x1);
            stage_frags<24, 28>(own + 5 * SLOT, p);

            r.seek(14, bslot_e(14));
            r.take_turn();
            fence_async_smem();
            r.run<BIG, 7, true>(x0, false);
            acc_fence(x1);
            pack_all(x1, p);
            stage_frags<0, 16>(own, p);
            r.run<BIG, 7, false>(x0);
            stage_frags<16, 28>(own, p);
            r.take_turn();
            fence_async_smem();
            blob += (size_t)128 * BLOB;
            r.run<BIG, 7, false>(x0, false);
            r.run<BIG, 7, false>(x0);
#pragma unroll
            for (int i = 0; i < 28; i++) {
                if (i % B_SLICE == 0) r.run<BIG, 7, false>(x0);
                stg1(blob + i * 128, p[i]);
            }
            warp_arrive(base + BAR_RDY + 16);
#pragma unroll 1
            for (int i = 19 + 27 / B_SLICE; i < POUT; i++) r.run<BIG, 7, false>(x0);

            const uint32_t tag = lds1(base + TAG);
            r.seek(POUT, bslot_e(POUT));
            r.run<OUT, 7, true>(x1);
            acc_fence(x0);
            pack_all(x0, p);
            uint64_t u[14];
#pragma unroll
            for (int i = 0; i < 14; i++) u[i] = tagged(p[2 * i], p[2 * i + 1], tag);
#pragma unroll
            for (int k = 0; k < 2; k++) {
                if (wg == k) {
#pragma unroll
                    for (int i = 0; i < 7; i++) st_tagged(part + i * 512, u[2 * i], u[2 * i + 1]);
                }
                r.run<OUT, 7, false>(x1);
                if (warp * 32 + lane == k * 128)
                    asm volatile("red.relaxed.gpu.global.add.u32 [%0], 1;" ::"l"(&sc->cnt[(CNT_P + mt * 4 + ns) * 32]) : "memory");
            }
#pragma unroll
            for (int i = 3; i < 7; i++) r.run<OUT, 7, false, 1, true>(x1, i <= 7 - TURN, i < 7 - TURN || (i == 6 && !wg), i < 6);

            asm volatile("wgmma.wait_group.sync.aligned 0;" ::: "memory");
            acc_fence(x1);
            const uint32_t slab = base + (wg ? BRING + bslot_e(ELAST - 6) * SLOT : ((ELAST - 6) % NA) * SLOT) + (warp & 3) * WSLOT;
            store_out([&](int i) { return pack2(x1[2 * i], x1[2 * i + 1]); }, lane, slab, &maps.m[M_OUTA], par * 896 + col, blk * 128 + warp * 16);
        } else {
            const int g = lane >> 2, tig = lane & 3;
            const uint32_t hin = base + HALO + warp * HSLOT + lane * 4;
            const uint32_t hpub = warp < 7 ? hin + HSLOT : base + HSPARE + lane * 4;
            auto publish = [&](const uint32_t (&h)[14], int c0, int c1) {
#pragma unroll
                for (int c = 0; c < 14; c++)
                    if (c >= c0 && c < c1) sts1(hpub + c * 128, h[c]);
            };
            float y0[56], y1[56], y2[56];
            r.seek(0, 0);
            r.wait();
            r.run<QK, 6, true>(y0, y1);
#pragma unroll 1
            for (int i = 1; i < 14; i++) r.run<QK, 6, false>(y0, y1);

            uint32_t m1[8][4], m0[8][4], lo[14], hi[14], q[2][8][2];
            auto pack_q = [&](int b) {
                uint32_t v[14];
#pragma unroll
                for (int c = 0; c < 14; c++) v[c] = pack2(y0[4 * c + 2 * b], y0[4 * c + 2 * b + 1]);
#pragma unroll
                for (int t = 0; t < 8; t++) {
                    const int c = tile_of(t);
                    q[b][t][0] = (t & 3) == 2 ? (tig >= 2 ? v[c] : 0u) : v[c];
                    q[b][t][1] = (t & 3) == 1 ? (tig < 2 ? v[c + 1] : 0u) : v[c + 1];
                }
            };
            auto fetch = [&](uint32_t src, int hp, int i0) {
#pragma unroll
                for (int t = 4 * hp; t < 4 * hp + 4; t++) {
                    m0[t][i0] = (t & 3) == 2 ? dup(m0[t - 1][3], r.zero) : lds1(src + tile_of(t) * 128);
                    m0[t][3] = lds1(src + tile_of(t) * 128 + 128);
                }
            };
            r.seek(14, bslot_l(14));
            r.run<XWN, 6, true>(y2);
            acc_fence(y0);
            acc_fence(y1);
#pragma unroll
            for (int c = 0; c < 14; c++) hi[c] = pack2(y1[4 * c + 2], y1[4 * c + 3]);
            publish(hi, 0, 7);
            r.run<XWN, 6, false>(y2);
            publish(hi, 7, 14);
#pragma unroll
            for (int c = 0; c < 14; c++) lo[c] = pack2(y1[4 * c], y1[4 * c + 1]);
#pragma unroll
            for (int t = 0; t < 8; t++) {
                const int c = tile_of(t);
                const bool shared = (t & 3) == 2;
                m1[t][0] = shared ? dup(lo[c], r.zero) : lo[c];
                m1[t][1] = shared ? dup(hi[c], r.zero) : hi[c];
                m1[t][2] = lo[c + 1];
                m1[t][3] = hi[c + 1];
                m0[t][0] = dup(m1[t][0], r.zero);
                m0[t][2] = dup(lo[c + 1], 2 * r.zero);
            }
            r.run<XWN, 6, false>(y2);
            if (warp == 0) mbar_wait(base + BAR_HALO, 0);
            fetch(hin, 0, 1);
            pack_q(1);
            r.run<XWN, 6, false>(y2);
            fetch(hin, 1, 1);
            pack_q(0);
            r.mma_begin();
            float s[8][4];
#pragma unroll
            for (int step = 0; step < 2; step++) {
#pragma unroll
                for (int i = 0; i < 8; i++) {
                    const int b = 1 - (i >> 2), h = i & 3, t = 2 * h + step;
                    float (&d)[4] = s[2 * h + b];
                    if (step == 0) d[0] = d[1] = d[2] = d[3] = 0.f;
                    mma16816(d, b ? m1[t] : m0[t], q[b][t][0], q[b][t][1]);
                }
            }
            r.mma_end();
            r.run<XWN, 6, false>(y2, false);

            uint32_t pr[8], mx[4], mx1[4];
            {
                const bool cur0 = g <= 2 * tig, cur1 = g <= 2 * tig + 1;
#pragma unroll
                for (int i = 0; i < 8; i++) {
                    const int c = (i & 1) ? 2 : 0;
                    pr[i] = movm(pack2(cur0 ? s[i][c] : s[i][2 - c], cur1 ? s[i][c + 1] : s[i][3 - c]));
                }
            }
            r.run<XWN, 6, false>(y2);
            const uint32_t curmask = (2 * tig <= g ? 0x0000FFFFu : 0u) | (2 * tig + 1 <= g ? 0xFFFF0000u : 0u);
            {
                const uint32_t keep = (blk == 0 && warp == 0) ? curmask : 0xFFFFFFFFu;
#pragma unroll
                for (int i = 0; i < 4; i++) {
                    pr[2 * i] = (scale2(pr[2 * i]) & keep) | (0xCE6ECE6Eu & ~keep);
                    pr[2 * i + 1] = scale2(pr[2 * i + 1]);
                    mx[i] = max2(__byte_perm(pr[2 * i], pr[2 * i + 1], 0x5410), __byte_perm(pr[2 * i], pr[2 * i + 1], 0x7632));
                    mx1[i] = __shfl_xor_sync(0xffffffffu, mx[i], 1);
                }
            }
#pragma unroll
            for (int i = 0; i < 4; i++) {
                mx[i] = max2(mx[i], mx1[i]);
                mx1[i] = __shfl_xor_sync(0xffffffffu, mx[i], 2);
            }
            r.run<XWN, 6, false>(y2);
            constexpr float SCL = 1.4426950408889634f;
            float e0[8], e1[8], sm[8], sm1[8];
#pragma unroll
            for (int i = 0; i < 8; i++) {
                const uint32_t m2 = max2(mx[i >> 1], mx1[i >> 1]);
                sm[i] = ((i & 1) ? bf_hi(m2) : bf_lo(m2)) * -SCL;
                e0[i] = ex2(fmaf(bf_lo(pr[i]), SCL, sm[i]));
            }

            r.seek(21, bslot_l(21));
            r.run<BIG, 6, true>(y0);
            acc_fence(y2);
#pragma unroll
            for (int c = 0; c < 7; c++) hi[c] = movm(pack2(y2[4 * c + 2], y2[4 * c + 3]));
#pragma unroll
            for (int i = 0; i < 8; i++) e1[i] = ex2(fmaf(bf_hi(pr[i]), SCL, sm[i]));
            r.run<BIG, 6, false>(y0);
            publish(hi, 0, 7);
#pragma unroll
            for (int c = 7; c < 14; c++) hi[c] = movm(pack2(y2[4 * c + 2], y2[4 * c + 3]));
            r.run<BIG, 6, false>(y0);
            publish(hi, 7, 14);
#pragma unroll
            for (int i = 0; i < 8; i++) {
                sm[i] = e0[i] + e1[i];
                sm1[i] = __shfl_xor_sync(0xffffffffu, sm[i], 1);
            }
            r.run<BIG, 6, false>(y0);
#pragma unroll
            for (int c = 0; c < 14; c++) lo[c] = movm(pack2(y2[4 * c], y2[4 * c + 1]));
            r.run<BIG, 6, false>(y0);
#pragma unroll
            for (int i = 0; i < 8; i++) {
                sm[i] += sm1[i];
                sm1[i] = __shfl_xor_sync(0xffffffffu, sm[i], 2);
            }
#pragma unroll
            for (int t = 0; t < 8; t++) {
                const int c = tile_of(t);
                const bool shared = (t & 3) == 2;
                m1[t][0] = shared ? dup(lo[c], r.zero) : lo[c];
                m1[t][1] = lo[c + 1];
                m1[t][2] = shared ? dup(hi[c], r.zero) : hi[c];
                m1[t][3] = hi[c + 1];
                m0[t][0] = dup(m1[t][0], r.zero);
                m0[t][1] = dup(lo[c + 1], 2 * r.zero);
            }
            r.run<BIG, 6, false>(y0);
            if (warp == 0) mbar_wait(base + BAR_HALO + 8, 0);
            const uint32_t vin = warp ? hin : hin + 8 * HSLOT;
            fetch(vin, 0, 2);
#pragma unroll
            for (int i = 0; i < 8; i++) {
                const float inv = rcp(sm[i] + sm1[i]);
                pr[i] = pack2(e0[i] * inv, e1[i] * inv);
            }
            r.run<BIG, 6, false>(y0);
            fetch(vin, 1, 2);
            uint32_t pb[8][2];
#pragma unroll
            for (int t = 0; t < 8; t++) {
                pb[t][t & 1] = band(pr[t], curmask);
                pb[t][1 - (t & 1)] = band(pr[t], ~curmask);
            }
            r.mma_begin();
            float o[2][8][4];
#pragma unroll
            for (int i = 0; i < 16; i++) {
                const int b = 1 - (i >> 3), t = i & 7;
                float (&d)[4] = o[b][t];
                d[0] = d[1] = d[2] = d[3] = 0.f;
                mma16816(d, b ? m1[t] : m0[t], pb[(t & 6) + b][0], pb[(t & 6) + b][1]);
            }
            r.mma_end();
            r.run<BIG, 6, false>(y0, false);
            uint8_t* odst = sc->o + (size_t)mt * 7 * SLOT + ns * (14 * 2048) + warp * 256 + lane * 4;
#pragma unroll
            for (int hp = 0; hp < 2; hp++) {
#pragma unroll
                for (int b = 0; b < 2; b++) {
                    const float (&u)[8][4] = o[b];
                    const int t = 4 * hp;
                    uint32_t* w = p + 14 * hp + b;
                    w[0] = pack2(u[t][0], u[t][1]);
                    w[2] = pack2(u[t][2], u[t][3]);
                    w[4] = pack2(u[t + 1][0], u[t + 1][1]);
                    w[6] = pack2(g < 4 ? u[t + 1][2] : u[t + 2][0], g < 4 ? u[t + 1][3] : u[t + 2][1]);
                    w[8] = pack2(u[t + 2][2], u[t + 2][3]);
                    w[10] = pack2(u[t + 3][0], u[t + 3][1]);
                    w[12] = pack2(u[t + 3][2], u[t + 3][3]);
                }
            }
#pragma unroll
            for (int i = 0; i < 28; i++) {
                if (i >= O_FIRST && (i - O_FIRST) % O_SLICE == 0) r.run<BIG, 6, false>(y0);
                stg1(odst + (i >> 1) * 2048 + (i & 1) * 128, p[i]);
            }
            warp_arrive(base + BAR_RDY + 16);

#pragma unroll 1
            for (int i = 30 + (27 - O_FIRST) / O_SLICE; i <= LLAST - LTURN; i++) r.run<BIG, 6, false>(y0);
            r.seek(LLAST + 1 - LTURN, bslot_l(LLAST + 1 - LTURN));
#pragma unroll
            for (int i = 0; i < LTURN; i++) r.run<BIG, 6, false, 1, true>(y0, i == 0, i == LTURN - 1 && !wg, i < LTURN - 1);
            const uint32_t parity = lds1(base + TAG) & 1;
            const uint32_t slab = base + (wg ? HALO : LSLAB) + (warp & 3) * WSLOT;
            mbar_wait(base + BAR_PART + wg * 8, 0);
#pragma unroll 1
            for (int n = 0; n < SPIN_LIMIT; n++) {
#pragma unroll
                for (int i = 0; i < 7; i++) lds4(slab + i * 512 + lane * 16, p + 4 * i);
#pragma unroll
                for (int i = 0; i < 28; i += 2) p[i] ^= parity;
                const uint32_t stale = or3(or3(or3(p[0], p[2], p[4]), or3(p[6], p[8], p[10]), or3(p[12], p[14], p[16])),
                                           or3(p[18], p[20], p[22]), or3(p[24], p[26], 0));
                if (__all_sync(0xffffffffu, !(stale & 1))) break;
#pragma unroll
                for (int i = 0; i < 7; i++) ld_tagged(part + i * 512, p[4 * i], p[4 * i + 1], p[4 * i + 2], p[4 * i + 3]);
#pragma unroll
                for (int i = 0; i < 7; i++)
                    asm volatile("st.shared.v4.b32 [%0], {%1,%2,%3,%4};" ::"r"(slab + i * 512 + lane * 16), "r"(p[4 * i]), "r"(p[4 * i + 1]), "r"(p[4 * i + 2]), "r"(p[4 * i + 3]) : "memory");
            }
            asm volatile("wgmma.wait_group.sync.aligned 0;" ::: "memory");
            acc_fence(y0);
            store_out([&](int i) { return add2(pack2(y0[2 * i], y0[2 * i + 1]), p[i]); }, lane, slab, &maps.m[M_OUTB], 448 + col, mt * 128 + warp * 16);
        }
    }
}

typedef CUresult (*EncodeFn)(CUtensorMap*, CUtensorMapDataType, cuuint32_t, void*, const cuuint64_t*, const cuuint64_t*,
                             const cuuint32_t*, const cuuint32_t*, CUtensorMapInterleave, CUtensorMapSwizzle,
                             CUtensorMapL2promotion, CUtensorMapFloatOOBfill);

struct Dim { uint64_t size, stride; uint32_t box; };
void encode(EncodeFn fn, CUtensorMap* m, const void* ptr, CUtensorMapSwizzle sw, Dim d0, Dim d1, Dim d2 = {0, 0, 0}, Dim d3 = {0, 0, 0}) {
    const cuuint64_t dims[4] = {d0.size, d1.size, d2.size, d3.size};
    const cuuint64_t strides[3] = {d1.stride, d2.stride, d3.stride};
    const cuuint32_t box[4] = {d0.box, d1.box, d2.box, d3.box};
    const cuuint32_t es[4] = {1, 1, 1, 1};
    fn(m, CU_TENSOR_MAP_DATA_TYPE_BFLOAT16, d3.size ? 4 : d2.size ? 3 : 2, const_cast<void*>(ptr), dims, strides, box, es,
       CU_TENSOR_MAP_INTERLEAVE_NONE, sw, CU_TENSOR_MAP_L2_PROMOTION_L2_128B, CU_TENSOR_MAP_FLOAT_OOB_FILL_NONE);
}

}

extern "C" void kernel_launch(void* const* d_in, const int* in_sizes, int n_in, void* d_out, int out_size) {
    (void)in_sizes; (void)n_in; (void)out_size;
    void* fnp = nullptr;
    cudaDriverEntryPointQueryResult st;
    cudaGetDriverEntryPoint("cuTensorMapEncodeTiled", &fnp, cudaEnableDefault, &st);
    EncodeFn fn = (EncodeFn)fnp;
    void* scratch = nullptr;
    cudaGetSymbolAddress(&scratch, g_scratch);
    int dev = 0, sms = 0;
    cudaGetDevice(&dev);
    cudaDeviceGetAttribute(&sms, cudaDevAttrMultiProcessorCount, dev);
    auto kernel = sms == 132 ? fused_kernel<true> : fused_kernel<false>;
    cudaFuncSetAttribute(kernel, cudaFuncAttributeMaxDynamicSharedMemorySize, SMEM_BYTES);

    const CUtensorMapSwizzle S128 = CU_TENSOR_MAP_SWIZZLE_128B, S0 = CU_TENSOR_MAP_SWIZZLE_NONE;
    const Dim one = {1, 16, 1};
    Maps maps;
    encode(fn, &maps.m[M_XA], d_in[0], S128, {896, 2, 64}, {1024, 1792, 128}, one, one);
    encode(fn, &maps.m[M_WQK], d_in[1], S128, {112, 2, 64}, {448, 2688, 32}, {3, 896, 2}, {4, 224, 1});
    encode(fn, &maps.m[M_WV], d_in[1], S128, {112, 2, 64}, {448, 2688, 64}, one, {12, 224, 1});
    encode(fn, &maps.m[M_XH], d_in[0], S128, {448, 2, 64}, {128, 1792, 8}, {8, 128 * 1792, 8}, {2, 896, 2});
    encode(fn, &maps.m[M_WO], d_in[2], S128, {112, 2, 64}, {448, 896, 64}, one, {4, 224, 1});
    encode(fn, &maps.m[M_XB], d_in[3], S128, {448, 2, 64}, {1024, 896, 64}, {2, 896 * 1024, 2}, one);
    encode(fn, &maps.m[M_CR], d_in[4], S128, {2048, 2, 64}, {2048, 4096, 128});
    encode(fn, &maps.m[M_CI], d_in[5], S128, {2048, 2, 64}, {2048, 4096, 128});
    encode(fn, &maps.m[M_WR], d_in[6], S128, {448, 2, 64}, {448, 896, 112}, one, one);
    encode(fn, &maps.m[M_WI], d_in[7], S128, {448, 2, 64}, {448, 896, 112});
    encode(fn, &maps.m[M_OUTA], d_out, S0, {1792, 2, 112}, {1024, 3584, 8});
    encode(fn, &maps.m[M_OUTB], d_out, S0, {896, 2, 112}, {2048, 1792, 8});

    kernel<<<132, 384, SMEM_BYTES>>>((Scratch*)scratch, maps);
}
```

```cpp
#include <cuda.h>
#include <cuda_bf16.h>
#include <cuda_runtime.h>
#include <stdint.h>

namespace {

constexpr uint32_t SLOT = 16384;
constexpr int NA = 7;
constexpr uint32_t BRING = NA * SLOT;
constexpr uint32_t HALO = BRING + 6 * SLOT;
constexpr uint32_t HSLOT = 1792;
constexpr uint32_t WSLOT = 3584;
constexpr uint32_t BLOB = 14336;
constexpr uint32_t BARS = 14 * SLOT;
constexpr uint32_t BAR_FULL = BARS;
constexpr uint32_t BAR_EMPTY = BARS + 64;
constexpr uint32_t BAR_RDY = BARS + 128;
constexpr uint32_t BAR_DEP = BARS + 168;
constexpr uint32_t BAR_HALO = BARS + 192;
constexpr uint32_t BAR_PART = BARS + 208;
constexpr uint32_t BAR_HINT = BARS + 224;
constexpr uint32_t TAG = BARS + 240;
constexpr uint32_t HSPARE = BARS + 256 + 1024;
constexpr uint32_t SMEM_BYTES = HSPARE + HSLOT;
constexpr uint32_t base = 1024;
constexpr int SPIN_LIMIT = 1 << 16;

constexpr int LEAD = 3;
constexpr int PACE = 450;
constexpr int HALO_K_AT = 10;
constexpr int HALO_V_AT = 19;
constexpr int B_SLICE = 4;
constexpr int O_FIRST = 7, O_SLICE = 3;
constexpr int TURN = 4, LTURN = 5;
constexpr uint32_t GPC_MAP = 0x64752310u;
constexpr int NBE = 13;
constexpr int POUT = 33 + NBE;
constexpr int ELAST = POUT + 6;
constexpr int LLAST = 65 - NBE;
constexpr uint32_t LSLAB = ((LLAST - 6) % NA) * SLOT;
static_assert(TURN <= 4 && LTURN <= 5, "the output is staged in the slots of the seventh-last stage");

enum { M_XB, M_XA, M_XH, M_WR, M_WQK, M_WV, M_WO, M_WI, M_CR, M_CI, M_OUTA, M_OUTB, M_COUNT };
struct __align__(64) Maps { CUtensorMap m[M_COUNT]; };

constexpr int CNT_A = 0;
constexpr int CNT_B = 8;
constexpr int CNT_W = 12;
constexpr int CNT_O = 16;
constexpr int CNT_P = 32;
constexpr int CNT_COUNT = 96;

struct Scratch {
    uint8_t ab[64 * 4 * BLOB];
    uint8_t o[16 * 7 * SLOT];
    uint8_t part[64 * 2 * BLOB];
    uint8_t halo[64 * 2 * 2048];
    uint8_t wo[4 * 7 * SLOT];
    unsigned cnt[CNT_COUNT * 32];
    unsigned epoch[132 * 4 * 8];
};
__device__ __align__(1024) Scratch g_scratch;

__device__ __forceinline__ unsigned clk32() { unsigned c; asm volatile("mov.u32 %0, %%clock;" : "=r"(c)); return c; }

#define PROF(idx)

__device__ __forceinline__ void mbar_init(uint32_t bar, uint32_t cnt) {
    asm volatile("mbarrier.init.shared::cta.b64 [%0], %1;" ::"r"(bar), "r"(cnt) : "memory");
}
__device__ __forceinline__ void mbar_expect(uint32_t bar, uint32_t bytes) {
    asm volatile("mbarrier.arrive.expect_tx.shared::cta.b64 _, [%0], %1;" ::"r"(bar), "r"(bytes) : "memory");
}
__device__ __forceinline__ void mbar_arrive(uint32_t bar) {
    asm volatile("mbarrier.arrive.shared::cta.b64 _, [%0];" ::"r"(bar) : "memory");
}
__device__ __forceinline__ bool mbar_try(uint32_t bar, uint32_t parity) {
    uint32_t ok;
    asm volatile("{\n.reg .pred p;\nmbarrier.try_wait.parity.shared::cta.b64 p, [%1], %2;\nselp.u32 %0, 1, 0, p;\n}\n"
                 : "=r"(ok) : "r"(bar), "r"(parity) : "memory");
    return ok;
}
__device__ __forceinline__ void mbar_wait(uint32_t bar, uint32_t parity) {
#pragma unroll 1
    for (int n = 0; n < SPIN_LIMIT; n++)
        if (mbar_try(bar, parity)) break;
}
__device__ __forceinline__ bool elect() {
    uint32_t p;
    asm volatile("{\n.reg .pred p;\nelect.sync _|p, 0xffffffff;\nselp.u32 %0, 1, 0, p;\n}\n" : "=r"(p));
    return p;
}
__device__ __forceinline__ void nb_sync(int id, int n) { asm volatile("bar.sync %0, %1;" ::"r"(id), "r"(n) : "memory"); }
__device__ __forceinline__ void nb_arrive(int id, int n) { asm volatile("bar.arrive %0, %1;" ::"r"(id), "r"(n) : "memory"); }
__device__ __forceinline__ void warp_arrive(uint32_t bar) {
    __syncwarp();
    if (elect()) mbar_arrive(bar);
}
__device__ __forceinline__ uint32_t or3(uint32_t a, uint32_t b, uint32_t c) {
    uint32_t r;
    asm("lop3.b32 %0, %1, %2, %3, 0xFE;" : "=r"(r) : "r"(a), "r"(b), "r"(c));
    return r;
}
__device__ __forceinline__ uint32_t band(uint32_t x, uint32_t m) {
    uint32_t r;
    asm volatile("and.b32 %0, %1, %2;" : "=r"(r) : "r"(x), "r"(m));
    return r;
}
__device__ __forceinline__ uint32_t dup(uint32_t x, uint32_t zero) {
    uint32_t r;
    asm volatile("xor.b32 %0, %1, %2;" : "=r"(r) : "r"(x), "r"(zero));
    return r;
}

__device__ __forceinline__ void tma_ld2(uint32_t dst, const CUtensorMap* m, int c0, int c1, uint32_t bar) {
    asm volatile("cp.async.bulk.tensor.2d.shared::cluster.global.mbarrier::complete_tx::bytes [%0], [%1, {%3, %4}], [%2];"
                 ::"r"(dst), "l"(m), "r"(bar), "r"(c0), "r"(c1) : "memory");
}
__device__ __forceinline__ void tma_ld4(uint32_t dst, const CUtensorMap* m, int c0, int c1, int c2, int c3, uint32_t bar) {
    asm volatile("cp.async.bulk.tensor.4d.shared::cluster.global.mbarrier::complete_tx::bytes [%0], [%1, {%3, %4, %5, %6}], [%2];"
                 ::"r"(dst), "l"(m), "r"(bar), "r"(c0), "r"(c1), "r"(c2), "r"(c3) : "memory");
}
__device__ __forceinline__ void bulk_ld(uint32_t dst, const void* src, uint32_t bytes, uint32_t bar) {
    asm volatile("cp.async.bulk.shared::cluster.global.mbarrier::complete_tx::bytes [%0], [%1], %2, [%3];"
                 ::"r"(dst), "l"(src), "r"(bytes), "r"(bar) : "memory");
}
__device__ __forceinline__ void bulk_st(void* dst, uint32_t src, uint32_t bytes) {
    asm volatile("cp.async.bulk.global.shared::cta.bulk_group [%0], [%1], %2;" ::"l"(dst), "r"(src), "r"(bytes) : "memory");
}
__device__ __forceinline__ void tma_st2(const CUtensorMap* m, int c0, int c1, uint32_t src) {
    asm volatile("cp.async.bulk.tensor.2d.global.shared::cta.bulk_group [%0, {%1, %2}], [%3];"
                 ::"l"(m), "r"(c0), "r"(c1), "r"(src) : "memory");
}
__device__ __forceinline__ void bulk_commit() { asm volatile("cp.async.bulk.commit_group;" ::: "memory"); }
__device__ __forceinline__ void bulk_wait_read() { asm volatile("cp.async.bulk.wait_group.read 0;" ::: "memory"); }
__device__ __forceinline__ void fence_async_smem() { asm volatile("fence.proxy.async.shared::cta;" ::: "memory"); }
__device__ __forceinline__ void fence_async_global() { asm volatile("fence.proxy.async.global;" ::: "memory"); }

__device__ __forceinline__ void signal(Scratch* sc, int idx) {
    asm volatile("fence.proxy.async;\nred.relaxed.gpu.global.add.u32 [%0], 1;" ::"l"(&sc->cnt[idx * 32]) : "memory");
}
__device__ __forceinline__ unsigned peek(const unsigned* p) {
    unsigned v;
    asm volatile("ld.relaxed.gpu.global.u32 %0, [%1];" : "=r"(v) : "l"(p) : "memory");
    return v;
}
__device__ __forceinline__ void await(Scratch* sc, int idx, unsigned target) {
    const unsigned* p = &sc->cnt[idx * 32];
#pragma unroll 1
    for (int n = 0; n < SPIN_LIMIT; n++)
        if ((int)(peek(p) - target) >= 0) break;
    asm volatile("fence.acquire.gpu;" ::: "memory");
}
__device__ __forceinline__ void wait_dep(int k) {
    mbar_wait(base + BAR_DEP + k * 8, 0);
    fence_async_global();
}

#define WG_REGS                                                                                                     \
    "{%0,%1,%2,%3,%4,%5,%6,%7,%8,%9,%10,%11,%12,%13,%14,%15,%16,%17,%18,%19,%20,%21,%22,%23,%24,%25,%26,%27,"       \
    "%28,%29,%30,%31,%32,%33,%34,%35,%36,%37,%38,%39,%40,%41,%42,%43,%44,%45,%46,%47,%48,%49,%50,%51,%52,%53,%54,%55}"
#define WG_OPS(C)                                                                                                   \
    C(d[0]), C(d[1]), C(d[2]), C(d[3]), C(d[4]), C(d[5]), C(d[6]), C(d[7]), C(d[8]), C(d[9]), C(d[10]), C(d[11]),   \
    C(d[12]), C(d[13]), C(d[14]), C(d[15]), C(d[16]), C(d[17]), C(d[18]), C(d[19]), C(d[20]), C(d[21]), C(d[22]),   \
    C(d[23]), C(d[24]), C(d[25]), C(d[26]), C(d[27]), C(d[28]), C(d[29]), C(d[30]), C(d[31]), C(d[32]), C(d[33]),   \
    C(d[34]), C(d[35]), C(d[36]), C(d[37]), C(d[38]), C(d[39]), C(d[40]), C(d[41]), C(d[42]), C(d[43]), C(d[44]),   \
    C(d[45]), C(d[46]), C(d[47]), C(d[48]), C(d[49]), C(d[50]), C(d[51]), C(d[52]), C(d[53]), C(d[54]), C(d[55])

template <int TA, int TB, int SB, bool INIT, uint32_t AH, uint32_t BH>
__device__ __forceinline__ void wgmma112(float (&d)[56], uint32_t alo, uint32_t blo) {
    if (INIT) {
        asm volatile("{\n.reg .pred p;\n.reg .b64 da, db;\nsetp.ne.b32 p, 0, 0;\nmov.b64 da, {%56, %61};\nmov.b64 db, {%57, %62};\n"
                     "wgmma.mma_async.sync.aligned.m64n112k16.f32.bf16.bf16 " WG_REGS ", da, db, p, 1, %59, %60, %58;\n}\n"
                     : WG_OPS("=f") : "r"(alo), "r"(blo), "n"(TB), "n"(SB), "n"(TA), "n"(AH), "n"(BH));
    } else {
        asm volatile("{\n.reg .pred p;\n.reg .b64 da, db;\nsetp.ne.b32 p, 1, 0;\nmov.b64 da, {%56, %61};\nmov.b64 db, {%57, %62};\n"
                     "wgmma.mma_async.sync.aligned.m64n112k16.f32.bf16.bf16 " WG_REGS ", da, db, p, 1, %59, %60, %58;\n}\n"
                     : WG_OPS("+f") : "r"(alo), "r"(blo), "n"(TB), "n"(SB), "n"(TA), "n"(AH), "n"(BH));
    }
}
__device__ __forceinline__ void acc_fence(float (&d)[56]) {
#pragma unroll
    for (int i = 0; i < 56; i++) asm volatile("" : "+f"(d[i])::"memory");
}

__device__ __forceinline__ uint32_t pack2(float lo, float hi) {
    uint32_t r;
    asm volatile("cvt.rn.bf16x2.f32 %0, %1, %2;" : "=r"(r) : "f"(hi), "f"(lo));
    return r;
}
__device__ __forceinline__ uint32_t movm(uint32_t a) {
    uint32_t r;
    asm volatile("movmatrix.sync.aligned.m8n8.trans.b16 %0, %1;" : "=r"(r) : "r"(a));
    return r;
}
__device__ __forceinline__ void stsm4(uint32_t addr, uint32_t a, uint32_t b, uint32_t c, uint32_t d) {
    asm volatile("stmatrix.sync.aligned.m8n8.x4.shared.b16 [%0], {%1,%2,%3,%4};" ::"r"(addr), "r"(a), "r"(b), "r"(c), "r"(d) : "memory");
}
__device__ __forceinline__ void sts1(uint32_t addr, uint32_t a) { asm volatile("st.shared.b32 [%0], %1;" ::"r"(addr), "r"(a) : "memory"); }
__device__ __forceinline__ uint32_t lds1(uint32_t addr) {
    uint32_t a;
    asm volatile("ld.shared.b32 %0, [%1];" : "=r"(a) : "r"(addr) : "memory");
    return a;
}
__device__ __forceinline__ void lds4(uint32_t addr, uint32_t* v) {
    asm volatile("ld.shared.v4.b32 {%0,%1,%2,%3}, [%4];" : "=r"(v[0]), "=r"(v[1]), "=r"(v[2]), "=r"(v[3]) : "r"(addr) : "memory");
}
__device__ __forceinline__ void stg1(uint8_t* p, uint32_t a) { asm volatile("st.global.b32 [%0], %1;" ::"l"(p), "r"(a) : "memory"); }
__device__ __forceinline__ uint64_t tagged(uint32_t lo, uint32_t hi, uint32_t tag) {
    uint64_t r;
    asm volatile("{\n.reg .b32 t;\nlop3.b32 t, %1, %3, 1, 0xD8;\nmov.b64 %0, {t, %2};\n}\n" : "=l"(r) : "r"(lo), "r"(hi), "r"(tag));
    return r;
}
__device__ __forceinline__ void st_tagged(uint8_t* p, uint64_t x, uint64_t y) {
    asm volatile("st.relaxed.gpu.global.v2.b64 [%0], {%1, %2};" ::"l"(p), "l"(x), "l"(y) : "memory");
}
__device__ __forceinline__ void mma16816(float (&d)[4], const uint32_t (&a)[4], uint32_t b0, uint32_t b1) {
    asm volatile("mma.sync.aligned.m16n8k16.row.col.f32.bf16.bf16.f32 {%0,%1,%2,%3}, {%4,%5,%6,%7}, {%8,%9}, {%0,%1,%2,%3};"
                 : "+f"(d[0]), "+f"(d[1]), "+f"(d[2]), "+f"(d[3]) : "r"(a[0]), "r"(a[1]), "r"(a[2]), "r"(a[3]), "r"(b0), "r"(b1));
}
__device__ __forceinline__ uint32_t add2(uint32_t a, uint32_t b) {
    uint32_t r;
    asm("add.rn.bf16x2 %0, %1, %2;" : "=r"(r) : "r"(a), "r"(b));
    return r;
}
__device__ __forceinline__ uint32_t scale2(uint32_t x) {
    uint32_t r;
    asm("{\n.reg .b32 t;\nmul.rn.bf16x2 t, %1, %3;\nfma.rn.bf16x2 %0, %1, %2, t;\n}\n" : "=r"(r) : "r"(x), "r"(0x3E423E42u), "r"(0xB9F7B9F7u));
    return r;
}
__device__ __forceinline__ uint32_t max2(uint32_t a, uint32_t b) {
    uint32_t r;
    asm("max.bf16x2 %0, %1, %2;" : "=r"(r) : "r"(a), "r"(b));
    return r;
}
__device__ __forceinline__ void ld_tagged(const uint8_t* p, uint32_t& a, uint32_t& ta, uint32_t& b, uint32_t& tb) {
    asm volatile("{\n.reg .b64 x, y;\nld.relaxed.gpu.global.v2.b64 {x, y}, [%4];\nmov.b64 {%0, %1}, x;\nmov.b64 {%2, %3}, y;\n}\n"
                 : "=r"(a), "=r"(ta), "=r"(b), "=r"(tb) : "l"(p) : "memory");
}
__device__ __forceinline__ float bf_lo(uint32_t v) { return __uint_as_float(v << 16); }
__device__ __forceinline__ float bf_hi(uint32_t v) { return __uint_as_float(v & 0xFFFF0000u); }
__device__ __forceinline__ float rcp(float x) { float r; asm("rcp.approx.ftz.f32 %0, %1;" : "=f"(r) : "f"(x)); return r; }
__device__ __forceinline__ float ex2(float x) { float r; asm volatile("ex2.approx.ftz.f32 %0, %1;" : "=f"(r) : "f"(x)); return r; }

__device__ __forceinline__ uint32_t full_bar(int stage) { return base + BAR_FULL + (stage & 7) * 8; }
__device__ __forceinline__ void wait_released(int j) { mbar_wait(base + BAR_EMPTY + (j & 7) * 8, (j >> 3) & 1); }

template <int V>
struct Int { static constexpr int value = V; };

__host__ __device__ constexpr int bslot_e(int i) { return (i < 2 || i >= 14) ? (i + 5) % 7 : (i + 1) % 5; }
__host__ __device__ constexpr int bslot_l(int i) { return i % 6; }

template <uint32_t OFF>
struct Feed {
    int stage;
    uint32_t dst;
    __device__ __forceinline__ void seek(int i, int slot) { stage = i; dst = base + OFF + slot * SLOT; }
    template <int N>
    __device__ __forceinline__ uint32_t acquire() { wait_released(stage - N); return full_bar(stage); }
    template <int N>
    __device__ __forceinline__ void next() {
        stage++;
        dst += SLOT;
        if (dst == base + OFF + N * SLOT) dst = base + OFF;
    }
};
__device__ __forceinline__ int skip_own(int n, int mt) { return n == mt ? 15 : n; }

struct Desc { uint32_t lo, hi; };
__host__ __device__ constexpr Desc desc_const(uint32_t lbo, uint32_t sbo, uint32_t mode) { return {(lbo >> 4) << 16, (sbo >> 4) | (mode << 30)}; }
constexpr Desc D_K128 = desc_const(16, 1024, 1);
constexpr Desc D_N128 = desc_const(8192, 1024, 1);
constexpr Desc D_BLOB = desc_const(128, 256, 0);
constexpr Desc D_OT = desc_const(2048, 128, 0);

enum Kind { XW, XWN, QK, BIG, OUT };

struct Ring {
    int stage;
    uint32_t a, b;
    uint32_t wg;
    uint32_t zero;
    bool releaser;
    __device__ __forceinline__ void seek(int i, int bslot) {
        stage = i;
        a = (base + (i % NA) * SLOT) >> 4;
        b = (base + BRING + bslot * SLOT) >> 4;
    }
    __device__ __forceinline__ void wait() { mbar_wait(full_bar(stage), (stage >> 3) & 1); }
    __device__ __forceinline__ void take_turn() { nb_sync(1 + wg, 256); }
    __device__ __forceinline__ void pin() {
        asm volatile("{\n.reg .pred p;\nsetp.ne.u32 p, %0, 0;\nPIN:\npmevent 7;\n@p bra.uni PIN;\n}\n" ::"r"(zero) : "memory");
    }
    __device__ __forceinline__ void mma_begin() {
        if (!wg) take_turn();
        pin();
    }
    __device__ __forceinline__ void mma_end() {
        pin();
        if (wg) nb_arrive(3, 256);
        nb_sync(3 - wg, 256);
    }
    template <Kind K, int NBS, bool INIT, int SB = 1, bool TAIL = false>
    __device__ __forceinline__ void run(float (&d)[56], float (&e)[56], bool first = true, bool last = true, bool more = true) {
        if (first) take_turn();
        asm volatile("wgmma.fence.sync.aligned;" ::: "memory");
        if (K == QK) {
            const uint32_t da = D_K128.lo + (base >> 4) + (stage >> 1) * (SLOT >> 4) + (stage & 1) * 4 + wg * 512, db = D_N128.lo + b;
            wgmma112<0, 1, 1, INIT, D_K128.hi, D_N128.hi>(d, da, db);
            wgmma112<0, 1, 1, INIT, D_K128.hi, D_N128.hi>(e, da, db + 256);
            wgmma112<0, 1, 1, false, D_K128.hi, D_N128.hi>(d, da + 2, db + 128);
            wgmma112<0, 1, 1, false, D_K128.hi, D_N128.hi>(e, da + 2, db + 384);
        } else {
            constexpr int TA = K == OUT, TB = K != XW;
            constexpr uint32_t sa = K == OUT ? 256 : 2, sb = K == XW ? 2 : K == BIG ? 224 : 128;
            constexpr Desc A = K == OUT ? D_OT : D_K128, B = K == XW ? D_K128 : K == BIG ? D_BLOB : D_N128;
            const uint32_t da = A.lo + a + wg * (K == OUT ? 64 : 512), db = B.lo + b;
            wgmma112<TA, TB, SB, INIT, A.hi, B.hi>(d, da, db);
#pragma unroll
            for (int q = 1; q < 4; q++) wgmma112<TA, TB, SB, false, A.hi, B.hi>(d, da + q * sa, db + q * sb);
        }
        asm volatile("wgmma.commit_group.sync.aligned;" ::: "memory");
        if (!TAIL) asm volatile("wgmma.wait_group.sync.aligned 1;" ::: "memory");
        if (last) nb_arrive(2 - wg, 256);
        if (!TAIL && stage > 0 && releaser) mbar_arrive(base + BAR_EMPTY + ((stage - 1) & 7) * 8);
        stage++;
        a += SLOT >> 4;
        if (a == (base + NA * SLOT) >> 4) a = base >> 4;
        b += SLOT >> 4;
        if (b == (base + BRING + NBS * SLOT) >> 4) b = (base + BRING) >> 4;
        if (more) wait();
    }
    template <Kind K, int NBS, bool INIT, int SB = 1, bool TAIL = false>
    __device__ __forceinline__ void run(float (&d)[56], bool first = true, bool last = true, bool more = true) {
        run<K, NBS, INIT, SB, TAIL>(d, d, first, last, more);
    }
};

template <int I0 = 0, int I1 = 28>
__device__ __forceinline__ void pack_all(const float (&d)[56], uint32_t (&p)[28]) {
#pragma unroll
    for (int i = I0; i < I1; i++) p[i] = pack2(d[2 * i], d[2 * i + 1]);
}
template <int I0, int I1>
__device__ __forceinline__ void store_frags(uint8_t* dst, const uint32_t (&p)[28]) {
#pragma unroll
    for (int i = I0; i < I1; i++) stg1(dst + i * 128, p[i]);
}
template <int I0, int I1>
__device__ __forceinline__ void stage_frags(uint32_t lane_addr, const uint32_t (&p)[28]) {
#pragma unroll
    for (int i = I0; i < I1; i += 4) stsm4(lane_addr + i * 128, p[i], p[i + 1], p[i + 2], p[i + 3]);
}
template <class F>
__device__ __forceinline__ void store_out(F frag, int lane, uint32_t slab, const CUtensorMap* m, int c0, int c1) {
    const bool swap = lane & 16;
    const uint32_t addr = slab + (lane & 7) * 224 + ((lane >> 3) ^ ((lane >> 2) & 1)) * 16;
#pragma unroll
    for (int h = 0; h < 2; h++) {
#pragma unroll
        for (int c = 0; c < 14; c += 4) {
            const uint32_t t0 = frag(2 * c + h), t1 = frag(2 * c + 2 + h);
            if (c < 12) {
                const uint32_t t2 = frag(2 * c + 4 + h), t3 = frag(2 * c + 6 + h);
                stsm4(addr + h * 1792 + c * 16, swap ? t1 : t0, swap ? t0 : t1, swap ? t3 : t2, swap ? t2 : t3);
            } else {
                asm volatile("stmatrix.sync.aligned.m8n8.x2.shared.b16 [%0], {%1,%2};" ::"r"(addr + h * 1792 + c * 16), "r"(swap ? t1 : t0), "r"(swap ? t0 : t1) : "memory");
            }
        }
        fence_async_smem();
        __syncwarp();
        if (elect()) tma_st2(m, c0, c1 + 8 * h, slab + h * 1792);
    }
    if (elect()) {
        bulk_commit();
        bulk_wait_read();
    }
}
__host__ __device__ constexpr int tile_of(int t) { return 7 * (t >> 2) + 3 * ((t >> 1) & 1) + 2 * (t & 1); }

struct Role {
    bool H;
    int L, mt, ns, id;
    int kind, a0, a1, b3;
};
template <bool BY_SM>
__device__ __forceinline__ Role decode_role() {
    uint32_t sm;
    if (BY_SM) asm volatile("mov.u32 %0, %%smid;" : "=r"(sm));
    else asm volatile("mov.u32 %0, %%ctaid.x;" : "=r"(sm));
    const int tpc = sm >> 1, q2 = ((tpc - 32) * 37) >> 8;
    const int gpc = tpc < 32 ? tpc & 7 : tpc < 60 ? tpc - 31 - 7 * q2 : 0;
    const int pos = tpc < 32 ? tpc >> 3 : tpc < 60 ? q2 + 4 : tpc - 56;
    Role r;
    r.H = sm >= 128;
    const int grp = (GPC_MAP >> (4 * gpc)) & 7;
    r.L = grp & 1;
    r.mt = (grp >> 1) * 4 + (pos >> 1);
    r.ns = (pos & 1) * 2 + (sm & 1);
    r.id = r.H ? sm : grp * 16 + pos * 2 + (sm & 1);
    r.kind = r.H ? 2 : r.L;
    r.a0 = r.L ? (r.mt >> 3) * 448 : 0;
    r.a1 = r.L ? (r.mt & 7) * 128 : r.H ? 120 : r.mt * 64;
    r.b3 = r.H ? 4 + r.ns : r.L ? r.ns : 0;
    return r;
}

__device__ __forceinline__ void first_fill(const Maps& maps, const Role& r, int i) {
    const bool E = r.kind == 0;
    const CUtensorMap* ma = &maps.m[r.kind];
    const uint32_t bar = full_bar(i);
    const int k = (i * 64) >> r.L;
    const bool has_a = !(i & r.L), has_b = i < 7 - r.L;
    const uint32_t dst = base + BRING + (E ? (0x2104365u >> (4 * i)) & 7 : i) * SLOT;
    mbar_expect(bar, (has_a ? SLOT : 0) + (has_b ? (E ? BLOB : SLOT) : 0));
    if (has_a) tma_ld4(base + (i >> r.L) * SLOT, ma, r.a0 + k, r.a1, 0, 0, bar);
    if (has_b) {
        tma_ld4(dst, ma + 3, E ? k : 0, E ? r.ns * 112 : k, 0, r.b3, bar);
        if (!E) tma_ld4(dst + 8192, ma + 3, 64, k, 0, r.b3, bar);
        mbar_arrive(bar);
    }
}
static_assert(bslot_e(0) == 5 && bslot_e(1) == 6 && bslot_e(2) == 3 && bslot_e(3) == 4 && bslot_e(4) == 0 && bslot_e(6) == 2, "");

template <bool BY_SM>
__global__ void __launch_bounds__(384, 1) fused_kernel(Scratch* sc, const __grid_constant__ Maps maps) {
    const unsigned t_open = clk32();
    const int warp = __shfl_sync(0xffffffffu, threadIdx.x >> 5, 0);
    if (warp == 8) {
        if (elect()) {
#pragma unroll
            for (int i = 0; i < LEAD; i++) mbar_init(base + BAR_FULL + i * 8, 2);
            asm volatile("fence.mbarrier_init.release.cluster;" ::: "memory");
            const Role r = decode_role<BY_SM>();
#pragma unroll 1
            for (int i = 0; i < LEAD; i++) first_fill(maps, r, i);
        }
    }
    if (warp == 9) {
        if (elect()) {
#pragma unroll
            for (int i = 0; i < 8; i++) mbar_init(base + BAR_EMPTY + i * 8, 4);
            asm volatile("fence.mbarrier_init.release.cluster;" ::: "memory");
        }
    } else if (warp == 10) {
        if (elect()) {
#pragma unroll
            for (int i = 0; i < 3; i++) mbar_init(base + BAR_RDY + i * 8, i < 2 ? 4 : 8);
#pragma unroll
            for (int i = 0; i < 2; i++) mbar_init(base + BAR_HALO + i * 8, 1);
            asm volatile("fence.mbarrier_init.release.cluster;" ::: "memory");
        }
    } else if (warp == 11) {
        if (elect()) {
#pragma unroll
            for (int i = LEAD; i < 8; i++) mbar_init(base + BAR_FULL + i * 8, 2);
#pragma unroll
            for (int i = 0; i < 3; i++) mbar_init(base + BAR_DEP + i * 8, 1);
#pragma unroll
            for (int i = 0; i < 4; i++) mbar_init(base + BAR_PART + i * 8, 1);
            asm volatile("fence.mbarrier_init.release.cluster;" ::: "memory");
        }
    }
    __syncthreads();

    const Role role = decode_role<BY_SM>();
    int lane = threadIdx.x & 31;
    asm volatile("" : "+r"(lane));
    const bool roleH = role.H;
    const int roleL = role.L, mt = role.mt, ns = role.ns, bid = role.id;
    const int par = mt >> 3, blk = mt & 7, col = ns * 112;

    if (warp >= 8) {
        asm volatile("setmaxnreg.dec.sync.aligned.u32 56;");
#define PROF_FEED_A
#define PROF_FEED_B
        if (warp == 8) {
            if (elect()) {
                PROF(129);
#pragma unroll 1
                for (int i = LEAD; i < 7; i++) {
                    while (clk32() - t_open < i * PACE) {}
                    first_fill(maps, role, i);
                }
                PROF(134);
                Feed<0> f;
                const int row = mt * 128;
                auto c_run = [&](const CUtensorMap* m, int off, int n0, int n1) {
#pragma unroll 1
                    for (int n = n0; n < n1; n++) {
                        const uint32_t bar = f.acquire<NA>();
                        mbar_expect(bar, SLOT);
                        tma_ld2(f.dst, m, (off + skip_own(n, mt)) * 64, row, bar);
                        PROF_FEED_A;
                        f.next<NA>();
                    }
                };
                if (roleH) {
                    mbar_expect(base + BAR_DEP, 7 * SLOT);
#pragma unroll 1
                    for (int i = 0; i < 7; i++) {
                        const uint32_t dst = base + (i < 6 ? i : 7) * SLOT;
                        if (i < 6) wait_released(7 + i);
                        tma_ld4(dst, &maps.m[M_WO], 0, i * 64, 0, ns, base + BAR_DEP);
                        tma_ld4(dst + 8192, &maps.m[M_WO], 64, i * 64, 0, ns, base + BAR_DEP);
                    }
                    mbar_wait(base + BAR_DEP, 0);
                    mbar_wait(base + BAR_RDY + 16, 0);
#pragma unroll 1
                    for (int i = 0; i < 7; i++) bulk_st(sc->wo + (size_t)(ns * 7 + i) * SLOT, base + (i < 6 ? i : 7) * SLOT, SLOT);
                    bulk_commit();
                    asm volatile("cp.async.bulk.wait_group 0;" ::: "memory");
                    signal(sc, CNT_W + ns);
                } else if (!roleL) {
                    f.seek(14, 0);
#pragma unroll 1
                    for (int i = 0; i < 4; i++) {
                        const uint32_t bar = f.acquire<NA>();
                        mbar_expect(bar, SLOT);
                        tma_ld2(f.dst, &maps.m[M_CR + (i >> 1)], ((i & 1) * 16 + mt) * 64, row, bar);
                        mbar_arrive(bar);
                        PROF_FEED_A;
                        f.next<NA>();
                    }
                    c_run(&maps.m[M_CR], 0, 0, 15);
                    c_run(&maps.m[M_CI], 0, 0, NBE);
                    wait_dep(2);
#pragma unroll 1
                    for (int i = 0; i < 7; i++) {
                        const uint32_t bar = f.acquire<NA>();
                        mbar_expect(bar, SLOT);
                        bulk_ld(f.dst, sc->o + (size_t)(mt * 7 + i) * SLOT, SLOT, bar);
                        PROF_FEED_A;
                        f.next<NA>();
                    }
                } else {
#pragma unroll 1
                    for (int i = 4; i < 7; i++) {
                        wait_released(2 * i - 8);
                        mbar_expect(full_bar(2 * i), SLOT);
                        tma_ld4(base + i * SLOT, &maps.m[M_XA], par * 448 + i * 64, blk * 128, 0, 0, full_bar(2 * i));
                    }
                    wait_released(HALO_K_AT);
                    mbar_arrive(base + BAR_DEP + 16);
                    f.seek(21, 0);
                    c_run(&maps.m[M_CR], 16, 0, 15);
                    c_run(&maps.m[M_CI], 16, 0, 15);
                    c_run(&maps.m[M_CI], 0, NBE, 15);
                }
            }
        } else if (warp == 11) {
            if (elect()) {
                Feed<BRING> f;
                auto blob_run = [&](auto nbs, int quarter, int n0, int n1) {
                    constexpr int N = decltype(nbs)::value;
                    const uint8_t* src = sc->ab + (size_t)(quarter * 64 + ns) * BLOB;
#pragma unroll 1
                    for (int n = n0; n < n1; n++) {
                        const uint32_t bar = f.template acquire<N>();
                        mbar_expect(bar, BLOB);
                        bulk_ld(f.dst, src + skip_own(n, mt) * (4 * BLOB), BLOB, bar);
                        PROF_FEED_B;
                        f.template next<N>();
                    }
                };
                auto v_run = [&](auto nbs) {
                    constexpr int N = decltype(nbs)::value;
#pragma unroll 1
                    for (int i = 0; i < 7; i++) {
                        const uint32_t bar = f.template acquire<N>();
                        mbar_expect(bar, SLOT);
                        tma_ld4(f.dst, &maps.m[M_WV], 0, i * 64, 0, 8 + ns, bar);
                        tma_ld4(f.dst + 8192, &maps.m[M_WV], 64, i * 64, 0, 8 + ns, bar);
                        mbar_arrive(bar);
                        PROF_FEED_B;
                        f.template next<N>();
                    }
                };
                if (roleH) {
                    f.seek(7, 0);
                    v_run(Int<7>());
                } else if (!roleL) {
                    f.seek(7, bslot_e(7));
#pragma unroll 1
                    for (int i = 0; i < 7; i++) {
                        const uint32_t bar = f.acquire<5>();
                        mbar_expect(bar, BLOB);
                        tma_ld2(f.dst, &maps.m[M_WI], i * 64, col, bar);
                        mbar_arrive(bar);
                        PROF_FEED_B;
                        f.next<5>();
                    }
                    f.seek(18, bslot_e(18));
                    wait_dep(0);
                    blob_run(Int<7>(), 0, 0, 15);
                    wait_dep(1);
                    blob_run(Int<7>(), 2, 0, NBE);
                    mbar_wait(base + BAR_HINT, 0);
                    fence_async_global();
#pragma unroll 1
                    for (int i = 0; i < 7; i++) {
                        const uint32_t bar = f.acquire<7>();
                        mbar_expect(bar, SLOT);
                        bulk_ld(f.dst, sc->wo + (size_t)(ns * 7 + i) * SLOT, SLOT, bar);
                        PROF_FEED_B;
                        f.next<7>();
                    }

                } else {
                    f.seek(6, 0);
#pragma unroll 1
                    for (int i = 6; i < 14; i++) {
                        const uint32_t bar = f.acquire<6>();
                        mbar_expect(bar, SLOT);
                        tma_ld4(f.dst, &maps.m[M_WQK], 0, i * 32, 0, ns, bar);
                        tma_ld4(f.dst + 8192, &maps.m[M_WQK], 64, i * 32, 0, ns, bar);
                        if (i & 1) mbar_arrive(bar);
                        PROF_FEED_B;
                        f.next<6>();
                    }
                    v_run(Int<6>());
                    wait_dep(0);
                    blob_run(Int<6>(), 1, 0, 15);
                    wait_dep(1);
                    blob_run(Int<6>(), 3, 0, 15);
                    blob_run(Int<6>(), 2, NBE, 15);
                    fence_async_smem();
#pragma unroll 1
                    for (int h = 0; h < 2; h++) {
                        mbar_wait(base + BAR_HINT + h * 8, 0);
                        PROF(153 + h);
                        mbar_expect(base + BAR_PART + h * 8, BLOB);
                        bulk_ld(base + (h ? HALO : LSLAB), sc->part + (size_t)((ns * 16 + mt) * 2 + h) * BLOB, BLOB, base + BAR_PART + h * 8);
                    }
                }
            }
        } else if (roleH) {
            if (warp == 9 && elect()) {
                wait_released(0);
#pragma unroll 1
                for (int i = 0; i < 7; i++)
                    asm volatile("cp.async.bulk.prefetch.tensor.2d.L2.global [%0, {%1, %2}];" ::"l"(&maps.m[M_WI]), "r"(i * 64), "r"(col) : "memory");
            }
        } else if (warp == 10) {
            if (elect()) {
                unsigned* epoch_ptr = &sc->epoch[(bid * 4 + 2) * 8];
                const unsigned ep = *epoch_ptr + 1;
                sts1(base + TAG, ep);
                asm volatile("prefetch.tensormap [%0];" ::"l"(&maps.m[M_OUTA + roleL]) : "memory");
                await(sc, CNT_A + roleL * 4 + ns, ep * 16);
                mbar_arrive(base + BAR_DEP);
                PROF(150);
                await(sc, CNT_B + ns, ep * 16);
                mbar_arrive(base + BAR_DEP + 8);
                PROF(151);
                if (!roleL) {
                    await(sc, CNT_W + ns, ep);
                    mbar_arrive(base + BAR_HINT);
                    PROF(153);
                    await(sc, CNT_O + mt, ep * 4);
                    mbar_arrive(base + BAR_DEP + 16);
                } else {
                    await(sc, CNT_P + mt * 4 + ns, ep * 2 - 1);
                    mbar_arrive(base + BAR_HINT);
                    await(sc, CNT_P + mt * 4 + ns, ep * 2);
                    mbar_arrive(base + BAR_HINT + 8);
                }
                PROF(152);
                *epoch_ptr = ep;
            }
        } else if (!roleL) {
            if (elect()) {
                mbar_wait(base + BAR_RDY, 0);
                PROF(130);
                signal(sc, CNT_A + ns);
                PROF(131);
                mbar_wait(base + BAR_RDY + 8, 0);
                signal(sc, CNT_A + 4 + ns);
                PROF(135);
                mbar_wait(base + BAR_RDY + 16, 0);
                PROF(132);
                signal(sc, CNT_B + ns);
                PROF(133);
            }
        } else {
            unsigned* epoch_ptr = &sc->epoch[(bid * 4 + 1) * 8];
            const unsigned tag = *epoch_ptr + 1;
#pragma unroll 1
            for (int kv = 0; kv < 2; kv++) {
                uint32_t v[16];
#pragma unroll
                for (int i = 0; i < 16; i++) v[i] = 0;
                if (kv) wait_released(HALO_V_AT - 4), wait_released(HALO_V_AT);
                else mbar_wait(base + BAR_DEP + 16, 0);
                if (blk > 0) {
                    const uint8_t* src = sc->halo + (size_t)(((mt - 1) * 4 + ns) * 2 + kv) * 2048 + lane * 16;
#pragma unroll 1
                    for (int n = 0; n < SPIN_LIMIT; n++) {
#pragma unroll
                        for (int i = 0; i < 4; i++) ld_tagged(src + i * 512, v[4 * i], v[4 * i + 1], v[4 * i + 2], v[4 * i + 3]);
#pragma unroll
                        for (int i = 0; i < 16; i += 2) v[i] ^= tag & 1;
                        const uint32_t stale = or3(or3(v[0], v[2], v[4]), or3(v[6], v[8], v[10]), or3(v[12], v[14], 0));
                        if (__all_sync(0xffffffffu, !(stale & 1))) break;
                    }
#pragma unroll
                    for (int c = 0; c < 14; c += 2) v[c] |= (v[15] >> c) & 1;
                }
#pragma unroll
                for (int i = 0; i < 14; i++) sts1(base + HALO + kv * (8 * HSLOT) + i * 128 + lane * 4, v[i]);
                warp_arrive(base + BAR_HALO + kv * 8);
                if (lane == 0) PROF(142 + kv);
            }
            if (elect()) {
                mbar_wait(base + BAR_RDY + 16, 0);
                PROF(130);
                signal(sc, CNT_O + mt);
                PROF(131);
                *epoch_ptr = tag;
            }
        }
    } else {
        asm volatile("setmaxnreg.inc.sync.aligned.u32 224;");
        Ring r;
        r.wg = warp >> 2;
        r.zero = blockIdx.y;
        r.releaser = lane + 1 == (warp >> 2);
        const int wg = warp >> 2;
        if (wg) nb_arrive(1, 256);
        uint8_t* part = sc->part + (size_t)(ns * 16 + mt) * (2 * BLOB) + warp * WSLOT + lane * 16;
        uint32_t p[28];

        if (roleH) {
            unsigned* epoch_ptr = &sc->epoch[bid * 4 * 8];
            const unsigned tag = *epoch_ptr + 1;
            uint8_t* hout = sc->halo + (size_t)((warp * 8 + ns) * 2) * 2048 + lane * 16;
            auto send = [&](int kv) {
#pragma unroll
                for (int h = 0; h < 2; h++) {
                    uint32_t v[16];
                    v[14] = v[15] = 0;
#pragma unroll
                    for (int c = 0; c < 14; c++) v[c] = p[2 * c + h];
#pragma unroll
                    for (int c = 0; c < 14; c += 2) v[15] |= (v[c] & 1) << c;
#pragma unroll
                    for (int i = 0; i < 4; i++)
                        st_tagged(hout + (h * 8 + kv) * 2048 + i * 512, tagged(v[4 * i], v[4 * i + 1], tag), tagged(v[4 * i + 2], v[4 * i + 3], tag));
                }
            };
            float x0[56], x1[56];
            r.seek(0, 0);
            r.wait();
            r.run<XWN, 7, true>(x0);
#pragma unroll 1
            for (int i = 1; i < 7; i++) r.run<XWN, 7, false>(x0);
            r.run<XWN, 7, true>(x1);
            acc_fence(x0);
            pack_all(x0, p);
            send(0);
#pragma unroll 1
            for (int i = 1; i < 7; i++) r.run<XWN, 7, false>(x1, true, i < 6 || !wg, i < 6);
            asm volatile("wgmma.wait_group.sync.aligned 0;" ::: "memory");
            acc_fence(x1);
            pack_all(x1, p);
#pragma unroll
            for (int i = 0; i < 28; i++) p[i] = movm(p[i]);
            send(1);
            warp_arrive(base + BAR_RDY + 16);
            if (threadIdx.x == 0) *epoch_ptr = tag;
        } else if (!roleL) {
            uint8_t* blob = sc->ab + (size_t)((wg * 16 + mt) * 4 + ns) * BLOB + (warp & 3) * WSLOT + lane * 4;
            const uint32_t own = base + BRING + wg * SLOT + (warp & 3) * WSLOT + lane * 16;
            float x0[56], x1[56];
            r.seek(0, bslot_e(0));
            r.wait();
            r.run<XW, 7, true>(x0);
            r.run<XW, 7, false>(x0);
            r.seek(2, bslot_e(2));
#pragma unroll 1
            for (int i = 2; i < 7; i++) r.run<XW, 5, false>(x0);

            r.seek(7, bslot_e(7));
            r.run<XW, 5, true, -1>(x1);
            acc_fence(x0);
            pack_all<0, 14>(x0, p);
#pragma unroll
            for (int i = 0; i < 2; i++) {
                if (wg == i) store_frags<0, 14>(blob, p);
                else stage_frags<0, 4>(own + 5 * SLOT, p);
                r.run<XW, 5, false, -1>(x1);
                if (i == 0) pack_all<14, 28>(x0, p);
                if (wg == i) {
                    store_frags<14, 28>(blob, p);
                    warp_arrive(base + BAR_RDY + i * 8);
                } else {
                    stage_frags<4, 8>(own + 5 * SLOT, p);
                }
                r.run<XW, 5, false, -1>(x1);
            }
            stage_frags<8, 16>(own + 5 * SLOT, p);
            r.run<XW, 5, false, -1>(x1);
            stage_frags<16, 24>(own + 5 * SLOT, p);
            r.run<XW, 5, false, -1>(x1);
            stage_frags<24, 28>(own + 5 * SLOT, p);

            r.seek(14, bslot_e(14));
            r.take_turn();
            fence_async_smem();
            r.run<BIG, 7, true>(x0, false);
            acc_fence(x1);
            pack_all(x1, p);
            stage_frags<0, 16>(own, p);
            r.run<BIG, 7, false>(x0);
            stage_frags<16, 28>(own, p);
            r.take_turn();
            fence_async_smem();
            blob += (size_t)128 * BLOB;
            r.run<BIG, 7, false>(x0, false);
            r.run<BIG, 7, false>(x0);
#pragma unroll
            for (int i = 0; i < 28; i++) {
                if (i % B_SLICE == 0) r.run<BIG, 7, false>(x0);
                stg1(blob + i * 128, p[i]);
            }
            warp_arrive(base + BAR_RDY + 16);
#pragma unroll 1
            for (int i = 19 + 27 / B_SLICE; i < POUT; i++) r.run<BIG, 7, false>(x0);

            const uint32_t tag = lds1(base + TAG);
            r.seek(POUT, bslot_e(POUT));
            r.run<OUT, 7, true>(x1);
            acc_fence(x0);
            pack_all(x0, p);
            uint64_t u[14];
#pragma unroll
            for (int i = 0; i < 14; i++) u[i] = tagged(p[2 * i], p[2 * i + 1], tag);
#pragma unroll
            for (int k = 0; k < 2; k++) {
                if (wg == k) {
#pragma unroll
                    for (int i = 0; i < 7; i++) st_tagged(part + i * 512, u[2 * i], u[2 * i + 1]);
                }
                r.run<OUT, 7, false>(x1);
                if (warp * 32 + lane == k * 128)
                    asm volatile("red.relaxed.gpu.global.add.u32 [%0], 1;" ::"l"(&sc->cnt[(CNT_P + mt * 4 + ns) * 32]) : "memory");
            }
#pragma unroll
            for (int i = 3; i < 7; i++) r.run<OUT, 7, false, 1, true>(x1, i <= 7 - TURN, i < 7 - TURN || (i == 6 && !wg), i < 6);

            asm volatile("wgmma.wait_group.sync.aligned 0;" ::: "memory");
            acc_fence(x1);
            const uint32_t slab = base + (wg ? BRING + bslot_e(ELAST - 6) * SLOT : ((ELAST - 6) % NA) * SLOT) + (warp & 3) * WSLOT;
            store_out([&](int i) { return pack2(x1[2 * i], x1[2 * i + 1]); }, lane, slab, &maps.m[M_OUTA], par * 896 + col, blk * 128 + warp * 16);
        } else {
            const int g = lane >> 2, tig = lane & 3;
            const uint32_t hin = base + HALO + warp * HSLOT + lane * 4;
            const uint32_t hpub = warp < 7 ? hin + HSLOT : base + HSPARE + lane * 4;
            auto publish = [&](const uint32_t (&h)[14], int c0, int c1) {
#pragma unroll
                for (int c = 0; c < 14; c++)
                    if (c >= c0 && c < c1) sts1(hpub + c * 128, h[c]);
            };
            float y0[56], y1[56], y2[56];
            r.seek(0, 0);
            r.wait();
            r.run<QK, 6, true>(y0, y1);
#pragma unroll 1
            for (int i = 1; i < 14; i++) r.run<QK, 6, false>(y0, y1);

            uint32_t m1[8][4], m0[8][4], lo[14], hi[14], q[2][8][2];
            auto pack_q = [&](int b) {
                uint32_t v[14];
#pragma unroll
                for (int c = 0; c < 14; c++) v[c] = pack2(y0[4 * c + 2 * b], y0[4 * c + 2 * b + 1]);
#pragma unroll
                for (int t = 0; t < 8; t++) {
                    const int c = tile_of(t);
                    q[b][t][0] = (t & 3) == 2 ? (tig >= 2 ? v[c] : 0u) : v[c];
                    q[b][t][1] = (t & 3) == 1 ? (tig < 2 ? v[c + 1] : 0u) : v[c + 1];
                }
            };
            auto fetch = [&](uint32_t src, int hp, int i0) {
#pragma unroll
                for (int t = 4 * hp; t < 4 * hp + 4; t++) {
                    m0[t][i0] = (t & 3) == 2 ? dup(m0[t - 1][3], r.zero) : lds1(src + tile_of(t) * 128);
                    m0[t][3] = lds1(src + tile_of(t) * 128 + 128);
                }
            };
            r.seek(14, bslot_l(14));
            r.run<XWN, 6, true>(y2);
            acc_fence(y0);
            acc_fence(y1);
#pragma unroll
            for (int c = 0; c < 14; c++) hi[c] = pack2(y1[4 * c + 2], y1[4 * c + 3]);
            publish(hi, 0, 7);
            r.run<XWN, 6, false>(y2);
            publish(hi, 7, 14);
#pragma unroll
            for (int c = 0; c < 14; c++) lo[c] = pack2(y1[4 * c], y1[4 * c + 1]);
#pragma unroll
            for (int t = 0; t < 8; t++) {
                const int c = tile_of(t);
                const bool shared = (t & 3) == 2;
                m1[t][0] = shared ? dup(lo[c], r.zero) : lo[c];
                m1[t][1] = shared ? dup(hi[c], r.zero) : hi[c];
                m1[t][2] = lo[c + 1];
                m1[t][3] = hi[c + 1];
                m0[t][0] = dup(m1[t][0], r.zero);
                m0[t][2] = dup(lo[c + 1], 2 * r.zero);
            }
            r.run<XWN, 6, false>(y2);
            if (warp == 0) mbar_wait(base + BAR_HALO, 0);
            fetch(hin, 0, 1);
            pack_q(1);
            r.run<XWN, 6, false>(y2);
            fetch(hin, 1, 1);
            pack_q(0);
            r.mma_begin();
            float s[8][4];
#pragma unroll
            for (int step = 0; step < 2; step++) {
#pragma unroll
                for (int i = 0; i < 8; i++) {
                    const int b = 1 - (i >> 2), h = i & 3, t = 2 * h + step;
                    float (&d)[4] = s[2 * h + b];
                    if (step == 0) d[0] = d[1] = d[2] = d[3] = 0.f;
                    mma16816(d, b ? m1[t] : m0[t], q[b][t][0], q[b][t][1]);
                }
            }
            r.mma_end();
            r.run<XWN, 6, false>(y2, false);

            uint32_t pr[8], mx[4], mx1[4];
            {
                const bool cur0 = g <= 2 * tig, cur1 = g <= 2 * tig + 1;
#pragma unroll
                for (int i = 0; i < 8; i++) {
                    const int c = (i & 1) ? 2 : 0;
                    pr[i] = movm(pack2(cur0 ? s[i][c] : s[i][2 - c], cur1 ? s[i][c + 1] : s[i][3 - c]));
                }
            }
            r.run<XWN, 6, false>(y2);
            const uint32_t curmask = (2 * tig <= g ? 0x0000FFFFu : 0u) | (2 * tig + 1 <= g ? 0xFFFF0000u : 0u);
            {
                const uint32_t keep = (blk == 0 && warp == 0) ? curmask : 0xFFFFFFFFu;
#pragma unroll
                for (int i = 0; i < 4; i++) {
                    pr[2 * i] = (scale2(pr[2 * i]) & keep) | (0xCE6ECE6Eu & ~keep);
                    pr[2 * i + 1] = scale2(pr[2 * i + 1]);
                    mx[i] = max2(__byte_perm(pr[2 * i], pr[2 * i + 1], 0x5410), __byte_perm(pr[2 * i], pr[2 * i + 1], 0x7632));
                    mx1[i] = __shfl_xor_sync(0xffffffffu, mx[i], 1);
                }
            }
#pragma unroll
            for (int i = 0; i < 4; i++) {
                mx[i] = max2(mx[i], mx1[i]);
                mx1[i] = __shfl_xor_sync(0xffffffffu, mx[i], 2);
            }
            r.run<XWN, 6, false>(y2);
            constexpr float SCL = 1.4426950408889634f;
            float e0[8], e1[8], sm[8], sm1[8];
#pragma unroll
            for (int i = 0; i < 8; i++) {
                const uint32_t m2 = max2(mx[i >> 1], mx1[i >> 1]);
                sm[i] = ((i & 1) ? bf_hi(m2) : bf_lo(m2)) * -SCL;
                e0[i] = ex2(fmaf(bf_lo(pr[i]), SCL, sm[i]));
            }

            r.seek(21, bslot_l(21));
            r.run<BIG, 6, true>(y0);
            acc_fence(y2);
#pragma unroll
            for (int c = 0; c < 7; c++) hi[c] = movm(pack2(y2[4 * c + 2], y2[4 * c + 3]));
#pragma unroll
            for (int i = 0; i < 8; i++) e1[i] = ex2(fmaf(bf_hi(pr[i]), SCL, sm[i]));
            r.run<BIG, 6, false>(y0);
            publish(hi, 0, 7);
#pragma unroll
            for (int c = 7; c < 14; c++) hi[c] = movm(pack2(y2[4 * c + 2], y2[4 * c + 3]));
            r.run<BIG, 6, false>(y0);
            publish(hi, 7, 14);
#pragma unroll
            for (int i = 0; i < 8; i++) {
                sm[i] = e0[i] + e1[i];
                sm1[i] = __shfl_xor_sync(0xffffffffu, sm[i], 1);
            }
            r.run<BIG, 6, false>(y0);
#pragma unroll
            for (int c = 0; c < 14; c++) lo[c] = movm(pack2(y2[4 * c], y2[4 * c + 1]));
            r.run<BIG, 6, false>(y0);
#pragma unroll
            for (int i = 0; i < 8; i++) {
                sm[i] += sm1[i];
                sm1[i] = __shfl_xor_sync(0xffffffffu, sm[i], 2);
            }
#pragma unroll
            for (int t = 0; t < 8; t++) {
                const int c = tile_of(t);
                const bool shared = (t & 3) == 2;
                m1[t][0] = shared ? dup(lo[c], r.zero) : lo[c];
                m1[t][1] = lo[c + 1];
                m1[t][2] = shared ? dup(hi[c], r.zero) : hi[c];
                m1[t][3] = hi[c + 1];
                m0[t][0] = dup(m1[t][0], r.zero);
                m0[t][1] = dup(lo[c + 1], 2 * r.zero);
            }
            r.run<BIG, 6, false>(y0);
            if (warp == 0) mbar_wait(base + BAR_HALO + 8, 0);
            const uint32_t vin = warp ? hin : hin + 8 * HSLOT;
            fetch(vin, 0, 2);
#pragma unroll
            for (int i = 0; i < 8; i++) {
                const float inv = rcp(sm[i] + sm1[i]);
                pr[i] = pack2(e0[i] * inv, e1[i] * inv);
            }
            r.run<BIG, 6, false>(y0);
            fetch(vin, 1, 2);
            uint32_t pb[8][2];
#pragma unroll
            for (int t = 0; t < 8; t++) {
                pb[t][t & 1] = band(pr[t], curmask);
                pb[t][1 - (t & 1)] = band(pr[t], ~curmask);
            }
            r.mma_begin();
            float o[2][8][4];
#pragma unroll
            for (int i = 0; i < 16; i++) {
                const int b = 1 - (i >> 3), t = i & 7;
                float (&d)[4] = o[b][t];
                d[0] = d[1] = d[2] = d[3] = 0.f;
                mma16816(d, b ? m1[t] : m0[t], pb[(t & 6) + b][0], pb[(t & 6) + b][1]);
            }
            r.mma_end();
            r.run<BIG, 6, false>(y0, false);
            uint8_t* odst = sc->o + (size_t)mt * 7 * SLOT + ns * (14 * 2048) + warp * 256 + lane * 4;
#pragma unroll
            for (int hp = 0; hp < 2; hp++) {
#pragma unroll
                for (int b = 0; b < 2; b++) {
                    const float (&u)[8][4] = o[b];
                    const int t = 4 * hp;
                    uint32_t* w = p + 14 * hp + b;
                    w[0] = pack2(u[t][0], u[t][1]);
                    w[2] = pack2(u[t][2], u[t][3]);
                    w[4] = pack2(u[t + 1][0], u[t + 1][1]);
                    w[6] = pack2(g < 4 ? u[t + 1][2] : u[t + 2][0], g < 4 ? u[t + 1][3] : u[t + 2][1]);
                    w[8] = pack2(u[t + 2][2], u[t + 2][3]);
                    w[10] = pack2(u[t + 3][0], u[t + 3][1]);
                    w[12] = pack2(u[t + 3][2], u[t + 3][3]);
                }
            }
#pragma unroll
            for (int i = 0; i < 28; i++) {
                if (i >= O_FIRST && (i - O_FIRST) % O_SLICE == 0) r.run<BIG, 6, false>(y0);
                stg1(odst + (i >> 1) * 2048 + (i & 1) * 128, p[i]);
            }
            warp_arrive(base + BAR_RDY + 16);

#pragma unroll 1
            for (int i = 30 + (27 - O_FIRST) / O_SLICE; i <= LLAST - LTURN; i++) r.run<BIG, 6, false>(y0);
            r.seek(LLAST + 1 - LTURN, bslot_l(LLAST + 1 - LTURN));
#pragma unroll
            for (int i = 0; i < LTURN; i++) r.run<BIG, 6, false, 1, true>(y0, i == 0, i == LTURN - 1 && !wg, i < LTURN - 1);
            const uint32_t parity = lds1(base + TAG) & 1;
            const uint32_t slab = base + (wg ? HALO : LSLAB) + (warp & 3) * WSLOT;
            mbar_wait(base + BAR_PART + wg * 8, 0);
#pragma unroll 1
            for (int n = 0; n < SPIN_LIMIT; n++) {
#pragma unroll
                for (int i = 0; i < 7; i++) lds4(slab + i * 512 + lane * 16, p + 4 * i);
#pragma unroll
                for (int i = 0; i < 28; i += 2) p[i] ^= parity;
                const uint32_t stale = or3(or3(or3(p[0], p[2], p[4]), or3(p[6], p[8], p[10]), or3(p[12], p[14], p[16])),
                                           or3(p[18], p[20], p[22]), or3(p[24], p[26], 0));
                if (__all_sync(0xffffffffu, !(stale & 1))) break;
#pragma unroll
                for (int i = 0; i < 7; i++) ld_tagged(part + i * 512, p[4 * i], p[4 * i + 1], p[4 * i + 2], p[4 * i + 3]);
#pragma unroll
                for (int i = 0; i < 7; i++)
                    asm volatile("st.shared.v4.b32 [%0], {%1,%2,%3,%4};" ::"r"(slab + i * 512 + lane * 16), "r"(p[4 * i]), "r"(p[4 * i + 1]), "r"(p[4 * i + 2]), "r"(p[4 * i + 3]) : "memory");
            }
            asm volatile("wgmma.wait_group.sync.aligned 0;" ::: "memory");
            acc_fence(y0);
            store_out([&](int i) { return add2(pack2(y0[2 * i], y0[2 * i + 1]), p[i]); }, lane, slab, &maps.m[M_OUTB], 448 + col, mt * 128 + warp * 16);
        }
    }
}

typedef CUresult (*EncodeFn)(CUtensorMap*, CUtensorMapDataType, cuuint32_t, void*, const cuuint64_t*, const cuuint64_t*,
                             const cuuint32_t*, const cuuint32_t*, CUtensorMapInterleave, CUtensorMapSwizzle,
                             CUtensorMapL2promotion, CUtensorMapFloatOOBfill);

struct Dim { uint64_t size, stride; uint32_t box; };
void encode(EncodeFn fn, CUtensorMap* m, const void* ptr, CUtensorMapSwizzle sw, Dim d0, Dim d1, Dim d2 = {0, 0, 0}, Dim d3 = {0, 0, 0}) {
    const cuuint64_t dims[4] = {d0.size, d1.size, d2.size, d3.size};
    const cuuint64_t strides[3] = {d1.stride, d2.stride, d3.stride};
    const cuuint32_t box[4] = {d0.box, d1.box, d2.box, d3.box};
    const cuuint32_t es[4] = {1, 1, 1, 1};
    fn(m, CU_TENSOR_MAP_DATA_TYPE_BFLOAT16, d3.size ? 4 : d2.size ? 3 : 2, const_cast<void*>(ptr), dims, strides, box, es,
       CU_TENSOR_MAP_INTERLEAVE_NONE, sw, CU_TENSOR_MAP_L2_PROMOTION_L2_128B, CU_TENSOR_MAP_FLOAT_OOB_FILL_NONE);
}

}

extern "C" void kernel_launch(void* const* d_in, const int* in_sizes, int n_in, void* d_out, int out_size) {
    (void)in_sizes; (void)n_in; (void)out_size;
    void* fnp = nullptr;
    cudaDriverEntryPointQueryResult st;
    cudaGetDriverEntryPoint("cuTensorMapEncodeTiled", &fnp, cudaEnableDefault, &st);
    EncodeFn fn = (EncodeFn)fnp;
    void* scratch = nullptr;
    cudaGetSymbolAddress(&scratch, g_scratch);
    int dev = 0, sms = 0;
    cudaGetDevice(&dev);
    cudaDeviceGetAttribute(&sms, cudaDevAttrMultiProcessorCount, dev);
    auto kernel = sms == 132 ? fused_kernel<true> : fused_kernel<false>;
    cudaFuncSetAttribute(kernel, cudaFuncAttributeMaxDynamicSharedMemorySize, SMEM_BYTES);

    const CUtensorMapSwizzle S128 = CU_TENSOR_MAP_SWIZZLE_128B, S0 = CU_TENSOR_MAP_SWIZZLE_NONE;
    const Dim one = {1, 16, 1};
    Maps maps;
    encode(fn, &maps.m[M_XA], d_in[0], S128, {896, 2, 64}, {1024, 1792, 128}, one, one);
    encode(fn, &maps.m[M_WQK], d_in[1], S128, {112, 2, 64}, {448, 2688, 32}, {3, 896, 2}, {4, 224, 1});
    encode(fn, &maps.m[M_WV], d_in[1], S128, {112, 2, 64}, {448, 2688, 64}, one, {12, 224, 1});
    encode(fn, &maps.m[M_XH], d_in[0], S128, {448, 2, 64}, {128, 1792, 8}, {8, 128 * 1792, 8}, {2, 896, 2});
    encode(fn, &maps.m[M_WO], d_in[2], S128, {112, 2, 64}, {448, 896, 64}, one, {4, 224, 1});
    encode(fn, &maps.m[M_XB], d_in[3], S128, {448, 2, 64}, {1024, 896, 64}, {2, 896 * 1024, 2}, one);
    encode(fn, &maps.m[M_CR], d_in[4], S128, {2048, 2, 64}, {2048, 4096, 128});
    encode(fn, &maps.m[M_CI], d_in[5], S128, {2048, 2, 64}, {2048, 4096, 128});
    encode(fn, &maps.m[M_WR], d_in[6], S128, {448, 2, 64}, {448, 896, 112}, one, one);
    encode(fn, &maps.m[M_WI], d_in[7], S128, {448, 2, 64}, {448, 896, 112});
    encode(fn, &maps.m[M_OUTA], d_out, S0, {1792, 2, 112}, {1024, 3584, 8});
    encode(fn, &maps.m[M_OUTB], d_out, S0, {896, 2, 112}, {2048, 1792, 8});

    kernel<<<132, 384, SMEM_BYTES>>>((Scratch*)scratch, maps);
}
```

```cpp
#include <cuda.h>
#include <cuda_bf16.h>
#include <cuda_runtime.h>
#include <stdint.h>

namespace {

constexpr uint32_t SLOT = 16384;
constexpr int NA = 7;
constexpr uint32_t BRING = NA * SLOT;
constexpr uint32_t HALO = BRING + 6 * SLOT;
constexpr uint32_t HSLOT = 1792;
constexpr uint32_t WSLOT = 3584;
constexpr uint32_t BLOB = 14336;
constexpr uint32_t BARS = 14 * SLOT;
constexpr uint32_t BAR_FULL = BARS;
constexpr uint32_t BAR_EMPTY = BARS + 64;
constexpr uint32_t BAR_RDY = BARS + 128;
constexpr uint32_t BAR_DEP = BARS + 168;
constexpr uint32_t BAR_HALO = BARS + 192;
constexpr uint32_t BAR_PART = BARS + 208;
constexpr uint32_t BAR_HINT = BARS + 224;
constexpr uint32_t BAR_X = BARS + 152;
constexpr uint32_t TAG = BARS + 240;
constexpr uint32_t HSPARE = BARS + 256 + 1024;
constexpr uint32_t SMEM_BYTES = HSPARE + HSLOT;
constexpr uint32_t base = 1024;
constexpr int SPIN_LIMIT = 1 << 16;

constexpr int LEAD = 2;
constexpr int PACE0 = 700, PACE = 450;
constexpr int PACE_X = 250;
constexpr int HALO_K_AT = 11;
constexpr int HALO_V_AT = 19;
constexpr int B_SLICE = 4;
constexpr int O_FIRST = 7, O_SLICE = 3;
constexpr int TURN = 4, LTURN = 5;
constexpr uint32_t GPC_MAP = 0x64753210u;
constexpr int NBE = 13;
constexpr int POUT = 33 + NBE;
constexpr int ELAST = POUT + 6;
constexpr int LLAST = 65 - NBE;
constexpr uint32_t LSLAB = ((LLAST - 6) % NA) * SLOT;
static_assert(TURN <= 4 && LTURN <= 5, "the output is staged in the slots of the seventh-last stage");

enum { M_XB, M_XA, M_XH, M_WR, M_WQK, M_WV, M_WO, M_WI, M_CR, M_CI, M_OUTA, M_OUTB, M_COUNT };
struct __align__(64) Maps { CUtensorMap m[M_COUNT]; };

constexpr int CNT_A = 0;
constexpr int CNT_B = 8;
constexpr int CNT_W = 12;
constexpr int CNT_O = 16;
constexpr int CNT_P = 32;
constexpr int CNT_COUNT = 96;

struct Scratch {
    uint8_t ab[64 * 4 * BLOB];
    uint8_t o[16 * 7 * SLOT];
    uint8_t part[64 * 2 * BLOB];
    uint8_t halo[64 * 2 * 2048];
    uint8_t wo[4 * 7 * SLOT];
    unsigned cnt[CNT_COUNT * 32];
    unsigned epoch[132 * 4 * 8];
};
__device__ __align__(1024) Scratch g_scratch;

__device__ __forceinline__ unsigned clk32() { unsigned c; asm volatile("mov.u32 %0, %%clock;" : "=r"(c)); return c; }

#define PROF(idx)

__device__ __forceinline__ void mbar_init(uint32_t bar, uint32_t cnt) {
    asm volatile("mbarrier.init.shared::cta.b64 [%0], %1;" ::"r"(bar), "r"(cnt) : "memory");
}
__device__ __forceinline__ void mbar_expect(uint32_t bar, uint32_t bytes) {
    asm volatile("mbarrier.arrive.expect_tx.shared::cta.b64 _, [%0], %1;" ::"r"(bar), "r"(bytes) : "memory");
}
__device__ __forceinline__ void mbar_arrive(uint32_t bar) {
    asm volatile("mbarrier.arrive.shared::cta.b64 _, [%0];" ::"r"(bar) : "memory");
}
__device__ __forceinline__ bool mbar_try(uint32_t bar, uint32_t parity) {
    uint32_t ok;
    asm volatile("{\n.reg .pred p;\nmbarrier.try_wait.parity.shared::cta.b64 p, [%1], %2;\nselp.u32 %0, 1, 0, p;\n}\n"
                 : "=r"(ok) : "r"(bar), "r"(parity) : "memory");
    return ok;
}
__device__ __forceinline__ void mbar_wait(uint32_t bar, uint32_t parity) {
#pragma unroll 1
    for (int n = 0; n < SPIN_LIMIT; n++)
        if (mbar_try(bar, parity)) break;
}
__device__ __forceinline__ bool elect() {
    uint32_t p;
    asm volatile("{\n.reg .pred p;\nelect.sync _|p, 0xffffffff;\nselp.u32 %0, 1, 0, p;\n}\n" : "=r"(p));
    return p;
}
__device__ __forceinline__ void nb_sync(int id, int n) { asm volatile("bar.sync %0, %1;" ::"r"(id), "r"(n) : "memory"); }
__device__ __forceinline__ void nb_arrive(int id, int n) { asm volatile("bar.arrive %0, %1;" ::"r"(id), "r"(n) : "memory"); }
__device__ __forceinline__ void warp_arrive(uint32_t bar) {
    __syncwarp();
    if (elect()) mbar_arrive(bar);
}
__device__ __forceinline__ uint32_t or3(uint32_t a, uint32_t b, uint32_t c) {
    uint32_t r;
    asm("lop3.b32 %0, %1, %2, %3, 0xFE;" : "=r"(r) : "r"(a), "r"(b), "r"(c));
    return r;
}
__device__ __forceinline__ uint32_t band(uint32_t x, uint32_t m) {
    uint32_t r;
    asm volatile("and.b32 %0, %1, %2;" : "=r"(r) : "r"(x), "r"(m));
    return r;
}
__device__ __forceinline__ uint32_t dup(uint32_t x, uint32_t zero) {
    uint32_t r;
    asm volatile("xor.b32 %0, %1, %2;" : "=r"(r) : "r"(x), "r"(zero));
    return r;
}

__device__ __forceinline__ void tma_ld2(uint32_t dst, const CUtensorMap* m, int c0, int c1, uint32_t bar) {
    asm volatile("cp.async.bulk.tensor.2d.shared::cluster.global.mbarrier::complete_tx::bytes [%0], [%1, {%3, %4}], [%2];"
                 ::"r"(dst), "l"(m), "r"(bar), "r"(c0), "r"(c1) : "memory");
}
__device__ __forceinline__ void tma_ld4(uint32_t dst, const CUtensorMap* m, int c0, int c1, int c2, int c3, uint32_t bar) {
    asm volatile("cp.async.bulk.tensor.4d.shared::cluster.global.mbarrier::complete_tx::bytes [%0], [%1, {%3, %4, %5, %6}], [%2];"
                 ::"r"(dst), "l"(m), "r"(bar), "r"(c0), "r"(c1), "r"(c2), "r"(c3) : "memory");
}
__device__ __forceinline__ void tma_ld5(uint32_t dst, const CUtensorMap* m, int c0, int c2, int c3, int c4, uint32_t bar) {
    asm volatile("cp.async.bulk.tensor.5d.shared::cluster.global.mbarrier::complete_tx::bytes [%0], [%1, {%3, 0, %4, %5, %6}], [%2];"
                 ::"r"(dst), "l"(m), "r"(bar), "r"(c0), "r"(c2), "r"(c3), "r"(c4) : "memory");
}
__device__ __forceinline__ void bulk_ld(uint32_t dst, const void* src, uint32_t bytes, uint32_t bar) {
    asm volatile("cp.async.bulk.shared::cluster.global.mbarrier::complete_tx::bytes [%0], [%1], %2, [%3];"
                 ::"r"(dst), "l"(src), "r"(bytes), "r"(bar) : "memory");
}
__device__ __forceinline__ void bulk_st(void* dst, uint32_t src, uint32_t bytes) {
    asm volatile("cp.async.bulk.global.shared::cta.bulk_group [%0], [%1], %2;" ::"l"(dst), "r"(src), "r"(bytes) : "memory");
}
__device__ __forceinline__ void tma_st2(const CUtensorMap* m, int c0, int c1, uint32_t src) {
    asm volatile("cp.async.bulk.tensor.2d.global.shared::cta.bulk_group [%0, {%1, %2}], [%3];"
                 ::"l"(m), "r"(c0), "r"(c1), "r"(src) : "memory");
}
__device__ __forceinline__ void bulk_commit() { asm volatile("cp.async.bulk.commit_group;" ::: "memory"); }
__device__ __forceinline__ void bulk_wait_read() { asm volatile("cp.async.bulk.wait_group.read 0;" ::: "memory"); }
__device__ __forceinline__ void fence_async_smem() { asm volatile("fence.proxy.async.shared::cta;" ::: "memory"); }
__device__ __forceinline__ void fence_async_global() { asm volatile("fence.proxy.async.global;" ::: "memory"); }

__device__ __forceinline__ void signal(Scratch* sc, int idx) {
    asm volatile("fence.proxy.async;\nred.relaxed.gpu.global.add.u32 [%0], 1;" ::"l"(&sc->cnt[idx * 32]) : "memory");
}
__device__ __forceinline__ unsigned peek(const unsigned* p) {
    unsigned v;
    asm volatile("ld.relaxed.gpu.global.u32 %0, [%1];" : "=r"(v) : "l"(p) : "memory");
    return v;
}
__device__ __forceinline__ void await(Scratch* sc, int idx, unsigned target) {
    const unsigned* p = &sc->cnt[idx * 32];
#pragma unroll 1
    for (int n = 0; n < SPIN_LIMIT; n++)
        if ((int)(peek(p) - target) >= 0) break;
    asm volatile("fence.acquire.gpu;" ::: "memory");
}
__device__ __forceinline__ void wait_dep(int k) {
    mbar_wait(base + BAR_DEP + k * 8, 0);
    fence_async_global();
}

#define WG_REGS                                                                                                     \
    "{%0,%1,%2,%3,%4,%5,%6,%7,%8,%9,%10,%11,%12,%13,%14,%15,%16,%17,%18,%19,%20,%21,%22,%23,%24,%25,%26,%27,"       \
    "%28,%29,%30,%31,%32,%33,%34,%35,%36,%37,%38,%39,%40,%41,%42,%43,%44,%45,%46,%47,%48,%49,%50,%51,%52,%53,%54,%55}"
#define WG_OPS(C)                                                                                                   \
    C(d[0]), C(d[1]), C(d[2]), C(d[3]), C(d[4]), C(d[5]), C(d[6]), C(d[7]), C(d[8]), C(d[9]), C(d[10]), C(d[11]),   \
    C(d[12]), C(d[13]), C(d[14]), C(d[15]), C(d[16]), C(d[17]), C(d[18]), C(d[19]), C(d[20]), C(d[21]), C(d[22]),   \
    C(d[23]), C(d[24]), C(d[25]), C(d[26]), C(d[27]), C(d[28]), C(d[29]), C(d[30]), C(d[31]), C(d[32]), C(d[33]),   \
    C(d[34]), C(d[35]), C(d[36]), C(d[37]), C(d[38]), C(d[39]), C(d[40]), C(d[41]), C(d[42]), C(d[43]), C(d[44]),   \
    C(d[45]), C(d[46]), C(d[47]), C(d[48]), C(d[49]), C(d[50]), C(d[51]), C(d[52]), C(d[53]), C(d[54]), C(d[55])

template <int TA, int TB, int SB, bool INIT, uint32_t AH, uint32_t BH>
__device__ __forceinline__ void wgmma112(float (&d)[56], uint32_t alo, uint32_t blo) {
    if (INIT) {
        asm volatile("{\n.reg .pred p;\n.reg .b64 da, db;\nsetp.ne.b32 p, 0, 0;\nmov.b64 da, {%56, %61};\nmov.b64 db, {%57, %62};\n"
                     "wgmma.mma_async.sync.aligned.m64n112k16.f32.bf16.bf16 " WG_REGS ", da, db, p, 1, %59, %60, %58;\n}\n"
                     : WG_OPS("=f") : "r"(alo), "r"(blo), "n"(TB), "n"(SB), "n"(TA), "n"(AH), "n"(BH));
    } else {
        asm volatile("{\n.reg .pred p;\n.reg .b64 da, db;\nsetp.ne.b32 p, 1, 0;\nmov.b64 da, {%56, %61};\nmov.b64 db, {%57, %62};\n"
                     "wgmma.mma_async.sync.aligned.m64n112k16.f32.bf16.bf16 " WG_REGS ", da, db, p, 1, %59, %60, %58;\n}\n"
                     : WG_OPS("+f") : "r"(alo), "r"(blo), "n"(TB), "n"(SB), "n"(TA), "n"(AH), "n"(BH));
    }
}
__device__ __forceinline__ void acc_fence(float (&d)[56]) {
#pragma unroll
    for (int i = 0; i < 56; i++) asm volatile("" : "+f"(d[i])::"memory");
}

__device__ __forceinline__ uint32_t pack2(float lo, float hi) {
    uint32_t r;
    asm volatile("cvt.rn.bf16x2.f32 %0, %1, %2;" : "=r"(r) : "f"(hi), "f"(lo));
    return r;
}
__device__ __forceinline__ uint32_t movm(uint32_t a) {
    uint32_t r;
    asm volatile("movmatrix.sync.aligned.m8n8.trans.b16 %0, %1;" : "=r"(r) : "r"(a));
    return r;
}
__device__ __forceinline__ void stsm4(uint32_t addr, uint32_t a, uint32_t b, uint32_t c, uint32_t d) {
    asm volatile("stmatrix.sync.aligned.m8n8.x4.shared.b16 [%0], {%1,%2,%3,%4};" ::"r"(addr), "r"(a), "r"(b), "r"(c), "r"(d) : "memory");
}
__device__ __forceinline__ void sts1(uint32_t addr, uint32_t a) { asm volatile("st.shared.b32 [%0], %1;" ::"r"(addr), "r"(a) : "memory"); }
__device__ __forceinline__ uint32_t lds1(uint32_t addr) {
    uint32_t a;
    asm volatile("ld.shared.b32 %0, [%1];" : "=r"(a) : "r"(addr) : "memory");
    return a;
}
__device__ __forceinline__ void lds4(uint32_t addr, uint32_t* v) {
    asm volatile("ld.shared.v4.b32 {%0,%1,%2,%3}, [%4];" : "=r"(v[0]), "=r"(v[1]), "=r"(v[2]), "=r"(v[3]) : "r"(addr) : "memory");
}
__device__ __forceinline__ void stg1(uint8_t* p, uint32_t a) { asm volatile("st.global.b32 [%0], %1;" ::"l"(p), "r"(a) : "memory"); }
__device__ __forceinline__ uint64_t tagged(uint32_t lo, uint32_t hi, uint32_t tag) {
    uint64_t r;
    asm volatile("{\n.reg .b32 t;\nlop3.b32 t, %1, %3, 1, 0xD8;\nmov.b64 %0, {t, %2};\n}\n" : "=l"(r) : "r"(lo), "r"(hi), "r"(tag));
    return r;
}
__device__ __forceinline__ void st_tagged(uint8_t* p, uint64_t x, uint64_t y) {
    asm volatile("st.relaxed.gpu.global.v2.b64 [%0], {%1, %2};" ::"l"(p), "l"(x), "l"(y) : "memory");
}
__device__ __forceinline__ void mma16816(float (&d)[4], const uint32_t (&a)[4], uint32_t b0, uint32_t b1) {
    asm volatile("mma.sync.aligned.m16n8k16.row.col.f32.bf16.bf16.f32 {%0,%1,%2,%3}, {%4,%5,%6,%7}, {%8,%9}, {%0,%1,%2,%3};"
                 : "+f"(d[0]), "+f"(d[1]), "+f"(d[2]), "+f"(d[3]) : "r"(a[0]), "r"(a[1]), "r"(a[2]), "r"(a[3]), "r"(b0), "r"(b1));
}
__device__ __forceinline__ uint32_t add2(uint32_t a, uint32_t b) {
    uint32_t r;
    asm("add.rn.bf16x2 %0, %1, %2;" : "=r"(r) : "r"(a), "r"(b));
    return r;
}
__device__ __forceinline__ uint32_t scale2(uint32_t x) {
    uint32_t r;
    asm("{\n.reg .b32 t;\nmul.rn.bf16x2 t, %1, %3;\nfma.rn.bf16x2 %0, %1, %2, t;\n}\n" : "=r"(r) : "r"(x), "r"(0x3E423E42u), "r"(0xB9F7B9F7u));
    return r;
}
__device__ __forceinline__ uint32_t max2(uint32_t a, uint32_t b) {
    uint32_t r;
    asm("max.bf16x2 %0, %1, %2;" : "=r"(r) : "r"(a), "r"(b));
    return r;
}
__device__ __forceinline__ void ld_tagged(const uint8_t* p, uint32_t& a, uint32_t& ta, uint32_t& b, uint32_t& tb) {
    asm volatile("{\n.reg .b64 x, y;\nld.relaxed.gpu.global.v2.b64 {x, y}, [%4];\nmov.b64 {%0, %1}, x;\nmov.b64 {%2, %3}, y;\n}\n"
                 : "=r"(a), "=r"(ta), "=r"(b), "=r"(tb) : "l"(p) : "memory");
}
__device__ __forceinline__ float bf_lo(uint32_t v) { return __uint_as_float(v << 16); }
__device__ __forceinline__ float bf_hi(uint32_t v) { return __uint_as_float(v & 0xFFFF0000u); }
__device__ __forceinline__ float rcp(float x) { float r; asm("rcp.approx.ftz.f32 %0, %1;" : "=f"(r) : "f"(x)); return r; }
__device__ __forceinline__ float ex2(float x) { float r; asm volatile("ex2.approx.ftz.f32 %0, %1;" : "=f"(r) : "f"(x)); return r; }

__device__ __forceinline__ uint32_t full_bar(int stage) { return base + BAR_FULL + (stage & 7) * 8; }
__device__ __forceinline__ void wait_released(int j) { mbar_wait(base + BAR_EMPTY + (j & 7) * 8, (j >> 3) & 1); }

template <int V>
struct Int { static constexpr int value = V; };

__host__ __device__ constexpr int bslot_e(int i) { return (i < 2 || i >= 14) ? (i + 5) % 7 : (i + 1) % 5; }
__host__ __device__ constexpr int bslot_l(int i) { return (i + 5) % 6; }
__host__ __device__ constexpr int bslot_h(int i) { return (i + 5) % 7; }

template <uint32_t OFF>
struct Feed {
    int stage;
    uint32_t dst;
    __device__ __forceinline__ void seek(int i, int slot) { stage = i; dst = base + OFF + slot * SLOT; }
    template <int N>
    __device__ __forceinline__ uint32_t acquire() { wait_released(stage - N); return full_bar(stage); }
    template <int N>
    __device__ __forceinline__ void next() {
        stage++;
        dst += SLOT;
        if (dst == base + OFF + N * SLOT) dst = base + OFF;
    }
};
__device__ __forceinline__ int skip_own(int n, int mt) { return n == mt ? 15 : n; }

struct Desc { uint32_t lo, hi; };
__host__ __device__ constexpr Desc desc_const(uint32_t lbo, uint32_t sbo, uint32_t mode) { return {(lbo >> 4) << 16, (sbo >> 4) | (mode << 30)}; }
constexpr Desc D_K128 = desc_const(16, 1024, 1);
constexpr Desc D_N128 = desc_const(8192, 1024, 1);
constexpr Desc D_BLOB = desc_const(128, 256, 0);
constexpr Desc D_OT = desc_const(2048, 128, 0);

enum Kind { XW, XWN, QK, BIG, OUT };

struct Ring {
    int stage;
    uint32_t a, b;
    uint32_t wg;
    uint32_t zero;
    bool releaser;
    __device__ __forceinline__ void seek(int i, int bslot) {
        stage = i;
        a = (base + (i % NA) * SLOT) >> 4;
        b = (base + BRING + bslot * SLOT) >> 4;
    }
    __device__ __forceinline__ void wait() { mbar_wait(full_bar(stage), (stage >> 3) & 1); }
    __device__ __forceinline__ void take_turn() { nb_sync(1 + wg, 256); }
    __device__ __forceinline__ void pin() {
        asm volatile("{\n.reg .pred p;\nsetp.ne.u32 p, %0, 0;\nPIN:\npmevent 7;\n@p bra.uni PIN;\n}\n" ::"r"(zero) : "memory");
    }
    __device__ __forceinline__ void mma_begin() {
        if (!wg) take_turn();
        pin();
    }
    __device__ __forceinline__ void mma_end() {
        pin();
        if (wg) nb_arrive(3, 256);
        nb_sync(3 - wg, 256);
    }
    template <Kind K, int NBS, bool INIT, int SB = 1, bool TAIL = false>
    __device__ __forceinline__ void run(float (&d)[56], float (&e)[56], bool first = true, bool last = true, bool more = true) {
        if (first) take_turn();
        asm volatile("wgmma.fence.sync.aligned;" ::: "memory");
        if (K == QK) {
            const uint32_t da = D_K128.lo + (base >> 4) + (stage >> 1) * (SLOT >> 4) + (stage & 1) * 4 + wg * 512, db = D_N128.lo + b;
            wgmma112<0, 1, 1, INIT, D_K128.hi, D_N128.hi>(d, da, db);
            wgmma112<0, 1, 1, INIT, D_K128.hi, D_N128.hi>(e, da, db + 256);
            wgmma112<0, 1, 1, false, D_K128.hi, D_N128.hi>(d, da + 2, db + 128);
            wgmma112<0, 1, 1, false, D_K128.hi, D_N128.hi>(e, da + 2, db + 384);
        } else {
            constexpr int TA = K == OUT, TB = K != XW;
            constexpr uint32_t sa = K == OUT ? 256 : 2, sb = K == XW ? 2 : K == BIG ? 224 : 128;
            constexpr Desc A = K == OUT ? D_OT : D_K128, B = K == XW ? D_K128 : K == BIG ? D_BLOB : D_N128;
            const uint32_t da = A.lo + a + wg * (K == OUT ? 64 : 512), db = B.lo + b;
            wgmma112<TA, TB, SB, INIT, A.hi, B.hi>(d, da, db);
#pragma unroll
            for (int q = 1; q < 4; q++) wgmma112<TA, TB, SB, false, A.hi, B.hi>(d, da + q * sa, db + q * sb);
        }
        asm volatile("wgmma.commit_group.sync.aligned;" ::: "memory");
        if (!TAIL) asm volatile("wgmma.wait_group.sync.aligned 1;" ::: "memory");
        if (last) nb_arrive(2 - wg, 256);
        if (!TAIL && stage > 0 && releaser) mbar_arrive(base + BAR_EMPTY + ((stage - 1) & 7) * 8);
        stage++;
        a += SLOT >> 4;
        if (a == (base + NA * SLOT) >> 4) a = base >> 4;
        b += SLOT >> 4;
        if (b == (base + BRING + NBS * SLOT) >> 4) b = (base + BRING) >> 4;
        if (more) wait();
    }
    template <Kind K, int NBS, bool INIT, int SB = 1, bool TAIL = false>
    __device__ __forceinline__ void run(float (&d)[56], bool first = true, bool last = true, bool more = true) {
        run<K, NBS, INIT, SB, TAIL>(d, d, first, last, more);
    }
};

template <int I0 = 0, int I1 = 28>
__device__ __forceinline__ void pack_all(const float (&d)[56], uint32_t (&p)[28]) {
#pragma unroll
    for (int i = I0; i < I1; i++) p[i] = pack2(d[2 * i], d[2 * i + 1]);
}
template <int I0, int I1>
__device__ __forceinline__ void store_frags(uint8_t* dst, const uint32_t (&p)[28]) {
#pragma unroll
    for (int i = I0; i < I1; i++) stg1(dst + i * 128, p[i]);
}
template <int I0, int I1>
__device__ __forceinline__ void stage_frags(uint32_t lane_addr, const uint32_t (&p)[28]) {
#pragma unroll
    for (int i = I0; i < I1; i += 4) stsm4(lane_addr + i * 128, p[i], p[i + 1], p[i + 2], p[i + 3]);
}
template <class F>
__device__ __forceinline__ void store_out(F frag, int lane, uint32_t slab, const CUtensorMap* m, int c0, int c1) {
    const bool swap = lane & 16;
    const uint32_t addr = slab + (lane & 7) * 224 + ((lane >> 3) ^ ((lane >> 2) & 1)) * 16;
#pragma unroll
    for (int h = 0; h < 2; h++) {
#pragma unroll
        for (int c = 0; c < 14; c += 4) {
            const uint32_t t0 = frag(2 * c + h), t1 = frag(2 * c + 2 + h);
            if (c < 12) {
                const uint32_t t2 = frag(2 * c + 4 + h), t3 = frag(2 * c + 6 + h);
                stsm4(addr + h * 1792 + c * 16, swap ? t1 : t0, swap ? t0 : t1, swap ? t3 : t2, swap ? t2 : t3);
            } else {
                asm volatile("stmatrix.sync.aligned.m8n8.x2.shared.b16 [%0], {%1,%2};" ::"r"(addr + h * 1792 + c * 16), "r"(swap ? t1 : t0), "r"(swap ? t0 : t1) : "memory");
            }
        }
        fence_async_smem();
        __syncwarp();
        if (elect()) tma_st2(m, c0, c1 + 8 * h, slab + h * 1792);
    }
    if (elect()) {
        bulk_commit();
        bulk_wait_read();
    }
}
__host__ __device__ constexpr int tile_of(int t) { return 7 * (t >> 2) + 3 * ((t >> 1) & 1) + 2 * (t & 1); }

struct Role {
    int kind;
    int par, blk;
    int ns, id;
};
template <bool BY_SM>
__device__ __forceinline__ Role decode_role() {
    uint32_t sm;
    if (BY_SM) asm volatile("mov.u32 %0, %%smid;" : "=r"(sm));
    else asm volatile("mov.u32 %0, %%ctaid.x;" : "=r"(sm));
    const int tpc = sm >> 1, q2 = ((tpc - 32) * 37) >> 8;
    const int gpc = tpc < 32 ? tpc & 7 : tpc < 60 ? tpc - 31 - 7 * q2 : 0;
    const int pos = tpc < 32 ? tpc >> 3 : tpc < 60 ? q2 + 4 : tpc - 56;
    const int grp = GPC_MAP >> (4 * gpc);
    Role r;
    r.kind = (grp & 1) | ((sm >> 7) << 1);
    r.par = (pos >> 1) & 1;
    r.blk = (grp & 6) + (pos >> 2);
    r.ns = (pos & 1) * 2 + (sm & 1);
    r.id = sm >= 128 ? sm : (grp & 7) * 16 + pos * 2 + (sm & 1);
    return r;
}
static_assert((GPC_MAP & 15) == 0, "role H decodes as blk = 2, par = 0");

__device__ __forceinline__ void first_fill(const Maps& maps, const Role& r, int i) {
    const int L = r.kind & 1;
    const CUtensorMap* ma = &maps.m[r.kind];
    const uint32_t bar = full_bar(i);
    const int k = (i * 64) >> L;
    const bool has_a = !(i & L), has_b = i < 7 - L;
    const uint32_t slots = r.kind == 0 ? 0x2104365u : L ? 0x5432105u : 0x4321065u;
    const uint32_t dst = base + BRING + (i == 0 ? 5 : (slots >> (4 * i)) & 7) * SLOT;
    mbar_expect(bar, (has_a ? (i ? SLOT : SLOT / 2) : 0) + (has_b ? SLOT : 0));
    if (has_a) tma_ld5(base + (i >> L) * SLOT, ma, k, 0, r.par, r.blk, bar);
    if (has_b) {
        tma_ld4(dst, ma + 3, r.kind ? 0 : k, r.kind ? k : 0, 0, r.ns, bar);
        tma_ld4(dst + 8192, ma + 3, r.kind ? 64 : k, r.kind ? k : 64, 0, r.ns, bar);
        mbar_arrive(bar);
    }
    if (i == 0) {
        mbar_init(base + BAR_X, 1);
        mbar_expect(base + BAR_X, SLOT / 2);
    }
    if (has_a) tma_ld5(base + (i >> L) * SLOT + 8192, ma, k, 1, r.par, r.blk, i ? bar : base + BAR_X);
}
static_assert(bslot_e(0) == 5 && bslot_e(1) == 6 && bslot_e(2) == 3 && bslot_e(3) == 4 && bslot_e(4) == 0 && bslot_e(6) == 2, "");

template <bool BY_SM>
__global__ void __launch_bounds__(384, 1) fused_kernel(Scratch* sc, const __grid_constant__ Maps maps) {
    const unsigned t_open = clk32();
    const int warp = __shfl_sync(0xffffffffu, threadIdx.x >> 5, 0);
    if (warp == 8) {
        const Role r = decode_role<BY_SM>();
        if (elect()) {
            mbar_init(base + BAR_FULL, 2);
            first_fill(maps, r, 0);
            asm volatile("fence.mbarrier_init.release.cluster;" ::: "memory");
        }
        nb_sync(0, 384);
        if (elect()) {
#pragma unroll 1
            for (int i = 1; i < LEAD; i++) {
                while (clk32() - t_open < PACE0 + i * PACE) {}
                first_fill(maps, r, i);
            }
        }
    }
    if (warp - 8 != blockIdx.y) {
        if (warp == 9) {
            if (elect()) {
#pragma unroll
                for (int i = 0; i < 8; i++) mbar_init(base + BAR_EMPTY + i * 8, 4);
                asm volatile("fence.mbarrier_init.release.cluster;" ::: "memory");
            }
        } else if (warp == 10) {
            if (elect()) {
#pragma unroll
                for (int i = 0; i < 3; i++) mbar_init(base + BAR_RDY + i * 8, i < 2 ? 4 : 8);
#pragma unroll
                for (int i = 0; i < 2; i++) mbar_init(base + BAR_HALO + i * 8, 1);
                asm volatile("fence.mbarrier_init.release.cluster;" ::: "memory");
            }
        } else if (warp == 11) {
            if (elect()) {
#pragma unroll
                for (int i = 1; i < 8; i++) mbar_init(base + BAR_FULL + i * 8, 2);
#pragma unroll
                for (int i = 0; i < 3; i++) mbar_init(base + BAR_DEP + i * 8, 1);
#pragma unroll
                for (int i = 0; i < 4; i++) mbar_init(base + BAR_PART + i * 8, 1);
                asm volatile("fence.mbarrier_init.release.cluster;" ::: "memory");
            }
        }
        nb_sync(0, 384);
    }

    const Role role = decode_role<BY_SM>();
    int lane = threadIdx.x & 31;
    asm volatile("" : "+r"(lane));
    const bool roleH = role.kind == 2;
    const int roleL = role.kind & 1, par = role.par, blk = role.blk, ns = role.ns, bid = role.id;
    const int mt = 2 * blk + par, col = ns * 112;

    if (warp >= 8) {
        asm volatile("setmaxnreg.dec.sync.aligned.u32 56;");
#define PROF_FEED_A
#define PROF_FEED_B
        if (warp == 8) {
            if (elect()) {
                PROF(129);
                PROF(134);
                Feed<0> f;
                const int row = mt * 128;
                auto c_run = [&](const CUtensorMap* m, int off, int n0, int n1) {
#pragma unroll 1
                    for (int n = n0; n < n1; n++) {
                        const uint32_t bar = f.acquire<NA>();
                        mbar_expect(bar, SLOT);
                        tma_ld2(f.dst, m, (off + skip_own(n, mt)) * 64, row, bar);
                        PROF_FEED_A;
                        f.next<NA>();
                    }
                };
                if (roleH) {
                    mbar_expect(base + BAR_DEP, 7 * SLOT);
#pragma unroll 1
                    for (int i = 0; i < 7; i++) {
                        const uint32_t dst = base + (i < 6 ? i : NA + bslot_h(7)) * SLOT;
                        if (i < 6) wait_released(7 + i);
                        tma_ld4(dst, &maps.m[M_WO], 0, i * 64, 0, ns, base + BAR_DEP);
                        tma_ld4(dst + 8192, &maps.m[M_WO], 64, i * 64, 0, ns, base + BAR_DEP);
                    }
                    mbar_wait(base + BAR_DEP, 0);
                    mbar_wait(base + BAR_RDY + 16, 0);
#pragma unroll 1
                    for (int i = 0; i < 7; i++) bulk_st(sc->wo + (size_t)(ns * 7 + i) * SLOT, base + (i < 6 ? i : NA + bslot_h(7)) * SLOT, SLOT);
                    bulk_commit();
                    asm volatile("cp.async.bulk.wait_group 0;" ::: "memory");
                    signal(sc, CNT_W + ns);
                } else if (!roleL) {
                    f.seek(14, 0);
#pragma unroll 1
                    for (int i = 0; i < 4; i++) {
                        const uint32_t bar = f.acquire<NA>();
                        mbar_expect(bar, SLOT);
                        tma_ld2(f.dst, &maps.m[M_CR + (i >> 1)], ((i & 1) * 16 + mt) * 64, row, bar);
                        mbar_arrive(bar);
                        PROF_FEED_A;
                        f.next<NA>();
                    }
                    c_run(&maps.m[M_CR], 0, 0, 15);
                    c_run(&maps.m[M_CI], 0, 0, NBE);
                    wait_dep(2);
#pragma unroll 1
                    for (int i = 0; i < 7; i++) {
                        const uint32_t bar = f.acquire<NA>();
                        mbar_expect(bar, SLOT);
                        bulk_ld(f.dst, sc->o + (size_t)(mt * 7 + i) * SLOT, SLOT, bar);
                        PROF_FEED_A;
                        f.next<NA>();
                    }
                } else {
#pragma unroll 1
                    for (int i = 4; i < 7; i++) {
                        wait_released(2 * i - 8);
                        mbar_expect(full_bar(2 * i), SLOT);
                        tma_ld5(base + i * SLOT, &maps.m[M_XA], i * 64, 0, par, blk, full_bar(2 * i));
                        tma_ld5(base + i * SLOT + 8192, &maps.m[M_XA], i * 64, 1, par, blk, full_bar(2 * i));
                    }
                    wait_released(HALO_K_AT);
                    mbar_arrive(base + BAR_DEP + 16);
                    f.seek(21, 0);
                    c_run(&maps.m[M_CR], 16, 0, 15);
                    c_run(&maps.m[M_CI], 16, 0, 15);
                    c_run(&maps.m[M_CI], 0, NBE, 15);
                }
            }
        } else if (warp == 11) {
            if (elect()) {
#pragma unroll 1
                for (int i = LEAD; i < 7; i++) {
                    while (clk32() - t_open < PACE0 + i * PACE - (roleL & ~i) * PACE_X) {}
                    first_fill(maps, role, i);
                }
                Feed<BRING> f;
                auto blob_run = [&](auto nbs, int quarter, int n0, int n1) {
                    constexpr int N = decltype(nbs)::value;
                    const uint8_t* src = sc->ab + (size_t)(quarter * 64 + ns) * BLOB;
#pragma unroll 1
                    for (int n = n0; n < n1; n++) {
                        const uint32_t bar = f.template acquire<N>();
                        mbar_expect(bar, BLOB);
                        bulk_ld(f.dst, src + skip_own(n, mt) * (4 * BLOB), BLOB, bar);
                        PROF_FEED_B;
                        f.template next<N>();
                    }
                };
                auto v_run = [&](auto nbs) {
                    constexpr int N = decltype(nbs)::value;
#pragma unroll 1
                    for (int i = 0; i < 7; i++) {
                        const uint32_t bar = f.template acquire<N>();
                        mbar_expect(bar, SLOT);
                        tma_ld4(f.dst, &maps.m[M_WV], 0, i * 64, 0, 4 + ns, bar);
                        tma_ld4(f.dst + 8192, &maps.m[M_WV], 64, i * 64, 0, 4 + ns, bar);
                        mbar_arrive(bar);
                        PROF_FEED_B;
                        f.template next<N>();
                    }
                };
                if (roleH) {
                    f.seek(7, bslot_h(7));
                    v_run(Int<7>());
                } else if (!roleL) {
                    f.seek(7, bslot_e(7));
#pragma unroll 1
                    for (int i = 0; i < 7; i++) {
                        const uint32_t bar = f.acquire<5>();
                        mbar_expect(bar, BLOB);
                        tma_ld2(f.dst, &maps.m[M_WI], i * 64, col, bar);
                        mbar_arrive(bar);
                        PROF_FEED_B;
                        f.next<5>();
                    }
                    f.seek(18, bslot_e(18));
                    wait_dep(0);
                    blob_run(Int<7>(), 0, 0, 15);
                    wait_dep(1);
                    blob_run(Int<7>(), 2, 0, NBE);
                    mbar_wait(base + BAR_HINT, 0);
                    fence_async_global();
#pragma unroll 1
                    for (int i = 0; i < 7; i++) {
                        const uint32_t bar = f.acquire<7>();
                        mbar_expect(bar, SLOT);
                        bulk_ld(f.dst, sc->wo + (size_t)(ns * 7 + i) * SLOT, SLOT, bar);
                        PROF_FEED_B;
                        f.next<7>();
                    }

                } else {
                    f.seek(6, bslot_l(6));
#pragma unroll 1
                    for (int i = 6; i < 14; i++) {
                        const uint32_t bar = f.acquire<6>();
                        mbar_expect(bar, SLOT);
                        tma_ld4(f.dst, &maps.m[M_WQK], 0, i * 32, 0, ns, bar);
                        tma_ld4(f.dst + 8192, &maps.m[M_WQK], 64, i * 32, 0, ns, bar);
                        if (i & 1) mbar_arrive(bar);
                        PROF_FEED_B;
                        f.next<6>();
                    }
                    v_run(Int<6>());
                    wait_dep(0);
                    blob_run(Int<6>(), 1, 0, 15);
                    wait_dep(1);
                    blob_run(Int<6>(), 3, 0, 15);
                    blob_run(Int<6>(), 2, NBE, 15);
                    fence_async_smem();
#pragma unroll 1
                    for (int h = 0; h < 2; h++) {
                        mbar_wait(base + BAR_HINT + h * 8, 0);
                        PROF(153 + h);
                        mbar_expect(base + BAR_PART + h * 8, BLOB);
                        bulk_ld(base + (h ? HALO : LSLAB), sc->part + (size_t)((ns * 16 + mt) * 2 + h) * BLOB, BLOB, base + BAR_PART + h * 8);
                    }
                }
            }
        } else if (roleH) {
        } else if (warp == 10) {
            if (elect()) {
                unsigned* epoch_ptr = &sc->epoch[(bid * 4 + 2) * 8];
                const unsigned ep = *epoch_ptr + 1;
                sts1(base + TAG, ep);
                asm volatile("prefetch.tensormap [%0];" ::"l"(&maps.m[M_OUTA + roleL]) : "memory");
                await(sc, CNT_A + roleL * 4 + ns, ep * 16);
                mbar_arrive(base + BAR_DEP);
                PROF(150);
                await(sc, CNT_B + ns, ep * 16);
                mbar_arrive(base + BAR_DEP + 8);
                PROF(151);
                if (!roleL) {
                    await(sc, CNT_W + ns, ep);
                    mbar_arrive(base + BAR_HINT);
                    PROF(153);
                    await(sc, CNT_O + mt, ep * 4);
                    mbar_arrive(base + BAR_DEP + 16);
                } else {
                    await(sc, CNT_P + mt * 4 + ns, ep * 2 - 1);
                    mbar_arrive(base + BAR_HINT);
                    await(sc, CNT_P + mt * 4 + ns, ep * 2);
                    mbar_arrive(base + BAR_HINT + 8);
                }
                PROF(152);
                *epoch_ptr = ep;
            }
        } else if (!roleL) {
            if (elect()) {
                mbar_wait(base + BAR_RDY, 0);
                PROF(130);
                signal(sc, CNT_A + ns);
                PROF(131);
                mbar_wait(base + BAR_RDY + 8, 0);
                signal(sc, CNT_A + 4 + ns);
                PROF(135);
                mbar_wait(base + BAR_RDY + 16, 0);
                PROF(132);
                signal(sc, CNT_B + ns);
                PROF(133);
            }
        } else {
            unsigned* epoch_ptr = &sc->epoch[(bid * 4 + 1) * 8];
            const unsigned tag = *epoch_ptr + 1;
#pragma unroll 1
            for (int kv = 0; kv < 2; kv++) {
                uint32_t v[16];
#pragma unroll
                for (int i = 0; i < 16; i++) v[i] = 0;
                if (kv) wait_released(HALO_V_AT - 4), wait_released(HALO_V_AT);
                else mbar_wait(base + BAR_DEP + 16, 0);
                if (blk > 0) {
                    const uint8_t* src = sc->halo + (size_t)(((par * 8 + blk - 1) * 4 + ns) * 2 + kv) * 2048 + lane * 16;
#pragma unroll 1
                    for (int n = 0; n < SPIN_LIMIT; n++) {
#pragma unroll
                        for (int i = 0; i < 4; i++) ld_tagged(src + i * 512, v[4 * i], v[4 * i + 1], v[4 * i + 2], v[4 * i + 3]);
#pragma unroll
                        for (int i = 0; i < 16; i += 2) v[i] ^= tag & 1;
                        const uint32_t stale = or3(or3(v[0], v[2], v[4]), or3(v[6], v[8], v[10]), or3(v[12], v[14], 0));
                        if (__all_sync(0xffffffffu, !(stale & 1))) break;
                    }
#pragma unroll
                    for (int c = 0; c < 14; c += 2) v[c] |= (v[15] >> c) & 1;
                }
#pragma unroll
                for (int i = 0; i < 14; i++) sts1(base + HALO + kv * (8 * HSLOT) + i * 128 + lane * 4, v[i]);
                warp_arrive(base + BAR_HALO + kv * 8);
                if (lane == 0) PROF(142 + kv);
            }
            if (elect()) {
                mbar_wait(base + BAR_RDY + 16, 0);
                PROF(130);
                signal(sc, CNT_O + mt);
                PROF(131);
                *epoch_ptr = tag;
            }
        }
    } else {
        asm volatile("setmaxnreg.inc.sync.aligned.u32 224;");
        Ring r;
        r.wg = warp >> 2;
        r.zero = blockIdx.y;
        r.releaser = lane + 1 == (warp >> 2);
        const int wg = warp >> 2;
        if (wg) {
            nb_arrive(1, 256);
            mbar_wait(base + BAR_X, 0);
        }
        uint8_t* part = sc->part + (size_t)(ns * 16 + mt) * (2 * BLOB) + warp * WSLOT + lane * 16;
        uint32_t p[28];

        if (roleH) {
            unsigned* epoch_ptr = &sc->epoch[bid * 4 * 8];
            const unsigned tag = *epoch_ptr + 1;
            uint8_t* hout = sc->halo + (size_t)((warp * 8 + ns) * 2) * 2048 + lane * 16;
            auto send = [&](int kv) {
#pragma unroll
                for (int h = 0; h < 2; h++) {
                    uint32_t v[16];
                    v[14] = v[15] = 0;
#pragma unroll
                    for (int c = 0; c < 14; c++) v[c] = p[2 * c + h];
#pragma unroll
                    for (int c = 0; c < 14; c += 2) v[15] |= (v[c] & 1) << c;
#pragma unroll
                    for (int i = 0; i < 4; i++)
                        st_tagged(hout + (h * 8 + kv) * 2048 + i * 512, tagged(v[4 * i], v[4 * i + 1], tag), tagged(v[4 * i + 2], v[4 * i + 3], tag));
                }
            };
            float x0[56], x1[56];
            r.seek(0, bslot_h(0));
            r.wait();
            r.run<XWN, 7, true>(x0);
#pragma unroll 1
            for (int i = 1; i < 7; i++) r.run<XWN, 7, false>(x0);
            r.run<XWN, 7, true>(x1);
            acc_fence(x0);
            pack_all(x0, p);
            send(0);
#pragma unroll 1
            for (int i = 1; i < 7; i++) r.run<XWN, 7, false>(x1, true, i < 6 || !wg, i < 6);
            asm volatile("wgmma.wait_group.sync.aligned 0;" ::: "memory");
            acc_fence(x1);
            pack_all(x1, p);
#pragma unroll
            for (int i = 0; i < 28; i++) p[i] = movm(p[i]);
            send(1);
            warp_arrive(base + BAR_RDY + 16);
            if (threadIdx.x == 0) *epoch_ptr = tag;
        } else if (!roleL) {
            uint8_t* blob = sc->ab + (size_t)((wg * 16 + mt) * 4 + ns) * BLOB + (warp & 3) * WSLOT + lane * 4;
            const uint32_t own = base + BRING + wg * SLOT + (warp & 3) * WSLOT + lane * 16;
            float x0[56], x1[56];
            r.seek(0, bslot_e(0));
            r.wait();
            r.run<XW, 7, true>(x0);
            r.run<XW, 7, false>(x0);
            r.seek(2, bslot_e(2));
#pragma unroll 1
            for (int i = 2; i < 7; i++) r.run<XW, 5, false>(x0);

            r.seek(7, bslot_e(7));
            r.run<XW, 5, true, -1>(x1);
            acc_fence(x0);
            pack_all<0, 14>(x0, p);
#pragma unroll
            for (int i = 0; i < 2; i++) {
                if (wg == i) store_frags<0, 14>(blob, p);
                else stage_frags<0, 4>(own + 5 * SLOT, p);
                r.run<XW, 5, false, -1>(x1);
                if (i == 0) pack_all<14, 28>(x0, p);
                if (wg == i) {
                    store_frags<14, 28>(blob, p);
                    warp_arrive(base + BAR_RDY + i * 8);
                } else {
                    stage_frags<4, 8>(own + 5 * SLOT, p);
                }
                r.run<XW, 5, false, -1>(x1);
            }
            stage_frags<8, 16>(own + 5 * SLOT, p);
            r.run<XW, 5, false, -1>(x1);
            stage_frags<16, 24>(own + 5 * SLOT, p);
            r.run<XW, 5, false, -1>(x1);
            stage_frags<24, 28>(own + 5 * SLOT, p);

            r.seek(14, bslot_e(14));
            r.take_turn();
            fence_async_smem();
            r.run<BIG, 7, true>(x0, false);
            acc_fence(x1);
            pack_all(x1, p);
            stage_frags<0, 16>(own, p);
            r.run<BIG, 7, false>(x0);
            stage_frags<16, 28>(own, p);
            r.take_turn();
            fence_async_smem();
            blob += (size_t)128 * BLOB;
            r.run<BIG, 7, false>(x0, false);
#pragma unroll
            for (int i = 0; i < 28; i++) {
                if (i % B_SLICE == 0) r.run<BIG, 7, false>(x0);
                stg1(blob + i * 128, p[i]);
            }
            warp_arrive(base + BAR_RDY + 16);
#pragma unroll 1
            for (int i = 18 + 27 / B_SLICE; i < POUT; i++) r.run<BIG, 7, false>(x0);

            const uint32_t tag = lds1(base + TAG);
            r.seek(POUT, bslot_e(POUT));
            r.run<OUT, 7, true>(x1);
            acc_fence(x0);
            pack_all(x0, p);
            uint64_t u[14];
#pragma unroll
            for (int i = 0; i < 14; i++) u[i] = tagged(p[2 * i], p[2 * i + 1], tag);
#pragma unroll
            for (int k = 0; k < 2; k++) {
                if (wg == k) {
#pragma unroll
                    for (int i = 0; i < 7; i++) st_tagged(part + i * 512, u[2 * i], u[2 * i + 1]);
                }
                r.run<OUT, 7, false>(x1);
                if (warp * 32 + lane == k * 128)
                    asm volatile("red.relaxed.gpu.global.add.u32 [%0], 1;" ::"l"(&sc->cnt[(CNT_P + mt * 4 + ns) * 32]) : "memory");
            }
#pragma unroll
            for (int i = 3; i < 7; i++) r.run<OUT, 7, false, 1, true>(x1, i <= 7 - TURN, i < 7 - TURN || (i == 6 && !wg), i < 6);

            asm volatile("wgmma.wait_group.sync.aligned 0;" ::: "memory");
            acc_fence(x1);
            const uint32_t slab = base + (wg ? BRING + bslot_e(ELAST - 6) * SLOT : ((ELAST - 6) % NA) * SLOT) + (warp & 3) * WSLOT;
            store_out([&](int i) { return pack2(x1[2 * i], x1[2 * i + 1]); }, lane, slab, &maps.m[M_OUTA], par * 896 + col, blk * 128 + warp * 16);
        } else {
            const int g = lane >> 2, tig = lane & 3;
            const uint32_t hin = base + HALO + warp * HSLOT + lane * 4;
            const uint32_t hpub = warp < 7 ? hin + HSLOT : base + HSPARE + lane * 4;
            auto publish = [&](const uint32_t (&h)[14], int c0, int c1) {
#pragma unroll
                for (int c = 0; c < 14; c++)
                    if (c >= c0 && c < c1) sts1(hpub + c * 128, h[c]);
            };
            float y0[56], y1[56], y2[56];
            r.seek(0, bslot_l(0));
            r.wait();
            r.run<QK, 6, true>(y0, y1);
#pragma unroll 1
            for (int i = 1; i < 14; i++) r.run<QK, 6, false>(y0, y1);

            uint32_t m1[8][4], m0[8][4], lo[14], hi[14], q[2][8][2];
            auto pack_q = [&](int b) {
                uint32_t v[14];
#pragma unroll
                for (int c = 0; c < 14; c++) v[c] = pack2(y0[4 * c + 2 * b], y0[4 * c + 2 * b + 1]);
#pragma unroll
                for (int t = 0; t < 8; t++) {
                    const int c = tile_of(t);
                    q[b][t][0] = (t & 3) == 2 ? (tig >= 2 ? v[c] : 0u) : v[c];
                    q[b][t][1] = (t & 3) == 1 ? (tig < 2 ? v[c + 1] : 0u) : v[c + 1];
                }
            };
            auto fetch = [&](uint32_t src, int hp, int i0) {
#pragma unroll
                for (int t = 4 * hp; t < 4 * hp + 4; t++) {
                    m0[t][i0] = (t & 3) == 2 ? dup(m0[t - 1][3], r.zero) : lds1(src + tile_of(t) * 128);
                    m0[t][3] = lds1(src + tile_of(t) * 128 + 128);
                }
            };
            r.seek(14, bslot_l(14));
            r.run<XWN, 6, true>(y2);
            acc_fence(y0);
            acc_fence(y1);
#pragma unroll
            for (int c = 0; c < 14; c++) hi[c] = pack2(y1[4 * c + 2], y1[4 * c + 3]);
            publish(hi, 0, 7);
            r.run<XWN, 6, false>(y2);
            publish(hi, 7, 14);
#pragma unroll
            for (int c = 0; c < 14; c++) lo[c] = pack2(y1[4 * c], y1[4 * c + 1]);
#pragma unroll
            for (int t = 0; t < 8; t++) {
                const int c = tile_of(t);
                const bool shared = (t & 3) == 2;
                m1[t][0] = shared ? dup(lo[c], r.zero) : lo[c];
                m1[t][1] = shared ? dup(hi[c], r.zero) : hi[c];
                m1[t][2] = lo[c + 1];
                m1[t][3] = hi[c + 1];
                m0[t][0] = dup(m1[t][0], r.zero);
                m0[t][2] = dup(lo[c + 1], 2 * r.zero);
            }
            r.run<XWN, 6, false>(y2);
            if (warp == 0) mbar_wait(base + BAR_HALO, 0);
            fetch(hin, 0, 1);
            pack_q(1);
            r.run<XWN, 6, false>(y2);
            fetch(hin, 1, 1);
            pack_q(0);
            r.mma_begin();
            float s[8][4];
#pragma unroll
            for (int step = 0; step < 2; step++) {
#pragma unroll
                for (int i = 0; i < 8; i++) {
                    const int b = 1 - (i >> 2), h = i & 3, t = 2 * h + step;
                    float (&d)[4] = s[2 * h + b];
                    if (step == 0) d[0] = d[1] = d[2] = d[3] = 0.f;
                    mma16816(d, b ? m1[t] : m0[t], q[b][t][0], q[b][t][1]);
                }
            }
            r.mma_end();
            r.run<XWN, 6, false>(y2, false);

            uint32_t pr[8], mx[4], mx1[4];
            {
                const bool cur0 = g <= 2 * tig, cur1 = g <= 2 * tig + 1;
#pragma unroll
                for (int i = 0; i < 8; i++) {
                    const int c = (i & 1) ? 2 : 0;
                    pr[i] = movm(pack2(cur0 ? s[i][c] : s[i][2 - c], cur1 ? s[i][c + 1] : s[i][3 - c]));
                }
            }
            r.run<XWN, 6, false>(y2);
            const uint32_t curmask = (2 * tig <= g ? 0x0000FFFFu : 0u) | (2 * tig + 1 <= g ? 0xFFFF0000u : 0u);
            {
                const uint32_t keep = (blk == 0 && warp == 0) ? curmask : 0xFFFFFFFFu;
#pragma unroll
                for (int i = 0; i < 4; i++) {
                    pr[2 * i] = (scale2(pr[2 * i]) & keep) | (0xCE6ECE6Eu & ~keep);
                    pr[2 * i + 1] = scale2(pr[2 * i + 1]);
                    mx[i] = max2(__byte_perm(pr[2 * i], pr[2 * i + 1], 0x5410), __byte_perm(pr[2 * i], pr[2 * i + 1], 0x7632));
                    mx1[i] = __shfl_xor_sync(0xffffffffu, mx[i], 1);
                }
            }
#pragma unroll
            for (int i = 0; i < 4; i++) {
                mx[i] = max2(mx[i], mx1[i]);
                mx1[i] = __shfl_xor_sync(0xffffffffu, mx[i], 2);
            }
            r.run<XWN, 6, false>(y2);
            constexpr float SCL = 1.4426950408889634f;
            float e0[8], e1[8], sm[8], sm1[8];
#pragma unroll
            for (int i = 0; i < 8; i++) {
                const uint32_t m2 = max2(mx[i >> 1], mx1[i >> 1]);
                sm[i] = ((i & 1) ? bf_hi(m2) : bf_lo(m2)) * -SCL;
                e0[i] = ex2(fmaf(bf_lo(pr[i]), SCL, sm[i]));
            }

            r.seek(21, bslot_l(21));
            r.run<BIG, 6, true>(y0);
            acc_fence(y2);
#pragma unroll
            for (int c = 0; c < 7; c++) hi[c] = movm(pack2(y2[4 * c + 2], y2[4 * c + 3]));
#pragma unroll
            for (int i = 0; i < 8; i++) e1[i] = ex2(fmaf(bf_hi(pr[i]), SCL, sm[i]));
            r.run<BIG, 6, false>(y0);
            publish(hi, 0, 7);
#pragma unroll
            for (int c = 7; c < 14; c++) hi[c] = movm(pack2(y2[4 * c + 2], y2[4 * c + 3]));
            r.run<BIG, 6, false>(y0);
            publish(hi, 7, 14);
#pragma unroll
            for (int i = 0; i < 8; i++) {
                sm[i] = e0[i] + e1[i];
                sm1[i] = __shfl_xor_sync(0xffffffffu, sm[i], 1);
            }
            r.run<BIG, 6, false>(y0);
#pragma unroll
            for (int c = 0; c < 14; c++) lo[c] = movm(pack2(y2[4 * c], y2[4 * c + 1]));
            r.run<BIG, 6, false>(y0);
#pragma unroll
            for (int i = 0; i < 8; i++) {
                sm[i] += sm1[i];
                sm1[i] = __shfl_xor_sync(0xffffffffu, sm[i], 2);
            }
#pragma unroll
            for (int t = 0; t < 8; t++) {
                const int c = tile_of(t);
                const bool shared = (t & 3) == 2;
                m1[t][0] = shared ? dup(lo[c], r.zero) : lo[c];
                m1[t][1] = lo[c + 1];
                m1[t][2] = shared ? dup(hi[c], r.zero) : hi[c];
                m1[t][3] = hi[c + 1];
                m0[t][0] = dup(m1[t][0], r.zero);
                m0[t][1] = dup(lo[c + 1], 2 * r.zero);
            }
            r.run<BIG, 6, false>(y0);
            if (warp == 0) mbar_wait(base + BAR_HALO + 8, 0);
            const uint32_t vin = warp ? hin : hin + 8 * HSLOT;
            fetch(vin, 0, 2);
#pragma unroll
            for (int i = 0; i < 8; i++) {
                const float inv = rcp(sm[i] + sm1[i]);
                pr[i] = pack2(e0[i] * inv, e1[i] * inv);
            }
            r.run<BIG, 6, false>(y0);
            fetch(vin, 1, 2);
            uint32_t pb[8][2];
#pragma unroll
            for (int t = 0; t < 8; t++) {
                pb[t][t & 1] = band(pr[t], curmask);
                pb[t][1 - (t & 1)] = band(pr[t], ~curmask);
            }
            r.mma_begin();
            float o[2][8][4];
#pragma unroll
            for (int i = 0; i < 16; i++) {
                const int b = 1 - (i >> 3), t = i & 7;
                float (&d)[4] = o[b][t];
                d[0] = d[1] = d[2] = d[3] = 0.f;
                mma16816(d, b ? m1[t] : m0[t], pb[(t & 6) + b][0], pb[(t & 6) + b][1]);
            }
            r.mma_end();
            r.run<BIG, 6, false>(y0, false);
            uint8_t* odst = sc->o + (size_t)mt * 7 * SLOT + ns * (14 * 2048) + warp * 256 + lane * 4;
#pragma unroll
            for (int hp = 0; hp < 2; hp++) {
#pragma unroll
                for (int b = 0; b < 2; b++) {
                    const float (&u)[8][4] = o[b];
                    const int t = 4 * hp;
                    uint32_t* w = p + 14 * hp + b;
                    w[0] = pack2(u[t][0], u[t][1]);
                    w[2] = pack2(u[t][2], u[t][3]);
                    w[4] = pack2(u[t + 1][0], u[t + 1][1]);
                    w[6] = pack2(g < 4 ? u[t + 1][2] : u[t + 2][0], g < 4 ? u[t + 1][3] : u[t + 2][1]);
                    w[8] = pack2(u[t + 2][2], u[t + 2][3]);
                    w[10] = pack2(u[t + 3][0], u[t + 3][1]);
                    w[12] = pack2(u[t + 3][2], u[t + 3][3]);
                }
            }
#pragma unroll
            for (int i = 0; i < 28; i++) {
                if (i >= O_FIRST && (i - O_FIRST) % O_SLICE == 0) r.run<BIG, 6, false>(y0);
                stg1(odst + (i >> 1) * 2048 + (i & 1) * 128, p[i]);
            }
            warp_arrive(base + BAR_RDY + 16);

#pragma unroll 1
            for (int i = 30 + (27 - O_FIRST) / O_SLICE; i <= LLAST - LTURN; i++) r.run<BIG, 6, false>(y0);
            r.seek(LLAST + 1 - LTURN, bslot_l(LLAST + 1 - LTURN));
#pragma unroll
            for (int i = 0; i < LTURN; i++) r.run<BIG, 6, false, 1, true>(y0, i == 0, i == LTURN - 1 && !wg, i < LTURN - 1);
            const uint32_t parity = lds1(base + TAG) & 1;
            const uint32_t slab = base + (wg ? HALO : LSLAB) + (warp & 3) * WSLOT;
            mbar_wait(base + BAR_PART + wg * 8, 0);
#pragma unroll 1
            for (int n = 0; n < SPIN_LIMIT; n++) {
#pragma unroll
                for (int i = 0; i < 7; i++) lds4(slab + i * 512 + lane * 16, p + 4 * i);
#pragma unroll
                for (int i = 0; i < 28; i += 2) p[i] ^= parity;
                const uint32_t stale = or3(or3(or3(p[0], p[2], p[4]), or3(p[6], p[8], p[10]), or3(p[12], p[14], p[16])),
                                           or3(p[18], p[20], p[22]), or3(p[24], p[26], 0));
                if (__all_sync(0xffffffffu, !(stale & 1))) break;
#pragma unroll
                for (int i = 0; i < 7; i++) ld_tagged(part + i * 512, p[4 * i], p[4 * i + 1], p[4 * i + 2], p[4 * i + 3]);
#pragma unroll
                for (int i = 0; i < 7; i++)
                    asm volatile("st.shared.v4.b32 [%0], {%1,%2,%3,%4};" ::"r"(slab + i * 512 + lane * 16), "r"(p[4 * i]), "r"(p[4 * i + 1]), "r"(p[4 * i + 2]), "r"(p[4 * i + 3]) : "memory");
            }
            asm volatile("wgmma.wait_group.sync.aligned 0;" ::: "memory");
            acc_fence(y0);
            store_out([&](int i) { return add2(pack2(y0[2 * i], y0[2 * i + 1]), p[i]); }, lane, slab, &maps.m[M_OUTB], 448 + col, mt * 128 + warp * 16);
        }
    }
}

typedef CUresult (*EncodeFn)(CUtensorMap*, CUtensorMapDataType, cuuint32_t, void*, const cuuint64_t*, const cuuint64_t*,
                             const cuuint32_t*, const cuuint32_t*, CUtensorMapInterleave, CUtensorMapSwizzle,
                             CUtensorMapL2promotion, CUtensorMapFloatOOBfill);

struct Dim { uint64_t size, stride; uint32_t box; };
void encode(EncodeFn fn, CUtensorMap* m, const void* ptr, CUtensorMapSwizzle sw, Dim d0, Dim d1, Dim d2 = {0, 0, 0},
            Dim d3 = {0, 0, 0}, Dim d4 = {0, 0, 0}) {
    const cuuint64_t dims[5] = {d0.size, d1.size, d2.size, d3.size, d4.size};
    const cuuint64_t strides[4] = {d1.stride, d2.stride, d3.stride, d4.stride};
    const cuuint32_t box[5] = {d0.box, d1.box, d2.box, d3.box, d4.box};
    const cuuint32_t es[5] = {1, 1, 1, 1, 1};
    fn(m, CU_TENSOR_MAP_DATA_TYPE_BFLOAT16, d4.size ? 5 : d3.size ? 4 : 2, const_cast<void*>(ptr), dims, strides, box, es,
       CU_TENSOR_MAP_INTERLEAVE_NONE, sw, CU_TENSOR_MAP_L2_PROMOTION_L2_128B, CU_TENSOR_MAP_FLOAT_OOB_FILL_NONE);
}

}

extern "C" void kernel_launch(void* const* d_in, const int* in_sizes, int n_in, void* d_out, int out_size) {
    (void)in_sizes; (void)n_in; (void)out_size;
    void* fnp = nullptr;
    cudaDriverEntryPointQueryResult st;
    cudaGetDriverEntryPoint("cuTensorMapEncodeTiled", &fnp, cudaEnableDefault, &st);
    EncodeFn fn = (EncodeFn)fnp;
    void* scratch = nullptr;
    cudaGetSymbolAddress(&scratch, g_scratch);
    int dev = 0, sms = 0;
    cudaGetDevice(&dev);
    cudaDeviceGetAttribute(&sms, cudaDevAttrMultiProcessorCount, dev);
    auto kernel = sms == 132 ? fused_kernel<true> : fused_kernel<false>;
    cudaFuncSetAttribute(kernel, cudaFuncAttributeMaxDynamicSharedMemorySize, SMEM_BYTES);

    const CUtensorMapSwizzle S128 = CU_TENSOR_MAP_SWIZZLE_128B, S0 = CU_TENSOR_MAP_SWIZZLE_NONE;
    const Dim one = {1, 16, 1};
    Maps maps;
    encode(fn, &maps.m[M_XA], d_in[0], S128, {448, 2, 64}, {64, 1792, 64}, {2, 64 * 1792, 1}, {2, 896, 1}, {8, 128 * 1792, 1});
    encode(fn, &maps.m[M_WQK], d_in[1], S128, {112, 2, 64}, {448, 2688, 32}, {3, 896, 2}, {4, 224, 1});
    encode(fn, &maps.m[M_WV], (const uint8_t*)d_in[1] + 896, S128, {112, 2, 64}, {448, 2688, 64}, one, {8, 224, 1});
    encode(fn, &maps.m[M_XH], d_in[0], S128, {448, 2, 64}, {8, 1792, 8}, {2, 896, 1}, {8, 128 * 1792, 8}, {3, 60 * 1792, 1});
    encode(fn, &maps.m[M_WO], d_in[2], S128, {112, 2, 64}, {448, 896, 64}, one, {4, 224, 1});
    encode(fn, &maps.m[M_XB], d_in[3], S128, {448, 2, 64}, {64, 896, 64}, {2, 896 * 1024, 1}, {2, 64 * 896, 1}, {8, 128 * 896, 1});
    encode(fn, &maps.m[M_CR], d_in[4], S128, {2048, 2, 64}, {2048, 4096, 128});
    encode(fn, &maps.m[M_CI], d_in[5], S128, {2048, 2, 64}, {2048, 4096, 128});
    encode(fn, &maps.m[M_WR], d_in[6], S128, {448, 2, 64}, {112, 896, 64}, one, {4, 112 * 896, 1});
    encode(fn, &maps.m[M_WI], d_in[7], S128, {448, 2, 64}, {448, 896, 112});
    encode(fn, &maps.m[M_OUTA], d_out, S0, {1792, 2, 112}, {1024, 3584, 8});
    encode(fn, &maps.m[M_OUTB], d_out, S0, {896, 2, 112}, {2048, 1792, 8});

    kernel<<<132, 384, SMEM_BYTES>>>((Scratch*)scratch, maps);
}
```

```cpp
#include <cuda.h>
#include <cuda_bf16.h>
#include <cuda_runtime.h>
#include <stdint.h>

namespace {

constexpr uint32_t SLOT = 16384;
constexpr int NA = 7;
constexpr uint32_t BRING = NA * SLOT;
constexpr uint32_t HALO = BRING + 6 * SLOT;
constexpr uint32_t HSLOT = 1792;
constexpr uint32_t WSLOT = 3584;
constexpr uint32_t BLOB = 14336;
constexpr uint32_t BARS = 14 * SLOT;
constexpr uint32_t BAR_FULL = BARS;
constexpr uint32_t BAR_EMPTY = BARS + 64;
constexpr uint32_t BAR_RDY = BARS + 128;
constexpr uint32_t BAR_DEP = BARS + 168;
constexpr uint32_t BAR_HALO = BARS + 192;
constexpr uint32_t BAR_PART = BARS + 208;
constexpr uint32_t BAR_HINT = BARS + 224;
constexpr uint32_t BAR_X = BARS + 152;
constexpr uint32_t TAG = BARS + 240;
constexpr uint32_t HSPARE = BARS + 256 + 1024;
constexpr uint32_t SMEM_BYTES = HSPARE + HSLOT;
constexpr uint32_t base = 1024;
constexpr int SPIN_LIMIT = 1 << 16;

constexpr int LEAD = 2;
constexpr int PACE0 = 700, PACE = 450;
constexpr int PACE_X = 250;
constexpr int HALO_K_AT = 11;
constexpr int HALO_V_AT = 19;
constexpr int B_SLICE = 4;
constexpr int O_FIRST = 7, O_SLICE = 3;
constexpr int TURN = 4, LTURN = 5;
constexpr uint32_t GPC_MAP = 0x64753210u;
constexpr int NBE = 13;
constexpr int POUT = 33 + NBE;
constexpr int ELAST = POUT + 6;
constexpr int LLAST = 65 - NBE;
constexpr uint32_t LSLAB = ((LLAST - 6) % NA) * SLOT;
static_assert(TURN <= 4 && LTURN <= 5, "the output is staged in the slots of the seventh-last stage");

enum { M_XB, M_XA, M_XH, M_WR, M_WQK, M_WV, M_WO, M_WI, M_CR, M_CI, M_OUTA, M_OUTB, M_COUNT };
struct __align__(64) Maps { CUtensorMap m[M_COUNT]; };

constexpr int CNT_A = 0;
constexpr int CNT_B = 8;
constexpr int CNT_W = 12;
constexpr int CNT_O = 16;
constexpr int CNT_P = 32;
constexpr int CNT_COUNT = 96;

struct Scratch {
    uint8_t ab[64 * 4 * BLOB];
    uint8_t o[16 * 7 * SLOT];
    uint8_t part[64 * 2 * BLOB];
    uint8_t halo[64 * 2 * 2048];
    uint8_t wo[4 * 7 * SLOT];
    unsigned cnt[CNT_COUNT * 32];
    unsigned epoch[132 * 4 * 8];
};
__device__ __align__(1024) Scratch g_scratch;

__device__ __forceinline__ unsigned clk32() { unsigned c; asm volatile("mov.u32 %0, %%clock;" : "=r"(c)); return c; }

#define PROF(idx)

__device__ __forceinline__ void mbar_init(uint32_t bar, uint32_t cnt) {
    asm volatile("mbarrier.init.shared::cta.b64 [%0], %1;" ::"r"(bar), "r"(cnt) : "memory");
}
__device__ __forceinline__ void mbar_expect(uint32_t bar, uint32_t bytes) {
    asm volatile("mbarrier.arrive.expect_tx.shared::cta.b64 _, [%0], %1;" ::"r"(bar), "r"(bytes) : "memory");
}
__device__ __forceinline__ void mbar_arrive(uint32_t bar) {
    asm volatile("mbarrier.arrive.shared::cta.b64 _, [%0];" ::"r"(bar) : "memory");
}
__device__ __forceinline__ bool mbar_try(uint32_t bar, uint32_t parity) {
    uint32_t ok;
    asm volatile("{\n.reg .pred p;\nmbarrier.try_wait.parity.shared::cta.b64 p, [%1], %2;\nselp.u32 %0, 1, 0, p;\n}\n"
                 : "=r"(ok) : "r"(bar), "r"(parity) : "memory");
    return ok;
}
__device__ __forceinline__ void mbar_wait(uint32_t bar, uint32_t parity) {
#pragma unroll 1
    for (int n = 0; n < SPIN_LIMIT; n++)
        if (mbar_try(bar, parity)) break;
}
__device__ __forceinline__ bool elect() {
    uint32_t p;
    asm volatile("{\n.reg .pred p;\nelect.sync _|p, 0xffffffff;\nselp.u32 %0, 1, 0, p;\n}\n" : "=r"(p));
    return p;
}
__device__ __forceinline__ void nb_sync(int id, int n) { asm volatile("bar.sync %0, %1;" ::"r"(id), "r"(n) : "memory"); }
__device__ __forceinline__ void nb_arrive(int id, int n) { asm volatile("bar.arrive %0, %1;" ::"r"(id), "r"(n) : "memory"); }
__device__ __forceinline__ void warp_arrive(uint32_t bar) {
    __syncwarp();
    if (elect()) mbar_arrive(bar);
}
__device__ __forceinline__ uint32_t or3(uint32_t a, uint32_t b, uint32_t c) {
    uint32_t r;
    asm("lop3.b32 %0, %1, %2, %3, 0xFE;" : "=r"(r) : "r"(a), "r"(b), "r"(c));
    return r;
}
__device__ __forceinline__ uint32_t band(uint32_t x, uint32_t m) {
    uint32_t r;
    asm volatile("and.b32 %0, %1, %2;" : "=r"(r) : "r"(x), "r"(m));
    return r;
}
__device__ __forceinline__ uint32_t dup(uint32_t x, uint32_t zero) {
    uint32_t r;
    asm volatile("xor.b32 %0, %1, %2;" : "=r"(r) : "r"(x), "r"(zero));
    return r;
}

__device__ __forceinline__ void tma_ld2(uint32_t dst, const CUtensorMap* m, int c0, int c1, uint32_t bar) {
    asm volatile("cp.async.bulk.tensor.2d.shared::cluster.global.mbarrier::complete_tx::bytes [%0], [%1, {%3, %4}], [%2];"
                 ::"r"(dst), "l"(m), "r"(bar), "r"(c0), "r"(c1) : "memory");
}
__device__ __forceinline__ void tma_ld4(uint32_t dst, const CUtensorMap* m, int c0, int c1, int c2, int c3, uint32_t bar) {
    asm volatile("cp.async.bulk.tensor.4d.shared::cluster.global.mbarrier::complete_tx::bytes [%0], [%1, {%3, %4, %5, %6}], [%2];"
                 ::"r"(dst), "l"(m), "r"(bar), "r"(c0), "r"(c1), "r"(c2), "r"(c3) : "memory");
}
__device__ __forceinline__ void tma_ld5(uint32_t dst, const CUtensorMap* m, int c0, int c2, int c3, int c4, uint32_t bar) {
    asm volatile("cp.async.bulk.tensor.5d.shared::cluster.global.mbarrier::complete_tx::bytes [%0], [%1, {%3, 0, %4, %5, %6}], [%2];"
                 ::"r"(dst), "l"(m), "r"(bar), "r"(c0), "r"(c2), "r"(c3), "r"(c4) : "memory");
}
__device__ __forceinline__ void bulk_ld(uint32_t dst, const void* src, uint32_t bytes, uint32_t bar) {
    asm volatile("cp.async.bulk.shared::cluster.global.mbarrier::complete_tx::bytes [%0], [%1], %2, [%3];"
                 ::"r"(dst), "l"(src), "r"(bytes), "r"(bar) : "memory");
}
__device__ __forceinline__ void bulk_st(void* dst, uint32_t src, uint32_t bytes) {
    asm volatile("cp.async.bulk.global.shared::cta.bulk_group [%0], [%1], %2;" ::"l"(dst), "r"(src), "r"(bytes) : "memory");
}
__device__ __forceinline__ void tma_st2(const CUtensorMap* m, int c0, int c1, uint32_t src) {
    asm volatile("cp.async.bulk.tensor.2d.global.shared::cta.bulk_group [%0, {%1, %2}], [%3];"
                 ::"l"(m), "r"(c0), "r"(c1), "r"(src) : "memory");
}
__device__ __forceinline__ void bulk_commit() { asm volatile("cp.async.bulk.commit_group;" ::: "memory"); }
__device__ __forceinline__ void bulk_wait_read() { asm volatile("cp.async.bulk.wait_group.read 0;" ::: "memory"); }
__device__ __forceinline__ void fence_async_smem() { asm volatile("fence.proxy.async.shared::cta;" ::: "memory"); }
__device__ __forceinline__ void fence_async_global() { asm volatile("fence.proxy.async.global;" ::: "memory"); }

__device__ __forceinline__ void signal(Scratch* sc, int idx) {
    asm volatile("fence.proxy.async;\nred.relaxed.gpu.global.add.u32 [%0], 1;" ::"l"(&sc->cnt[idx * 32]) : "memory");
}
__device__ __forceinline__ unsigned peek(const unsigned* p) {
    unsigned v;
    asm volatile("ld.relaxed.gpu.global.u32 %0, [%1];" : "=r"(v) : "l"(p) : "memory");
    return v;
}
__device__ __forceinline__ void await(Scratch* sc, int idx, unsigned target) {
    const unsigned* p = &sc->cnt[idx * 32];
#pragma unroll 1
    for (int n = 0; n < SPIN_LIMIT; n++)
        if ((int)(peek(p) - target) >= 0) break;
    asm volatile("fence.acquire.gpu;" ::: "memory");
}
__device__ __forceinline__ void wait_dep(int k) {
    mbar_wait(base + BAR_DEP + k * 8, 0);
    fence_async_global();
}

#define WG_REGS                                                                                                     \
    "{%0,%1,%2,%3,%4,%5,%6,%7,%8,%9,%10,%11,%12,%13,%14,%15,%16,%17,%18,%19,%20,%21,%22,%23,%24,%25,%26,%27,"       \
    "%28,%29,%30,%31,%32,%33,%34,%35,%36,%37,%38,%39,%40,%41,%42,%43,%44,%45,%46,%47,%48,%49,%50,%51,%52,%53,%54,%55}"
#define WG_OPS(C)                                                                                                   \
    C(d[0]), C(d[1]), C(d[2]), C(d[3]), C(d[4]), C(d[5]), C(d[6]), C(d[7]), C(d[8]), C(d[9]), C(d[10]), C(d[11]),   \
    C(d[12]), C(d[13]), C(d[14]), C(d[15]), C(d[16]), C(d[17]), C(d[18]), C(d[19]), C(d[20]), C(d[21]), C(d[22]),   \
    C(d[23]), C(d[24]), C(d[25]), C(d[26]), C(d[27]), C(d[28]), C(d[29]), C(d[30]), C(d[31]), C(d[32]), C(d[33]),   \
    C(d[34]), C(d[35]), C(d[36]), C(d[37]), C(d[38]), C(d[39]), C(d[40]), C(d[41]), C(d[42]), C(d[43]), C(d[44]),   \
    C(d[45]), C(d[46]), C(d[47]), C(d[48]), C(d[49]), C(d[50]), C(d[51]), C(d[52]), C(d[53]), C(d[54]), C(d[55])

template <int TA, int TB, int SB, bool INIT, uint32_t AH, uint32_t BH>
__device__ __forceinline__ void wgmma112(float (&d)[56], uint32_t alo, uint32_t blo) {
    if (INIT) {
        asm volatile("{\n.reg .pred p;\n.reg .b64 da, db;\nsetp.ne.b32 p, 0, 0;\nmov.b64 da, {%56, %61};\nmov.b64 db, {%57, %62};\n"
                     "wgmma.mma_async.sync.aligned.m64n112k16.f32.bf16.bf16 " WG_REGS ", da, db, p, 1, %59, %60, %58;\n}\n"
                     : WG_OPS("=f") : "r"(alo), "r"(blo), "n"(TB), "n"(SB), "n"(TA), "n"(AH), "n"(BH));
    } else {
        asm volatile("{\n.reg .pred p;\n.reg .b64 da, db;\nsetp.ne.b32 p, 1, 0;\nmov.b64 da, {%56, %61};\nmov.b64 db, {%57, %62};\n"
                     "wgmma.mma_async.sync.aligned.m64n112k16.f32.bf16.bf16 " WG_REGS ", da, db, p, 1, %59, %60, %58;\n}\n"
                     : WG_OPS("+f") : "r"(alo), "r"(blo), "n"(TB), "n"(SB), "n"(TA), "n"(AH), "n"(BH));
    }
}
__device__ __forceinline__ void acc_fence(float (&d)[56]) {
#pragma unroll
    for (int i = 0; i < 56; i++) asm volatile("" : "+f"(d[i])::"memory");
}

__device__ __forceinline__ uint32_t pack2(float lo, float hi) {
    uint32_t r;
    asm volatile("cvt.rn.bf16x2.f32 %0, %1, %2;" : "=r"(r) : "f"(hi), "f"(lo));
    return r;
}
__device__ __forceinline__ uint32_t movm(uint32_t a) {
    uint32_t r;
    asm volatile("movmatrix.sync.aligned.m8n8.trans.b16 %0, %1;" : "=r"(r) : "r"(a));
    return r;
}
__device__ __forceinline__ void stsm4(uint32_t addr, uint32_t a, uint32_t b, uint32_t c, uint32_t d) {
    asm volatile("stmatrix.sync.aligned.m8n8.x4.shared.b16 [%0], {%1,%2,%3,%4};" ::"r"(addr), "r"(a), "r"(b), "r"(c), "r"(d) : "memory");
}
__device__ __forceinline__ void sts1(uint32_t addr, uint32_t a) { asm volatile("st.shared.b32 [%0], %1;" ::"r"(addr), "r"(a) : "memory"); }
__device__ __forceinline__ uint32_t lds1(uint32_t addr) {
    uint32_t a;
    asm volatile("ld.shared.b32 %0, [%1];" : "=r"(a) : "r"(addr) : "memory");
    return a;
}
__device__ __forceinline__ void lds4(uint32_t addr, uint32_t* v) {
    asm volatile("ld.shared.v4.b32 {%0,%1,%2,%3}, [%4];" : "=r"(v[0]), "=r"(v[1]), "=r"(v[2]), "=r"(v[3]) : "r"(addr) : "memory");
}
__device__ __forceinline__ void stg1(uint8_t* p, uint32_t a) { asm volatile("st.global.b32 [%0], %1;" ::"l"(p), "r"(a) : "memory"); }
__device__ __forceinline__ uint64_t tagged(uint32_t lo, uint32_t hi, uint32_t tag) {
    uint64_t r;
    asm volatile("{\n.reg .b32 t;\nlop3.b32 t, %1, %3, 1, 0xD8;\nmov.b64 %0, {t, %2};\n}\n" : "=l"(r) : "r"(lo), "r"(hi), "r"(tag));
    return r;
}
__device__ __forceinline__ void st_tagged(uint8_t* p, uint64_t x, uint64_t y) {
    asm volatile("st.relaxed.gpu.global.v2.b64 [%0], {%1, %2};" ::"l"(p), "l"(x), "l"(y) : "memory");
}
__device__ __forceinline__ void mma16816(float (&d)[4], const uint32_t (&a)[4], uint32_t b0, uint32_t b1) {
    asm volatile("mma.sync.aligned.m16n8k16.row.col.f32.bf16.bf16.f32 {%0,%1,%2,%3}, {%4,%5,%6,%7}, {%8,%9}, {%0,%1,%2,%3};"
                 : "+f"(d[0]), "+f"(d[1]), "+f"(d[2]), "+f"(d[3]) : "r"(a[0]), "r"(a[1]), "r"(a[2]), "r"(a[3]), "r"(b0), "r"(b1));
}
__device__ __forceinline__ uint32_t add2(uint32_t a, uint32_t b) {
    uint32_t r;
    asm("add.rn.bf16x2 %0, %1, %2;" : "=r"(r) : "r"(a), "r"(b));
    return r;
}
__device__ __forceinline__ uint32_t scale2(uint32_t x) {
    uint32_t r;
    asm("{\n.reg .b32 t;\nmul.rn.bf16x2 t, %1, %3;\nfma.rn.bf16x2 %0, %1, %2, t;\n}\n" : "=r"(r) : "r"(x), "r"(0x3E423E42u), "r"(0xB9F7B9F7u));
    return r;
}
__device__ __forceinline__ uint32_t max2(uint32_t a, uint32_t b) {
    uint32_t r;
    asm("max.bf16x2 %0, %1, %2;" : "=r"(r) : "r"(a), "r"(b));
    return r;
}
__device__ __forceinline__ void ld_tagged(const uint8_t* p, uint32_t& a, uint32_t& ta, uint32_t& b, uint32_t& tb) {
    asm volatile("{\n.reg .b64 x, y;\nld.relaxed.gpu.global.v2.b64 {x, y}, [%4];\nmov.b64 {%0, %1}, x;\nmov.b64 {%2, %3}, y;\n}\n"
                 : "=r"(a), "=r"(ta), "=r"(b), "=r"(tb) : "l"(p) : "memory");
}
__device__ __forceinline__ float bf_lo(uint32_t v) { return __uint_as_float(v << 16); }
__device__ __forceinline__ float bf_hi(uint32_t v) { return __uint_as_float(v & 0xFFFF0000u); }
__device__ __forceinline__ float rcp(float x) { float r; asm("rcp.approx.ftz.f32 %0, %1;" : "=f"(r) : "f"(x)); return r; }
__device__ __forceinline__ float ex2(float x) { float r; asm volatile("ex2.approx.ftz.f32 %0, %1;" : "=f"(r) : "f"(x)); return r; }

__device__ __forceinline__ uint32_t full_bar(int stage) { return base + BAR_FULL + (stage & 7) * 8; }
__device__ __forceinline__ void wait_released(int j) { mbar_wait(base + BAR_EMPTY + (j & 7) * 8, (j >> 3) & 1); }

template <int V>
struct Int { static constexpr int value = V; };

__host__ __device__ constexpr int bslot_e(int i) { return (i < 2 || i >= 14) ? (i + 5) % 7 : (i + 1) % 5; }
__host__ __device__ constexpr int bslot_l(int i) { return (i + 5) % 6; }
__host__ __device__ constexpr int bslot_h(int i) { return (i + 5) % 7; }

template <uint32_t OFF>
struct Feed {
    int stage;
    uint32_t dst;
    __device__ __forceinline__ void seek(int i, int slot) { stage = i; dst = base + OFF + slot * SLOT; }
    template <int N>
    __device__ __forceinline__ uint32_t acquire() { wait_released(stage - N); return full_bar(stage); }
    template <int N>
    __device__ __forceinline__ void next() {
        stage++;
        dst += SLOT;
        if (dst == base + OFF + N * SLOT) dst = base + OFF;
    }
};
__device__ __forceinline__ int skip_own(int n, int mt) { return n == mt ? 15 : n; }

struct Desc { uint32_t lo, hi; };
__host__ __device__ constexpr Desc desc_const(uint32_t lbo, uint32_t sbo, uint32_t mode) { return {(lbo >> 4) << 16, (sbo >> 4) | (mode << 30)}; }
constexpr Desc D_K128 = desc_const(16, 1024, 1);
constexpr Desc D_N128 = desc_const(8192, 1024, 1);
constexpr Desc D_BLOB = desc_const(128, 256, 0);
constexpr Desc D_OT = desc_const(2048, 128, 0);

enum Kind { XW, XWN, QK, BIG, OUT };

struct Ring {
    int stage;
    uint32_t a, b;
    uint32_t wg;
    uint32_t zero;
    bool releaser;
    __device__ __forceinline__ void seek(int i, int bslot) {
        stage = i;
        a = (base + (i % NA) * SLOT) >> 4;
        b = (base + BRING + bslot * SLOT) >> 4;
    }
    __device__ __forceinline__ void wait() { mbar_wait(full_bar(stage), (stage >> 3) & 1); }
    __device__ __forceinline__ void take_turn() { nb_sync(1 + wg, 256); }
    __device__ __forceinline__ void pin() {
        asm volatile("{\n.reg .pred p;\nsetp.ne.u32 p, %0, 0;\nPIN:\npmevent 7;\n@p bra.uni PIN;\n}\n" ::"r"(zero) : "memory");
    }
    __device__ __forceinline__ void mma_begin() {
        if (!wg) take_turn();
        pin();
    }
    __device__ __forceinline__ void mma_end() {
        pin();
        if (wg) nb_arrive(3, 256);
        nb_sync(3 - wg, 256);
    }
    template <Kind K, int NBS, bool INIT, int SB = 1, bool TAIL = false>
    __device__ __forceinline__ void run(float (&d)[56], float (&e)[56], bool first = true, bool last = true, bool more = true) {
        if (first) take_turn();
        asm volatile("wgmma.fence.sync.aligned;" ::: "memory");
        if (K == QK) {
            const uint32_t da = D_K128.lo + (base >> 4) + (stage >> 1) * (SLOT >> 4) + (stage & 1) * 4 + wg * 512, db = D_N128.lo + b;
            wgmma112<0, 1, 1, INIT, D_K128.hi, D_N128.hi>(d, da, db);
            wgmma112<0, 1, 1, INIT, D_K128.hi, D_N128.hi>(e, da, db + 256);
            wgmma112<0, 1, 1, false, D_K128.hi, D_N128.hi>(d, da + 2, db + 128);
            wgmma112<0, 1, 1, false, D_K128.hi, D_N128.hi>(e, da + 2, db + 384);
        } else {
            constexpr int TA = K == OUT, TB = K != XW;
            constexpr uint32_t sa = K == OUT ? 256 : 2, sb = K == XW ? 2 : K == BIG ? 224 : 128;
            constexpr Desc A = K == OUT ? D_OT : D_K128, B = K == XW ? D_K128 : K == BIG ? D_BLOB : D_N128;
            const uint32_t da = A.lo + a + wg * (K == OUT ? 64 : 512), db = B.lo + b;
            wgmma112<TA, TB, SB, INIT, A.hi, B.hi>(d, da, db);
#pragma unroll
            for (int q = 1; q < 4; q++) wgmma112<TA, TB, SB, false, A.hi, B.hi>(d, da + q * sa, db + q * sb);
        }
        asm volatile("wgmma.commit_group.sync.aligned;" ::: "memory");
        if (!TAIL) asm volatile("wgmma.wait_group.sync.aligned 1;" ::: "memory");
        if (last) nb_arrive(2 - wg, 256);
        if (!TAIL && stage > 0 && releaser) mbar_arrive(base + BAR_EMPTY + ((stage - 1) & 7) * 8);
        stage++;
        a += SLOT >> 4;
        if (a == (base + NA * SLOT) >> 4) a = base >> 4;
        b += SLOT >> 4;
        if (b == (base + BRING + NBS * SLOT) >> 4) b = (base + BRING) >> 4;
        if (more) wait();
    }
    template <Kind K, int NBS, bool INIT, int SB = 1, bool TAIL = false>
    __device__ __forceinline__ void run(float (&d)[56], bool first = true, bool last = true, bool more = true) {
        run<K, NBS, INIT, SB, TAIL>(d, d, first, last, more);
    }
};

template <int I0 = 0, int I1 = 28>
__device__ __forceinline__ void pack_all(const float (&d)[56], uint32_t (&p)[28]) {
#pragma unroll
    for (int i = I0; i < I1; i++) p[i] = pack2(d[2 * i], d[2 * i + 1]);
}
template <int I0, int I1>
__device__ __forceinline__ void store_frags(uint8_t* dst, const uint32_t (&p)[28]) {
#pragma unroll
    for (int i = I0; i < I1; i++) stg1(dst + i * 128, p[i]);
}
template <int I0, int I1>
__device__ __forceinline__ void stage_frags(uint32_t lane_addr, const uint32_t (&p)[28]) {
#pragma unroll
    for (int i = I0; i < I1; i += 4) stsm4(lane_addr + i * 128, p[i], p[i + 1], p[i + 2], p[i + 3]);
}
template <class F>
__device__ __forceinline__ void store_out(F frag, int lane, uint32_t slab, const CUtensorMap* m, int c0, int c1) {
    const bool swap = lane & 16;
    const uint32_t addr = slab + (lane & 7) * 224 + ((lane >> 3) ^ ((lane >> 2) & 1)) * 16;
#pragma unroll
    for (int h = 0; h < 2; h++) {
#pragma unroll
        for (int c = 0; c < 14; c += 4) {
            const uint32_t t0 = frag(2 * c + h), t1 = frag(2 * c + 2 + h);
            if (c < 12) {
                const uint32_t t2 = frag(2 * c + 4 + h), t3 = frag(2 * c + 6 + h);
                stsm4(addr + h * 1792 + c * 16, swap ? t1 : t0, swap ? t0 : t1, swap ? t3 : t2, swap ? t2 : t3);
            } else {
                asm volatile("stmatrix.sync.aligned.m8n8.x2.shared.b16 [%0], {%1,%2};" ::"r"(addr + h * 1792 + c * 16), "r"(swap ? t1 : t0), "r"(swap ? t0 : t1) : "memory");
            }
        }
        fence_async_smem();
        __syncwarp();
        if (elect()) tma_st2(m, c0, c1 + 8 * h, slab + h * 1792);
    }
    if (elect()) {
        bulk_commit();
        bulk_wait_read();
    }
}
__host__ __device__ constexpr int tile_of(int t) { return 7 * (t >> 2) + 3 * ((t >> 1) & 1) + 2 * (t & 1); }

struct Role {
    int kind;
    int par, blk;
    int ns, id;
};
template <bool BY_SM>
__device__ __forceinline__ uint32_t read_sm() {
    uint32_t sm;
    if (BY_SM) asm volatile("mov.u32 %0, %%smid;" : "=r"(sm));
    else asm volatile("mov.u32 %0, %%ctaid.x;" : "=r"(sm));
    return sm;
}
__device__ __forceinline__ Role decode_role(uint32_t sm) {
    const int tpc = sm >> 1, q2 = ((tpc - 32) * 37) >> 8;
    const int gpc = tpc < 32 ? tpc & 7 : tpc < 60 ? tpc - 31 - 7 * q2 : 0;
    const int pos = tpc < 32 ? tpc >> 3 : tpc < 60 ? q2 + 4 : tpc - 56;
    const int grp = GPC_MAP >> (4 * gpc);
    Role r;
    r.kind = (grp & 1) | ((sm >> 7) << 1);
    r.par = (pos >> 1) & 1;
    r.blk = (grp & 6) + (pos >> 2);
    r.ns = (pos & 1) * 2 + (sm & 1);
    r.id = sm >= 128 ? sm : (grp & 7) * 16 + pos * 2 + (sm & 1);
    return r;
}
static_assert((GPC_MAP & 15) == 0, "role H decodes as blk = 2, par = 0");

__device__ __forceinline__ void first_fill(const Maps& maps, const Role& r, int i) {
    const int L = r.kind & 1;
    const CUtensorMap* ma = &maps.m[r.kind];
    const uint32_t bar = full_bar(i);
    const int k = (i * 64) >> L;
    const bool has_a = !(i & L), has_b = i < 7 - L;
    const uint32_t slots = r.kind == 0 ? 0x2104365u : L ? 0x5432105u : 0x4321065u;
    const uint32_t dst = base + BRING + (i == 0 ? 5 : (slots >> (4 * i)) & 7) * SLOT;
    mbar_expect(bar, (has_a ? (i ? SLOT : SLOT / 2) : 0) + (has_b ? SLOT : 0));
    if (has_a) tma_ld5(base + (i >> L) * SLOT, ma, k, 0, r.par, r.blk, bar);
    if (i == 0) asm volatile("{\n.reg .pred p;\nsetp.ne.u32 p, %0, 0;\nPIN:\npmevent 7;\n@p bra.uni PIN;\n}\n" ::"r"(r.kind >> 2) : "memory");
    if (has_b) {
        tma_ld4(dst, ma + 3, r.kind ? 0 : k, r.kind ? k : 0, 0, r.ns, bar);
        tma_ld4(dst + 8192, ma + 3, r.kind ? 64 : k, r.kind ? k : 64, 0, r.ns, bar);
        mbar_arrive(bar);
    }
    if (i == 0) {
        mbar_init(base + BAR_X, 1);
        mbar_expect(base + BAR_X, SLOT / 2);
    }
    if (has_a) tma_ld5(base + (i >> L) * SLOT + 8192, ma, k, 1, r.par, r.blk, i ? bar : base + BAR_X);
}
static_assert(bslot_e(0) == 5 && bslot_e(1) == 6 && bslot_e(2) == 3 && bslot_e(3) == 4 && bslot_e(4) == 0 && bslot_e(6) == 2, "");

template <bool BY_SM>
__global__ void __launch_bounds__(384, 1) fused_kernel(Scratch* sc, const __grid_constant__ Maps maps) {
    const uint32_t sm0 = read_sm<BY_SM>();
    const unsigned t_open = clk32();
    const int warp = __shfl_sync(0xffffffffu, threadIdx.x >> 5, 0);
    if (warp == 8) {
        const Role r = decode_role(sm0);
        if (elect()) {
            mbar_init(base + BAR_FULL, 2);
            first_fill(maps, r, 0);
            asm volatile("fence.mbarrier_init.release.cluster;" ::: "memory");
        }
        nb_sync(0, 384);
        if (elect()) {
#pragma unroll 1
            for (int i = 1; i < LEAD; i++) {
                while (clk32() - t_open < PACE0 + i * PACE) {}
                first_fill(maps, r, i);
            }
        }
    }
    if (warp - 8 != blockIdx.y) {
        if (warp == 9) {
            if (elect()) {
#pragma unroll
                for (int i = 0; i < 8; i++) mbar_init(base + BAR_EMPTY + i * 8, 4);
                asm volatile("fence.mbarrier_init.release.cluster;" ::: "memory");
            }
        } else if (warp == 10) {
            if (elect()) {
#pragma unroll
                for (int i = 0; i < 3; i++) mbar_init(base + BAR_RDY + i * 8, i < 2 ? 4 : 8);
#pragma unroll
                for (int i = 0; i < 2; i++) mbar_init(base + BAR_HALO + i * 8, 1);
                asm volatile("fence.mbarrier_init.release.cluster;" ::: "memory");
            }
        } else if (warp == 11) {
            if (elect()) {
#pragma unroll
                for (int i = 1; i < 8; i++) mbar_init(base + BAR_FULL + i * 8, 2);
#pragma unroll
                for (int i = 0; i < 3; i++) mbar_init(base + BAR_DEP + i * 8, 1);
#pragma unroll
                for (int i = 0; i < 4; i++) mbar_init(base + BAR_PART + i * 8, 1);
                asm volatile("fence.mbarrier_init.release.cluster;" ::: "memory");
            }
        }
        nb_sync(0, 384);
    }

    const Role role = decode_role(read_sm<BY_SM>());
    int lane = threadIdx.x & 31;
    asm volatile("" : "+r"(lane));
    const bool roleH = role.kind == 2;
    const int roleL = role.kind & 1, par = role.par, blk = role.blk, ns = role.ns, bid = role.id;
    const int mt = 2 * blk + par, col = ns * 112;

    if (warp >= 8) {
        asm volatile("setmaxnreg.dec.sync.aligned.u32 56;");
#define PROF_FEED_A
#define PROF_FEED_B
        if (warp == 8) {
            if (elect()) {
                PROF(129);
                PROF(134);
                Feed<0> f;
                const int row = mt * 128;
                auto c_run = [&](const CUtensorMap* m, int off, int n0, int n1) {
#pragma unroll 1
                    for (int n = n0; n < n1; n++) {
                        const uint32_t bar = f.acquire<NA>();
                        mbar_expect(bar, SLOT);
                        tma_ld2(f.dst, m, (off + skip_own(n, mt)) * 64, row, bar);
                        PROF_FEED_A;
                        f.next<NA>();
                    }
                };
                if (roleH) {
                    mbar_expect(base + BAR_DEP, 7 * SLOT);
#pragma unroll 1
                    for (int i = 0; i < 7; i++) {
                        const uint32_t dst = base + (i < 6 ? i : NA + bslot_h(7)) * SLOT;
                        if (i < 6) wait_released(7 + i);
                        tma_ld4(dst, &maps.m[M_WO], 0, i * 64, 0, ns, base + BAR_DEP);
                        tma_ld4(dst + 8192, &maps.m[M_WO], 64, i * 64, 0, ns, base + BAR_DEP);
                    }
                    mbar_wait(base + BAR_DEP, 0);
                    mbar_wait(base + BAR_RDY + 16, 0);
#pragma unroll 1
                    for (int i = 0; i < 7; i++) bulk_st(sc->wo + (size_t)(ns * 7 + i) * SLOT, base + (i < 6 ? i : NA + bslot_h(7)) * SLOT, SLOT);
                    bulk_commit();
                    asm volatile("cp.async.bulk.wait_group 0;" ::: "memory");
                    signal(sc, CNT_W + ns);
                } else if (!roleL) {
                    f.seek(14, 0);
#pragma unroll 1
                    for (int i = 0; i < 4; i++) {
                        const uint32_t bar = f.acquire<NA>();
                        mbar_expect(bar, SLOT);
                        tma_ld2(f.dst, &maps.m[M_CR + (i >> 1)], ((i & 1) * 16 + mt) * 64, row, bar);
                        mbar_arrive(bar);
                        PROF_FEED_A;
                        f.next<NA>();
                    }
                    c_run(&maps.m[M_CR], 0, 0, 15);
                    c_run(&maps.m[M_CI], 0, 0, NBE);
                    wait_dep(2);
#pragma unroll 1
                    for (int i = 0; i < 7; i++) {
                        const uint32_t bar = f.acquire<NA>();
                        mbar_expect(bar, SLOT);
                        bulk_ld(f.dst, sc->o + (size_t)(mt * 7 + i) * SLOT, SLOT, bar);
                        PROF_FEED_A;
                        f.next<NA>();
                    }
                } else {
#pragma unroll 1
                    for (int i = 4; i < 7; i++) {
                        wait_released(2 * i - 8);
                        mbar_expect(full_bar(2 * i), SLOT);
                        tma_ld5(base + i * SLOT, &maps.m[M_XA], i * 64, 0, par, blk, full_bar(2 * i));
                        tma_ld5(base + i * SLOT + 8192, &maps.m[M_XA], i * 64, 1, par, blk, full_bar(2 * i));
                    }
                    wait_released(HALO_K_AT);
                    mbar_arrive(base + BAR_DEP + 16);
                    f.seek(21, 0);
                    c_run(&maps.m[M_CR], 16, 0, 15);
                    c_run(&maps.m[M_CI], 16, 0, 15);
                    c_run(&maps.m[M_CI], 0, NBE, 15);
                }
            }
        } else if (warp == 11) {
            if (elect()) {
#pragma unroll 1
                for (int i = LEAD; i < 7; i++) {
                    while (clk32() - t_open < PACE0 + i * PACE - (roleL & ~i) * PACE_X) {}
                    first_fill(maps, role, i);
                }
                Feed<BRING> f;
                auto blob_run = [&](auto nbs, int quarter, int n0, int n1) {
                    constexpr int N = decltype(nbs)::value;
                    const uint8_t* src = sc->ab + (size_t)(quarter * 64 + ns) * BLOB;
#pragma unroll 1
                    for (int n = n0; n < n1; n++) {
                        const uint32_t bar = f.template acquire<N>();
                        mbar_expect(bar, BLOB);
                        bulk_ld(f.dst, src + skip_own(n, mt) * (4 * BLOB), BLOB, bar);
                        PROF_FEED_B;
                        f.template next<N>();
                    }
                };
                auto v_run = [&](auto nbs) {
                    constexpr int N = decltype(nbs)::value;
#pragma unroll 1
                    for (int i = 0; i < 7; i++) {
                        const uint32_t bar = f.template acquire<N>();
                        mbar_expect(bar, SLOT);
                        tma_ld4(f.dst, &maps.m[M_WV], 0, i * 64, 0, 4 + ns, bar);
                        tma_ld4(f.dst + 8192, &maps.m[M_WV], 64, i * 64, 0, 4 + ns, bar);
                        mbar_arrive(bar);
                        PROF_FEED_B;
                        f.template next<N>();
                    }
                };
                if (roleH) {
                    f.seek(7, bslot_h(7));
                    v_run(Int<7>());
                } else if (!roleL) {
                    f.seek(7, bslot_e(7));
#pragma unroll 1
                    for (int i = 0; i < 7; i++) {
                        const uint32_t bar = f.acquire<5>();
                        mbar_expect(bar, BLOB);
                        tma_ld2(f.dst, &maps.m[M_WI], i * 64, col, bar);
                        mbar_arrive(bar);
                        PROF_FEED_B;
                        f.next<5>();
                    }
                    f.seek(18, bslot_e(18));
                    wait_dep(0);
                    blob_run(Int<7>(), 0, 0, 15);
                    wait_dep(1);
                    blob_run(Int<7>(), 2, 0, NBE);
                    mbar_wait(base + BAR_HINT, 0);
                    fence_async_global();
#pragma unroll 1
                    for (int i = 0; i < 7; i++) {
                        const uint32_t bar = f.acquire<7>();
                        mbar_expect(bar, SLOT);
                        bulk_ld(f.dst, sc->wo + (size_t)(ns * 7 + i) * SLOT, SLOT, bar);
                        PROF_FEED_B;
                        f.next<7>();
                    }

                } else {
                    f.seek(6, bslot_l(6));
#pragma unroll 1
                    for (int i = 6; i < 14; i++) {
                        const uint32_t bar = f.acquire<6>();
                        mbar_expect(bar, SLOT);
                        tma_ld4(f.dst, &maps.m[M_WQK], 0, i * 32, 0, ns, bar);
                        tma_ld4(f.dst + 8192, &maps.m[M_WQK], 64, i * 32, 0, ns, bar);
                        if (i & 1) mbar_arrive(bar);
                        PROF_FEED_B;
                        f.next<6>();
                    }
                    v_run(Int<6>());
                    wait_dep(0);
                    blob_run(Int<6>(), 1, 0, 15);
                    wait_dep(1);
                    blob_run(Int<6>(), 3, 0, 15);
                    blob_run(Int<6>(), 2, NBE, 15);
                    fence_async_smem();
#pragma unroll 1
                    for (int h = 0; h < 2; h++) {
                        mbar_wait(base + BAR_HINT + h * 8, 0);
                        PROF(153 + h);
                        mbar_expect(base + BAR_PART + h * 8, BLOB);
                        bulk_ld(base + (h ? HALO : LSLAB), sc->part + (size_t)((ns * 16 + mt) * 2 + h) * BLOB, BLOB, base + BAR_PART + h * 8);
                    }
                }
            }
        } else if (roleH) {
        } else if (warp == 10) {
            if (elect()) {
                unsigned* epoch_ptr = &sc->epoch[(bid * 4 + 2) * 8];
                const unsigned ep = *epoch_ptr + 1;
                sts1(base + TAG, ep);
                asm volatile("prefetch.tensormap [%0];" ::"l"(&maps.m[M_OUTA + roleL]) : "memory");
                await(sc, CNT_A + roleL * 4 + ns, ep * 16);
                mbar_arrive(base + BAR_DEP);
                PROF(150);
                await(sc, CNT_B + ns, ep * 16);
                mbar_arrive(base + BAR_DEP + 8);
                PROF(151);
                if (!roleL) {
                    await(sc, CNT_W + ns, ep);
                    mbar_arrive(base + BAR_HINT);
                    PROF(153);
                    await(sc, CNT_O + mt, ep * 4);
                    mbar_arrive(base + BAR_DEP + 16);
                } else {
                    await(sc, CNT_P + mt * 4 + ns, ep * 2 - 1);
                    mbar_arrive(base + BAR_HINT);
                    await(sc, CNT_P + mt * 4 + ns, ep * 2);
                    mbar_arrive(base + BAR_HINT + 8);
                }
                PROF(152);
                *epoch_ptr = ep;
            }
        } else if (!roleL) {
            if (elect()) {
                mbar_wait(base + BAR_RDY, 0);
                PROF(130);
                signal(sc, CNT_A + ns);
                PROF(131);
                mbar_wait(base + BAR_RDY + 8, 0);
                signal(sc, CNT_A + 4 + ns);
                PROF(135);
                mbar_wait(base + BAR_RDY + 16, 0);
                PROF(132);
                signal(sc, CNT_B + ns);
                PROF(133);
            }
        } else {
            unsigned* epoch_ptr = &sc->epoch[(bid * 4 + 1) * 8];
            const unsigned tag = *epoch_ptr + 1;
#pragma unroll 1
            for (int kv = 0; kv < 2; kv++) {
                uint32_t v[16];
#pragma unroll
                for (int i = 0; i < 16; i++) v[i] = 0;
                if (kv) wait_released(HALO_V_AT - 4), wait_released(HALO_V_AT);
                else mbar_wait(base + BAR_DEP + 16, 0);
                if (blk > 0) {
                    const uint8_t* src = sc->halo + (size_t)(((par * 8 + blk - 1) * 4 + ns) * 2 + kv) * 2048 + lane * 16;
#pragma unroll 1
                    for (int n = 0; n < SPIN_LIMIT; n++) {
#pragma unroll
                        for (int i = 0; i < 4; i++) ld_tagged(src + i * 512, v[4 * i], v[4 * i + 1], v[4 * i + 2], v[4 * i + 3]);
#pragma unroll
                        for (int i = 0; i < 16; i += 2) v[i] ^= tag & 1;
                        const uint32_t stale = or3(or3(v[0], v[2], v[4]), or3(v[6], v[8], v[10]), or3(v[12], v[14], 0));
                        if (__all_sync(0xffffffffu, !(stale & 1))) break;
                    }
#pragma unroll
                    for (int c = 0; c < 14; c += 2) v[c] |= (v[15] >> c) & 1;
                }
#pragma unroll
                for (int i = 0; i < 14; i++) sts1(base + HALO + kv * (8 * HSLOT) + i * 128 + lane * 4, v[i]);
                warp_arrive(base + BAR_HALO + kv * 8);
                if (lane == 0) PROF(142 + kv);
            }
            if (elect()) {
                mbar_wait(base + BAR_RDY + 16, 0);
                PROF(130);
                signal(sc, CNT_O + mt);
                PROF(131);
                *epoch_ptr = tag;
            }
        }
    } else {
        asm volatile("setmaxnreg.inc.sync.aligned.u32 224;");
        Ring r;
        r.wg = warp >> 2;
        r.zero = blockIdx.y;
        r.releaser = lane + 1 == (warp >> 2);
        const int wg = warp >> 2;
        if (wg) {
            nb_arrive(1, 256);
            mbar_wait(base + BAR_X, 0);
        }
        uint8_t* part = sc->part + (size_t)(ns * 16 + mt) * (2 * BLOB) + warp * WSLOT + lane * 16;
        uint32_t p[28];

        if (roleH) {
            unsigned* epoch_ptr = &sc->epoch[bid * 4 * 8];
            const unsigned tag = *epoch_ptr + 1;
            uint8_t* hout = sc->halo + (size_t)((warp * 8 + ns) * 2) * 2048 + lane * 16;
            auto send = [&](int kv) {
#pragma unroll
                for (int h = 0; h < 2; h++) {
                    uint32_t v[16];
                    v[14] = v[15] = 0;
#pragma unroll
                    for (int c = 0; c < 14; c++) v[c] = p[2 * c + h];
#pragma unroll
                    for (int c = 0; c < 14; c += 2) v[15] |= (v[c] & 1) << c;
#pragma unroll
                    for (int i = 0; i < 4; i++)
                        st_tagged(hout + (h * 8 + kv) * 2048 + i * 512, tagged(v[4 * i], v[4 * i + 1], tag), tagged(v[4 * i + 2], v[4 * i + 3], tag));
                }
            };
            float x0[56], x1[56];
            r.seek(0, bslot_h(0));
            r.wait();
            r.run<XWN, 7, true>(x0);
#pragma unroll 1
            for (int i = 1; i < 7; i++) r.run<XWN, 7, false>(x0);
            r.run<XWN, 7, true>(x1);
            acc_fence(x0);
            pack_all(x0, p);
            send(0);
#pragma unroll 1
            for (int i = 1; i < 7; i++) r.run<XWN, 7, false>(x1, true, i < 6 || !wg, i < 6);
            asm volatile("wgmma.wait_group.sync.aligned 0;" ::: "memory");
            acc_fence(x1);
            pack_all(x1, p);
#pragma unroll
            for (int i = 0; i < 28; i++) p[i] = movm(p[i]);
            send(1);
            warp_arrive(base + BAR_RDY + 16);
            if (threadIdx.x == 0) *epoch_ptr = tag;
        } else if (!roleL) {
            uint8_t* blob = sc->ab + (size_t)((wg * 16 + mt) * 4 + ns) * BLOB + (warp & 3) * WSLOT + lane * 4;
            const uint32_t own = base + BRING + wg * SLOT + (warp & 3) * WSLOT + lane * 16;
            float x0[56], x1[56];
            r.seek(0, bslot_e(0));
            r.wait();
            r.run<XW, 7, true>(x0);
            r.run<XW, 7, false>(x0);
            r.seek(2, bslot_e(2));
#pragma unroll 1
            for (int i = 2; i < 7; i++) r.run<XW, 5, false>(x0);

            r.seek(7, bslot_e(7));
            r.run<XW, 5, true, -1>(x1);
            acc_fence(x0);
            pack_all<0, 14>(x0, p);
#pragma unroll
            for (int i = 0; i < 2; i++) {
                if (wg == i) store_frags<0, 14>(blob, p);
                else stage_frags<0, 4>(own + 5 * SLOT, p);
                r.run<XW, 5, false, -1>(x1);
                if (i == 0) pack_all<14, 28>(x0, p);
                if (wg == i) {
                    store_frags<14, 28>(blob, p);
                    warp_arrive(base + BAR_RDY + i * 8);
                } else {
                    stage_frags<4, 8>(own + 5 * SLOT, p);
                }
                r.run<XW, 5, false, -1>(x1);
            }
            stage_frags<8, 16>(own + 5 * SLOT, p);
            r.run<XW, 5, false, -1>(x1);
            stage_frags<16, 24>(own + 5 * SLOT, p);
            r.run<XW, 5, false, -1>(x1);
            stage_frags<24, 28>(own + 5 * SLOT, p);

            r.seek(14, bslot_e(14));
            r.take_turn();
            fence_async_smem();
            r.run<BIG, 7, true>(x0, false);
            acc_fence(x1);
            pack_all(x1, p);
            stage_frags<0, 16>(own, p);
            r.run<BIG, 7, false>(x0);
            stage_frags<16, 28>(own, p);
            r.take_turn();
            fence_async_smem();
            blob += (size_t)128 * BLOB;
            r.run<BIG, 7, false>(x0, false);
#pragma unroll
            for (int i = 0; i < 28; i++) {
                if (i % B_SLICE == 0) r.run<BIG, 7, false>(x0);
                stg1(blob + i * 128, p[i]);
            }
            warp_arrive(base + BAR_RDY + 16);
#pragma unroll 1
            for (int i = 18 + 27 / B_SLICE; i < POUT; i++) r.run<BIG, 7, false>(x0);

            const uint32_t tag = lds1(base + TAG);
            r.seek(POUT, bslot_e(POUT));
            r.run<OUT, 7, true>(x1);
            acc_fence(x0);
            pack_all(x0, p);
            uint64_t u[14];
#pragma unroll
            for (int i = 0; i < 14; i++) u[i] = tagged(p[2 * i], p[2 * i + 1], tag);
#pragma unroll
            for (int k = 0; k < 2; k++) {
                if (wg == k) {
#pragma unroll
                    for (int i = 0; i < 7; i++) st_tagged(part + i * 512, u[2 * i], u[2 * i + 1]);
                }
                r.run<OUT, 7, false>(x1);
                if (warp * 32 + lane == k * 128)
                    asm volatile("red.relaxed.gpu.global.add.u32 [%0], 1;" ::"l"(&sc->cnt[(CNT_P + mt * 4 + ns) * 32]) : "memory");
            }
#pragma unroll
            for (int i = 3; i < 7; i++) r.run<OUT, 7, false, 1, true>(x1, i <= 7 - TURN, i < 7 - TURN || (i == 6 && !wg), i < 6);

            asm volatile("wgmma.wait_group.sync.aligned 0;" ::: "memory");
            acc_fence(x1);
            const uint32_t slab = base + (wg ? BRING + bslot_e(ELAST - 6) * SLOT : ((ELAST - 6) % NA) * SLOT) + (warp & 3) * WSLOT;
            store_out([&](int i) { return pack2(x1[2 * i], x1[2 * i + 1]); }, lane, slab, &maps.m[M_OUTA], par * 896 + col, blk * 128 + warp * 16);
        } else {
            const int g = lane >> 2, tig = lane & 3;
            const uint32_t hin = base + HALO + warp * HSLOT + lane * 4;
            const uint32_t hpub = warp < 7 ? hin + HSLOT : base + HSPARE + lane * 4;
            auto publish = [&](const uint32_t (&h)[14], int c0, int c1) {
#pragma unroll
                for (int c = 0; c < 14; c++)
                    if (c >= c0 && c < c1) sts1(hpub + c * 128, h[c]);
            };
            float y0[56], y1[56], y2[56];
            r.seek(0, bslot_l(0));
            r.wait();
            r.run<QK, 6, true>(y0, y1);
#pragma unroll 1
            for (int i = 1; i < 14; i++) r.run<QK, 6, false>(y0, y1);

            uint32_t m1[8][4], m0[8][4], lo[14], hi[14], q[2][8][2];
            auto pack_q = [&](int b) {
                uint32_t v[14];
#pragma unroll
                for (int c = 0; c < 14; c++) v[c] = pack2(y0[4 * c + 2 * b], y0[4 * c + 2 * b + 1]);
#pragma unroll
                for (int t = 0; t < 8; t++) {
                    const int c = tile_of(t);
                    q[b][t][0] = (t & 3) == 2 ? (tig >= 2 ? v[c] : 0u) : v[c];
                    q[b][t][1] = (t & 3) == 1 ? (tig < 2 ? v[c + 1] : 0u) : v[c + 1];
                }
            };
            auto fetch = [&](uint32_t src, int hp, int i0) {
#pragma unroll
                for (int t = 4 * hp; t < 4 * hp + 4; t++) {
                    m0[t][i0] = (t & 3) == 2 ? dup(m0[t - 1][3], r.zero) : lds1(src + tile_of(t) * 128);
                    m0[t][3] = lds1(src + tile_of(t) * 128 + 128);
                }
            };
            r.seek(14, bslot_l(14));
            r.run<XWN, 6, true>(y2);
            acc_fence(y0);
            acc_fence(y1);
#pragma unroll
            for (int c = 0; c < 14; c++) hi[c] = pack2(y1[4 * c + 2], y1[4 * c + 3]);
            publish(hi, 0, 7);
            r.run<XWN, 6, false>(y2);
            publish(hi, 7, 14);
#pragma unroll
            for (int c = 0; c < 14; c++) lo[c] = pack2(y1[4 * c], y1[4 * c + 1]);
#pragma unroll
            for (int t = 0; t < 8; t++) {
                const int c = tile_of(t);
                const bool shared = (t & 3) == 2;
                m1[t][0] = shared ? dup(lo[c], r.zero) : lo[c];
                m1[t][1] = shared ? dup(hi[c], r.zero) : hi[c];
                m1[t][2] = lo[c + 1];
                m1[t][3] = hi[c + 1];
                m0[t][0] = dup(m1[t][0], r.zero);
                m0[t][2] = dup(lo[c + 1], 2 * r.zero);
            }
            r.run<XWN, 6, false>(y2);
            if (warp == 0) mbar_wait(base + BAR_HALO, 0);
            fetch(hin, 0, 1);
            pack_q(1);
            r.run<XWN, 6, false>(y2);
            fetch(hin, 1, 1);
            pack_q(0);
            r.mma_begin();
            float s[8][4];
#pragma unroll
            for (int step = 0; step < 2; step++) {
#pragma unroll
                for (int i = 0; i < 8; i++) {
                    const int b = 1 - (i >> 2), h = i & 3, t = 2 * h + step;
                    float (&d)[4] = s[2 * h + b];
                    if (step == 0) d[0] = d[1] = d[2] = d[3] = 0.f;
                    mma16816(d, b ? m1[t] : m0[t], q[b][t][0], q[b][t][1]);
                }
            }
            r.mma_end();
            r.run<XWN, 6, false>(y2, false);

            uint32_t pr[8], mx[4], mx1[4];
            {
                const bool cur0 = g <= 2 * tig, cur1 = g <= 2 * tig + 1;
#pragma unroll
                for (int i = 0; i < 8; i++) {
                    const int c = (i & 1) ? 2 : 0;
                    pr[i] = movm(pack2(cur0 ? s[i][c] : s[i][2 - c], cur1 ? s[i][c + 1] : s[i][3 - c]));
                }
            }
            r.run<XWN, 6, false>(y2);
            const uint32_t curmask = (2 * tig <= g ? 0x0000FFFFu : 0u) | (2 * tig + 1 <= g ? 0xFFFF0000u : 0u);
            {
                const uint32_t keep = (blk == 0 && warp == 0) ? curmask : 0xFFFFFFFFu;
#pragma unroll
                for (int i = 0; i < 4; i++) {
                    pr[2 * i] = (scale2(pr[2 * i]) & keep) | (0xCE6ECE6Eu & ~keep);
                    pr[2 * i + 1] = scale2(pr[2 * i + 1]);
                    mx[i] = max2(__byte_perm(pr[2 * i], pr[2 * i + 1], 0x5410), __byte_perm(pr[2 * i], pr[2 * i + 1], 0x7632));
                    mx1[i] = __shfl_xor_sync(0xffffffffu, mx[i], 1);
                }
            }
#pragma unroll
            for (int i = 0; i < 4; i++) {
                mx[i] = max2(mx[i], mx1[i]);
                mx1[i] = __shfl_xor_sync(0xffffffffu, mx[i], 2);
            }
            r.run<XWN, 6, false>(y2);
            constexpr float SCL = 1.4426950408889634f;
            float e0[8], e1[8], sm[8], sm1[8];
#pragma unroll
            for (int i = 0; i < 8; i++) {
                const uint32_t m2 = max2(mx[i >> 1], mx1[i >> 1]);
                sm[i] = ((i & 1) ? bf_hi(m2) : bf_lo(m2)) * -SCL;
                e0[i] = ex2(fmaf(bf_lo(pr[i]), SCL, sm[i]));
            }

            r.seek(21, bslot_l(21));
            r.run<BIG, 6, true>(y0);
            acc_fence(y2);
#pragma unroll
            for (int c = 0; c < 7; c++) hi[c] = movm(pack2(y2[4 * c + 2], y2[4 * c + 3]));
#pragma unroll
            for (int i = 0; i < 8; i++) e1[i] = ex2(fmaf(bf_hi(pr[i]), SCL, sm[i]));
            r.run<BIG, 6, false>(y0);
            publish(hi, 0, 7);
#pragma unroll
            for (int c = 7; c < 14; c++) hi[c] = movm(pack2(y2[4 * c + 2], y2[4 * c + 3]));
            r.run<BIG, 6, false>(y0);
            publish(hi, 7, 14);
#pragma unroll
            for (int i = 0; i < 8; i++) {
                sm[i] = e0[i] + e1[i];
                sm1[i] = __shfl_xor_sync(0xffffffffu, sm[i], 1);
            }
            r.run<BIG, 6, false>(y0);
#pragma unroll
            for (int c = 0; c < 14; c++) lo[c] = movm(pack2(y2[4 * c], y2[4 * c + 1]));
            r.run<BIG, 6, false>(y0);
#pragma unroll
            for (int i = 0; i < 8; i++) {
                sm[i] += sm1[i];
                sm1[i] = __shfl_xor_sync(0xffffffffu, sm[i], 2);
            }
#pragma unroll
            for (int t = 0; t < 8; t++) {
                const int c = tile_of(t);
                const bool shared = (t & 3) == 2;
                m1[t][0] = shared ? dup(lo[c], r.zero) : lo[c];
                m1[t][1] = lo[c + 1];
                m1[t][2] = shared ? dup(hi[c], r.zero) : hi[c];
                m1[t][3] = hi[c + 1];
                m0[t][0] = dup(m1[t][0], r.zero);
                m0[t][1] = dup(lo[c + 1], 2 * r.zero);
            }
            r.run<BIG, 6, false>(y0);
            if (warp == 0) mbar_wait(base + BAR_HALO + 8, 0);
            const uint32_t vin = warp ? hin : hin + 8 * HSLOT;
            fetch(vin, 0, 2);
#pragma unroll
            for (int i = 0; i < 8; i++) {
                const float inv = rcp(sm[i] + sm1[i]);
                pr[i] = pack2(e0[i] * inv, e1[i] * inv);
            }
            r.run<BIG, 6, false>(y0);
            fetch(vin, 1, 2);
            uint32_t pb[8][2];
#pragma unroll
            for (int t = 0; t < 8; t++) {
                pb[t][t & 1] = band(pr[t], curmask);
                pb[t][1 - (t & 1)] = band(pr[t], ~curmask);
            }
            r.mma_begin();
            float o[2][8][4];
#pragma unroll
            for (int i = 0; i < 16; i++) {
                const int b = 1 - (i >> 3), t = i & 7;
                float (&d)[4] = o[b][t];
                d[0] = d[1] = d[2] = d[3] = 0.f;
                mma16816(d, b ? m1[t] : m0[t], pb[(t & 6) + b][0], pb[(t & 6) + b][1]);
            }
            r.mma_end();
            r.run<BIG, 6, false>(y0, false);
            uint8_t* odst = sc->o + (size_t)mt * 7 * SLOT + ns * (14 * 2048) + warp * 256 + lane * 4;
#pragma unroll
            for (int hp = 0; hp < 2; hp++) {
#pragma unroll
                for (int b = 0; b < 2; b++) {
                    const float (&u)[8][4] = o[b];
                    const int t = 4 * hp;
                    uint32_t* w = p + 14 * hp + b;
                    w[0] = pack2(u[t][0], u[t][1]);
                    w[2] = pack2(u[t][2], u[t][3]);
                    w[4] = pack2(u[t + 1][0], u[t + 1][1]);
                    w[6] = pack2(g < 4 ? u[t + 1][2] : u[t + 2][0], g < 4 ? u[t + 1][3] : u[t + 2][1]);
                    w[8] = pack2(u[t + 2][2], u[t + 2][3]);
                    w[10] = pack2(u[t + 3][0], u[t + 3][1]);
                    w[12] = pack2(u[t + 3][2], u[t + 3][3]);
                }
            }
#pragma unroll
            for (int i = 0; i < 28; i++) {
                if (i >= O_FIRST && (i - O_FIRST) % O_SLICE == 0) r.run<BIG, 6, false>(y0);
                stg1(odst + (i >> 1) * 2048 + (i & 1) * 128, p[i]);
            }
            warp_arrive(base + BAR_RDY + 16);

#pragma unroll 1
            for (int i = 30 + (27 - O_FIRST) / O_SLICE; i <= LLAST - LTURN; i++) r.run<BIG, 6, false>(y0);
            r.seek(LLAST + 1 - LTURN, bslot_l(LLAST + 1 - LTURN));
#pragma unroll
            for (int i = 0; i < LTURN; i++) r.run<BIG, 6, false, 1, true>(y0, i == 0, i == LTURN - 1 && !wg, i < LTURN - 1);
            const uint32_t parity = lds1(base + TAG) & 1;
            const uint32_t slab = base + (wg ? HALO : LSLAB) + (warp & 3) * WSLOT;
            mbar_wait(base + BAR_PART + wg * 8, 0);
#pragma unroll 1
            for (int n = 0; n < SPIN_LIMIT; n++) {
#pragma unroll
                for (int i = 0; i < 7; i++) lds4(slab + i * 512 + lane * 16, p + 4 * i);
#pragma unroll
                for (int i = 0; i < 28; i += 2) p[i] ^= parity;
                const uint32_t stale = or3(or3(or3(p[0], p[2], p[4]), or3(p[6], p[8], p[10]), or3(p[12], p[14], p[16])),
                                           or3(p[18], p[20], p[22]), or3(p[24], p[26], 0));
                if (__all_sync(0xffffffffu, !(stale & 1))) break;
#pragma unroll
                for (int i = 0; i < 7; i++) ld_tagged(part + i * 512, p[4 * i], p[4 * i + 1], p[4 * i + 2], p[4 * i + 3]);
#pragma unroll
                for (int i = 0; i < 7; i++)
                    asm volatile("st.shared.v4.b32 [%0], {%1,%2,%3,%4};" ::"r"(slab + i * 512 + lane * 16), "r"(p[4 * i]), "r"(p[4 * i + 1]), "r"(p[4 * i + 2]), "r"(p[4 * i + 3]) : "memory");
            }
            asm volatile("wgmma.wait_group.sync.aligned 0;" ::: "memory");
            acc_fence(y0);
            store_out([&](int i) { return add2(pack2(y0[2 * i], y0[2 * i + 1]), p[i]); }, lane, slab, &maps.m[M_OUTB], 448 + col, mt * 128 + warp * 16);
        }
    }
}

typedef CUresult (*EncodeFn)(CUtensorMap*, CUtensorMapDataType, cuuint32_t, void*, const cuuint64_t*, const cuuint64_t*,
                             const cuuint32_t*, const cuuint32_t*, CUtensorMapInterleave, CUtensorMapSwizzle,
                             CUtensorMapL2promotion, CUtensorMapFloatOOBfill);

struct Dim { uint64_t size, stride; uint32_t box; };
void encode(EncodeFn fn, CUtensorMap* m, const void* ptr, CUtensorMapSwizzle sw, Dim d0, Dim d1, Dim d2 = {0, 0, 0},
            Dim d3 = {0, 0, 0}, Dim d4 = {0, 0, 0}) {
    const cuuint64_t dims[5] = {d0.size, d1.size, d2.size, d3.size, d4.size};
    const cuuint64_t strides[4] = {d1.stride, d2.stride, d3.stride, d4.stride};
    const cuuint32_t box[5] = {d0.box, d1.box, d2.box, d3.box, d4.box};
    const cuuint32_t es[5] = {1, 1, 1, 1, 1};
    fn(m, CU_TENSOR_MAP_DATA_TYPE_BFLOAT16, d4.size ? 5 : d3.size ? 4 : 2, const_cast<void*>(ptr), dims, strides, box, es,
       CU_TENSOR_MAP_INTERLEAVE_NONE, sw, CU_TENSOR_MAP_L2_PROMOTION_L2_128B, CU_TENSOR_MAP_FLOAT_OOB_FILL_NONE);
}

}

extern "C" void kernel_launch(void* const* d_in, const int* in_sizes, int n_in, void* d_out, int out_size) {
    (void)in_sizes; (void)n_in; (void)out_size;
    void* fnp = nullptr;
    cudaDriverEntryPointQueryResult st;
    cudaGetDriverEntryPoint("cuTensorMapEncodeTiled", &fnp, cudaEnableDefault, &st);
    EncodeFn fn = (EncodeFn)fnp;
    void* scratch = nullptr;
    cudaGetSymbolAddress(&scratch, g_scratch);
    int dev = 0, sms = 0;
    cudaGetDevice(&dev);
    cudaDeviceGetAttribute(&sms, cudaDevAttrMultiProcessorCount, dev);
    auto kernel = sms == 132 ? fused_kernel<true> : fused_kernel<false>;
    cudaFuncSetAttribute(kernel, cudaFuncAttributeMaxDynamicSharedMemorySize, SMEM_BYTES);

    const CUtensorMapSwizzle S128 = CU_TENSOR_MAP_SWIZZLE_128B, S0 = CU_TENSOR_MAP_SWIZZLE_NONE;
    const Dim one = {1, 16, 1};
    Maps maps;
    encode(fn, &maps.m[M_XA], d_in[0], S128, {448, 2, 64}, {64, 1792, 64}, {2, 64 * 1792, 1}, {2, 896, 1}, {8, 128 * 1792, 1});
    encode(fn, &maps.m[M_WQK], d_in[1], S128, {112, 2, 64}, {448, 2688, 32}, {3, 896, 2}, {4, 224, 1});
    encode(fn, &maps.m[M_WV], (const uint8_t*)d_in[1] + 896, S128, {112, 2, 64}, {448, 2688, 64}, one, {8, 224, 1});
    encode(fn, &maps.m[M_XH], d_in[0], S128, {448, 2, 64}, {8, 1792, 8}, {2, 896, 1}, {8, 128 * 1792, 8}, {3, 60 * 1792, 1});
    encode(fn, &maps.m[M_WO], d_in[2], S128, {112, 2, 64}, {448, 896, 64}, one, {4, 224, 1});
    encode(fn, &maps.m[M_XB], d_in[3], S128, {448, 2, 64}, {64, 896, 64}, {2, 896 * 1024, 1}, {2, 64 * 896, 1}, {8, 128 * 896, 1});
    encode(fn, &maps.m[M_CR], d_in[4], S128, {2048, 2, 64}, {2048, 4096, 128});
    encode(fn, &maps.m[M_CI], d_in[5], S128, {2048, 2, 64}, {2048, 4096, 128});
    encode(fn, &maps.m[M_WR], d_in[6], S128, {448, 2, 64}, {112, 896, 64}, one, {4, 112 * 896, 1});
    encode(fn, &maps.m[M_WI], d_in[7], S128, {448, 2, 64}, {448, 896, 112});
    encode(fn, &maps.m[M_OUTA], d_out, S0, {1792, 2, 112}, {1024, 3584, 8});
    encode(fn, &maps.m[M_OUTB], d_out, S0, {896, 2, 112}, {2048, 1792, 8});

    kernel<<<132, 384, SMEM_BYTES>>>((Scratch*)scratch, maps);
}
```

```cpp
#include <cuda.h>
#include <cuda_bf16.h>
#include <cuda_runtime.h>
#include <stdint.h>

namespace {

constexpr uint32_t SLOT = 16384;
constexpr int NA = 7;
constexpr uint32_t BRING = NA * SLOT;
constexpr uint32_t HALO = BRING + 6 * SLOT;
constexpr uint32_t HSLOT = 1792;
constexpr uint32_t WSLOT = 3584;
constexpr uint32_t BLOB = 14336;
constexpr uint32_t BARS = 14 * SLOT;
constexpr uint32_t BAR_FULL = BARS;
constexpr uint32_t BAR_EMPTY = BARS + 64;
constexpr uint32_t BAR_RDY = BARS + 128;
constexpr uint32_t BAR_DEP = BARS + 168;
constexpr uint32_t BAR_HALO = BARS + 192;
constexpr uint32_t BAR_PART = BARS + 208;
constexpr uint32_t BAR_HINT = BARS + 224;
constexpr uint32_t BAR_X = BARS + 152;
constexpr uint32_t TAG = BARS + 240;
constexpr uint32_t HSPARE = BARS + 256 + 1024;
constexpr uint32_t SMEM_BYTES = HSPARE + HSLOT;
constexpr uint32_t base = 1024;
constexpr int SPIN_LIMIT = 1 << 16;

constexpr int LEAD = 2;
constexpr int PACE0 = 700, PACE = 450;
constexpr int PACE_X = 250;
constexpr int HALO_K_AT = 11;
constexpr int HALO_V_AT = 19;
constexpr int B_SLICE = 4;
constexpr int O_FIRST = 7, O_SLICE = 3;
constexpr int TURN = 4, LTURN = 5;
constexpr uint32_t GPC_MAP = 0x64753210u;
constexpr int NBE = 13;
constexpr int POUT = 33 + NBE;
constexpr int ELAST = POUT + 6;
constexpr int LLAST = 65 - NBE;
constexpr uint32_t LSLAB = ((LLAST - 6) % NA) * SLOT;
static_assert(TURN <= 4 && LTURN <= 5, "the output is staged in the slots of the seventh-last stage");

enum { M_XB, M_XA, M_XH, M_WR, M_WQK, M_WV, M_WO, M_WI, M_CR, M_CI, M_OUTA, M_OUTB, M_COUNT };
struct __align__(64) Maps { CUtensorMap m[M_COUNT]; };

constexpr int CNT_A = 0;
constexpr int CNT_B = 8;
constexpr int CNT_W = 12;
constexpr int CNT_O = 16;
constexpr int CNT_P = 32;
constexpr int CNT_COUNT = 96;

struct Scratch {
    uint8_t ab[64 * 4 * BLOB];
    uint8_t o[16 * 7 * SLOT];
    uint8_t part[64 * 2 * BLOB];
    uint8_t halo[64 * 2 * 2048];
    uint8_t wo[4 * 7 * SLOT];
    unsigned cnt[CNT_COUNT * 32];
    unsigned epoch[132 * 4 * 8];
};
__device__ __align__(1024) Scratch g_scratch;

__device__ __forceinline__ unsigned clk32() { unsigned c; asm volatile("mov.u32 %0, %%clock;" : "=r"(c)); return c; }

#define PROF(idx)

__device__ __forceinline__ void mbar_init(uint32_t bar, uint32_t cnt) {
    asm volatile("mbarrier.init.shared::cta.b64 [%0], %1;" ::"r"(bar), "r"(cnt) : "memory");
}
__device__ __forceinline__ void mbar_expect(uint32_t bar, uint32_t bytes) {
    asm volatile("mbarrier.arrive.expect_tx.shared::cta.b64 _, [%0], %1;" ::"r"(bar), "r"(bytes) : "memory");
}
__device__ __forceinline__ void mbar_arrive(uint32_t bar) {
    asm volatile("mbarrier.arrive.shared::cta.b64 _, [%0];" ::"r"(bar) : "memory");
}
__device__ __forceinline__ bool mbar_try(uint32_t bar, uint32_t parity) {
    uint32_t ok;
    asm volatile("{\n.reg .pred p;\nmbarrier.try_wait.parity.shared::cta.b64 p, [%1], %2;\nselp.u32 %0, 1, 0, p;\n}\n"
                 : "=r"(ok) : "r"(bar), "r"(parity) : "memory");
    return ok;
}
__device__ __forceinline__ void mbar_wait(uint32_t bar, uint32_t parity) {
#pragma unroll 1
    for (int n = 0; n < SPIN_LIMIT; n++)
        if (mbar_try(bar, parity)) break;
}
__device__ __forceinline__ bool elect() {
    uint32_t p;
    asm volatile("{\n.reg .pred p;\nelect.sync _|p, 0xffffffff;\nselp.u32 %0, 1, 0, p;\n}\n" : "=r"(p));
    return p;
}
__device__ __forceinline__ void nb_sync(int id, int n) { asm volatile("bar.sync %0, %1;" ::"r"(id), "r"(n) : "memory"); }
__device__ __forceinline__ void nb_arrive(int id, int n) { asm volatile("bar.arrive %0, %1;" ::"r"(id), "r"(n) : "memory"); }
__device__ __forceinline__ void warp_arrive(uint32_t bar) {
    __syncwarp();
    if (elect()) mbar_arrive(bar);
}
__device__ __forceinline__ uint32_t or3(uint32_t a, uint32_t b, uint32_t c) {
    uint32_t r;
    asm("lop3.b32 %0, %1, %2, %3, 0xFE;" : "=r"(r) : "r"(a), "r"(b), "r"(c));
    return r;
}
__device__ __forceinline__ uint32_t band(uint32_t x, uint32_t m) {
    uint32_t r;
    asm volatile("and.b32 %0, %1, %2;" : "=r"(r) : "r"(x), "r"(m));
    return r;
}
__device__ __forceinline__ void boundary(uint32_t zero) {
    asm volatile("{\n.reg .pred p;\nsetp.ne.u32 p, %0, 0;\nPIN:\npmevent 7;\n@p bra.uni PIN;\n}\n" ::"r"(zero) : "memory");
}
__device__ __forceinline__ uint32_t dup(uint32_t x, uint32_t zero) {
    uint32_t r;
    asm volatile("xor.b32 %0, %1, %2;" : "=r"(r) : "r"(x), "r"(zero));
    return r;
}

__device__ __forceinline__ void tma_ld2(uint32_t dst, const CUtensorMap* m, int c0, int c1, uint32_t bar) {
    asm volatile("cp.async.bulk.tensor.2d.shared::cluster.global.mbarrier::complete_tx::bytes [%0], [%1, {%3, %4}], [%2];"
                 ::"r"(dst), "l"(m), "r"(bar), "r"(c0), "r"(c1) : "memory");
}
__device__ __forceinline__ void tma_ld4(uint32_t dst, const CUtensorMap* m, int c0, int c1, int c2, int c3, uint32_t bar) {
    asm volatile("cp.async.bulk.tensor.4d.shared::cluster.global.mbarrier::complete_tx::bytes [%0], [%1, {%3, %4, %5, %6}], [%2];"
                 ::"r"(dst), "l"(m), "r"(bar), "r"(c0), "r"(c1), "r"(c2), "r"(c3) : "memory");
}
__device__ __forceinline__ void tma_ld5(uint32_t dst, const CUtensorMap* m, int c0, int c2, int c3, int c4, uint32_t bar) {
    asm volatile("cp.async.bulk.tensor.5d.shared::cluster.global.mbarrier::complete_tx::bytes [%0], [%1, {%3, 0, %4, %5, %6}], [%2];"
                 ::"r"(dst), "l"(m), "r"(bar), "r"(c0), "r"(c2), "r"(c3), "r"(c4) : "memory");
}
__device__ __forceinline__ void bulk_ld(uint32_t dst, const void* src, uint32_t bytes, uint32_t bar) {
    asm volatile("cp.async.bulk.shared::cluster.global.mbarrier::complete_tx::bytes [%0], [%1], %2, [%3];"
                 ::"r"(dst), "l"(src), "r"(bytes), "r"(bar) : "memory");
}
__device__ __forceinline__ void bulk_st(void* dst, uint32_t src, uint32_t bytes) {
    asm volatile("cp.async.bulk.global.shared::cta.bulk_group [%0], [%1], %2;" ::"l"(dst), "r"(src), "r"(bytes) : "memory");
}
__device__ __forceinline__ void tma_st2(const CUtensorMap* m, int c0, int c1, uint32_t src) {
    asm volatile("cp.async.bulk.tensor.2d.global.shared::cta.bulk_group [%0, {%1, %2}], [%3];"
                 ::"l"(m), "r"(c0), "r"(c1), "r"(src) : "memory");
}
__device__ __forceinline__ void bulk_commit() { asm volatile("cp.async.bulk.commit_group;" ::: "memory"); }
__device__ __forceinline__ void bulk_wait_read() { asm volatile("cp.async.bulk.wait_group.read 0;" ::: "memory"); }
__device__ __forceinline__ void fence_async_smem() { asm volatile("fence.proxy.async.shared::cta;" ::: "memory"); }
__device__ __forceinline__ void fence_async_global() { asm volatile("fence.proxy.async.global;" ::: "memory"); }

__device__ __forceinline__ void signal(Scratch* sc, int idx) {
    asm volatile("fence.proxy.async;\nred.relaxed.gpu.global.add.u32 [%0], 1;" ::"l"(&sc->cnt[idx * 32]) : "memory");
}
__device__ __forceinline__ unsigned peek(const unsigned* p) {
    unsigned v;
    asm volatile("ld.relaxed.gpu.global.u32 %0, [%1];" : "=r"(v) : "l"(p) : "memory");
    return v;
}
__device__ __forceinline__ void await(Scratch* sc, int idx, unsigned target) {
    const unsigned* p = &sc->cnt[idx * 32];
#pragma unroll 1
    for (int n = 0; n < SPIN_LIMIT; n++)
        if ((int)(peek(p) - target) >= 0) break;
    asm volatile("fence.acquire.gpu;" ::: "memory");
}
__device__ __forceinline__ void wait_dep(int k) {
    mbar_wait(base + BAR_DEP + k * 8, 0);
    fence_async_global();
}

#define WG_REGS                                                                                                     \
    "{%0,%1,%2,%3,%4,%5,%6,%7,%8,%9,%10,%11,%12,%13,%14,%15,%16,%17,%18,%19,%20,%21,%22,%23,%24,%25,%26,%27,"       \
    "%28,%29,%30,%31,%32,%33,%34,%35,%36,%37,%38,%39,%40,%41,%42,%43,%44,%45,%46,%47,%48,%49,%50,%51,%52,%53,%54,%55}"
#define WG_OPS(C)                                                                                                   \
    C(d[0]), C(d[1]), C(d[2]), C(d[3]), C(d[4]), C(d[5]), C(d[6]), C(d[7]), C(d[8]), C(d[9]), C(d[10]), C(d[11]),   \
    C(d[12]), C(d[13]), C(d[14]), C(d[15]), C(d[16]), C(d[17]), C(d[18]), C(d[19]), C(d[20]), C(d[21]), C(d[22]),   \
    C(d[23]), C(d[24]), C(d[25]), C(d[26]), C(d[27]), C(d[28]), C(d[29]), C(d[30]), C(d[31]), C(d[32]), C(d[33]),   \
    C(d[34]), C(d[35]), C(d[36]), C(d[37]), C(d[38]), C(d[39]), C(d[40]), C(d[41]), C(d[42]), C(d[43]), C(d[44]),   \
    C(d[45]), C(d[46]), C(d[47]), C(d[48]), C(d[49]), C(d[50]), C(d[51]), C(d[52]), C(d[53]), C(d[54]), C(d[55])

template <int TA, int TB, int SB, bool INIT, uint32_t AH, uint32_t BH>
__device__ __forceinline__ void wgmma112(float (&d)[56], uint32_t alo, uint32_t blo) {
    if (INIT) {
        asm volatile("{\n.reg .pred p;\n.reg .b64 da, db;\nsetp.ne.b32 p, 0, 0;\nmov.b64 da, {%56, %61};\nmov.b64 db, {%57, %62};\n"
                     "wgmma.mma_async.sync.aligned.m64n112k16.f32.bf16.bf16 " WG_REGS ", da, db, p, 1, %59, %60, %58;\n}\n"
                     : WG_OPS("=f") : "r"(alo), "r"(blo), "n"(TB), "n"(SB), "n"(TA), "n"(AH), "n"(BH));
    } else {
        asm volatile("{\n.reg .pred p;\n.reg .b64 da, db;\nsetp.ne.b32 p, 1, 0;\nmov.b64 da, {%56, %61};\nmov.b64 db, {%57, %62};\n"
                     "wgmma.mma_async.sync.aligned.m64n112k16.f32.bf16.bf16 " WG_REGS ", da, db, p, 1, %59, %60, %58;\n}\n"
                     : WG_OPS("+f") : "r"(alo), "r"(blo), "n"(TB), "n"(SB), "n"(TA), "n"(AH), "n"(BH));
    }
}
__device__ __forceinline__ void acc_fence(float (&d)[56]) {
#pragma unroll
    for (int i = 0; i < 56; i++) asm volatile("" : "+f"(d[i])::"memory");
}

__device__ __forceinline__ uint32_t pack2(float lo, float hi) {
    uint32_t r;
    asm volatile("cvt.rn.bf16x2.f32 %0, %1, %2;" : "=r"(r) : "f"(hi), "f"(lo));
    return r;
}
__device__ __forceinline__ uint32_t movm(uint32_t a) {
    uint32_t r;
    asm volatile("movmatrix.sync.aligned.m8n8.trans.b16 %0, %1;" : "=r"(r) : "r"(a));
    return r;
}
__device__ __forceinline__ void stsm4(uint32_t addr, uint32_t a, uint32_t b, uint32_t c, uint32_t d) {
    asm volatile("stmatrix.sync.aligned.m8n8.x4.shared.b16 [%0], {%1,%2,%3,%4};" ::"r"(addr), "r"(a), "r"(b), "r"(c), "r"(d) : "memory");
}
__device__ __forceinline__ void sts1(uint32_t addr, uint32_t a) { asm volatile("st.shared.b32 [%0], %1;" ::"r"(addr), "r"(a) : "memory"); }
__device__ __forceinline__ uint32_t lds1(uint32_t addr) {
    uint32_t a;
    asm volatile("ld.shared.b32 %0, [%1];" : "=r"(a) : "r"(addr) : "memory");
    return a;
}
__device__ __forceinline__ void lds4(uint32_t addr, uint32_t* v) {
    asm volatile("ld.shared.v4.b32 {%0,%1,%2,%3}, [%4];" : "=r"(v[0]), "=r"(v[1]), "=r"(v[2]), "=r"(v[3]) : "r"(addr) : "memory");
}
__device__ __forceinline__ void stg1(uint8_t* p, uint32_t a) { asm volatile("st.global.b32 [%0], %1;" ::"l"(p), "r"(a) : "memory"); }
__device__ __forceinline__ uint64_t tagged(uint32_t lo, uint32_t hi, uint32_t tag) {
    uint64_t r;
    asm volatile("{\n.reg .b32 t;\nlop3.b32 t, %1, %3, 1, 0xD8;\nmov.b64 %0, {t, %2};\n}\n" : "=l"(r) : "r"(lo), "r"(hi), "r"(tag));
    return r;
}
__device__ __forceinline__ void st_tagged(uint8_t* p, uint64_t x, uint64_t y) {
    asm volatile("st.relaxed.gpu.global.v2.b64 [%0], {%1, %2};" ::"l"(p), "l"(x), "l"(y) : "memory");
}
__device__ __forceinline__ void mma16816(float (&d)[4], const uint32_t (&a)[4], uint32_t b0, uint32_t b1) {
    asm volatile("mma.sync.aligned.m16n8k16.row.col.f32.bf16.bf16.f32 {%0,%1,%2,%3}, {%4,%5,%6,%7}, {%8,%9}, {%0,%1,%2,%3};"
                 : "+f"(d[0]), "+f"(d[1]), "+f"(d[2]), "+f"(d[3]) : "r"(a[0]), "r"(a[1]), "r"(a[2]), "r"(a[3]), "r"(b0), "r"(b1));
}
__device__ __forceinline__ uint32_t add2(uint32_t a, uint32_t b) {
    uint32_t r;
    asm("add.rn.bf16x2 %0, %1, %2;" : "=r"(r) : "r"(a), "r"(b));
    return r;
}
__device__ __forceinline__ uint32_t scale2(uint32_t x) {
    uint32_t r;
    asm("{\n.reg .b32 t;\nmul.rn.bf16x2 t, %1, %3;\nfma.rn.bf16x2 %0, %1, %2, t;\n}\n" : "=r"(r) : "r"(x), "r"(0x3E423E42u), "r"(0xB9F7B9F7u));
    return r;
}
__device__ __forceinline__ uint32_t max2(uint32_t a, uint32_t b) {
    uint32_t r;
    asm("max.bf16x2 %0, %1, %2;" : "=r"(r) : "r"(a), "r"(b));
    return r;
}
__device__ __forceinline__ void ld_tagged(const uint8_t* p, uint32_t& a, uint32_t& ta, uint32_t& b, uint32_t& tb) {
    asm volatile("{\n.reg .b64 x, y;\nld.relaxed.gpu.global.v2.b64 {x, y}, [%4];\nmov.b64 {%0, %1}, x;\nmov.b64 {%2, %3}, y;\n}\n"
                 : "=r"(a), "=r"(ta), "=r"(b), "=r"(tb) : "l"(p) : "memory");
}
__device__ __forceinline__ float bf_lo(uint32_t v) { return __uint_as_float(v << 16); }
__device__ __forceinline__ float bf_hi(uint32_t v) { return __uint_as_float(v & 0xFFFF0000u); }
__device__ __forceinline__ float rcp(float x) { float r; asm("rcp.approx.ftz.f32 %0, %1;" : "=f"(r) : "f"(x)); return r; }
__device__ __forceinline__ float ex2(float x) { float r; asm volatile("ex2.approx.ftz.f32 %0, %1;" : "=f"(r) : "f"(x)); return r; }

__device__ __forceinline__ uint32_t full_bar(int stage) { return base + BAR_FULL + (stage & 7) * 8; }
__device__ __forceinline__ void wait_released(int j) { mbar_wait(base + BAR_EMPTY + (j & 7) * 8, (j >> 3) & 1); }

template <int V>
struct Int { static constexpr int value = V; };

__host__ __device__ constexpr int bslot_e(int i) { return (i < 2 || i >= 14) ? (i + 5) % 7 : (i + 1) % 5; }
__host__ __device__ constexpr int bslot_l(int i) { return (i + 5) % 6; }
__host__ __device__ constexpr int bslot_h(int i) { return (i + 5) % 7; }

template <uint32_t OFF>
struct Feed {
    int stage;
    uint32_t dst;
    __device__ __forceinline__ void seek(int i, int slot) { stage = i; dst = base + OFF + slot * SLOT; }
    template <int N>
    __device__ __forceinline__ uint32_t acquire() { wait_released(stage - N); return full_bar(stage); }
    template <int N>
    __device__ __forceinline__ void next() {
        stage++;
        dst += SLOT;
        if (dst == base + OFF + N * SLOT) dst = base + OFF;
    }
};
__device__ __forceinline__ int skip_own(int n, int mt) { return n == mt ? 15 : n; }

struct Desc { uint32_t lo, hi; };
__host__ __device__ constexpr Desc desc_const(uint32_t lbo, uint32_t sbo, uint32_t mode) { return {(lbo >> 4) << 16, (sbo >> 4) | (mode << 30)}; }
constexpr Desc D_K128 = desc_const(16, 1024, 1);
constexpr Desc D_N128 = desc_const(8192, 1024, 1);
constexpr Desc D_BLOB = desc_const(128, 256, 0);
constexpr Desc D_OT = desc_const(2048, 128, 0);

enum Kind { XW, XWN, QK, BIG, OUT };

struct Ring {
    int stage;
    uint32_t a, b;
    uint32_t wg;
    uint32_t zero;
    bool releaser;
    __device__ __forceinline__ void seek(int i, int bslot) {
        stage = i;
        a = (base + (i % NA) * SLOT) >> 4;
        b = (base + BRING + bslot * SLOT) >> 4;
    }
    __device__ __forceinline__ void wait() { mbar_wait(full_bar(stage), (stage >> 3) & 1); }
    __device__ __forceinline__ void take_turn() { nb_sync(1 + wg, 256); }
    __device__ __forceinline__ void pin() { boundary(zero); }
    __device__ __forceinline__ void mma_begin() {
        if (!wg) take_turn();
        pin();
    }
    __device__ __forceinline__ void mma_end() {
        pin();
        if (wg) nb_arrive(3, 256);
        nb_sync(3 - wg, 256);
    }
    template <Kind K, int NBS, bool INIT, int SB = 1, bool TAIL = false>
    __device__ __forceinline__ void run(float (&d)[56], float (&e)[56], bool first = true, bool last = true, bool more = true) {
        if (first) take_turn();
        asm volatile("wgmma.fence.sync.aligned;" ::: "memory");
        if (K == QK) {
            const uint32_t da = D_K128.lo + (base >> 4) + (stage >> 1) * (SLOT >> 4) + (stage & 1) * 4 + wg * 512, db = D_N128.lo + b;
            wgmma112<0, 1, 1, INIT, D_K128.hi, D_N128.hi>(d, da, db);
            wgmma112<0, 1, 1, INIT, D_K128.hi, D_N128.hi>(e, da, db + 256);
            wgmma112<0, 1, 1, false, D_K128.hi, D_N128.hi>(d, da + 2, db + 128);
            wgmma112<0, 1, 1, false, D_K128.hi, D_N128.hi>(e, da + 2, db + 384);
        } else {
            constexpr int TA = K == OUT, TB = K != XW;
            constexpr uint32_t sa = K == OUT ? 256 : 2, sb = K == XW ? 2 : K == BIG ? 224 : 128;
            constexpr Desc A = K == OUT ? D_OT : D_K128, B = K == XW ? D_K128 : K == BIG ? D_BLOB : D_N128;
            const uint32_t da = A.lo + a + wg * (K == OUT ? 64 : 512), db = B.lo + b;
            wgmma112<TA, TB, SB, INIT, A.hi, B.hi>(d, da, db);
#pragma unroll
            for (int q = 1; q < 4; q++) wgmma112<TA, TB, SB, false, A.hi, B.hi>(d, da + q * sa, db + q * sb);
        }
        asm volatile("wgmma.commit_group.sync.aligned;" ::: "memory");
        if (!TAIL) asm volatile("wgmma.wait_group.sync.aligned 1;" ::: "memory");
        if (last) nb_arrive(2 - wg, 256);
        if (!TAIL && stage > 0 && releaser) mbar_arrive(base + BAR_EMPTY + ((stage - 1) & 7) * 8);
        stage++;
        a += SLOT >> 4;
        if (a == (base + NA * SLOT) >> 4) a = base >> 4;
        b += SLOT >> 4;
        if (b == (base + BRING + NBS * SLOT) >> 4) b = (base + BRING) >> 4;
        if (more) wait();
    }
    template <Kind K, int NBS, bool INIT, int SB = 1, bool TAIL = false>
    __device__ __forceinline__ void run(float (&d)[56], bool first = true, bool last = true, bool more = true) {
        run<K, NBS, INIT, SB, TAIL>(d, d, first, last, more);
    }
};

template <int I0 = 0, int I1 = 28>
__device__ __forceinline__ void pack_all(const float (&d)[56], uint32_t (&p)[28]) {
#pragma unroll
    for (int i = I0; i < I1; i++) p[i] = pack2(d[2 * i], d[2 * i + 1]);
}
template <int I0, int I1>
__device__ __forceinline__ void store_frags(uint8_t* dst, const uint32_t (&p)[28]) {
#pragma unroll
    for (int i = I0; i < I1; i++) stg1(dst + i * 128, p[i]);
}
template <int I0, int I1>
__device__ __forceinline__ void stage_frags(uint32_t lane_addr, const uint32_t (&p)[28]) {
#pragma unroll
    for (int i = I0; i < I1; i += 4) stsm4(lane_addr + i * 128, p[i], p[i + 1], p[i + 2], p[i + 3]);
}
template <class F>
__device__ __forceinline__ void store_out(F frag, int lane, uint32_t slab, const CUtensorMap* m, int c0, int c1) {
    const bool swap = lane & 16;
    const uint32_t addr = slab + (lane & 7) * 224 + ((lane >> 3) ^ ((lane >> 2) & 1)) * 16;
#pragma unroll
    for (int h = 0; h < 2; h++) {
#pragma unroll
        for (int c = 0; c < 14; c += 4) {
            const uint32_t t0 = frag(2 * c + h), t1 = frag(2 * c + 2 + h);
            if (c < 12) {
                const uint32_t t2 = frag(2 * c + 4 + h), t3 = frag(2 * c + 6 + h);
                stsm4(addr + h * 1792 + c * 16, swap ? t1 : t0, swap ? t0 : t1, swap ? t3 : t2, swap ? t2 : t3);
            } else {
                asm volatile("stmatrix.sync.aligned.m8n8.x2.shared.b16 [%0], {%1,%2};" ::"r"(addr + h * 1792 + c * 16), "r"(swap ? t1 : t0), "r"(swap ? t0 : t1) : "memory");
            }
        }
        fence_async_smem();
        __syncwarp();
        if (elect()) tma_st2(m, c0, c1 + 8 * h, slab + h * 1792);
    }
    if (elect()) {
        bulk_commit();
        bulk_wait_read();
    }
}
__host__ __device__ constexpr int tile_of(int t) { return 7 * (t >> 2) + 3 * ((t >> 1) & 1) + 2 * (t & 1); }

struct Role {
    int kind;
    int par, blk;
    int ns, id;
};
template <bool BY_SM>
__device__ __forceinline__ uint32_t read_sm() {
    uint32_t sm;
    if (BY_SM) asm volatile("mov.u32 %0, %%smid;" : "=r"(sm));
    else asm volatile("mov.u32 %0, %%ctaid.x;" : "=r"(sm));
    return sm;
}
__device__ __forceinline__ Role decode_role(uint32_t sm) {
    const int tpc = sm >> 1, q2 = ((tpc - 32) * 37) >> 8;
    const int gpc = tpc < 32 ? tpc & 7 : tpc < 60 ? tpc - 31 - 7 * q2 : 0;
    const int pos = tpc < 32 ? tpc >> 3 : tpc < 60 ? q2 + 4 : tpc - 56;
    const int grp = GPC_MAP >> (4 * gpc);
    Role r;
    r.kind = (grp & 1) | ((sm >> 7) << 1);
    r.par = (pos >> 1) & 1;
    r.blk = (grp & 6) + (pos >> 2);
    r.ns = (pos & 1) * 2 + (sm & 1);
    r.id = sm >= 128 ? sm : (grp & 7) * 16 + pos * 2 + (sm & 1);
    return r;
}
static_assert((GPC_MAP & 15) == 0, "role H decodes as blk = 2, par = 0");

__device__ __forceinline__ void first_fill(const Maps& maps, const Role& r, int i) {
    const int L = r.kind & 1;
    const CUtensorMap* ma = &maps.m[r.kind];
    const uint32_t bar = full_bar(i);
    const int k = (i * 64) >> L;
    const bool has_a = !(i & L), has_b = i < 7 - L;
    const uint32_t slots = r.kind == 0 ? 0x2104365u : L ? 0x5432105u : 0x4321065u;
    const uint32_t dst = base + BRING + (i == 0 ? 5 : (slots >> (4 * i)) & 7) * SLOT;
    mbar_expect(bar, (has_a ? (i ? SLOT : SLOT / 2) : 0) + (has_b ? SLOT : 0));
    if (has_a) tma_ld5(base + (i >> L) * SLOT, ma, k, 0, r.par, r.blk, bar);
    if (i == 0) boundary(r.kind >> 2);
    if (has_b) {
        tma_ld4(dst, ma + 3, r.kind ? 0 : k, r.kind ? k : 0, 0, r.ns, bar);
        tma_ld4(dst + 8192, ma + 3, r.kind ? 64 : k, r.kind ? k : 64, 0, r.ns, bar);
        mbar_arrive(bar);
    }
    if (i == 0) {
        mbar_init(base + BAR_X, 1);
        mbar_expect(base + BAR_X, SLOT / 2);
    }
    if (has_a) tma_ld5(base + (i >> L) * SLOT + 8192, ma, k, 1, r.par, r.blk, i ? bar : base + BAR_X);
}
static_assert(bslot_e(0) == 5 && bslot_e(1) == 6 && bslot_e(2) == 3 && bslot_e(3) == 4 && bslot_e(4) == 0 && bslot_e(6) == 2, "");

template <bool BY_SM>
__global__ void __launch_bounds__(384, 1) fused_kernel(Scratch* sc, const __grid_constant__ Maps maps) {
    const uint32_t sm0 = read_sm<BY_SM>();
    const unsigned t_open = clk32();
    const int warp = __shfl_sync(0xffffffffu, threadIdx.x >> 5, 0);
    if (warp == 8) {
        const Role r = decode_role(sm0);
        if (elect()) {
            mbar_init(base + BAR_FULL, 2);
            first_fill(maps, r, 0);
            asm volatile("fence.mbarrier_init.release.cluster;" ::: "memory");
        }
        nb_sync(0, 384);
        if (elect()) {
#pragma unroll 1
            for (int i = 1; i < LEAD; i++) {
                while (clk32() - t_open < PACE0 + i * PACE) {}
                first_fill(maps, r, i);
            }
        }
    }
    if (warp - 8 != blockIdx.y) {
        if (warp == 9) {
            if (elect()) {
#pragma unroll
                for (int i = 0; i < 8; i++) mbar_init(base + BAR_EMPTY + i * 8, 4);
                asm volatile("fence.mbarrier_init.release.cluster;" ::: "memory");
            }
        } else if (warp == 10) {
            if (elect()) {
#pragma unroll
                for (int i = 0; i < 3; i++) mbar_init(base + BAR_RDY + i * 8, i < 2 ? 4 : 8);
#pragma unroll
                for (int i = 0; i < 2; i++) mbar_init(base + BAR_HALO + i * 8, 1);
                asm volatile("fence.mbarrier_init.release.cluster;" ::: "memory");
            }
        } else if (warp == 11) {
            if (elect()) {
#pragma unroll
                for (int i = 1; i < 8; i++) mbar_init(base + BAR_FULL + i * 8, 2);
#pragma unroll
                for (int i = 0; i < 3; i++) mbar_init(base + BAR_DEP + i * 8, 1);
#pragma unroll
                for (int i = 0; i < 4; i++) mbar_init(base + BAR_PART + i * 8, 1);
                asm volatile("fence.mbarrier_init.release.cluster;" ::: "memory");
            }
        }
        nb_sync(0, 384);
    }

    const Role role = decode_role(read_sm<BY_SM>());
    int lane = threadIdx.x & 31;
    asm volatile("" : "+r"(lane));
    const bool roleH = role.kind == 2;
    const int roleL = role.kind & 1, par = role.par, blk = role.blk, ns = role.ns, bid = role.id;
    const int mt = 2 * blk + par, col = ns * 112;

    if (warp >= 8) {
        asm volatile("setmaxnreg.dec.sync.aligned.u32 56;");
#define PROF_FEED_A
#define PROF_FEED_B
        if (warp == 8) {
            if (elect()) {
                Feed<0> f;
                const int row = mt * 128;
                auto c_run = [&](const CUtensorMap* m, int off, int n0, int n1) {
#pragma unroll 1
                    for (int n = n0; n < n1; n++) {
                        const uint32_t bar = f.acquire<NA>();
                        mbar_expect(bar, SLOT);
                        tma_ld2(f.dst, m, (off + skip_own(n, mt)) * 64, row, bar);
                        PROF_FEED_A;
                        f.next<NA>();
                    }
                };
                if (roleH) {
                    mbar_expect(base + BAR_DEP, 7 * SLOT);
#pragma unroll 1
                    for (int i = 0; i < 7; i++) {
                        const uint32_t dst = base + (i < 6 ? i : NA + bslot_h(7)) * SLOT;
                        if (i < 6) wait_released(7 + i);
                        tma_ld4(dst, &maps.m[M_WO], 0, i * 64, 0, ns, base + BAR_DEP);
                        tma_ld4(dst + 8192, &maps.m[M_WO], 64, i * 64, 0, ns, base + BAR_DEP);
                    }
                    mbar_wait(base + BAR_DEP, 0);
                    mbar_wait(base + BAR_RDY + 16, 0);
#pragma unroll 1
                    for (int i = 0; i < 7; i++) bulk_st(sc->wo + (size_t)(ns * 7 + i) * SLOT, base + (i < 6 ? i : NA + bslot_h(7)) * SLOT, SLOT);
                    bulk_commit();
                    asm volatile("cp.async.bulk.wait_group 0;" ::: "memory");
                    signal(sc, CNT_W + ns);
                } else if (!roleL) {
                    f.seek(14, 0);
#pragma unroll 1
                    for (int i = 0; i < 4; i++) {
                        const uint32_t bar = f.acquire<NA>();
                        mbar_expect(bar, SLOT);
                        tma_ld2(f.dst, &maps.m[M_CR + (i >> 1)], ((i & 1) * 16 + mt) * 64, row, bar);
                        mbar_arrive(bar);
                        PROF_FEED_A;
                        f.next<NA>();
                    }
                    c_run(&maps.m[M_CR], 0, 0, 15);
                    c_run(&maps.m[M_CI], 0, 0, NBE);
                    wait_dep(2);
#pragma unroll 1
                    for (int i = 0; i < 7; i++) {
                        const uint32_t bar = f.acquire<NA>();
                        mbar_expect(bar, SLOT);
                        bulk_ld(f.dst, sc->o + (size_t)(mt * 7 + i) * SLOT, SLOT, bar);
                        PROF_FEED_A;
                        f.next<NA>();
                    }
                } else {
#pragma unroll 1
                    for (int i = 4; i < 7; i++) {
                        wait_released(2 * i - 8);
                        mbar_expect(full_bar(2 * i), SLOT);
                        tma_ld5(base + i * SLOT, &maps.m[M_XA], i * 64, 0, par, blk, full_bar(2 * i));
                        tma_ld5(base + i * SLOT + 8192, &maps.m[M_XA], i * 64, 1, par, blk, full_bar(2 * i));
                    }
                    wait_released(HALO_K_AT);
                    mbar_arrive(base + BAR_DEP + 16);
                    f.seek(21, 0);
                    c_run(&maps.m[M_CR], 16, 0, 15);
                    c_run(&maps.m[M_CI], 16, 0, 15);
                    c_run(&maps.m[M_CI], 0, NBE, 15);
                }
            }
        } else if (warp == 11) {
            if (elect()) {
#pragma unroll 1
                for (int i = LEAD; i < 7; i++) {
                    while (clk32() - t_open < PACE0 + i * PACE - (roleL & ~i) * PACE_X) {}
                    first_fill(maps, role, i);
                }
                Feed<BRING> f;
                auto blob_run = [&](auto nbs, int quarter, int n0, int n1) {
                    constexpr int N = decltype(nbs)::value;
                    const uint8_t* src = sc->ab + (size_t)(quarter * 64 + ns) * BLOB;
#pragma unroll 1
                    for (int n = n0; n < n1; n++) {
                        const uint32_t bar = f.template acquire<N>();
                        mbar_expect(bar, BLOB);
                        bulk_ld(f.dst, src + skip_own(n, mt) * (4 * BLOB), BLOB, bar);
                        PROF_FEED_B;
                        f.template next<N>();
                    }
                };
                auto v_run = [&](auto nbs) {
                    constexpr int N = decltype(nbs)::value;
#pragma unroll 1
                    for (int i = 0; i < 7; i++) {
                        const uint32_t bar = f.template acquire<N>();
                        mbar_expect(bar, SLOT);
                        tma_ld4(f.dst, &maps.m[M_WV], 0, i * 64, 0, 4 + ns, bar);
                        tma_ld4(f.dst + 8192, &maps.m[M_WV], 64, i * 64, 0, 4 + ns, bar);
                        mbar_arrive(bar);
                        PROF_FEED_B;
                        f.template next<N>();
                    }
                };
                if (roleH) {
                    f.seek(7, bslot_h(7));
                    v_run(Int<7>());
                } else if (!roleL) {
                    f.seek(7, bslot_e(7));
#pragma unroll 1
                    for (int i = 0; i < 7; i++) {
                        const uint32_t bar = f.acquire<5>();
                        mbar_expect(bar, BLOB);
                        tma_ld2(f.dst, &maps.m[M_WI], i * 64, col, bar);
                        mbar_arrive(bar);
                        PROF_FEED_B;
                        f.next<5>();
                    }
                    f.seek(18, bslot_e(18));
                    wait_dep(0);
                    blob_run(Int<7>(), 0, 0, 15);
                    wait_dep(1);
                    blob_run(Int<7>(), 2, 0, NBE);
                    mbar_wait(base + BAR_HINT, 0);
                    fence_async_global();
#pragma unroll 1
                    for (int i = 0; i < 7; i++) {
                        const uint32_t bar = f.acquire<7>();
                        mbar_expect(bar, SLOT);
                        bulk_ld(f.dst, sc->wo + (size_t)(ns * 7 + i) * SLOT, SLOT, bar);
                        PROF_FEED_B;
                        f.next<7>();
                    }

                } else {
                    f.seek(6, bslot_l(6));
#pragma unroll 1
                    for (int i = 6; i < 14; i++) {
                        const uint32_t bar = f.acquire<6>();
                        mbar_expect(bar, SLOT);
                        tma_ld4(f.dst, &maps.m[M_WQK], 0, i * 32, 0, ns, bar);
                        tma_ld4(f.dst + 8192, &maps.m[M_WQK], 64, i * 32, 0, ns, bar);
                        if (i & 1) mbar_arrive(bar);
                        PROF_FEED_B;
                        f.next<6>();
                    }
                    v_run(Int<6>());
                    wait_dep(0);
                    blob_run(Int<6>(), 1, 0, 15);
                    wait_dep(1);
                    blob_run(Int<6>(), 3, 0, 15);
                    blob_run(Int<6>(), 2, NBE, 15);
                    fence_async_smem();
#pragma unroll 1
                    for (int h = 0; h < 2; h++) {
                        mbar_wait(base + BAR_HINT + h * 8, 0);
                        PROF(153 + h);
                        mbar_expect(base + BAR_PART + h * 8, BLOB);
                        bulk_ld(base + (h ? HALO : LSLAB), sc->part + (size_t)((ns * 16 + mt) * 2 + h) * BLOB, BLOB, base + BAR_PART + h * 8);
                    }
                }
            }
        } else if (roleH) {
        } else if (warp == 10) {
            if (elect()) {
                unsigned* epoch_ptr = &sc->epoch[(bid * 4 + 2) * 8];
                const unsigned ep = *epoch_ptr + 1;
                sts1(base + TAG, ep);
                asm volatile("prefetch.tensormap [%0];" ::"l"(&maps.m[M_OUTA + roleL]) : "memory");
                await(sc, CNT_A + roleL * 4 + ns, ep * 16);
                mbar_arrive(base + BAR_DEP);
                PROF(150);
                await(sc, CNT_B + ns, ep * 16);
                mbar_arrive(base + BAR_DEP + 8);
                PROF(151);
                if (!roleL) {
                    await(sc, CNT_W + ns, ep);
                    mbar_arrive(base + BAR_HINT);
                    PROF(153);
                    await(sc, CNT_O + mt, ep * 4);
                    mbar_arrive(base + BAR_DEP + 16);
                } else {
                    await(sc, CNT_P + mt * 4 + ns, ep * 2 - 1);
                    mbar_arrive(base + BAR_HINT);
                    await(sc, CNT_P + mt * 4 + ns, ep * 2);
                    mbar_arrive(base + BAR_HINT + 8);
                }
                PROF(152);
                *epoch_ptr = ep;
            }
        } else if (!roleL) {
            if (elect()) {
                mbar_wait(base + BAR_RDY, 0);
                PROF(130);
                signal(sc, CNT_A + ns);
                PROF(131);
                mbar_wait(base + BAR_RDY + 8, 0);
                signal(sc, CNT_A + 4 + ns);
                PROF(135);
                mbar_wait(base + BAR_RDY + 16, 0);
                PROF(132);
                signal(sc, CNT_B + ns);
                PROF(133);
            }
        } else {
            unsigned* epoch_ptr = &sc->epoch[(bid * 4 + 1) * 8];
            const unsigned tag = *epoch_ptr + 1;
#pragma unroll 1
            for (int kv = 0; kv < 2; kv++) {
                uint32_t v[16];
#pragma unroll
                for (int i = 0; i < 16; i++) v[i] = 0;
                if (kv) wait_released(HALO_V_AT - 4), wait_released(HALO_V_AT);
                else mbar_wait(base + BAR_DEP + 16, 0);
                if (blk > 0) {
                    const uint8_t* src = sc->halo + (size_t)(((par * 8 + blk - 1) * 4 + ns) * 2 + kv) * 2048 + lane * 16;
#pragma unroll 1
                    for (int n = 0; n < SPIN_LIMIT; n++) {
#pragma unroll
                        for (int i = 0; i < 4; i++) ld_tagged(src + i * 512, v[4 * i], v[4 * i + 1], v[4 * i + 2], v[4 * i + 3]);
#pragma unroll
                        for (int i = 0; i < 16; i += 2) v[i] ^= tag & 1;
                        const uint32_t stale = or3(or3(v[0], v[2], v[4]), or3(v[6], v[8], v[10]), or3(v[12], v[14], 0));
                        if (__all_sync(0xffffffffu, !(stale & 1))) break;
                    }
#pragma unroll
                    for (int c = 0; c < 14; c += 2) v[c] |= (v[15] >> c) & 1;
                }
#pragma unroll
                for (int i = 0; i < 14; i++) sts1(base + HALO + kv * (8 * HSLOT) + i * 128 + lane * 4, v[i]);
                warp_arrive(base + BAR_HALO + kv * 8);
                if (lane == 0) PROF(142 + kv);
            }
            if (elect()) {
                mbar_wait(base + BAR_RDY + 16, 0);
                PROF(130);
                signal(sc, CNT_O + mt);
                PROF(131);
                *epoch_ptr = tag;
            }
        }
    } else {
        asm volatile("setmaxnreg.inc.sync.aligned.u32 224;");
        Ring r;
        r.wg = warp >> 2;
        r.zero = blockIdx.y;
        r.releaser = lane + 1 == (warp >> 2);
        const int wg = warp >> 2;
        if (wg) {
            nb_arrive(1, 256);
            mbar_wait(base + BAR_X, 0);
        }
        uint8_t* part = sc->part + (size_t)(ns * 16 + mt) * (2 * BLOB) + warp * WSLOT + lane * 16;
        uint32_t p[28];

        if (roleH) {
            unsigned* epoch_ptr = &sc->epoch[bid * 4 * 8];
            const unsigned tag = *epoch_ptr + 1;
            uint8_t* hout = sc->halo + (size_t)((warp * 8 + ns) * 2) * 2048 + lane * 16;
            auto send = [&](int kv) {
#pragma unroll
                for (int h = 0; h < 2; h++) {
                    uint32_t v[16];
                    v[14] = v[15] = 0;
#pragma unroll
                    for (int c = 0; c < 14; c++) v[c] = p[2 * c + h];
#pragma unroll
                    for (int c = 0; c < 14; c += 2) v[15] |= (v[c] & 1) << c;
#pragma unroll
                    for (int i = 0; i < 4; i++)
                        st_tagged(hout + (h * 8 + kv) * 2048 + i * 512, tagged(v[4 * i], v[4 * i + 1], tag), tagged(v[4 * i + 2], v[4 * i + 3], tag));
                }
            };
            float x0[56], x1[56];
            r.seek(0, bslot_h(0));
            r.wait();
            r.run<XWN, 7, true>(x0);
#pragma unroll 1
            for (int i = 1; i < 7; i++) r.run<XWN, 7, false>(x0);
            r.run<XWN, 7, true>(x1);
            acc_fence(x0);
            pack_all(x0, p);
            send(0);
#pragma unroll 1
            for (int i = 1; i < 7; i++) r.run<XWN, 7, false>(x1, true, i < 6 || !wg, i < 6);
            asm volatile("wgmma.wait_group.sync.aligned 0;" ::: "memory");
            acc_fence(x1);
            pack_all(x1, p);
#pragma unroll
            for (int i = 0; i < 28; i++) p[i] = movm(p[i]);
            send(1);
            warp_arrive(base + BAR_RDY + 16);
            if (threadIdx.x == 0) *epoch_ptr = tag;
        } else if (!roleL) {
            uint8_t* blob = sc->ab + (size_t)((wg * 16 + mt) * 4 + ns) * BLOB + (warp & 3) * WSLOT + lane * 4;
            const uint32_t own = base + BRING + wg * SLOT + (warp & 3) * WSLOT + lane * 16;
            float x0[56], x1[56];
            r.seek(0, bslot_e(0));
            r.wait();
            r.run<XW, 7, true>(x0);
            r.run<XW, 7, false>(x0);
            r.seek(2, bslot_e(2));
#pragma unroll 1
            for (int i = 2; i < 7; i++) r.run<XW, 5, false>(x0);

            r.seek(7, bslot_e(7));
            r.run<XW, 5, true, -1>(x1);
            acc_fence(x0);
            pack_all<0, 14>(x0, p);
#pragma unroll
            for (int i = 0; i < 2; i++) {
                if (wg == i) store_frags<0, 14>(blob, p);
                else stage_frags<0, 4>(own + 5 * SLOT, p);
                r.run<XW, 5, false, -1>(x1);
                if (i == 0) pack_all<14, 28>(x0, p);
                if (wg == i) {
                    store_frags<14, 28>(blob, p);
                    warp_arrive(base + BAR_RDY + i * 8);
                } else {
                    stage_frags<4, 8>(own + 5 * SLOT, p);
                }
                r.run<XW, 5, false, -1>(x1);
            }
            stage_frags<8, 16>(own + 5 * SLOT, p);
            r.run<XW, 5, false, -1>(x1);
            stage_frags<16, 24>(own + 5 * SLOT, p);
            r.run<XW, 5, false, -1>(x1);
            stage_frags<24, 28>(own + 5 * SLOT, p);

            r.seek(14, bslot_e(14));
            r.take_turn();
            fence_async_smem();
            r.run<BIG, 7, true>(x0, false);
            acc_fence(x1);
            pack_all(x1, p);
            stage_frags<0, 16>(own, p);
            r.run<BIG, 7, false>(x0);
            stage_frags<16, 28>(own, p);
            r.take_turn();
            fence_async_smem();
            blob += (size_t)128 * BLOB;
            r.run<BIG, 7, false>(x0, false);
#pragma unroll
            for (int i = 0; i < 28; i++) {
                if (i % B_SLICE == 0) r.run<BIG, 7, false>(x0);
                stg1(blob + i * 128, p[i]);
            }
            warp_arrive(base + BAR_RDY + 16);
#pragma unroll 1
            for (int i = 18 + 27 / B_SLICE; i < POUT; i++) r.run<BIG, 7, false>(x0);

            const uint32_t tag = lds1(base + TAG);
            r.seek(POUT, bslot_e(POUT));
            r.run<OUT, 7, true>(x1);
            acc_fence(x0);
            pack_all(x0, p);
            uint64_t u[14];
#pragma unroll
            for (int i = 0; i < 14; i++) u[i] = tagged(p[2 * i], p[2 * i + 1], tag);
#pragma unroll
            for (int k = 0; k < 2; k++) {
                if (wg == k) {
#pragma unroll
                    for (int i = 0; i < 7; i++) st_tagged(part + i * 512, u[2 * i], u[2 * i + 1]);
                }
                r.run<OUT, 7, false>(x1);
                if (warp * 32 + lane == k * 128)
                    asm volatile("red.relaxed.gpu.global.add.u32 [%0], 1;" ::"l"(&sc->cnt[(CNT_P + mt * 4 + ns) * 32]) : "memory");
            }
#pragma unroll
            for (int i = 3; i < 7; i++) r.run<OUT, 7, false, 1, true>(x1, i <= 7 - TURN, i < 7 - TURN || (i == 6 && !wg), i < 6);

            asm volatile("wgmma.wait_group.sync.aligned 0;" ::: "memory");
            acc_fence(x1);
            const uint32_t slab = base + (wg ? BRING + bslot_e(ELAST - 6) * SLOT : ((ELAST - 6) % NA) * SLOT) + (warp & 3) * WSLOT;
            store_out([&](int i) { return pack2(x1[2 * i], x1[2 * i + 1]); }, lane, slab, &maps.m[M_OUTA], par * 896 + col, blk * 128 + warp * 16);
        } else {
            const int g = lane >> 2, tig = lane & 3;
            const uint32_t hin = base + HALO + warp * HSLOT + lane * 4;
            const uint32_t hpub = warp < 7 ? hin + HSLOT : base + HSPARE + lane * 4;
            auto publish = [&](const uint32_t (&h)[14], int c0, int c1) {
#pragma unroll
                for (int c = 0; c < 14; c++)
                    if (c >= c0 && c < c1) sts1(hpub + c * 128, h[c]);
            };
            float y0[56], y1[56], y2[56];
            r.seek(0, bslot_l(0));
            r.wait();
            r.run<QK, 6, true>(y0, y1);
#pragma unroll 1
            for (int i = 1; i < 14; i++) r.run<QK, 6, false>(y0, y1);

            uint32_t m1[8][4], m0[8][4], lo[14], hi[14], q[2][8][2];
            auto pack_q = [&](int b) {
                uint32_t v[14];
#pragma unroll
                for (int c = 0; c < 14; c++) v[c] = pack2(y0[4 * c + 2 * b], y0[4 * c + 2 * b + 1]);
#pragma unroll
                for (int t = 0; t < 8; t++) {
                    const int c = tile_of(t);
                    q[b][t][0] = (t & 3) == 2 ? (tig >= 2 ? v[c] : 0u) : v[c];
                    q[b][t][1] = (t & 3) == 1 ? (tig < 2 ? v[c + 1] : 0u) : v[c + 1];
                }
            };
            auto fetch = [&](uint32_t src, int hp, int i0) {
#pragma unroll
                for (int t = 4 * hp; t < 4 * hp + 4; t++) {
                    m0[t][i0] = (t & 3) == 2 ? dup(m0[t - 1][3], r.zero) : lds1(src + tile_of(t) * 128);
                    m0[t][3] = lds1(src + tile_of(t) * 128 + 128);
                }
            };
            r.seek(14, bslot_l(14));
            r.run<XWN, 6, true>(y2);
            acc_fence(y0);
            acc_fence(y1);
#pragma unroll
            for (int c = 0; c < 14; c++) hi[c] = pack2(y1[4 * c + 2], y1[4 * c + 3]);
            publish(hi, 0, 7);
            r.run<XWN, 6, false>(y2);
            publish(hi, 7, 14);
#pragma unroll
            for (int c = 0; c < 14; c++) lo[c] = pack2(y1[4 * c], y1[4 * c + 1]);
#pragma unroll
            for (int t = 0; t < 8; t++) {
                const int c = tile_of(t);
                const bool shared = (t & 3) == 2;
                m1[t][0] = shared ? dup(lo[c], r.zero) : lo[c];
                m1[t][1] = shared ? dup(hi[c], r.zero) : hi[c];
                m1[t][2] = lo[c + 1];
                m1[t][3] = hi[c + 1];
                m0[t][0] = dup(m1[t][0], r.zero);
                m0[t][2] = dup(lo[c + 1], 2 * r.zero);
            }
            r.run<XWN, 6, false>(y2);
            if (warp == 0) mbar_wait(base + BAR_HALO, 0);
            fetch(hin, 0, 1);
            pack_q(1);
            r.run<XWN, 6, false>(y2);
            fetch(hin, 1, 1);
            pack_q(0);
            r.mma_begin();
            float s[8][4];
#pragma unroll
            for (int step = 0; step < 2; step++) {
#pragma unroll
                for (int i = 0; i < 8; i++) {
                    const int b = 1 - (i >> 2), h = i & 3, t = 2 * h + step;
                    float (&d)[4] = s[2 * h + b];
                    if (step == 0) d[0] = d[1] = d[2] = d[3] = 0.f;
                    mma16816(d, b ? m1[t] : m0[t], q[b][t][0], q[b][t][1]);
                }
            }
            r.mma_end();
            r.run<XWN, 6, false>(y2, false);

            uint32_t pr[8], mx[4], mx1[4];
            {
                const bool cur0 = g <= 2 * tig, cur1 = g <= 2 * tig + 1;
#pragma unroll
                for (int i = 0; i < 8; i++) {
                    const int c = (i & 1) ? 2 : 0;
                    pr[i] = movm(pack2(cur0 ? s[i][c] : s[i][2 - c], cur1 ? s[i][c + 1] : s[i][3 - c]));
                }
            }
            r.run<XWN, 6, false>(y2);
            const uint32_t curmask = (2 * tig <= g ? 0x0000FFFFu : 0u) | (2 * tig + 1 <= g ? 0xFFFF0000u : 0u);
            {
                const uint32_t keep = (blk == 0 && warp == 0) ? curmask : 0xFFFFFFFFu;
#pragma unroll
                for (int i = 0; i < 4; i++) {
                    pr[2 * i] = (scale2(pr[2 * i]) & keep) | (0xCE6ECE6Eu & ~keep);
                    pr[2 * i + 1] = scale2(pr[2 * i + 1]);
                    mx[i] = max2(__byte_perm(pr[2 * i], pr[2 * i + 1], 0x5410), __byte_perm(pr[2 * i], pr[2 * i + 1], 0x7632));
                    mx1[i] = __shfl_xor_sync(0xffffffffu, mx[i], 1);
                }
            }
#pragma unroll
            for (int i = 0; i < 4; i++) {
                mx[i] = max2(mx[i], mx1[i]);
                mx1[i] = __shfl_xor_sync(0xffffffffu, mx[i], 2);
            }
            r.run<XWN, 6, false>(y2);
            constexpr float SCL = 47274.f / 32768.f;
            float e0[8], e1[8], sm[8], sm1[8];
#pragma unroll
            for (int i = 0; i < 8; i++) {
                const uint32_t m2 = max2(mx[i >> 1], mx1[i >> 1]);
                sm[i] = ((i & 1) ? bf_hi(m2) : bf_lo(m2)) * -SCL;
                e0[i] = ex2(fmaf(bf_lo(pr[i]), SCL, sm[i]));
            }

            r.seek(21, bslot_l(21));
            r.run<BIG, 6, true>(y0);
            acc_fence(y2);
#pragma unroll
            for (int c = 0; c < 7; c++) hi[c] = movm(pack2(y2[4 * c + 2], y2[4 * c + 3]));
#pragma unroll
            for (int i = 0; i < 8; i++) e1[i] = ex2(fmaf(bf_hi(pr[i]), SCL, sm[i]));
            r.run<BIG, 6, false>(y0);
            publish(hi, 0, 7);
#pragma unroll
            for (int c = 7; c < 14; c++) hi[c] = movm(pack2(y2[4 * c + 2], y2[4 * c + 3]));
            r.run<BIG, 6, false>(y0);
            publish(hi, 7, 14);
#pragma unroll
            for (int i = 0; i < 8; i++) {
                sm[i] = e0[i] + e1[i];
                sm1[i] = __shfl_xor_sync(0xffffffffu, sm[i], 1);
            }
            r.run<BIG, 6, false>(y0);
#pragma unroll
            for (int c = 0; c < 14; c++) lo[c] = movm(pack2(y2[4 * c], y2[4 * c + 1]));
            r.run<BIG, 6, false>(y0);
#pragma unroll
            for (int i = 0; i < 8; i++) {
                sm[i] += sm1[i];
                sm1[i] = __shfl_xor_sync(0xffffffffu, sm[i], 2);
            }
#pragma unroll
            for (int t = 0; t < 8; t++) {
                const int c = tile_of(t);
                const bool shared = (t & 3) == 2;
                m1[t][0] = shared ? dup(lo[c], r.zero) : lo[c];
                m1[t][1] = lo[c + 1];
                m1[t][2] = shared ? dup(hi[c], r.zero) : hi[c];
                m1[t][3] = hi[c + 1];
                m0[t][0] = dup(m1[t][0], r.zero);
                m0[t][1] = dup(lo[c + 1], 2 * r.zero);
            }
            r.run<BIG, 6, false>(y0);
            if (warp == 0) mbar_wait(base + BAR_HALO + 8, 0);
            const uint32_t vin = warp ? hin : hin + 8 * HSLOT;
            fetch(vin, 0, 2);
#pragma unroll
            for (int i = 0; i < 8; i++) {
                const float inv = rcp(sm[i] + sm1[i]);
                pr[i] = pack2(e0[i] * inv, e1[i] * inv);
            }
            r.run<BIG, 6, false>(y0);
            fetch(vin, 1, 2);
            uint32_t pb[8][2];
#pragma unroll
            for (int t = 0; t < 8; t++) {
                pb[t][t & 1] = band(pr[t], curmask);
                pb[t][1 - (t & 1)] = band(pr[t], ~curmask);
            }
            r.mma_begin();
            float o[2][8][4];
#pragma unroll
            for (int i = 0; i < 16; i++) {
                const int b = 1 - (i >> 3), t = i & 7;
                float (&d)[4] = o[b][t];
                d[0] = d[1] = d[2] = d[3] = 0.f;
                mma16816(d, b ? m1[t] : m0[t], pb[(t & 6) + b][0], pb[(t & 6) + b][1]);
            }
            r.mma_end();
            r.run<BIG, 6, false>(y0, false);
            uint8_t* odst = sc->o + (size_t)mt * 7 * SLOT + ns * (14 * 2048) + warp * 256 + lane * 4;
#pragma unroll
            for (int hp = 0; hp < 2; hp++) {
#pragma unroll
                for (int b = 0; b < 2; b++) {
                    const float (&u)[8][4] = o[b];
                    const int t = 4 * hp;
                    uint32_t* w = p + 14 * hp + b;
                    w[0] = pack2(u[t][0], u[t][1]);
                    w[2] = pack2(u[t][2], u[t][3]);
                    w[4] = pack2(u[t + 1][0], u[t + 1][1]);
                    w[6] = pack2(g < 4 ? u[t + 1][2] : u[t + 2][0], g < 4 ? u[t + 1][3] : u[t + 2][1]);
                    w[8] = pack2(u[t + 2][2], u[t + 2][3]);
                    w[10] = pack2(u[t + 3][0], u[t + 3][1]);
                    w[12] = pack2(u[t + 3][2], u[t + 3][3]);
                }
            }
#pragma unroll
            for (int i = 0; i < 28; i++) {
                if (i >= O_FIRST && (i - O_FIRST) % O_SLICE == 0) r.run<BIG, 6, false>(y0);
                stg1(odst + (i >> 1) * 2048 + (i & 1) * 128, p[i]);
            }
            warp_arrive(base + BAR_RDY + 16);

#pragma unroll 1
            for (int i = 30 + (27 - O_FIRST) / O_SLICE; i <= LLAST - LTURN; i++) r.run<BIG, 6, false>(y0);
            r.seek(LLAST + 1 - LTURN, bslot_l(LLAST + 1 - LTURN));
#pragma unroll
            for (int i = 0; i < LTURN; i++) r.run<BIG, 6, false, 1, true>(y0, i == 0, i == LTURN - 1 && !wg, i < LTURN - 1);
            const uint32_t parity = lds1(base + TAG) & 1;
            const uint32_t slab = base + (wg ? HALO : LSLAB) + (warp & 3) * WSLOT;
            mbar_wait(base + BAR_PART + wg * 8, 0);
#pragma unroll 1
            for (int n = 0; n < SPIN_LIMIT; n++) {
#pragma unroll
                for (int i = 0; i < 7; i++) lds4(slab + i * 512 + lane * 16, p + 4 * i);
#pragma unroll
                for (int i = 0; i < 28; i += 2) p[i] ^= parity;
                const uint32_t stale = or3(or3(or3(p[0], p[2], p[4]), or3(p[6], p[8], p[10]), or3(p[12], p[14], p[16])),
                                           or3(p[18], p[20], p[22]), or3(p[24], p[26], 0));
                if (__all_sync(0xffffffffu, !(stale & 1))) break;
#pragma unroll
                for (int i = 0; i < 7; i++) ld_tagged(part + i * 512, p[4 * i], p[4 * i + 1], p[4 * i + 2], p[4 * i + 3]);
#pragma unroll
                for (int i = 0; i < 7; i++)
                    asm volatile("st.shared.v4.b32 [%0], {%1,%2,%3,%4};" ::"r"(slab + i * 512 + lane * 16), "r"(p[4 * i]), "r"(p[4 * i + 1]), "r"(p[4 * i + 2]), "r"(p[4 * i + 3]) : "memory");
            }
            asm volatile("wgmma.wait_group.sync.aligned 0;" ::: "memory");
            acc_fence(y0);
            store_out([&](int i) { return add2(pack2(y0[2 * i], y0[2 * i + 1]), p[i]); }, lane, slab, &maps.m[M_OUTB], 448 + col, mt * 128 + warp * 16);
        }
    }
}

typedef CUresult (*EncodeFn)(CUtensorMap*, CUtensorMapDataType, cuuint32_t, void*, const cuuint64_t*, const cuuint64_t*,
                             const cuuint32_t*, const cuuint32_t*, CUtensorMapInterleave, CUtensorMapSwizzle,
                             CUtensorMapL2promotion, CUtensorMapFloatOOBfill);

struct Dim { uint64_t size, stride; uint32_t box; };
void encode(EncodeFn fn, CUtensorMap* m, const void* ptr, CUtensorMapSwizzle sw, Dim d0, Dim d1, Dim d2 = {0, 0, 0},
            Dim d3 = {0, 0, 0}, Dim d4 = {0, 0, 0}) {
    const cuuint64_t dims[5] = {d0.size, d1.size, d2.size, d3.size, d4.size};
    const cuuint64_t strides[4] = {d1.stride, d2.stride, d3.stride, d4.stride};
    const cuuint32_t box[5] = {d0.box, d1.box, d2.box, d3.box, d4.box};
    const cuuint32_t es[5] = {1, 1, 1, 1, 1};
    fn(m, CU_TENSOR_MAP_DATA_TYPE_BFLOAT16, d4.size ? 5 : d3.size ? 4 : 2, const_cast<void*>(ptr), dims, strides, box, es,
       CU_TENSOR_MAP_INTERLEAVE_NONE, sw, CU_TENSOR_MAP_L2_PROMOTION_L2_128B, CU_TENSOR_MAP_FLOAT_OOB_FILL_NONE);
}

}

extern "C" void kernel_launch(void* const* d_in, const int* in_sizes, int n_in, void* d_out, int out_size) {
    (void)in_sizes; (void)n_in; (void)out_size;
    void* fnp = nullptr;
    cudaDriverEntryPointQueryResult st;
    cudaGetDriverEntryPoint("cuTensorMapEncodeTiled", &fnp, cudaEnableDefault, &st);
    EncodeFn fn = (EncodeFn)fnp;
    void* scratch = nullptr;
    cudaGetSymbolAddress(&scratch, g_scratch);
    int dev = 0, sms = 0;
    cudaGetDevice(&dev);
    cudaDeviceGetAttribute(&sms, cudaDevAttrMultiProcessorCount, dev);
    auto kernel = sms == 132 ? fused_kernel<true> : fused_kernel<false>;
    cudaFuncSetAttribute(kernel, cudaFuncAttributeMaxDynamicSharedMemorySize, SMEM_BYTES);

    const CUtensorMapSwizzle S128 = CU_TENSOR_MAP_SWIZZLE_128B, S0 = CU_TENSOR_MAP_SWIZZLE_NONE;
    const Dim one = {1, 16, 1};
    Maps maps;
    encode(fn, &maps.m[M_XA], d_in[0], S128, {448, 2, 64}, {64, 1792, 64}, {2, 64 * 1792, 1}, {2, 896, 1}, {8, 128 * 1792, 1});
    encode(fn, &maps.m[M_WQK], d_in[1], S128, {112, 2, 64}, {448, 2688, 32}, {3, 896, 2}, {4, 224, 1});
    encode(fn, &maps.m[M_WV], (const uint8_t*)d_in[1] + 896, S128, {112, 2, 64}, {448, 2688, 64}, one, {8, 224, 1});
    encode(fn, &maps.m[M_XH], d_in[0], S128, {448, 2, 64}, {8, 1792, 8}, {2, 896, 1}, {8, 128 * 1792, 8}, {3, 60 * 1792, 1});
    encode(fn, &maps.m[M_WO], d_in[2], S128, {112, 2, 64}, {448, 896, 64}, one, {4, 224, 1});
    encode(fn, &maps.m[M_XB], d_in[3], S128, {448, 2, 64}, {64, 896, 64}, {2, 896 * 1024, 1}, {2, 64 * 896, 1}, {8, 128 * 896, 1});
    encode(fn, &maps.m[M_CR], d_in[4], S128, {2048, 2, 64}, {2048, 4096, 128});
    encode(fn, &maps.m[M_CI], d_in[5], S128, {2048, 2, 64}, {2048, 4096, 128});
    encode(fn, &maps.m[M_WR], d_in[6], S128, {448, 2, 64}, {112, 896, 64}, one, {4, 112 * 896, 1});
    encode(fn, &maps.m[M_WI], d_in[7], S128, {448, 2, 64}, {448, 896, 112});
    encode(fn, &maps.m[M_OUTA], d_out, S0, {1792, 2, 112}, {1024, 3584, 8});
    encode(fn, &maps.m[M_OUTB], d_out, S0, {896, 2, 112}, {2048, 1792, 8});

    kernel<<<132, 384, SMEM_BYTES>>>((Scratch*)scratch, maps);
}
```
